```python
import torch

def _softmax(x, axis=-1):
    return torch.softmax(x, dim=axis)

def _gelu(x):
    return torch.nn.functional.gelu(x, approximate='tanh')

def _silu(x):
    return torch.nn.functional.silu(x)

def _sigmoid(x):
    return torch.sigmoid(x)

def _layernorm(x, axis=-1, eps=1e-05):
    m = x.mean(dim=axis, keepdim=True)
    v = x.var(dim=axis, keepdim=True, unbiased=False)
    return (x - m) / torch.sqrt(v + eps)

def _scatter_add(tgt, idx, src, axis=0):
    return tgt.clone().index_add_(axis, idx, src)

def _segment_sum(src, seg, n):
    out = torch.zeros((n,) + src.shape[1:], dtype=src.dtype)
    return out.index_add_(0, seg, src)

def _pad(x, pw):
    flat = tuple((v for pair in reversed(pw) for v in pair))
    return torch.nn.functional.pad(x, flat)
kernel_name = 'gated_mix__compressed_kv_cla__memory_aug_recurrent_mem_tr__prompt'

def setup_inputs():

    _w = lambda a: (lambda t: t.to(torch.bfloat16) if t.is_floating_point() else t)(torch.as_tensor(a))

    def _A_setup():
        B, H, Sq, Sk, D, M = (1, 32, 2048, 2048, 128, 512)
        Dc = 4 * D
        return {'x': _w((lambda *s: torch.randn(*s, dtype=torch.bfloat16) * 0.05)(B, Sq, M)), 'c_kv': _w((lambda *s: torch.randn(*s, dtype=torch.bfloat16) * 0.8)(B, Sk, Dc)), 'w_q': _w((lambda *s: torch.randn(*s, dtype=torch.bfloat16) * 6.4)(M, H, D) * M ** (-0.5)), 'w_uk': _w((lambda *s: torch.randn(*s, dtype=torch.bfloat16) * 6.4)(Dc, H, D) * Dc ** (-0.5)), 'w_uv': _w((lambda *s: torch.randn(*s, dtype=torch.bfloat16) * 0.8)(Dc, H, D) * Dc ** (-0.5)), 'w_o': _w((lambda *s: torch.randn(*s, dtype=torch.bfloat16) * 0.8)(H, D, M) * (H * D) ** (-0.5))}
    _A_in = _A_setup()

    def _B_setup():
        B, S, Dm = (1, 2048, 512)
        H, Dh = (32, 128)
        M, seg = (8, 32)
        seg = min(seg, S)
        S = S // seg * seg
        return {'x': _w((lambda *s: torch.randn(*s, dtype=torch.bfloat16) * 0.05)(B, S, Dm)), 'mem0': _w((lambda *s: torch.randn(*s, dtype=torch.bfloat16) * 0.8)(B, M, Dm)), 'Wq': _w((lambda *s: torch.randn(*s, dtype=torch.bfloat16) * 3.2)(Dm, H, Dh) * Dm ** (-0.5)), 'Wk': _w((lambda *s: torch.randn(*s, dtype=torch.bfloat16) * 3.2)(Dm, H, Dh) * Dm ** (-0.5)), 'Wv': _w((lambda *s: torch.randn(*s, dtype=torch.bfloat16) * 0.8)(Dm, H, Dh) * Dm ** (-0.5)), 'Wo': _w((lambda *s: torch.randn(*s, dtype=torch.bfloat16) * 0.8)(H, Dh, Dm) * (H * Dh) ** (-0.5)), 'seg_len': seg}
    _B_in = _B_setup()
    return {'A_x': _A_in['x'], 'A_c_kv': _A_in['c_kv'], 'A_w_q': _A_in['w_q'], 'A_w_uk': _A_in['w_uk'], 'A_w_uv': _A_in['w_uv'], 'A_w_o': _A_in['w_o'], 'B_x': _B_in['x'], 'B_mem0': _B_in['mem0'], 'B_Wq': _B_in['Wq'], 'B_Wk': _B_in['Wk'], 'B_Wv': _B_in['Wv'], 'B_Wo': _B_in['Wo'], 'B_seg_len': _B_in['seg_len'], 'gate_w': _w((lambda *s: torch.randn(*s, dtype=torch.bfloat16) * 0.05)(512) * 16.0)}

def reference(A_x, A_c_kv, A_w_q, A_w_uk, A_w_uv, A_w_o, B_x, B_mem0, B_Wq, B_Wk, B_Wv, B_Wo, B_seg_len, gate_w):

    def _A_ref(x, c_kv, w_q, w_uk, w_uv, w_o):
        B, Sq, M = (x.shape[0], x.shape[1], x.shape[2])
        Sk = c_kv.shape[1]
        H, D = (w_q.shape[1], w_q.shape[2])
        q = torch.einsum('bqm,mhd->bhqd', x, w_q)
        k = torch.einsum('bkc,chd->bhkd', c_kv, w_uk)
        v = torch.einsum('bkc,chd->bhkd', c_kv, w_uv)
        scores = torch.einsum('bhqd,bhkd->bhqk', q, k) * D ** (-0.5)
        off = Sk - Sq
        qi = torch.arange(Sq)[:, None]
        kj = torch.arange(Sk)[None, :]
        cmask = kj <= qi + off
        scores = torch.where(cmask[None, None], scores, -1000000000.0)
        p = _softmax(scores, axis=-1)
        ctx = torch.einsum('bhqk,bhkd->bhqd', p, v)
        return torch.einsum('bhqd,hdm->bqm', ctx, w_o)

    def _B_ref(x, mem0, Wq, Wk, Wv, Wo, seg_len):
        B, S, Dm = x.shape
        H, Dh = (Wq.shape[1], Wq.shape[2])
        M = mem0.shape[1]
        scale = Dh ** (-0.5)
        n_seg = S // seg_len
        L = M + seg_len
        idx = torch.arange(L)
        mask = (idx[:, None] < M) | (idx[:, None] >= idx[None, :])
        mem = mem0
        outs = []
        for s in range(n_seg):
            xs = x[:, s * seg_len:(s + 1) * seg_len, :].clone()
            h = torch.concatenate([mem, xs], axis=1)
            q = torch.einsum('btd,dhe->bhte', h, Wq)
            k = torch.einsum('btd,dhe->bhte', h, Wk)
            v = torch.einsum('btd,dhe->bhte', h, Wv)
            scores = torch.einsum('bhqe,bhke->bhqk', q, k) * scale
            scores = torch.where(mask[None, None], scores, -1000000000.0)
            p = _softmax(scores, axis=-1)
            o = torch.einsum('bhqk,bhke->bhqe', p, v)
            o = torch.einsum('bhte,hed->btd', o, Wo)
            mem = o[:, :M, :].clone()
            outs.append(o[:, M:, :])
        return torch.concatenate(outs, axis=1)
    x = A_x
    g = _sigmoid((x * gate_w).sum(-1, keepdims=True))
    a = _A_ref(x, A_c_kv, A_w_q, A_w_uk, A_w_uv, A_w_o)
    b = _B_ref(x, B_mem0, B_Wq, B_Wk, B_Wv, B_Wo, B_seg_len)
    return g * a + (1 - g) * b
```

```cpp
#include <cuda_runtime.h>
#include <cuda_bf16.h>
#include <cuda.h>
#include <stdint.h>

constexpr int SEQ = 2048;
constexpr int DM = 512;
constexpr int NH = 32;
constexpr int HD = 128;
constexpr int NQ = NH * HD;
constexpr int SEGL = 32;
constexpr int NMEM = 8;
constexpr int NSEG = SEQ / SEGL;

typedef __nv_bfloat16 bf16;

__device__ bf16 g_QA[SEQ * NQ];
__device__ bf16 g_KA[SEQ * NQ];
__device__ bf16 g_VA[SEQ * NQ];
__device__ bf16 g_ctxA[SEQ * NQ];
__device__ bf16 g_ctxB[SEQ * NQ];
constexpr int CT_PROJ = 0, CT_ATTN = 1, CT_FIN = 5;
constexpr int CT_AP = 64;
#define O2_HE 18
constexpr int CT_CA = 128;
constexpr int CT_CB = 160;
constexpr int CT_OP = 192;
constexpr int CT_N = 224;
__device__ unsigned int g_ctr[CT_N];
__device__ uint2 g_xbuf[2 * 8 * 8 * 128];

#define FA_GRID 84

#define TS_BEGIN(id)
#define TS_END(id)
__device__ __forceinline__ void pdl_launch_dependents() { asm volatile("griddepcontrol.launch_dependents;" ::: "memory"); }
__device__ __forceinline__ void wait_ctr(int idx, unsigned int n) {
    unsigned int v; int it = 0;
    do { asm volatile("ld.acquire.gpu.global.u32 %0, [%1];" : "=r"(v) : "l"(&g_ctr[idx]) : "memory"); } while (v < n && ++it < (1 << 22));
    asm volatile("fence.proxy.async;" ::: "memory");
}
__device__ __forceinline__ void signal_ctr(int idx) {
    asm volatile("fence.proxy.async;" ::: "memory");
    __threadfence();
    atomicAdd(&g_ctr[idx], 1u);
}
__device__ __forceinline__ uint32_t smem_u32(const void* p) {
    return (uint32_t)__cvta_generic_to_shared(p);
}
__device__ __forceinline__ void mbar_init(uint32_t bar, uint32_t count) {
    asm volatile("mbarrier.init.shared::cta.b64 [%0], %1;" :: "r"(bar), "r"(count));
}
__device__ __forceinline__ void mbar_expect_tx(uint32_t bar, uint32_t bytes) {
    asm volatile("mbarrier.arrive.expect_tx.shared::cta.b64 _, [%0], %1;" :: "r"(bar), "r"(bytes) : "memory");
}
__device__ __forceinline__ void mbar_arrive(uint32_t bar) {
    asm volatile("mbarrier.arrive.shared::cta.b64 _, [%0];" :: "r"(bar) : "memory");
}
__device__ __forceinline__ void mbar_wait(uint32_t bar, uint32_t parity) {
    asm volatile(
        "{\n"
        ".reg .pred p, q;\n"
        ".reg .u32 c;\n"
        "mov.u32 c, 0;\n"
        "WAIT_LOOP:\n"
        "mbarrier.try_wait.parity.shared::cta.b64 p, [%0], %1;\n"
        "@p bra WAIT_DONE;\n"
        "add.u32 c, c, 1;\n"
        "setp.lt.u32 q, c, 4000000;\n"
        "@q bra WAIT_LOOP;\n"
        "WAIT_DONE:\n"
        "}\n" :: "r"(bar), "r"(parity) : "memory");
}
__device__ __forceinline__ void tma_load_2d(uint32_t dst, const CUtensorMap* map, uint32_t bar, int c0, int c1) {
    asm volatile(
        "cp.async.bulk.tensor.2d.shared::cluster.global.mbarrier::complete_tx::bytes [%0], [%1, {%3, %4}], [%2];"
        :: "r"(dst), "l"((uint64_t)map), "r"(bar), "r"(c0), "r"(c1) : "memory");
}
__device__ __forceinline__ void wgmma_fence() { asm volatile("wgmma.fence.sync.aligned;" ::: "memory"); }
__device__ __forceinline__ void wgmma_commit() { asm volatile("wgmma.commit_group.sync.aligned;" ::: "memory"); }
template <int N> __device__ __forceinline__ void wgmma_wait() {
    asm volatile("wgmma.wait_group.sync.aligned %0;" :: "n"(N) : "memory");
}
__device__ __forceinline__ uint64_t make_desc(uint32_t addr, uint32_t lbo, uint32_t sbo) {
    uint64_t d = 0;
    d |= (uint64_t)((addr & 0x3FFFF) >> 4);
    d |= (uint64_t)((lbo >> 4) & 0x3FFF) << 16;
    d |= (uint64_t)((sbo >> 4) & 0x3FFF) << 32;
    d |= (uint64_t)1 << 62;
    return d;
}

#define ACC64(d) \
    "+f"(d[0]), "+f"(d[1]), "+f"(d[2]), "+f"(d[3]), "+f"(d[4]), "+f"(d[5]), "+f"(d[6]), "+f"(d[7]), \
    "+f"(d[8]), "+f"(d[9]), "+f"(d[10]), "+f"(d[11]), "+f"(d[12]), "+f"(d[13]), "+f"(d[14]), "+f"(d[15]), \
    "+f"(d[16]), "+f"(d[17]), "+f"(d[18]), "+f"(d[19]), "+f"(d[20]), "+f"(d[21]), "+f"(d[22]), "+f"(d[23]), \
    "+f"(d[24]), "+f"(d[25]), "+f"(d[26]), "+f"(d[27]), "+f"(d[28]), "+f"(d[29]), "+f"(d[30]), "+f"(d[31]), \
    "+f"(d[32]), "+f"(d[33]), "+f"(d[34]), "+f"(d[35]), "+f"(d[36]), "+f"(d[37]), "+f"(d[38]), "+f"(d[39]), \
    "+f"(d[40]), "+f"(d[41]), "+f"(d[42]), "+f"(d[43]), "+f"(d[44]), "+f"(d[45]), "+f"(d[46]), "+f"(d[47]), \
    "+f"(d[48]), "+f"(d[49]), "+f"(d[50]), "+f"(d[51]), "+f"(d[52]), "+f"(d[53]), "+f"(d[54]), "+f"(d[55]), \
    "+f"(d[56]), "+f"(d[57]), "+f"(d[58]), "+f"(d[59]), "+f"(d[60]), "+f"(d[61]), "+f"(d[62]), "+f"(d[63])
#define ACC64_STR \
    "{%0, %1, %2, %3, %4, %5, %6, %7, %8, %9, %10, %11, %12, %13, %14, %15, " \
    "%16, %17, %18, %19, %20, %21, %22, %23, %24, %25, %26, %27, %28, %29, %30, %31, " \
    "%32, %33, %34, %35, %36, %37, %38, %39, %40, %41, %42, %43, %44, %45, %46, %47, " \
    "%48, %49, %50, %51, %52, %53, %54, %55, %56, %57, %58, %59, %60, %61, %62, %63}"

template <int TB>
__device__ __forceinline__ void wgmma_ss_n128(float (&d)[64], uint64_t da, uint64_t db, int scale_d) {
    asm volatile(
        "{\n.reg .pred p;\nsetp.ne.b32 p, %66, 0;\n"
        "wgmma.mma_async.sync.aligned.m64n128k16.f32.bf16.bf16 " ACC64_STR ", %64, %65, p, 1, 1, 0, %67;\n}\n"
        : ACC64(d) : "l"(da), "l"(db), "r"(scale_d), "n"(TB));
}
__device__ __forceinline__ uint32_t desc_lo(uint32_t addr, uint32_t lbo) { return ((addr & 0x3FFFF) >> 4) | ((lbo >> 4) << 16); }
template <int TB>
__device__ __forceinline__ void wgmma_ss_n128_lo(float (&d)[64], uint32_t da_lo, uint32_t db_lo, int scale_d) {
    asm volatile(
        "{\n.reg .pred p;\n.reg .b64 da, db;\nsetp.ne.b32 p, %66, 0;\n"
        "mov.b64 da, {%64, 0x40000040};\nmov.b64 db, {%65, 0x40000040};\n"
        "wgmma.mma_async.sync.aligned.m64n128k16.f32.bf16.bf16 " ACC64_STR ", da, db, p, 1, 1, 0, %67;\n}\n"
        : ACC64(d) : "r"(da_lo), "r"(db_lo), "r"(scale_d), "n"(TB));
}
__device__ __forceinline__ void wgmma_rs_n128_tb(float (&d)[64], uint32_t a0, uint32_t a1, uint32_t a2, uint32_t a3,
                                                 uint64_t db, int scale_d) {
    asm volatile(
        "{\n.reg .pred p;\nsetp.ne.b32 p, %69, 0;\n"
        "wgmma.mma_async.sync.aligned.m64n128k16.f32.bf16.bf16 " ACC64_STR ", {%64, %65, %66, %67}, %68, p, 1, 1, 1;\n}\n"
        : ACC64(d) : "r"(a0), "r"(a1), "r"(a2), "r"(a3), "l"(db), "r"(scale_d));
}
__device__ __forceinline__ void wgmma_rs_n80(float (&d)[40], const uint32_t (&a)[4], uint32_t db_lo, int scale_d) {
    asm volatile(
        "{\n.reg .pred p;\n.reg .b64 db;\nsetp.ne.b32 p, %45, 0;\nmov.b64 db, {%44, 0x40000040};\n"
        "wgmma.mma_async.sync.aligned.m64n80k16.f32.bf16.bf16 "
        "{%0, %1, %2, %3, %4, %5, %6, %7, %8, %9, %10, %11, %12, %13, %14, %15, %16, %17, %18, %19, %20, %21, %22, %23, %24, %25, %26, %27, %28, %29, %30, %31, %32, %33, %34, %35, %36, %37, %38, %39}, "
        "{%40, %41, %42, %43}, db, p, 1, 1, 0;\n}\n"
        : "+f"(d[0]), "+f"(d[1]), "+f"(d[2]), "+f"(d[3]), "+f"(d[4]), "+f"(d[5]), "+f"(d[6]), "+f"(d[7]), "+f"(d[8]), "+f"(d[9]), "+f"(d[10]), "+f"(d[11]), "+f"(d[12]), "+f"(d[13]), "+f"(d[14]), "+f"(d[15]), "+f"(d[16]), "+f"(d[17]), "+f"(d[18]), "+f"(d[19]), "+f"(d[20]), "+f"(d[21]), "+f"(d[22]), "+f"(d[23]), "+f"(d[24]), "+f"(d[25]), "+f"(d[26]), "+f"(d[27]), "+f"(d[28]), "+f"(d[29]), "+f"(d[30]), "+f"(d[31]), "+f"(d[32]), "+f"(d[33]), "+f"(d[34]), "+f"(d[35]), "+f"(d[36]), "+f"(d[37]), "+f"(d[38]), "+f"(d[39])
        : "r"(a[0]), "r"(a[1]), "r"(a[2]), "r"(a[3]), "r"(db_lo), "r"(scale_d));
}
__device__ __forceinline__ void wgmma_ss_n256_tb(float (&d)[128], uint64_t da, uint64_t db, int scale_d) {
    asm volatile(
        "{\n.reg .pred p;\nsetp.ne.b32 p, %130, 0;\n"
        "wgmma.mma_async.sync.aligned.m64n256k16.f32.bf16.bf16 {%0, %1, %2, %3, %4, %5, %6, %7, %8, %9, %10, %11, %12, %13, %14, %15, %16, %17, %18, %19, %20, %21, %22, %23, %24, %25, %26, %27, %28, %29, %30, %31, %32, %33, %34, %35, %36, %37, %38, %39, %40, %41, %42, %43, %44, %45, %46, %47, %48, %49, %50, %51, %52, %53, %54, %55, %56, %57, %58, %59, %60, %61, %62, %63, %64, %65, %66, %67, %68, %69, %70, %71, %72, %73, %74, %75, %76, %77, %78, %79, %80, %81, %82, %83, %84, %85, %86, %87, %88, %89, %90, %91, %92, %93, %94, %95, %96, %97, %98, %99, %100, %101, %102, %103, %104, %105, %106, %107, %108, %109, %110, %111, %112, %113, %114, %115, %116, %117, %118, %119, %120, %121, %122, %123, %124, %125, %126, %127}, %128, %129, p, 1, 1, 0, 1;\n}\n"
        : "+f"(d[0]), "+f"(d[1]), "+f"(d[2]), "+f"(d[3]), "+f"(d[4]), "+f"(d[5]), "+f"(d[6]), "+f"(d[7]), "+f"(d[8]), "+f"(d[9]), "+f"(d[10]), "+f"(d[11]), "+f"(d[12]), "+f"(d[13]), "+f"(d[14]), "+f"(d[15]), "+f"(d[16]), "+f"(d[17]), "+f"(d[18]), "+f"(d[19]), "+f"(d[20]), "+f"(d[21]), "+f"(d[22]), "+f"(d[23]), "+f"(d[24]), "+f"(d[25]), "+f"(d[26]), "+f"(d[27]), "+f"(d[28]), "+f"(d[29]), "+f"(d[30]), "+f"(d[31]), "+f"(d[32]), "+f"(d[33]), "+f"(d[34]), "+f"(d[35]), "+f"(d[36]), "+f"(d[37]), "+f"(d[38]), "+f"(d[39]), "+f"(d[40]), "+f"(d[41]), "+f"(d[42]), "+f"(d[43]), "+f"(d[44]), "+f"(d[45]), "+f"(d[46]), "+f"(d[47]), "+f"(d[48]), "+f"(d[49]), "+f"(d[50]), "+f"(d[51]), "+f"(d[52]), "+f"(d[53]), "+f"(d[54]), "+f"(d[55]), "+f"(d[56]), "+f"(d[57]), "+f"(d[58]), "+f"(d[59]), "+f"(d[60]), "+f"(d[61]), "+f"(d[62]), "+f"(d[63]), "+f"(d[64]), "+f"(d[65]), "+f"(d[66]), "+f"(d[67]), "+f"(d[68]), "+f"(d[69]), "+f"(d[70]), "+f"(d[71]), "+f"(d[72]), "+f"(d[73]), "+f"(d[74]), "+f"(d[75]), "+f"(d[76]), "+f"(d[77]), "+f"(d[78]), "+f"(d[79]), "+f"(d[80]), "+f"(d[81]), "+f"(d[82]), "+f"(d[83]), "+f"(d[84]), "+f"(d[85]), "+f"(d[86]), "+f"(d[87]), "+f"(d[88]), "+f"(d[89]), "+f"(d[90]), "+f"(d[91]), "+f"(d[92]), "+f"(d[93]), "+f"(d[94]), "+f"(d[95]), "+f"(d[96]), "+f"(d[97]), "+f"(d[98]), "+f"(d[99]), "+f"(d[100]), "+f"(d[101]), "+f"(d[102]), "+f"(d[103]), "+f"(d[104]), "+f"(d[105]), "+f"(d[106]), "+f"(d[107]), "+f"(d[108]), "+f"(d[109]), "+f"(d[110]), "+f"(d[111]), "+f"(d[112]), "+f"(d[113]), "+f"(d[114]), "+f"(d[115]), "+f"(d[116]), "+f"(d[117]), "+f"(d[118]), "+f"(d[119]), "+f"(d[120]), "+f"(d[121]), "+f"(d[122]), "+f"(d[123]), "+f"(d[124]), "+f"(d[125]), "+f"(d[126]), "+f"(d[127])
        : "l"(da), "l"(db), "r"(scale_d));
}
__device__ __forceinline__ void stmatrix_x4(uint32_t addr, uint32_t r0, uint32_t r1, uint32_t r2, uint32_t r3) {
    asm volatile("stmatrix.sync.aligned.m8n8.x4.shared.b16 [%0], {%1, %2, %3, %4};" :: "r"(addr), "r"(r0), "r"(r1), "r"(r2), "r"(r3) : "memory");
}
__device__ __forceinline__ void tma_store_2d(const CUtensorMap* map, uint32_t src, int c0, int c1) {
    asm volatile("cp.async.bulk.tensor.2d.global.shared::cta.bulk_group [%0, {%2, %3}], [%1];"
                 :: "l"((uint64_t)map), "r"(src), "r"(c0), "r"(c1) : "memory");
}
__device__ __forceinline__ float ex2f(float x) { float y; asm("ex2.approx.ftz.f32 %0, %1;" : "=f"(y) : "f"(x)); return y; }
__device__ __forceinline__ uint32_t pack_bf16(float lo, float hi) {
    __nv_bfloat162 v = __floats2bfloat162_rn(lo, hi);
    return *reinterpret_cast<uint32_t*>(&v);
}
__device__ __forceinline__ void mma_16816(float (&c)[4], uint32_t a0, uint32_t a1, uint32_t a2, uint32_t a3,
                                          uint32_t b0, uint32_t b1) {
    asm volatile(
        "mma.sync.aligned.m16n8k16.row.col.f32.bf16.bf16.f32 {%0,%1,%2,%3}, {%4,%5,%6,%7}, {%8,%9}, {%0,%1,%2,%3};"
        : "+f"(c[0]), "+f"(c[1]), "+f"(c[2]), "+f"(c[3])
        : "r"(a0), "r"(a1), "r"(a2), "r"(a3), "r"(b0), "r"(b1));
}
__device__ __forceinline__ void ldmatrix_x4_trans(uint32_t& r0, uint32_t& r1, uint32_t& r2, uint32_t& r3, uint32_t addr) {
    asm volatile("ldmatrix.sync.aligned.m8n8.x4.trans.shared.b16 {%0,%1,%2,%3}, [%4];"
                 : "=r"(r0), "=r"(r1), "=r"(r2), "=r"(r3) : "r"(addr));
}

struct AttnParams {
    CUtensorMap mapQ, mapK, mapV;
    CUtensorMap mapO;
};
constexpr int FA_STAGES = 2;
constexpr int FA_SMEM = 32768 + FA_STAGES * 65536 + 32768 + 1024 + 256;
constexpr int FA_ITEMS = 16 * NH;
#define FA_RETIRE 100000
#define FA_LASTG 8
__device__ __forceinline__ int fa_qt(int t) {
    constexpr int T0 = (32 - FA_LASTG) * 16;
    return t < T0 ? 15 - ((t & 127) >> 3) : 15 - (t - T0) / FA_LASTG;
}
__device__ __forceinline__ int fa_head(int t) {
    constexpr int T0 = (32 - FA_LASTG) * 16;
    return t < T0 ? (t >> 7) * 8 + (t & 7) : (32 - FA_LASTG) + (t - T0) % FA_LASTG;
}

__global__ void __launch_bounds__(384, 1) attn_kernel(const __grid_constant__ AttnParams P, int retire_cta) {
    extern __shared__ uint8_t smem_raw[];
    uint32_t sbase = (smem_u32(smem_raw) + 1023) & ~1023u;
    const uint32_t sQ = sbase;
    const uint32_t sKV = sbase + 32768;
    const uint32_t sO = sKV + FA_STAGES * 65536;
    const uint32_t bars = sO + 32768;
    const uint32_t bar_q = bars, bar_qe = bars + 8, bar_kf = bars + 16, bar_vf = bar_kf + 8 * FA_STAGES, bar_e = bar_vf + 8 * FA_STAGES,
                   bar_ek = bar_e + 8 * FA_STAGES, slot = bar_ek + 8 * FA_STAGES, bar_of = slot + 16, bar_oe = bar_of + 16, oslot = bar_oe + 16;
    const int warp = threadIdx.x >> 5;
    TS_BEGIN(1);
    int tfirst = 0;
    if (threadIdx.x == 256) tfirst = (int)atomicAdd(&g_ctr[CT_ATTN], 1u);
    if (threadIdx.x == 0) {
        mbar_init(bar_q, 1); mbar_init(bar_qe, 8);
        for (int i = 0; i < FA_STAGES; i++) { mbar_init(bar_kf + 8 * i, 1); mbar_init(bar_vf + 8 * i, 1); mbar_init(bar_e + 8 * i, 8); mbar_init(bar_ek + 8 * i, 8); }
        for (int i = 0; i < 2; i++) { mbar_init(bar_of + 8 * i, 1); mbar_init(bar_oe + 8 * i, 1); }
        asm volatile("fence.mbarrier_init.release.cluster;" ::: "memory");
    }
    if (threadIdx.x == 256) asm volatile("st.shared.s32 [%0], %1;" :: "r"(slot + 8), "r"(tfirst) : "memory");
    __syncthreads();
    pdl_launch_dependents();
    if (warp >= 8) {
        asm volatile("setmaxnreg.dec.sync.aligned.u32 40;");
        if (threadIdx.x == 288 || threadIdx.x == 320) {
            const int wg = threadIdx.x == 288 ? 0 : 1;
            const uint32_t stg = sO + wg * 16384;
            for (int n = 0;; n++) {
                mbar_wait(bar_of + 8 * wg, n & 1);
                int t;
                asm volatile("ld.shared.s32 %0, [%1];" : "=r"(t) : "r"(oslot + wg * 4) : "memory");
                if (t < 0) break;
                const int qt = fa_qt(t), h = fa_head(t);
                tma_store_2d(&P.mapO, stg, 0, h * SEQ + qt * 128 + wg * 64);
                tma_store_2d(&P.mapO, stg + 8192, 64, h * SEQ + qt * 128 + wg * 64);
                asm volatile("cp.async.bulk.commit_group;" ::: "memory");
                asm volatile("cp.async.bulk.wait_group.read 0;" ::: "memory");
                mbar_arrive(bar_oe + 8 * wg);
                asm volatile("cp.async.bulk.wait_group 0;" ::: "memory");
                signal_ctr(CT_CA + qt * 2 + (h >= O2_HE));
            }
        }
        if (threadIdx.x == 256) {
            int it = 0, hp_ready = 0;
            for (int item = 0;; item++) {
                int t = tfirst;
                if (item > 0) {
                    bool quit = false;
                    if ((int)blockIdx.x >= retire_cta) {
                        unsigned int v;
                        asm volatile("ld.relaxed.gpu.global.u32 %0, [%1];" : "=r"(v) : "l"(&g_ctr[CT_ATTN]) : "memory");
                        quit = v >= FA_RETIRE;
                    }
                    t = quit ? FA_ITEMS : (int)atomicAdd(&g_ctr[CT_ATTN], 1u);
                }
                const bool valid = t < FA_ITEMS;
                const int qt = fa_qt(t), h = fa_head(t);
                if (valid && !((hp_ready >> (h >> 1)) & 1)) { wait_ctr(CT_AP + (h >> 1), 96u); hp_ready |= 1 << (h >> 1); }
                mbar_wait(bar_qe, (item & 1) ^ 1);
                asm volatile("st.shared.s32 [%0], %1;" :: "r"(slot + (item & 1) * 4), "r"(valid ? t : -1) : "memory");
                if (!valid) { mbar_arrive(bar_q); break; }
                mbar_expect_tx(bar_q, 32768);
                tma_load_2d(sQ, &P.mapQ, bar_q, 0, h * SEQ + qt * 128);
                tma_load_2d(sQ + 16384, &P.mapQ, bar_q, 64, h * SEQ + qt * 128);
                for (int j = 0; j <= qt; j++, it++) {
                    const int s = it % FA_STAGES;
                    mbar_wait(bar_ek + 8 * s, ((it / FA_STAGES) & 1) ^ 1);
                    const uint32_t sk = sKV + s * 65536, sv = sk + 32768;
                    mbar_expect_tx(bar_kf + 8 * s, 32768);
                    tma_load_2d(sk, &P.mapK, bar_kf + 8 * s, 0, h * SEQ + j * 128);
                    tma_load_2d(sk + 16384, &P.mapK, bar_kf + 8 * s, 64, h * SEQ + j * 128);
                    mbar_wait(bar_e + 8 * s, ((it / FA_STAGES) & 1) ^ 1);
                    mbar_expect_tx(bar_vf + 8 * s, 32768);
                    tma_load_2d(sv, &P.mapV, bar_vf + 8 * s, 0, h * SEQ + j * 128);
                    tma_load_2d(sv + 16384, &P.mapV, bar_vf + 8 * s, 64, h * SEQ + j * 128);
                }
            }
        }
    } else {
        asm volatile("setmaxnreg.inc.sync.aligned.u32 232;");
        const int wg = warp >> 2;
        const int lane = threadIdx.x & 31;
        float o[64];
        float mrow0, mrow1, lrow0, lrow1;
        const float sc = 0.08838834764831845f * 1.4426950408889634f;
        const int r0 = wg * 64 + (warp & 3) * 16 + (lane >> 2);
        float sacc[64];
        uint32_t pa[32];
        float a0 = 1.f, a1 = 1.f;
        auto issue_qk = [&](int it) {
            const int s = it % FA_STAGES;
            const uint32_t sk = sKV + s * 65536;
            mbar_wait(bar_kf + 8 * s, (it / FA_STAGES) & 1);
            wgmma_fence();
#pragma unroll
            for (int kk = 0; kk < 8; kk++) {
                uint64_t da = make_desc(sQ + (kk >> 2) * 16384 + wg * 8192 + (kk & 3) * 32, 16, 1024);
                uint64_t db = make_desc(sk + (kk >> 2) * 16384 + (kk & 3) * 32, 16, 1024);
                wgmma_ss_n128<0>(sacc, da, db, kk != 0);
            }
            wgmma_commit();
        };
        auto issue_pv = [&](int it) {
            const int s = it % FA_STAGES;
            const uint32_t sv = sKV + s * 65536 + 32768;
            mbar_wait(bar_vf + 8 * s, (it / FA_STAGES) & 1);
            wgmma_fence();
#pragma unroll
            for (int kk = 0; kk < 8; kk++) {
                uint64_t db = make_desc(sv + kk * 2048, 16384, 1024);
                wgmma_rs_n128_tb(o, pa[kk * 4 + 0], pa[kk * 4 + 1], pa[kk * 4 + 2], pa[kk * 4 + 3], db, 1);
            }
            wgmma_commit();
        };
        auto softmax_stats = [&](bool diag) {
            if (diag) {
#pragma unroll
                for (int i = 0; i < 64; i++) {
                    int col = (i >> 2) * 8 + (lane & 3) * 2 + (i & 1);
                    int row = r0 + ((i & 2) ? 8 : 0);
                    if (col > row) sacc[i] = -INFINITY;
                }
            }
            float mx0 = -INFINITY, mx1 = -INFINITY;
#pragma unroll
            for (int i = 0; i < 16; i++) {
                mx0 = fmaxf(mx0, fmaxf(sacc[i * 4 + 0], sacc[i * 4 + 1]));
                mx1 = fmaxf(mx1, fmaxf(sacc[i * 4 + 2], sacc[i * 4 + 3]));
            }
            mx0 = fmaxf(mx0, __shfl_xor_sync(0xffffffff, mx0, 1));
            mx0 = fmaxf(mx0, __shfl_xor_sync(0xffffffff, mx0, 2));
            mx1 = fmaxf(mx1, __shfl_xor_sync(0xffffffff, mx1, 1));
            mx1 = fmaxf(mx1, __shfl_xor_sync(0xffffffff, mx1, 2));
            const float mn0 = fmaxf(mrow0, mx0), mn1 = fmaxf(mrow1, mx1);
            a0 = ex2f((mrow0 - mn0) * sc); a1 = ex2f((mrow1 - mn1) * sc);
            mrow0 = mn0; mrow1 = mn1;
            const float ms0 = mn0 * sc, ms1 = mn1 * sc;
            float sum0 = 0.f, sum1 = 0.f;
#pragma unroll
            for (int i = 0; i < 16; i++) {
                sacc[i * 4 + 0] = ex2f(fmaf(sacc[i * 4 + 0], sc, -ms0));
                sacc[i * 4 + 1] = ex2f(fmaf(sacc[i * 4 + 1], sc, -ms0));
                sacc[i * 4 + 2] = ex2f(fmaf(sacc[i * 4 + 2], sc, -ms1));
                sacc[i * 4 + 3] = ex2f(fmaf(sacc[i * 4 + 3], sc, -ms1));
                sum0 += sacc[i * 4 + 0] + sacc[i * 4 + 1];
                sum1 += sacc[i * 4 + 2] + sacc[i * 4 + 3];
            }
            lrow0 = lrow0 * a0 + sum0;
            lrow1 = lrow1 * a1 + sum1;
        };
        auto pack_p = [&]() {
#pragma unroll
            for (int i = 0; i < 16; i++) {
                pa[i * 2 + 0] = pack_bf16(sacc[i * 4 + 0], sacc[i * 4 + 1]);
                pa[i * 2 + 1] = pack_bf16(sacc[i * 4 + 2], sacc[i * 4 + 3]);
            }
        };
        int it = 0;
        if (wg == 1) asm volatile("bar.arrive 1, 256;" ::: "memory");
        for (int item = 0;; item++) {
            mbar_wait(bar_q, item & 1);
            int t;
            asm volatile("ld.shared.s32 %0, [%1];" : "=r"(t) : "r"(slot + (item & 1) * 4) : "memory");
            if (t < 0) {
                if ((threadIdx.x & 127) == 0) {
                    mbar_wait(bar_oe + 8 * wg, (item & 1) ^ 1);
                    asm volatile("st.shared.s32 [%0], %1;" :: "r"(oslot + wg * 4), "r"(-1) : "memory");
                    mbar_arrive(bar_of + 8 * wg);
                }
                break;
            }
            const int qt = fa_qt(t);
            const int nkv = qt + 1;
#pragma unroll
            for (int i = 0; i < 64; i++) o[i] = 0.f;
            mrow0 = -INFINITY; mrow1 = -INFINITY; lrow0 = 0.f; lrow1 = 0.f;
            asm volatile("bar.sync %0, 256;" :: "r"(1 + wg) : "memory");
            issue_qk(it);
            asm volatile("bar.arrive %0, 256;" :: "r"(2 - wg) : "memory");
            wgmma_wait<0>();
            if (lane == 0) { mbar_arrive(bar_ek + 8 * (it % FA_STAGES)); if (nkv == 1) mbar_arrive(bar_qe); }
            softmax_stats(nkv == 1);
            pack_p();
#pragma unroll 1
            for (int j = 1; j < nkv; j++) {
                asm volatile("bar.sync %0, 256;" :: "r"(1 + wg) : "memory");
                issue_qk(it + j);
                issue_pv(it + j - 1);
                asm volatile("bar.arrive %0, 256;" :: "r"(2 - wg) : "memory");
                wgmma_wait<1>();
                if (lane == 0) { mbar_arrive(bar_ek + 8 * ((it + j) % FA_STAGES)); if (j == nkv - 1) mbar_arrive(bar_qe); }
                softmax_stats(j == nkv - 1);
                wgmma_wait<0>();
                if (lane == 0) mbar_arrive(bar_e + 8 * ((it + j - 1) % FA_STAGES));
#pragma unroll
                for (int i = 0; i < 16; i++) {
                    o[i * 4 + 0] *= a0; o[i * 4 + 1] *= a0; o[i * 4 + 2] *= a1; o[i * 4 + 3] *= a1;
                }
                pack_p();
            }
            issue_pv(it + nkv - 1);
            wgmma_wait<0>();
            if (lane == 0) mbar_arrive(bar_e + 8 * ((it + nkv - 1) % FA_STAGES));
            it += nkv;
            lrow0 += __shfl_xor_sync(0xffffffff, lrow0, 1);
            lrow0 += __shfl_xor_sync(0xffffffff, lrow0, 2);
            lrow1 += __shfl_xor_sync(0xffffffff, lrow1, 1);
            lrow1 += __shfl_xor_sync(0xffffffff, lrow1, 2);
            const float i0 = 1.f / lrow0, i1 = 1.f / lrow1;
            const uint32_t stg = sO + wg * 16384;
            mbar_wait(bar_oe + 8 * wg, (item & 1) ^ 1);
            {
                const int row = (warp & 3) * 16 + (lane >> 2);
#pragma unroll
                for (int i = 0; i < 4; i++) {
                    const int ch = i * 4 + (lane & 3);
                    const uint32_t a = stg + (ch >> 3) * 8192 + row * 128 + (((ch & 7) ^ (row & 7)) << 4);
                    const float* q = &o[i * 16];
                    asm volatile("st.shared.v4.b32 [%0], {%1, %2, %3, %4};" :: "r"(a), "r"(pack_bf16(q[0] * i0, q[1] * i0)), "r"(pack_bf16(q[4] * i0, q[5] * i0)),
                                 "r"(pack_bf16(q[8] * i0, q[9] * i0)), "r"(pack_bf16(q[12] * i0, q[13] * i0)) : "memory");
                    asm volatile("st.shared.v4.b32 [%0], {%1, %2, %3, %4};" :: "r"(a + 1024), "r"(pack_bf16(q[2] * i1, q[3] * i1)), "r"(pack_bf16(q[6] * i1, q[7] * i1)),
                                 "r"(pack_bf16(q[10] * i1, q[11] * i1)), "r"(pack_bf16(q[14] * i1, q[15] * i1)) : "memory");
                }
            }
            asm volatile("fence.proxy.async.shared::cta;" ::: "memory");
            asm volatile("bar.sync %0, 128;" :: "r"(3 + wg) : "memory");
            if ((threadIdx.x & 127) == 0) {
                asm volatile("st.shared.s32 [%0], %1;" :: "r"(oslot + wg * 4), "r"(t) : "memory");
                mbar_arrive(bar_of + 8 * wg);
            }
        }
        TS_END(1);
    }
}

__device__ __forceinline__ uint32_t cluster_ctarank() {
    uint32_t r; asm volatile("mov.u32 %0, %%cluster_ctarank;" : "=r"(r)); return r;
}
__device__ __forceinline__ uint32_t mapa_u32(uint32_t addr, uint32_t rank) {
    uint32_t r; asm volatile("mapa.shared::cluster.u32 %0, %1, %2;" : "=r"(r) : "r"(addr), "r"(rank)); return r;
}
__device__ __forceinline__ void cluster_sync_all() {
    asm volatile("barrier.cluster.arrive.release.aligned;\nbarrier.cluster.wait.acquire.aligned;" ::: "memory");
}
__device__ __forceinline__ void st_async_v4(uint32_t addr, uint32_t a, uint32_t b, uint32_t c, uint32_t d, uint32_t mbar) {
    asm volatile("st.async.weak.shared::cluster.mbarrier::complete_tx::bytes.v4.b32 [%0], {%1, %2, %3, %4}, [%5];"
                 :: "r"(addr), "r"(a), "r"(b), "r"(c), "r"(d), "r"(mbar) : "memory");
}
__device__ __forceinline__ void st_async_v2(uint32_t addr, uint32_t a, uint32_t b, uint32_t mbar) {
    asm volatile("st.async.weak.shared::cluster.mbarrier::complete_tx::bytes.v2.b32 [%0], {%1, %2}, [%3];"
                 :: "r"(addr), "r"(a), "r"(b), "r"(mbar) : "memory");
}
__device__ __forceinline__ void st_async_b32(uint32_t addr, uint32_t a, uint32_t mbar) {
    asm volatile("st.async.weak.shared::cluster.mbarrier::complete_tx::bytes.b32 [%0], %1, [%2];" :: "r"(addr), "r"(a), "r"(mbar) : "memory");
}
__device__ __forceinline__ void pace(int cycles) {
    if (cycles > 0) {
        uint32_t t0, t;
        asm volatile("mov.u32 %0, %%clock;" : "=r"(t0));
        do { asm volatile("mov.u32 %0, %%clock;" : "=r"(t)); } while (t - t0 < (uint32_t)cycles);
    }
}
__device__ __forceinline__ void mbar_wait_cl(uint32_t bar, uint32_t parity) {
    uint32_t done = 0;
    for (int it = 0; it < (1 << 22) && !done; it++) {
        asm volatile(
            "{\n.reg .pred p;\n"
            "mbarrier.try_wait.parity.shared::cta.b64 p, [%1], %2;\n"
            "selp.u32 %0, 1, 0, p;\n}\n" : "=r"(done) : "r"(bar), "r"(parity) : "memory");
    }
}
__device__ __forceinline__ uint32_t mbar_test(uint32_t bar, uint32_t parity) {
    uint32_t done;
    asm volatile(
        "{\n.reg .pred p;\n"
        "mbarrier.test_wait.parity.shared::cta.b64 p, [%1], %2;\n"
        "selp.u32 %0, 1, 0, p;\n}\n" : "=r"(done) : "r"(bar), "r"(parity) : "memory");
    return done;
}
__device__ __forceinline__ void ldmatrix_x4(uint32_t& r0, uint32_t& r1, uint32_t& r2, uint32_t& r3, uint32_t addr) {
    asm volatile("ldmatrix.sync.aligned.m8n8.x4.shared.b16 {%0,%1,%2,%3}, [%4];"
                 : "=r"(r0), "=r"(r1), "=r"(r2), "=r"(r3) : "r"(addr));
}
__device__ __forceinline__ void cp_async16(uint32_t dst, const void* src) {
    asm volatile("cp.async.cg.shared.global [%0], [%1], 16;" :: "r"(dst), "l"(src) : "memory");
}
__device__ __forceinline__ float bf16r(float x) { return __uint_as_float(pack_bf16(0.f, x) & 0xffff0000u); }

#define DBG(i)
#define DBGW(i, w)
#define DBGD(i, w, dep)
__device__ __forceinline__ void tma_load_2d_mc(uint32_t dst, const CUtensorMap* map, uint32_t bar, int c0, int c1, uint16_t mask) {
    asm volatile(
        "cp.async.bulk.tensor.2d.shared::cluster.global.mbarrier::complete_tx::bytes.multicast::cluster [%0], [%1, {%3, %4}], [%2], %5;"
        :: "r"(dst), "l"((uint64_t)map), "r"(bar), "r"(c0), "r"(c1), "h"(mask) : "memory");
}
__device__ __forceinline__ void bulk_s2s(uint32_t dst_cl, uint32_t src, uint32_t bytes, uint32_t bar_cl) {
    asm volatile("cp.async.bulk.shared::cluster.shared::cta.mbarrier::complete_tx::bytes [%0], [%1], %2, [%3];"
                 :: "r"(dst_cl), "r"(src), "r"(bytes), "r"(bar_cl) : "memory");
}
__device__ __forceinline__ void fence_async_smem() { asm volatile("fence.proxy.async.shared::cta;" ::: "memory"); }
template <int ID, int N> __device__ __forceinline__ void bar_sync() { asm volatile("bar.sync %0, %1;" :: "n"(ID), "n"(N) : "memory"); }
template <int ID, int N> __device__ __forceinline__ void bar_arrive() { asm volatile("bar.arrive %0, %1;" :: "n"(ID), "n"(N) : "memory"); }
__device__ __forceinline__ void sts32(uint32_t a, uint32_t v) { asm volatile("st.shared.u32 [%0], %1;" :: "r"(a), "r"(v) : "memory"); }
__device__ __forceinline__ void ldsm_x4(uint32_t* r, uint32_t addr) {
    asm volatile("ldmatrix.sync.aligned.m8n8.x4.shared.b16 {%0,%1,%2,%3}, [%4];" : "=r"(r[0]), "=r"(r[1]), "=r"(r[2]), "=r"(r[3]) : "r"(addr) : "memory");
}
#define DHI128 "0x40000040"
#define DHI32 "0xC0000010"
__device__ __forceinline__ void wgmma_rs_n32(float (&d)[16], const uint32_t (&a)[4], uint32_t db_lo) {
    asm volatile(
        "{\n.reg .b64 db;\nmov.b64 db, {%20, " DHI128 "};\n"
        "wgmma.mma_async.sync.aligned.m64n32k16.f32.bf16.bf16 {%0,%1,%2,%3,%4,%5,%6,%7,%8,%9,%10,%11,%12,%13,%14,%15}, {%16,%17,%18,%19}, db, 1, 1, 1, 0;\n}\n"
        : "+f"(d[0]), "+f"(d[1]), "+f"(d[2]), "+f"(d[3]), "+f"(d[4]), "+f"(d[5]), "+f"(d[6]), "+f"(d[7]), "+f"(d[8]), "+f"(d[9]), "+f"(d[10]),
          "+f"(d[11]), "+f"(d[12]), "+f"(d[13]), "+f"(d[14]), "+f"(d[15])
        : "r"(a[0]), "r"(a[1]), "r"(a[2]), "r"(a[3]), "r"(db_lo));
}
__device__ __forceinline__ void wgmma_ss_n8(float (&d)[4], uint32_t da_lo, uint32_t db_lo) {
    asm volatile(
        "{\n.reg .b64 da, db;\nmov.b64 da, {%4, " DHI128 "};\nmov.b64 db, {%5, " DHI32 "};\n"
        "wgmma.mma_async.sync.aligned.m64n8k16.f32.bf16.bf16 {%0,%1,%2,%3}, da, db, 1, 1, 1, 1, 0;\n}\n"
        : "+f"(d[0]), "+f"(d[1]), "+f"(d[2]), "+f"(d[3]) : "r"(da_lo), "r"(db_lo));
}
__device__ __forceinline__ void wgmma_ss_n40(float (&d)[20], uint32_t da_lo, uint32_t db_lo) {
    asm volatile(
        "{\n.reg .b64 da, db;\nmov.b64 da, {%20, " DHI128 "};\nmov.b64 db, {%21, " DHI128 "};\n"
        "wgmma.mma_async.sync.aligned.m64n40k16.f32.bf16.bf16 {%0,%1,%2,%3,%4,%5,%6,%7,%8,%9,%10,%11,%12,%13,%14,%15,%16,%17,%18,%19}, da, db, 1, 1, 1, 0, 0;\n}\n"
        : "+f"(d[0]), "+f"(d[1]), "+f"(d[2]), "+f"(d[3]), "+f"(d[4]), "+f"(d[5]), "+f"(d[6]), "+f"(d[7]), "+f"(d[8]), "+f"(d[9]), "+f"(d[10]),
          "+f"(d[11]), "+f"(d[12]), "+f"(d[13]), "+f"(d[14]), "+f"(d[15]), "+f"(d[16]), "+f"(d[17]), "+f"(d[18]), "+f"(d[19])
        : "r"(da_lo), "r"(db_lo));
}
template <bool B128>
__device__ __forceinline__ void wgmma_ss_n32(float (&d)[16], uint32_t da_lo, uint32_t db_lo) {
    asm volatile(
        "{\n.reg .b64 da, db;\nmov.b64 da, {%16, " DHI32 "};\nmov.b64 db, {%17, %18};\n"
        "wgmma.mma_async.sync.aligned.m64n32k16.f32.bf16.bf16 {%0,%1,%2,%3,%4,%5,%6,%7,%8,%9,%10,%11,%12,%13,%14,%15}, da, db, 1, 1, 1, 0, 0;\n}\n"
        : "+f"(d[0]), "+f"(d[1]), "+f"(d[2]), "+f"(d[3]), "+f"(d[4]), "+f"(d[5]), "+f"(d[6]), "+f"(d[7]), "+f"(d[8]), "+f"(d[9]), "+f"(d[10]),
          "+f"(d[11]), "+f"(d[12]), "+f"(d[13]), "+f"(d[14]), "+f"(d[15])
        : "r"(da_lo), "r"(db_lo), "n"(B128 ? 0x40000040u : 0xC0000010u));
}

constexpr uint32_t C2_WO = 0;
constexpr uint32_t C2_XB = 65536;
constexpr uint32_t C2_QX = 131072;
constexpr uint32_t C2_KX = 135168;
constexpr uint32_t C2_VT = 141312;
constexpr uint32_t C2_MB = 153600;
constexpr uint32_t C2_OB = 161792;
constexpr uint32_t C2_QM = 169984;
constexpr uint32_t C2_SC = 171008;
constexpr uint32_t C2_PB = 174080;
constexpr uint32_t C2_PX = 175104;
constexpr uint32_t C2_SX = 178176;
#define C2_NS 4
constexpr uint32_t C2_WS = 198656;
constexpr uint32_t C2_BAR = C2_WS + 3 * C2_NS * 2048;
constexpr uint32_t C2_TR = C2_BAR + 256;
constexpr int C2_SMEM = C2_TR;
#define CH_POLL_DELAY 200

__device__ __forceinline__ void c2_load_w(uint32_t (&w)[32][4], const bf16* __restrict__ W, int rank, int col, uint32_t ws) {
#pragma unroll
    for (int e = 0; e < 32; e++) {
        const bf16* p = W + (size_t)((((rank - (e >> 2)) & 7) * 64) + (e & 3) * 16) * NQ + col;
        w[e][0] = __ldg(reinterpret_cast<const uint32_t*>(p));
        w[e][1] = __ldg(reinterpret_cast<const uint32_t*>(p + NQ));
        w[e][2] = __ldg(reinterpret_cast<const uint32_t*>(p + 8 * NQ));
        w[e][3] = __ldg(reinterpret_cast<const uint32_t*>(p + 9 * NQ));
    }
#pragma unroll
    for (int e = 0; e < 32; e++) {
        const uint32_t w0 = w[e][0], w1 = w[e][1], w2 = w[e][2], w3 = w[e][3];
        w[e][0] = __byte_perm(w0, w1, 0x5410); w[e][1] = __byte_perm(w0, w1, 0x7632);
        w[e][2] = __byte_perm(w2, w3, 0x5410); w[e][3] = __byte_perm(w2, w3, 0x7632);
        if (e < C2_NS) stmatrix_x4(ws + e * 2048, w[e][0], w[e][1], w[e][2], w[e][3]);
    }
    fence_async_smem();
    asm volatile("bar.sync %0, 128;" :: "r"(8 + (threadIdx.x >> 7)) : "memory");
}
__device__ __forceinline__ void c2_xstream(float (&acc)[16], const uint32_t (&w)[32][4], uint32_t xlo, uint32_t rank, uint32_t wslo) {
#pragma unroll
    for (int i = 0; i < 16; i++) acc[i] = 0.f;
    wgmma_fence();
#pragma unroll
    for (int e = 0; e < 32; e++) {
        if (e < C2_NS) wgmma_ss_n32<true>(acc, wslo + e * 128, xlo + ((rank - (e >> 2)) & 7) * 256 + (e & 3) * 2);
        else wgmma_rs_n32(acc, w[e], xlo + ((rank - (e >> 2)) & 7) * 256 + (e & 3) * 2);
    }
    wgmma_commit();
    wgmma_wait<0>();
}
__device__ __forceinline__ void c2_mma_slot(float (&a)[4][4], const uint32_t (&w)[32][4], int slot, const uint32_t (&b)[8], uint32_t ws) {
#pragma unroll
    for (int kk = 3; kk >= 0; kk--) {
        const int e = slot * 4 + kk;
        if (e < C2_NS) {
            uint32_t t[4];
            ldsm_x4(t, ws + e * 2048);
            mma_16816(a[kk], t[0], t[1], t[2], t[3], b[2 * kk], b[2 * kk + 1]);
        } else mma_16816(a[kk], w[e][0], w[e][1], w[e][2], w[e][3], b[2 * kk], b[2 * kk + 1]);
    }
}

__global__ void __cluster_dims__(8, 1, 1) __launch_bounds__(384, 1)
chain_kernel(const __grid_constant__ CUtensorMap mapX, const bf16* __restrict__ mem0, const bf16* __restrict__ Wq, const bf16* __restrict__ Wk,
             const bf16* __restrict__ Wv, const bf16* __restrict__ Wo) {
    extern __shared__ __align__(1024) uint8_t smem_chain[];
    const uint32_t sb = smem_u32(smem_chain);
    const uint32_t dlo = ((sb & 0x3FFFF) >> 4) | (1u << 16);
    const int tid = threadIdx.x, lane = tid & 31;
    const int warp = __shfl_sync(0xffffffff, tid >> 5, 0), wg = warp >> 2, w4 = warp & 3;
    const uint32_t rank = cluster_ctarank();
    const int C = blockIdx.x >> 3;
    const int h = C * 4 + (rank >> 1);
    const int g = lane >> 2, qc = lane & 3;
    pdl_launch_dependents();
    TS_BEGIN(2);
    const uint32_t bar_m = sb + C2_BAR, bar_o = bar_m + 64, bar_sc = bar_m + 128, bar_x = bar_m + 136, bar_sx = bar_m + 152;
    if (tid == 0) {
        for (int j = 0; j < 8; j++) { mbar_init(bar_m + 8 * j, j ? 1 : 4); mbar_init(bar_o + 8 * j, j ? 1 : 4); }
        for (int j = 0; j < 5; j++) mbar_init(bar_sc + 8 * j, 1);
        asm volatile("fence.mbarrier_init.release.cluster;" ::: "memory");
    }
    __syncthreads();
    cluster_sync_all();
    if (tid == 0) {
        mbar_expect_tx(bar_x, 32768);
        tma_load_2d_mc(sb + C2_XB + rank * 4096, &mapX, bar_x, rank * 64, 0, (uint16_t)0xff);
    }
    for (int i = tid; i < 2048; i += 384) {
        const int k = i >> 2, b = i & 3;
        const uint4* p = reinterpret_cast<const uint4*>(Wo + (size_t)(C * 512 + ((rank - (k >> 6)) & 7) * 64 + (k & 63)) * DM + rank * 64 + b * 16);
        const uint4 u = __ldg(p), v = __ldg(p + 1);
        const uint32_t a = sb + C2_WO + k * 128;
        asm volatile("st.shared.v4.b32 [%0], {%1, %2, %3, %4};" :: "r"(a + (((2 * b) ^ (k & 7)) << 4)), "r"(__byte_perm(u.x, u.y, 0x5410)),
                     "r"(__byte_perm(u.z, u.w, 0x5410)), "r"(__byte_perm(v.x, v.y, 0x5410)), "r"(__byte_perm(v.z, v.w, 0x5410)) : "memory");
        asm volatile("st.shared.v4.b32 [%0], {%1, %2, %3, %4};" :: "r"(a + (((2 * b + 1) ^ (k & 7)) << 4)), "r"(__byte_perm(u.x, u.y, 0x7632)),
                     "r"(__byte_perm(u.z, u.w, 0x7632)), "r"(__byte_perm(v.x, v.y, 0x7632)), "r"(__byte_perm(v.z, v.w, 0x7632)) : "memory");
    }
    for (int i = tid; i < 512; i += 384) {
        const int sl = i >> 6, kk = (i >> 4) & 3, row = (i >> 1) & 7, hf = i & 1;
        const uint4 u = __ldg(reinterpret_cast<const uint4*>(mem0 + row * DM + ((rank - sl) & 7) * 64 + kk * 16 + hf * 8));
        asm volatile("st.shared.v4.b32 [%0], {%1, %2, %3, %4};" :: "r"(sb + C2_MB + sl * 1024 + kk * 256 + row * 32 + ((hf ^ (row >> 2)) << 4)),
                     "r"(u.x), "r"(u.y), "r"(u.z), "r"(u.w) : "memory");
    }
    for (int i = tid; i < 2 * 512 + 256; i += 384)
        sts32(sb + (i < 1024 ? C2_VT + (i >> 9) * 6144 + 4096 + (i & 511) * 4 : C2_PX + 2048 + (i - 1024) * 4), 0u);
    fence_async_smem();
    __syncthreads();

    const uint32_t l32 = (lane >> 4) * 256 + (lane & 7) * 32 + ((((lane >> 3) & 1) ^ ((lane >> 2) & 1)) << 4);
    const uint32_t t32 = w4 * 256 + qc * 64 + (((g >> 2) ^ (qc >> 1)) << 4) + (g & 3) * 4;
    const uint32_t t128 = qc * 256 + (((2 * w4 + (g >> 2)) ^ (2 * qc)) << 4) + (g & 3) * 4;
    const uint32_t a32 = (w4 * 16 + (lane & 15)) * 32 + (((lane >> 4) ^ ((lane >> 2) & 1)) << 4);
    const uint32_t ws = sb + C2_WS + wg * (C2_NS * 2048) + a32;
    uint32_t w[32][4];
    const int wcol = h * HD + (rank & 1) * 64 + w4 * 16 + 2 * g + 2 * qc * NQ;
    auto proj_mem = [&](float (&a)[4][4], int s) {
        uint32_t b[8];
#pragma unroll
        for (int i = 0; i < 16; i++) a[i >> 2][i & 3] = 0.f;
        const uint32_t par = (s & 1) ^ 1;
        if (s > 0) mbar_wait(bar_m, par);
#pragma unroll
        for (int i = 0; i < 8; i++) {
            ldsm_x4(b, sb + C2_MB + l32 + i * 1024);
            ldsm_x4(b + 4, sb + C2_MB + l32 + i * 1024 + 512);
            uint32_t nxt = 1;
            if (i < 7 && s > 0) nxt = mbar_test(bar_m + 8 * (i + 1), par);
            c2_mma_slot(a, w, i, b, ws);
            if (i < 7 && !nxt) mbar_wait(bar_m + 8 * (i + 1), par);
            if (i == 0) DBGW(1 + 16 * wg, 0);
            if (i == 6) DBGW(2 + 16 * wg, 0);
        }
#pragma unroll
        for (int i = 0; i < 4; i++) a[0][i] = (a[0][i] + a[1][i]) + (a[2][i] + a[3][i]);
    };
    auto store_x = [&](const float (&acc)[16], uint32_t base) {
#pragma unroll
        for (int j = 0; j < 4; j++) {
            sts32(base + t128 + j * 1024, pack_bf16(acc[4 * j], acc[4 * j + 2]));
            sts32(base + (t128 ^ 16) + 128 + j * 1024, pack_bf16(acc[4 * j + 1], acc[4 * j + 3]));
        }
    };
    const float scale = 0.08838834764831845f, l2e = 1.4426950408889634f;

    if (wg == 0) {
        c2_load_w(w, Wq, rank, wcol, ws);
        TS_END(6);
        TS_BEGIN(5);
#pragma unroll 1
        for (int s = 0; s < NSEG; s++) {
            {
                float acc[16];
                mbar_wait(bar_x + 8 * (s & 1), (s >> 1) & 1);
                c2_xstream(acc, w, dlo + ((C2_XB + (s & 1) * 32768) >> 4), rank, dlo + ((C2_WS + 0 * C2_NS * 2048) >> 4));
                if (s > 0) bar_sync<5, 256>();
                store_x(acc, sb + C2_QX);
            }
            DBGW(0, 0);
            if (s == NSEG - 1) {
                bar_sync<1, 384>();
                fence_async_smem();
                bar_arrive<6, 256>();
                bar_arrive<4, 384>();
                break;
            }
            {
                float a[4][4];
                proj_mem(a, s);
                sts32(sb + C2_QM + t32, pack_bf16(a[0][0], a[0][2]));
                sts32(sb + C2_QM + t32 + 32, pack_bf16(a[0][1], a[0][3]));
            }
            DBGW(3, 0);
            if (w4 < 3) {
                uint32_t ka[4][4], qb[8];
                float c[4] = {0.f, 0.f, 0.f, 0.f}, c2[4] = {0.f, 0.f, 0.f, 0.f};
                const int row = w4 * 16 + (lane & 15);
                bar_sync<1, 384>();
#pragma unroll
                for (int kk = 0; kk < 4; kk++) ldsm_x4(ka[kk], sb + C2_KX + row * 128 + (((2 * kk + (lane >> 4)) ^ (row & 7)) << 4));
                ldsm_x4(qb, sb + C2_QM + l32);
                ldsm_x4(qb + 4, sb + C2_QM + l32 + 512);
                mma_16816(c, ka[0][0], ka[0][1], ka[0][2], ka[0][3], qb[0], qb[1]);
                mma_16816(c2, ka[1][0], ka[1][1], ka[1][2], ka[1][3], qb[2], qb[3]);
                mma_16816(c, ka[2][0], ka[2][1], ka[2][2], ka[2][3], qb[4], qb[5]);
                mma_16816(c2, ka[3][0], ka[3][1], ka[3][2], ka[3][3], qb[6], qb[7]);
                const uint32_t u0 = __float_as_uint(c[0] + c2[0]), u1 = __float_as_uint(c[1] + c2[1]);
                const uint32_t u2 = __float_as_uint(c[2] + c2[2]), u3 = __float_as_uint(c[3] + c2[3]);
                if (w4 < 2) {
                    const uint32_t a = sb + C2_SC + w4 * 512 + lane * 16;
                    st_async_v4(mapa_u32(a + 1280, rank ^ 1), u0, u1, u2, u3, mapa_u32(bar_sc, rank ^ 1));
                    st_async_v4(mapa_u32(a, rank), u0, u1, u2, u3, mapa_u32(bar_sc, rank));
                } else {
                    const uint32_t a = sb + C2_SC + 1024 + lane * 8;
                    st_async_v2(mapa_u32(a + 1280, rank ^ 1), u0, u1, mapa_u32(bar_sc, rank ^ 1));
                    st_async_v2(mapa_u32(a, rank), u0, u1, mapa_u32(bar_sc, rank));
                }
                bar_arrive<2, 224>();
                DBGW(4, 2);
            } else {
                bar_arrive<1, 384>();
                mbar_wait(bar_sc, s & 1);
                DBG(5);
                float v[10];
                {
                    float4 x0, x1, y0, y1; float2 x2, y2;
                    const uint32_t a = sb + C2_SC + lane * 16;
                    asm volatile("ld.shared.v4.f32 {%0, %1, %2, %3}, [%4];" : "=f"(x0.x), "=f"(x0.y), "=f"(x0.z), "=f"(x0.w) : "r"(a) : "memory");
                    asm volatile("ld.shared.v4.f32 {%0, %1, %2, %3}, [%4];" : "=f"(y0.x), "=f"(y0.y), "=f"(y0.z), "=f"(y0.w) : "r"(a + 1280) : "memory");
                    asm volatile("ld.shared.v4.f32 {%0, %1, %2, %3}, [%4];" : "=f"(x1.x), "=f"(x1.y), "=f"(x1.z), "=f"(x1.w) : "r"(a + 512) : "memory");
                    asm volatile("ld.shared.v4.f32 {%0, %1, %2, %3}, [%4];" : "=f"(y1.x), "=f"(y1.y), "=f"(y1.z), "=f"(y1.w) : "r"(a + 1792) : "memory");
                    asm volatile("ld.shared.v2.f32 {%0, %1}, [%2];" : "=f"(x2.x), "=f"(x2.y) : "r"(sb + C2_SC + 1024 + lane * 8) : "memory");
                    asm volatile("ld.shared.v2.f32 {%0, %1}, [%2];" : "=f"(y2.x), "=f"(y2.y) : "r"(sb + C2_SC + 2304 + lane * 8) : "memory");
                    v[0] = x0.x + y0.x; v[1] = x0.y + y0.y; v[2] = x0.z + y0.z; v[3] = x0.w + y0.w;
                    v[4] = x1.x + y1.x; v[5] = x1.y + y1.y; v[6] = x1.z + y1.z; v[7] = x1.w + y1.w;
                    v[8] = x2.x + y2.x; v[9] = x2.y + y2.y;
                }
                float m0 = fmaxf(fmaxf(fmaxf(v[0], v[2]), fmaxf(v[4], v[6])), v[8]);
                float m1 = fmaxf(fmaxf(fmaxf(v[1], v[3]), fmaxf(v[5], v[7])), v[9]);
#pragma unroll
                for (int o = 4; o < 32; o <<= 1) {
                    m0 = fmaxf(m0, __shfl_xor_sync(0xffffffff, m0, o));
                    m1 = fmaxf(m1, __shfl_xor_sync(0xffffffff, m1, o));
                }
                const float sl = scale * l2e;
                m0 *= sl; m1 *= sl;
#pragma unroll
                for (int j = 0; j < 5; j++)
                    sts32(sb + C2_PB + j * 128 + lane * 4, pack_bf16(ex2f(fmaf(v[2 * j], sl, -m0)), ex2f(fmaf(v[2 * j + 1], sl, -m1))));
                bar_arrive<3, 160>();
                DBG(6);
            }
            fence_async_smem();
            bar_arrive<6, 256>();
            {
                float acc[4] = {0.f, 0.f, 0.f, 0.f};
#pragma unroll
                for (int i = 0; i < 8; i++) {
                    mbar_wait(bar_o + 8 * i, s & 1);
                    if (i == 0) DBGW(7, 0);
                    if (i == 1) DBGW(8, 0);
                    if (i == 7) DBGW(9, 0);
                    wgmma_fence();
#pragma unroll
                    for (int kk = 0; kk < 4; kk++)
                        wgmma_ss_n8(acc, dlo + ((C2_WO + i * 8192 + kk * 2048) >> 4), dlo + ((C2_OB + i * 1024 + kk * 256) >> 4));
                }
                wgmma_commit();
                wgmma_wait<0>();
                const uint32_t tag = ((s >> 1) & 1) ^ 1;
                const uint32_t u0 = (pack_bf16(acc[0], acc[2]) & ~1u) | tag, u1 = pack_bf16(acc[1], acc[3]);
                uint2* dst = g_xbuf + (((s & 1) * 8 + rank) * 8 + C) * 128 + tid;
                asm volatile("{\n.reg .b64 v;\nmov.b64 v, {%1, %2};\nst.relaxed.gpu.global.b64 [%0], v;\n}" :: "l"(dst), "r"(u0), "r"(u1) : "memory");
                bar_arrive<4, 384>();
                DBGW(10, 0);
            }
        }
    } else if (wg == 1) {
        c2_load_w(w, Wk, rank, wcol, ws);
#pragma unroll 1
        for (int s = 0; s <= NSEG; s++) {
            if (s < NSEG) {
                {
                    float acc[16];
                    mbar_wait(bar_x + 8 * (s & 1), (s >> 1) & 1);
                    c2_xstream(acc, w, dlo + ((C2_XB + (s & 1) * 32768) >> 4), rank, dlo + ((C2_WS + 1 * C2_NS * 2048) >> 4));
                    store_x(acc, sb + C2_KX);
                }
                DBGW(16, 0);
                float a[4][4];
                proj_mem(a, s);
                sts32(sb + C2_KX + 4096 + t128, pack_bf16(a[0][0], a[0][2]));
                sts32(sb + C2_KX + 4096 + (t128 ^ 16) + 128, pack_bf16(a[0][1], a[0][3]));
                bar_arrive<1, 384>();
                DBGW(19, 0);
                if (w4 == 0) {
                    if (s < NSEG - 1) {
                        if (lane < 16 && (lane & 7)) mbar_expect_tx(bar_m + 8 * lane, 1024);
                        if (lane == 0) mbar_expect_tx(bar_sc, 2560);
                        if (lane == 8) {
                            mbar_expect_tx(bar_x + 8 * ((s + 1) & 1), 32768);
                            tma_load_2d_mc(sb + C2_XB + ((s + 1) & 1) * 32768 + rank * 4096, &mapX, bar_x + 8 * ((s + 1) & 1), rank * 64, (s + 1) * SEGL, (uint16_t)0xff);
                            if (s + 2 < NSEG)
                                asm volatile("cp.async.bulk.prefetch.tensor.2d.L2.global [%0, {%1, %2}];" :: "l"((uint64_t)&mapX), "r"(rank * 64), "r"((s + 2) * SEGL) : "memory");
                        }
                    }
                    if (lane == 16) mbar_expect_tx(bar_sx + 8 * (s & 1), 5120);
                    __syncwarp();
                }
            }
            if (s > 0) {
                mbar_wait(bar_sx + 8 * ((s - 1) & 1), ((s - 1) >> 1) & 1);
                const uint32_t a = sb + C2_SX + ((s - 1) & 1) * 10240 + w4 * 1280 + lane * 8;
                float v[10];
                const int lim = 8 * w4 + g - 2 * qc;
#pragma unroll
                for (int j = 0; j < 5; j++) {
                    float2 x, y;
                    asm volatile("ld.shared.v2.f32 {%0, %1}, [%2];" : "=f"(x.x), "=f"(x.y) : "r"(a + j * 256) : "memory");
                    asm volatile("ld.shared.v2.f32 {%0, %1}, [%2];" : "=f"(y.x), "=f"(y.y) : "r"(a + 5120 + j * 256) : "memory");
                    v[2 * j] = (j < 4 && 8 * j > lim) ? -INFINITY : x.x + y.x;
                    v[2 * j + 1] = (j < 4 && 8 * j + 1 > lim) ? -INFINITY : x.y + y.y;
                }
                float mx = fmaxf(fmaxf(fmaxf(v[0], v[1]), fmaxf(v[2], v[3])), fmaxf(fmaxf(v[4], v[5]), fmaxf(v[6], v[7])));
                mx = fmaxf(mx, fmaxf(v[8], v[9]));
                mx = fmaxf(mx, __shfl_xor_sync(0xffffffff, mx, 1));
                mx = fmaxf(mx, __shfl_xor_sync(0xffffffff, mx, 2));
                const float sl = scale * l2e;
                mx *= sl;
#pragma unroll
                for (int j = 0; j < 10; j++) v[j] = ex2f(fmaf(v[j], sl, -mx));
                float sm = ((v[0] + v[1]) + (v[2] + v[3])) + ((v[4] + v[5]) + (v[6] + v[7])) + (v[8] + v[9]);
                sm += __shfl_xor_sync(0xffffffff, sm, 1);
                sm += __shfl_xor_sync(0xffffffff, sm, 2);
                float inv;
                asm("rcp.approx.ftz.f32 %0, %1;" : "=f"(inv) : "f"(sm));
                const uint32_t pa = sb + C2_PX + w4 * 256 + g * 32 + ((g >> 2) << 4) + qc * 4;
#pragma unroll
                for (int j = 0; j < 5; j++) sts32((pa ^ ((j & 1) << 4)) + (j >> 1) * 1024, pack_bf16(v[2 * j] * inv, v[2 * j + 1] * inv));
            }
            fence_async_smem();
            if (s < NSEG) bar_sync<6, 256>(); else bar_sync<7, 128>();
            DBGW(20, 0);
            if (s < NSEG - 1) mbar_wait(bar_o, s & 1);
            if (s < NSEG) {
                float sx[20];
#pragma unroll
                for (int i = 0; i < 20; i++) sx[i] = 0.f;
                wgmma_fence();
#pragma unroll
                for (int kk = 0; kk < 4; kk++) wgmma_ss_n40(sx, dlo + (C2_QX >> 4) + kk * 2, dlo + (C2_KX >> 4) + kk * 2);
                wgmma_commit();
                wgmma_wait<0>();
                if (s < NSEG - 1) bar_arrive<5, 256>();
                if (w4 < 2) {
                    const uint32_t a = sb + C2_SX + (s & 1) * 10240 + w4 * 2560 + lane * 8;
#pragma unroll
                    for (int j = 0; j < 5; j++) {
                        asm volatile("st.shared.v2.f32 [%0], {%1, %2};" :: "r"(a + j * 256), "f"(sx[4 * j]), "f"(sx[4 * j + 1]) : "memory");
                        asm volatile("st.shared.v2.f32 [%0], {%1, %2};" :: "r"(a + 1280 + j * 256), "f"(sx[4 * j + 2]), "f"(sx[4 * j + 3]) : "memory");
                    }
                }
            }
            DBGW(21, 0);
            if (s > 0) {
                float cx[16];
#pragma unroll
                for (int i = 0; i < 16; i++) cx[i] = 0.f;
                wgmma_fence();
#pragma unroll
                for (int kk = 0; kk < 3; kk++)
                    wgmma_ss_n32<false>(cx, dlo + ((C2_VT + ((s - 1) & 1) * 6144 + kk * 2048) >> 4), dlo + ((C2_PX + kk * 1024) >> 4));
                wgmma_commit();
                wgmma_wait<0>();
                uint32_t* dst = reinterpret_cast<uint32_t*>(g_ctxB + ((size_t)h * SEQ + (s - 1) * SEGL + 2 * qc) * HD + (rank & 1) * 64 + w4 * 16 + 2 * g);
#pragma unroll
                for (int j = 0; j < 4; j++) {
                    dst[j * 8 * (HD / 2)] = pack_bf16(cx[4 * j], cx[4 * j + 2]);
                    dst[(j * 8 + 1) * (HD / 2)] = pack_bf16(cx[4 * j + 1], cx[4 * j + 3]);
                }
            }
            DBGW(22, 0);
            if (s < NSEG) {
                fence_async_smem();
                bar_sync<4, 384>();
            }
        }
        bar_sync<7, 128>();
        if (tid == 128) signal_ctr(CT_CB);
    } else {
        c2_load_w(w, Wv, rank, wcol, ws);
#pragma unroll 1
        for (int s = 0; s < NSEG; s++) {
            uint32_t va[5][2];
            {
                float a[4][4];
                uint32_t b[2][8];
#pragma unroll
                for (int i = 0; i < 16; i++) a[i >> 2][i & 3] = 0.f;
                if (s > 0) mbar_wait(bar_m, (s & 1) ^ 1);
                ldsm_x4(b[0], sb + C2_MB + l32);
                ldsm_x4(b[0] + 4, sb + C2_MB + l32 + 512);
                c2_mma_slot(a, w, 0, b[0], ws);
                bar_sync<1, 384>();
                DBGW(24, 0);
#pragma unroll
                for (int i = 1; i < 8; i++) {
                    ldsm_x4(b[i & 1], sb + C2_MB + l32 + i * 1024);
                    ldsm_x4(b[i & 1] + 4, sb + C2_MB + l32 + i * 1024 + 512);
                    if (i > 1) c2_mma_slot(a, w, i - 1, b[(i - 1) & 1], ws);
                }
                c2_mma_slot(a, w, 7, b[1], ws);
                va[4][0] = pack_bf16((a[0][0] + a[1][0]) + (a[2][0] + a[3][0]), (a[0][1] + a[1][1]) + (a[2][1] + a[3][1]));
                va[4][1] = pack_bf16((a[0][2] + a[1][2]) + (a[2][2] + a[3][2]), (a[0][3] + a[1][3]) + (a[2][3] + a[3][3]));
            }
            asm volatile("stmatrix.sync.aligned.m8n8.x2.shared.b16 [%0], {%1, %2};" :: "r"(sb + C2_VT + (s & 1) * 6144 + a32 + 4096), "r"(va[4][0]), "r"(va[4][1]) : "memory");
            DBGW(25, 0);
            if (s < NSEG - 1) bar_sync<2, 224>();
            {
                float acc[16];
                c2_xstream(acc, w, dlo + ((C2_XB + (s & 1) * 32768) >> 4), rank, dlo + ((C2_WS + 2 * C2_NS * 2048) >> 4));
#pragma unroll
                for (int j = 0; j < 4; j++) { va[j][0] = pack_bf16(acc[4 * j], acc[4 * j + 1]); va[j][1] = pack_bf16(acc[4 * j + 2], acc[4 * j + 3]); }
            }
            DBGW(26, 0);
            if (s < NSEG - 1) {
                uint32_t p[5];
                bar_sync<3, 160>();
                DBGW(27, 0);
                ldmatrix_x4_trans(p[0], p[1], p[2], p[3], sb + C2_PB + lane * 16);
                asm volatile("ldmatrix.sync.aligned.m8n8.x1.trans.shared.b16 {%0}, [%1];" : "=r"(p[4]) : "r"(sb + C2_PB + 512 + (lane & 7) * 16) : "memory");
                float oa[4] = {0.f, 0.f, 0.f, 0.f}, ob[4] = {0.f, 0.f, 0.f, 0.f}, sa[4] = {0.f, 0.f, 0.f, 0.f}, sc[4] = {0.f, 0.f, 0.f, 0.f};
                const uint32_t one = 0x3f803f80u;
                mma_16816(sa, one, one, one, one, p[0], p[1]);
                mma_16816(oa, va[0][0], va[0][1], va[1][0], va[1][1], p[0], p[1]);
                mma_16816(sc, one, one, one, one, p[2], p[3]);
                mma_16816(ob, va[2][0], va[2][1], va[3][0], va[3][1], p[2], p[3]);
                mma_16816(sa, one, one, one, one, p[4], 0u);
                mma_16816(oa, va[4][0], va[4][1], 0u, 0u, p[4], 0u);
                float i0, i1;
                asm("rcp.approx.ftz.f32 %0, %1;" : "=f"(i0) : "f"(sa[0] + sc[0]));
                asm("rcp.approx.ftz.f32 %0, %1;" : "=f"(i1) : "f"(sa[1] + sc[1]));
                sts32(sb + C2_OB + t32, pack_bf16((oa[0] + ob[0]) * i0, (oa[2] + ob[2]) * i0));
                sts32(sb + C2_OB + t32 + 32, pack_bf16((oa[1] + ob[1]) * i1, (oa[3] + ob[3]) * i1));
                fence_async_smem();
                __syncwarp();
                if (lane == 0) mbar_arrive(bar_o);
                else if (lane < 8) {
                    const uint32_t d = (rank + lane) & 7;
                    bulk_s2s(mapa_u32(sb + C2_OB + lane * 1024 + w4 * 256, d), sb + C2_OB + w4 * 256, 256, mapa_u32(bar_o + 8 * lane, d));
                }
                __syncwarp();
                DBGW(28, 0);
            }
            {
                const uint32_t a = sb + C2_VT + (s & 1) * 6144 + a32;
                stmatrix_x4(a, va[0][0], va[0][1], va[1][0], va[1][1]);
                stmatrix_x4(a + 2048, va[2][0], va[2][1], va[3][0], va[3][1]);
            }
            fence_async_smem();
            bar_sync<4, 384>();
            DBGW(29, 0);
            if (tid == 256) {
                const uint32_t a = sb + C2_SX + (s & 1) * 10240;
                bulk_s2s(mapa_u32(a + 5120, rank ^ 1), a, 5120, mapa_u32(bar_sx + 8 * (s & 1), rank ^ 1));
            }
            if (s == NSEG - 1) break;
            pace(CH_POLL_DELAY);
            {
                const uint2* src = g_xbuf + ((s & 1) * 8 + rank) * 1024 + (tid - 256);
                const uint32_t tag = ((s >> 1) & 1) ^ 1;
                uint32_t p[8][2];
                for (int it = 0; it < (1 << 20); it++) {
#pragma unroll
                    for (int k = 0; k < 8; k++)
                        asm volatile("{\n.reg .b64 v;\nld.relaxed.gpu.global.b64 v, [%2];\nmov.b64 {%0, %1}, v;\n}" : "=r"(p[k][0]), "=r"(p[k][1]) : "l"(src + k * 128) : "memory");
                    uint32_t bad[4];
#pragma unroll
                    for (int k = 0; k < 4; k++) asm("lop3.b32 %0, %1, %2, %3, 0x7e;" : "=r"(bad[k]) : "r"(p[2 * k][0]), "r"(p[2 * k + 1][0]), "r"(tag));
                    asm("lop3.b32 %0, %0, %1, %2, 0xfe;" : "+r"(bad[0]) : "r"(bad[1]), "r"(bad[2]));
                    asm("lop3.b32 %0, %0, %1, 1, 0xa8;" : "+r"(bad[0]) : "r"(bad[3]));
                    if (__all_sync(0xffffffff, bad[0] == 0u)) break;
                }
                DBGW(30, 0);
                float r[4];
#pragma unroll
                for (int e = 0; e < 2; e++) {
                    float lo[8], hi[8];
#pragma unroll
                    for (int k = 0; k < 8; k++) { lo[k] = __uint_as_float(p[k][e] << 16); hi[k] = __uint_as_float(p[k][e] & 0xffff0000u); }
                    r[2 * e] = ((lo[0] + lo[1]) + (lo[2] + lo[3])) + ((lo[4] + lo[5]) + (lo[6] + lo[7]));
                    r[2 * e + 1] = ((hi[0] + hi[1]) + (hi[2] + hi[3])) + ((hi[4] + hi[5]) + (hi[6] + hi[7]));
                }
                const uint32_t m0 = pack_bf16(r[0], r[1]), m1 = pack_bf16(r[2], r[3]);
#pragma unroll
                for (int i = 1; i < 8; i++) {
                    const uint32_t d = (rank + i) & 7;
                    const uint32_t ra = mapa_u32(sb + C2_MB + i * 1024 + t32, d), rb = mapa_u32(bar_m + 8 * i, d);
                    st_async_b32(ra, m0, rb);
                    st_async_b32(ra + 32, m1, rb);
                }
                sts32(sb + C2_MB + t32, m0);
                sts32(sb + C2_MB + t32 + 32, m1);
                __syncwarp();
                if (lane == 0) mbar_arrive(bar_m);
                DBGW(31, 0);
            }
        }
        g_xbuf[((8 + rank) * 8 + C) * 128 + (tid - 256)] = make_uint2(0u, 0u);
    }
    __syncthreads();
    cluster_sync_all();
    TS_END(2);
}

struct Proj2Params {
    CUtensorMap mapA[2];
    CUtensorMap mapW[3];
    bf16* out[3];
};
#define P2T(i)
#define P2_NOMMA 0
#define P2_NOLOAD 0
constexpr int P2_STAGES = 6;
constexpr int P2_SMEM = 131072 + P2_STAGES * 16384 + 1024 + 1024;
constexpr int P2_ITEMS = 168 + 48;
__device__ __forceinline__ int p2_reps(int t) { return t >= 168 ? 1 : 2; }
__device__ __forceinline__ void p2_tile(int t, int w, int& z, int& mp, int& head) {
    if (t >= 168) { w += ((t - 168) & 1) * 2; t = 168 + ((t - 168) >> 1); }
    const int hq = t / 24, v = t % 24;
    mp = v & 7;
    if (v < 16) { head = hq * 4 + (v >> 3) * 2 + (w >> 1); z = 1 + (w & 1); }
    else { head = hq * 4 + w; z = 0; }
}
__device__ __forceinline__ void mbar_arrive_remote(uint32_t bar_cluster_addr) {
    asm volatile("mbarrier.arrive.release.cluster.shared::cluster.b64 _, [%0];" :: "r"(bar_cluster_addr) : "memory");
}
__device__ __forceinline__ void mbar_arrive_cl(uint32_t bar_cluster_addr) {
    asm volatile("mbarrier.arrive.shared::cluster.b64 _, [%0];" :: "r"(bar_cluster_addr) : "memory");
}
__device__ __forceinline__ void mbar_wait_acq_cluster(uint32_t bar, uint32_t parity) {
    asm volatile(
        "{\n"
        ".reg .pred p, q;\n"
        ".reg .u32 c;\n"
        "mov.u32 c, 0;\n"
        "WAIT_LOOP_C:\n"
        "mbarrier.try_wait.parity.acquire.cluster.shared::cta.b64 p, [%0], %1;\n"
        "@p bra WAIT_DONE_C;\n"
        "add.u32 c, c, 1;\n"
        "setp.lt.u32 q, c, 4000000;\n"
        "@q bra WAIT_LOOP_C;\n"
        "WAIT_DONE_C:\n"
        "}\n" :: "r"(bar), "r"(parity) : "memory");
}
__device__ __forceinline__ uint4 quad_transpose(uint32_t p0, uint32_t p1, uint32_t p2, uint32_t p3, int lane) {
    const bool o1 = lane & 1, o2 = lane & 2;
    uint32_t s0 = o1 ? p0 : p1, s1 = o1 ? p2 : p3;
    s0 = __shfl_xor_sync(0xffffffff, s0, 1); s1 = __shfl_xor_sync(0xffffffff, s1, 1);
    const uint32_t a_lo = o1 ? s0 : p0, a_hi = o1 ? p1 : s0, b_lo = o1 ? s1 : p2, b_hi = o1 ? p3 : s1;
    uint32_t t0 = o2 ? a_lo : b_lo, t1 = o2 ? a_hi : b_hi;
    t0 = __shfl_xor_sync(0xffffffff, t0, 2); t1 = __shfl_xor_sync(0xffffffff, t1, 2);
    return o2 ? make_uint4(t0, t1, b_lo, b_hi) : make_uint4(a_lo, a_hi, t0, t1);
}
#define P2_PACE 35
#define P2_PACE2 0
template <bool PERM, int PACE = 0>
__device__ __forceinline__ void store_frag_128(const float (&acc)[64], bf16* obase, int lane) {
#pragma unroll
    for (int rr = 0; rr < 2; rr++)
#pragma unroll
        for (int g = 0; g < 4; g++) {
            const float* a = &acc[g * 16 + rr * 2];
            const uint32_t p0 = pack_bf16(a[0], a[1]), p1 = pack_bf16(a[4], a[5]), p2 = pack_bf16(a[8], a[9]), p3 = pack_bf16(a[12], a[13]);
            *reinterpret_cast<uint4*>(obase + (size_t)(rr * 8) * HD + g * 32) = PERM ? make_uint4(p0, p1, p2, p3) : quad_transpose(p0, p1, p2, p3, lane);
            pace(PACE);
        }
}
__global__ void __cluster_dims__(2, 1, 1) __launch_bounds__(384, 1) proj2_kernel(const __grid_constant__ Proj2Params P) {
    extern __shared__ uint8_t smem_raw[];
    const uint32_t sbase = (smem_u32(smem_raw) + 1023) & ~1023u;
    const uint32_t sA = sbase, sB = sbase + 131072, sC = sB + P2_STAGES * 16384;
    const uint32_t bars = sC;
    const uint32_t a_full = bars, a_empty = bars + 64, b_full = bars + 128, b_empty = b_full + 8 * P2_STAGES;
    const uint32_t item_bar = b_empty + 8 * P2_STAGES, item_in = item_bar + 16, slot = item_in + 16;
    const uint32_t note_bar = slot + 16, note_free = note_bar + 64, note = note_free + 64;
    const int warp = threadIdx.x >> 5, lane = threadIdx.x & 31;
    const uint32_t rank = cluster_ctarank();
    TS_BEGIN(0);
    if (threadIdx.x == 0) {
        for (int i = 0; i < 8; i++) { mbar_init(a_full + 8 * i, 1); mbar_init(a_empty + 8 * i, 2); }
        for (int i = 0; i < P2_STAGES; i++) { mbar_init(b_full + 8 * i, 1); mbar_init(b_empty + 8 * i, 2); }
        mbar_init(item_bar, 1); mbar_init(item_bar + 8, 1); mbar_init(item_in, 2); mbar_init(item_in + 8, 2);
        for (int i = 0; i < 8; i++) { mbar_init(note_bar + 8 * i, 1); mbar_init(note_free + 8 * i, 1); }
        asm volatile("fence.mbarrier_init.release.cluster;" ::: "memory");
    }
    __syncthreads();
    cluster_sync_all();
    pdl_launch_dependents();
    if (warp == 9) {
        if (lane == 0) {
            for (int n = 0;; n++) {
                const int e = (n & 1) * 4 + ((n >> 1) & 3);
                mbar_wait(note_bar + 8 * e, (n >> 3) & 1);
                int m;
                asm volatile("ld.shared.s32 %0, [%1];" : "=r"(m) : "r"(note + e * 4) : "memory");
                mbar_arrive(note_free + 8 * e);
                if (m < 0) break;
                signal_ctr(m);
            }
        }
    } else if (warp == 10) {
        if (lane == 0) {
            auto publish = [&](int ic, int tq) {
                const int t = tq < P2_ITEMS ? tq : -1;
                asm volatile("st.shared.s32 [%0], %1;" :: "r"(slot + (ic & 3) * 4), "r"(t) : "memory");
                mbar_arrive(item_bar + 8 * (ic & 1));
                st_async_b32(mapa_u32(slot + (ic & 3) * 4, 1), (uint32_t)t, mapa_u32(item_bar + 8 * (ic & 1), 1));
            };
            const int npair = (int)(gridDim.x >> 1), pair = (int)(blockIdx.x >> 1);
            if (rank == 0) publish(0, pair);
            for (int ic = 0;; ic++) {
                if (rank == 1) mbar_expect_tx(item_bar + 8 * (ic & 1), 4);
                mbar_wait(item_bar + 8 * (ic & 1), (ic >> 1) & 1);
                int t;
                asm volatile("ld.shared.s32 %0, [%1];" : "=r"(t) : "r"(slot + (ic & 3) * 4) : "memory");
                if (t < 0) break;
                int z0, mp, h0;
                p2_tile(t, 0, z0, mp, h0);
                const int aidx = z0 >= 1 ? 1 : 0;
                const int m0 = (2 * mp + (int)rank) * 128;
                for (int k = 0; k < 8; k++) {
                    mbar_wait(a_empty + 8 * k, (ic & 1) ^ 1);
                    if (P2_NOLOAD) mbar_arrive(a_full + 8 * k); else {
                    mbar_expect_tx(a_full + 8 * k, 16384);
                    tma_load_2d(sA + k * 16384, &P.mapA[aidx], a_full + 8 * k, k * 64, m0); }
                }
                if (rank == 0) {
                    mbar_wait(item_in + 8 * (ic & 1), (ic >> 1) & 1);
                    publish(ic + 1, ic == 0 ? npair + pair : 2 * npair + (int)atomicAdd(&g_ctr[CT_PROJ], 1u));
                }
            }
        }
    } else if (warp == 8 || warp == 11) {
        if (lane == 0) {
            const int par2 = warp == 8 ? 0 : 1;
            int it = 0; uint32_t bph = 0;
            for (int ic = 0;; ic++) {
                mbar_wait(item_bar + 8 * (ic & 1), (ic >> 1) & 1);
                int t;
                asm volatile("ld.shared.s32 %0, [%1];" : "=r"(t) : "r"(slot + (ic & 3) * 4) : "memory");
                if (t < 0) break;
                const int nt = 2 * p2_reps(t);
                for (int w = 0; w < nt; w++) {
                    int z, mp, hd;
                    p2_tile(t, w, z, mp, hd);
                    for (int k = 0; k < 8; k++) {
                        const int s = it; const uint32_t phb = bph;
                        if (++it == P2_STAGES) { it = 0; bph ^= 1; }
                        if ((k & 1) != par2) continue;
                        mbar_wait(b_empty + 8 * s, phb ^ 1);
                        if (P2_NOLOAD) { mbar_arrive(b_full + 8 * s); continue; }
                        mbar_expect_tx(b_full + 8 * s, 16384);
                        tma_load_2d_mc(sB + s * 16384 + rank * 8192, &P.mapW[z], b_full + 8 * s, hd * 128 + (int)rank * 64, k * 64, (uint16_t)3);
                    }
                }
            }
        }
    } else {
        const int wg = warp >> 2;
        float acc[2][64];
        const uint32_t a_lo = desc_lo(sA, 16), b_lo0 = desc_lo(sB, 8192);
        const bool elected = (threadIdx.x & 127) == 0;
        int s = (wg * 8) % P2_STAGES;
        uint32_t ph = ((wg * 8) / P2_STAGES) & 1;
        int nnote = 0;
        if (wg == 1) asm volatile("bar.arrive 3, 256;" ::: "memory");
        for (int ic = 0;; ic++) {
            mbar_wait(item_bar + 8 * (ic & 1), (ic >> 1) & 1);
            int t;
            asm volatile("ld.shared.s32 %0, [%1];" : "=r"(t) : "r"(slot + (ic & 3) * 4) : "memory");
            P2T(7);
            if (wg == 0 && t < 0) {
                if (elected) {
                    const int e = nnote & 3;
                    mbar_wait(note_free + 8 * e, ((nnote >> 2) & 1) ^ 1);
                    asm volatile("st.shared.s32 [%0], %1;" :: "r"(note + e * 4), "r"(-1) : "memory");
                    mbar_arrive(note_bar + 8 * e);
                }
            }
            if (t < 0) break;
            const int reps = p2_reps(t);
#pragma unroll 1
            for (int rp = 0; rp < reps; rp++) {
            const bool first = rp == 0, last = rp == reps - 1;
            int z, mp, head;
            p2_tile(t, rp * 2 + wg, z, mp, head);
            asm volatile("bar.sync %0, 256;" :: "r"(3 + wg) : "memory");
            P2T(0);
            if (wg == 1 && last && elected) mbar_arrive_cl(mapa_u32(item_in + 8 * (ic & 1), 0));
            int sprev = 0;
#pragma unroll
            for (int k = 0; k < 8; k++) {
                if (k == 0) P2T(5);
                if (wg == 0 && first) mbar_wait(a_full + 8 * k, ic & 1);
                if (k == 0) P2T(6);
                mbar_wait(b_full + 8 * s, ph);
                if (k == 7) asm volatile("bar.arrive %0, 256;" :: "r"(4 - wg) : "memory");
                if (k == 0) P2T(1);
                if (k == 7) P2T(2);
                const uint32_t b_lo = b_lo0 + s * 1024;
                wgmma_fence();
#pragma unroll
                for (int kk = 0; kk < (P2_NOMMA ? 1 : 4); kk++) {
                    wgmma_ss_n128_lo<1>(acc[0], a_lo + k * 1024 + kk * 2, b_lo + kk * 128, (k | kk) != 0);
                    wgmma_ss_n128_lo<1>(acc[1], a_lo + k * 1024 + 512 + kk * 2, b_lo + kk * 128, (k | kk) != 0);
                }
                wgmma_commit();
                if (k > 0) {
                    wgmma_wait<1>();
                    if (elected) {
                        const uint32_t e = b_empty + 8 * sprev;
                        mbar_arrive_cl(mapa_u32(e, 0)); mbar_arrive_cl(mapa_u32(e, 1));
                        if (last) mbar_arrive(a_empty + 8 * (k - 1));
                    }
                }
                sprev = s;
                if (++s == P2_STAGES) { s = 0; ph ^= 1; }
            }
            wgmma_wait<0>();
            P2T(3);
            if (elected) {
                const uint32_t e = b_empty + 8 * sprev;
                mbar_arrive_cl(mapa_u32(e, 0)); mbar_arrive_cl(mapa_u32(e, 1));
                if (last) mbar_arrive(a_empty + 8 * 7);
            }
            s += 8 % P2_STAGES; ph ^= (8 / P2_STAGES) & 1;
            if (s >= P2_STAGES) { s -= P2_STAGES; ph ^= 1; }
            const int m0 = (2 * mp + (int)rank) * 128;
            bf16* obase = P.out[z] + ((size_t)head * SEQ + m0 + (warp & 3) * 16 + (lane >> 2)) * HD + (lane & 3) * 8;
            store_frag_128<true, P2_PACE>(acc[0], obase, lane); store_frag_128<true, P2_PACE>(acc[1], obase + (size_t)64 * HD, lane);
            P2T(4);
            {
                asm volatile("bar.sync %0, 128;" :: "r"(1 + wg) : "memory");
                if (elected) {
                    const int e = wg * 4 + (nnote & 3);
                    mbar_wait(note_free + 8 * e, ((nnote >> 2) & 1) ^ 1);
                    asm volatile("st.shared.s32 [%0], %1;" :: "r"(note + e * 4), "r"(CT_AP + (head >> 1)) : "memory");
                    mbar_arrive(note_bar + 8 * e);
                }
                nnote++;
            }
            }
        }
        TS_END(0);
    }
    __syncthreads();
    cluster_sync_all();
}

struct OutParams {
    CUtensorMap mapCtx[2];
    CUtensorMap mapWo[2];
    CUtensorMap mapPart;
};
__device__ float g_part[4 * SEQ * DM];

#define OT(i)
constexpr int O2_STAGES = 4;
constexpr int O2_SMEM = O2_STAGES * 49152 + 1024 + 256;

__global__ void __cluster_dims__(2, 1, 1) __launch_bounds__(352, 1)
out2_kernel(const __grid_constant__ OutParams P, const bf16* __restrict__ x, const bf16* __restrict__ gate_w, bf16* __restrict__ out) {
    extern __shared__ uint8_t smem_raw[];
    const uint32_t sbase = (smem_u32(smem_raw) + 1023) & ~1023u;
    const uint32_t bar_full = sbase + O2_STAGES * 49152, bar_empty = bar_full + 8 * O2_STAGES;
    __shared__ float s_gate[32];
    const int warp = threadIdx.x >> 5, lane = threadIdx.x & 31;
    const uint32_t rank = cluster_ctarank();
    const int cid = blockIdx.x >> 1;
    const int late = cid >> 5, mp = (cid >> 1) & 7, nh = cid & 1;
    const int b = late ? 1 - ((cid >> 4) & 1) : (cid >> 4) & 1, kq = b * 2 + late;
    const int h0 = late ? O2_HE : 0;
    const int KT = late ? 2 * (NH - O2_HE) : 2 * O2_HE;
    const int m0 = (2 * mp + (int)rank) * 128, n0 = nh * 256;
    TS_BEGIN(4);
    OT(0);
    if (threadIdx.x == 0) {
        for (int i = 0; i < O2_STAGES; i++) { mbar_init(bar_full + 8 * i, 1); mbar_init(bar_empty + 8 * i, 4); }
        asm volatile("fence.mbarrier_init.release.cluster;" ::: "memory");
    }
    __syncthreads();
    asm volatile("barrier.cluster.arrive.release.aligned;" ::: "memory");
    if (threadIdx.x == 256) wait_ctr(b == 0 ? CT_CA + (m0 >> 7) * 2 + late : CT_CB, (unsigned)(b == 0 ? KT : 64));
    __syncwarp();
    asm volatile("barrier.cluster.wait.acquire.aligned;" ::: "memory");
    if (warp >= 8) {
        if (lane == 0) {
            int s = 0; uint32_t ph = 0;
            for (int i = 0; i < KT; i++) {
                mbar_wait(bar_empty + 8 * s, ph ^ 1);
                const uint32_t sa = sbase + s * 49152;
                const int head = h0 + (i >> 1), dk = (i & 1) * 64;
                if (warp == 8) {
                    mbar_expect_tx(bar_full + 8 * s, 49152);
                    tma_load_2d(sa, &P.mapCtx[b], bar_full + 8 * s, dk, head * SEQ + m0);
                } else {
                    const int j = (int)rank * 2 + (warp - 9);
                    tma_load_2d_mc(sa + 16384 + j * 8192, &P.mapWo[b], bar_full + 8 * s, n0 + j * 64, head * HD + dk, (uint16_t)3);
                }
                if (++s == O2_STAGES) { s = 0; ph ^= 1; }
            }
        }
    } else {
        const int wg = warp >> 2;
        const bool elected = (threadIdx.x & 127) == 0;
        float acc[128];
        {
            const int r = m0 + kq * 32 + (threadIdx.x >> 3);
            float sum = 0.f;
#pragma unroll
            for (int c = 0; c < 8; c++) {
                const int col = c * 64 + (threadIdx.x & 7) * 8;
                const uint4 xv = __ldg(reinterpret_cast<const uint4*>(x + (size_t)r * DM + col));
                const uint4 gv = __ldg(reinterpret_cast<const uint4*>(gate_w + col));
                const bf16* xp = reinterpret_cast<const bf16*>(&xv);
                const bf16* gp = reinterpret_cast<const bf16*>(&gv);
#pragma unroll
                for (int e = 0; e < 8; e++)
                    sum += __bfloat162float(__float2bfloat16(__bfloat162float(xp[e]) * __bfloat162float(gp[e])));
            }
            sum += __shfl_xor_sync(0xffffffff, sum, 1);
            sum += __shfl_xor_sync(0xffffffff, sum, 2);
            sum += __shfl_xor_sync(0xffffffff, sum, 4);
            sum = __bfloat162float(__float2bfloat16(sum));
            if ((threadIdx.x & 7) == 0) s_gate[threadIdx.x >> 3] = __bfloat162float(__float2bfloat16(1.f / (1.f + __expf(-sum))));
        }
        int s = 0, sprev = 0; uint32_t ph = 0;
#pragma unroll 1
        for (int i = 0; i < KT; i++) {
            mbar_wait(bar_full + 8 * s, ph);
            if (i == 0) OT(1);
            if (i == 8) OT(2);
            const uint32_t sa = sbase + s * 49152 + wg * 8192, sb = sbase + s * 49152 + 16384;
            wgmma_fence();
#pragma unroll
            for (int kk = 0; kk < 4; kk++)
                wgmma_ss_n256_tb(acc, make_desc(sa + kk * 32, 16, 1024), make_desc(sb + kk * 2048, 8192, 1024), (i | kk) != 0);
            wgmma_commit();
            if (i > 0) {
                wgmma_wait<1>();
                if (elected) { const uint32_t e = bar_empty + 8 * sprev; mbar_arrive_cl(mapa_u32(e, 0)); mbar_arrive_cl(mapa_u32(e, 1)); }
            }
            sprev = s;
            if (++s == O2_STAGES) { s = 0; ph ^= 1; }
        }
        wgmma_wait<0>();
        OT(3);
        {
            const int r = wg * 64 + (warp & 3) * 16 + (lane >> 2);
            if ((warp >> 1) == kq) {
#pragma unroll
                for (int j = 0; j < 32; j++) {
                    const uint32_t a = sbase + (j >> 2) * 16384 + r * 128 + ((((j & 3) * 2 + ((lane & 3) >> 1)) ^ (r & 7)) << 4) + (lane & 1) * 8;
                    asm volatile("st.shared.v2.f32 [%0], {%1, %2};" :: "r"(a), "f"(acc[j * 4 + 0]), "f"(acc[j * 4 + 1]) : "memory");
                    asm volatile("st.shared.v2.f32 [%0], {%1, %2};" :: "r"(a + 1024), "f"(acc[j * 4 + 2]), "f"(acc[j * 4 + 3]) : "memory");
                }
            } else {
                float* pp = g_part + ((size_t)kq * SEQ + m0 + r) * DM + n0 + (lane & 3) * 2;
#pragma unroll
                for (int j = 0; j < 32; j++) {
                    *reinterpret_cast<float2*>(pp + j * 8) = make_float2(acc[j * 4 + 0], acc[j * 4 + 1]);
                    *reinterpret_cast<float2*>(pp + 8 * DM + j * 8) = make_float2(acc[j * 4 + 2], acc[j * 4 + 3]);
                }
            }
        }
        asm volatile("bar.sync 1, 256;" ::: "memory");
        OT(4);
        unsigned int* ctr = &g_ctr[CT_OP + (2 * mp + (int)rank) * 2 + nh];
        if (threadIdx.x == 0) {
            asm volatile("fence.proxy.async;" ::: "memory");
            __threadfence();
            atomicAdd(ctr, 1u);
            unsigned int v; int it = 0;
            do { asm volatile("ld.acquire.gpu.global.u32 %0, [%1];" : "=r"(v) : "l"(ctr) : "memory"); } while (v < 4u && ++it < (1 << 22));
        }
        asm volatile("bar.sync 1, 256;" ::: "memory");
        OT(5);
        {
            const int c8 = threadIdx.x & 31, r0 = threadIdx.x >> 5;
            float4 u[4][3][2];
#pragma unroll
            for (int i = 0; i < 4; i++)
#pragma unroll
                for (int q = 1; q < 4; q++) {
                    const float4* p4 = reinterpret_cast<const float4*>(g_part + ((size_t)((kq + q) & 3) * SEQ + m0 + kq * 32 + r0 + i * 8) * DM + n0 + c8 * 8);
                    asm volatile("ld.relaxed.gpu.global.v4.f32 {%0, %1, %2, %3}, [%4];"
                                 : "=f"(u[i][q - 1][0].x), "=f"(u[i][q - 1][0].y), "=f"(u[i][q - 1][0].z), "=f"(u[i][q - 1][0].w) : "l"(p4) : "memory");
                    asm volatile("ld.relaxed.gpu.global.v4.f32 {%0, %1, %2, %3}, [%4];"
                                 : "=f"(u[i][q - 1][1].x), "=f"(u[i][q - 1][1].y), "=f"(u[i][q - 1][1].z), "=f"(u[i][q - 1][1].w) : "l"(p4 + 1) : "memory");
                }
#pragma unroll
            for (int i = 0; i < 4; i++) {
                const int rl = kq * 32 + r0 + i * 8;
                const float ga = s_gate[r0 + i * 8], gb = 1.f - ga;
                float o8[8];
#pragma unroll
                for (int hf = 0; hf < 2; hf++) {
                    float4 own;
                    const uint32_t a = sbase + (c8 >> 2) * 16384 + rl * 128 + ((((c8 & 3) * 2 + hf) ^ (rl & 7)) << 4);
                    asm volatile("ld.shared.v4.f32 {%0, %1, %2, %3}, [%4];" : "=f"(own.x), "=f"(own.y), "=f"(own.z), "=f"(own.w) : "r"(a) : "memory");
                    const int qp = ((kq ^ 1) - kq) & 3;
                    const float4 pa = qp == 1 ? u[i][0][hf] : u[i][2][hf];
                    const float4 o1 = u[i][1][hf];
                    const float4 o2 = qp == 1 ? u[i][2][hf] : u[i][0][hf];
                    const float gm = b == 0 ? ga : gb, go = b == 0 ? gb : ga;
                    o8[hf * 4 + 0] = gm * (own.x + pa.x) + go * (o1.x + o2.x);
                    o8[hf * 4 + 1] = gm * (own.y + pa.y) + go * (o1.y + o2.y);
                    o8[hf * 4 + 2] = gm * (own.z + pa.z) + go * (o1.z + o2.z);
                    o8[hf * 4 + 3] = gm * (own.w + pa.w) + go * (o1.w + o2.w);
                }
                *reinterpret_cast<uint4*>(out + (size_t)(m0 + rl) * DM + n0 + c8 * 8) =
                    make_uint4(pack_bf16(o8[0], o8[1]), pack_bf16(o8[2], o8[3]), pack_bf16(o8[4], o8[5]), pack_bf16(o8[6], o8[7]));
            }
        }
        OT(6);
        if (threadIdx.x == 0) {
            const unsigned int tk = atomicAdd(&g_ctr[CT_FIN], 1u);
            asm volatile("st.shared.u32 [%0], %1;" :: "r"(bar_empty + 8 * O2_STAGES), "r"(tk) : "memory");
        }
        asm volatile("bar.sync 1, 256;" ::: "memory");
        unsigned int tk;
        asm volatile("ld.shared.u32 %0, [%1];" : "=r"(tk) : "r"(bar_empty + 8 * O2_STAGES) : "memory");
        if (tk == gridDim.x - 1 && threadIdx.x < CT_N) g_ctr[threadIdx.x] = 0u;
    }
    __syncthreads();
    cluster_sync_all();
    TS_END(4);
}

typedef CUresult (*PFN_encodeTiled)(CUtensorMap*, CUtensorMapDataType, cuuint32_t, void*, const cuuint64_t*,
                                    const cuuint64_t*, const cuuint32_t*, const cuuint32_t*, CUtensorMapInterleave,
                                    CUtensorMapSwizzle, CUtensorMapL2promotion, CUtensorMapFloatOOBfill);
static PFN_encodeTiled g_encode = nullptr;

static void make_map(CUtensorMap* m, const void* ptr, uint64_t rows, uint64_t cols, uint32_t box_rows, bool sw64 = false) {
    cuuint64_t dims[2] = {cols, rows};
    cuuint64_t strides[1] = {cols * 2};
    cuuint32_t box[2] = {sw64 ? 32u : 64u, box_rows};
    cuuint32_t es[2] = {1, 1};
    g_encode(m, CU_TENSOR_MAP_DATA_TYPE_BFLOAT16, 2, const_cast<void*>(ptr), dims, strides, box, es,
             CU_TENSOR_MAP_INTERLEAVE_NONE, sw64 ? CU_TENSOR_MAP_SWIZZLE_64B : CU_TENSOR_MAP_SWIZZLE_128B, CU_TENSOR_MAP_L2_PROMOTION_L2_256B,
             CU_TENSOR_MAP_FLOAT_OOB_FILL_NONE);
}

template <typename... KArgs, typename... Args>
static void launch_pdl(void (*kernel)(KArgs...), int grid, int block, size_t smem, cudaStream_t st, bool pdl, Args... args) {
    cudaLaunchConfig_t cfg = {};
    cfg.gridDim = dim3(grid); cfg.blockDim = dim3(block); cfg.dynamicSmemBytes = smem; cfg.stream = st;
    cudaLaunchAttribute at[1];
    at[0].id = cudaLaunchAttributeProgrammaticStreamSerialization;
    at[0].val.programmaticStreamSerializationAllowed = 1;
    cfg.attrs = at; cfg.numAttrs = pdl ? 1 : 0;
    cudaLaunchKernelEx(&cfg, kernel, KArgs(args)...);
}

extern "C" void kernel_launch(void* const* d_in, const int* in_sizes, int n_in, void* d_out, int out_size) {
    const bf16* x = (const bf16*)d_in[0];
    const bf16* ckv = (const bf16*)d_in[1];
    const bf16* wq = (const bf16*)d_in[2];
    const bf16* wuk = (const bf16*)d_in[3];
    const bf16* wuv = (const bf16*)d_in[4];
    const bf16* wo = (const bf16*)d_in[5];
    const bf16* mem0 = (const bf16*)d_in[7];
    const bf16* Wq = (const bf16*)d_in[8];
    const bf16* Wk = (const bf16*)d_in[9];
    const bf16* Wv = (const bf16*)d_in[10];
    const bf16* Wo = (const bf16*)d_in[11];
    const bf16* gate_w = (const bf16*)d_in[13];
    bf16* out = (bf16*)d_out;

    static Proj2Params P2;
    static CUtensorMap mapX;
    static AttnParams AP;
    static OutParams OP;
    static bool init = false;
    static const void* last_in[14];
    bool same = init;
    for (int i = 0; i < 14 && same; i++) same = last_in[i] == d_in[i];
    if (!init) {
        cudaDriverEntryPointQueryResult qr;
        cudaGetDriverEntryPoint("cuTensorMapEncodeTiled", (void**)&g_encode, cudaEnableDefault, &qr);
        cudaFuncSetAttribute(proj2_kernel, cudaFuncAttributeMaxDynamicSharedMemorySize, P2_SMEM);
        cudaFuncSetAttribute(attn_kernel, cudaFuncAttributeMaxDynamicSharedMemorySize, FA_SMEM);
        cudaFuncSetAttribute(chain_kernel, cudaFuncAttributeMaxDynamicSharedMemorySize, C2_SMEM);
        cudaFuncSetAttribute(out2_kernel, cudaFuncAttributeMaxDynamicSharedMemorySize, O2_SMEM);
        init = true;
    }
    if (!same) {
        for (int i = 0; i < 14; i++) last_in[i] = d_in[i];
        void *pQA, *pKA, *pVA, *pCA, *pCB;
        cudaGetSymbolAddress(&pQA, g_QA); cudaGetSymbolAddress(&pKA, g_KA); cudaGetSymbolAddress(&pVA, g_VA);
        cudaGetSymbolAddress(&pCA, g_ctxA); cudaGetSymbolAddress(&pCB, g_ctxB);
        make_map(&P2.mapA[0], x, SEQ, DM, 128);
        make_map(&P2.mapA[1], ckv, SEQ, DM, 128);
        const void* ws[3] = {wq, wuk, wuv};
        void* cs[3] = {pQA, pKA, pVA};
        for (int i = 0; i < 3; i++) { make_map(&P2.mapW[i], ws[i], DM, NQ, 64); P2.out[i] = (bf16*)cs[i]; }
        make_map(&mapX, x, SEQ, DM, SEGL);
        make_map(&AP.mapQ, pQA, NH * SEQ, HD, 128);
        make_map(&AP.mapK, pKA, NH * SEQ, HD, 128);
        make_map(&AP.mapV, pVA, NH * SEQ, HD, 128);
        make_map(&AP.mapO, pCA, NH * SEQ, HD, 64);
        make_map(&OP.mapCtx[0], pCA, NH * SEQ, HD, 128);
        make_map(&OP.mapCtx[1], pCB, NH * SEQ, HD, 128);
        make_map(&OP.mapWo[0], wo, NQ, DM, 64);
        make_map(&OP.mapWo[1], Wo, NQ, DM, 64);
        {
            void* pP; cudaGetSymbolAddress(&pP, g_part);
            cuuint64_t dims[2] = {DM, 4 * SEQ}; cuuint64_t strides[1] = {DM * 4}; cuuint32_t box[2] = {32, 32}; cuuint32_t es[2] = {1, 1};
            g_encode(&OP.mapPart, CU_TENSOR_MAP_DATA_TYPE_FLOAT32, 2, pP, dims, strides, box, es, CU_TENSOR_MAP_INTERLEAVE_NONE,
                     CU_TENSOR_MAP_SWIZZLE_128B, CU_TENSOR_MAP_L2_PROMOTION_NONE, CU_TENSOR_MAP_FLOAT_OOB_FILL_NONE);
        }
    }
    cudaStream_t s1 = cudaStreamPerThread;
    const bool pdl = true;
    launch_pdl(chain_kernel, 64, 384, C2_SMEM, s1, false, mapX, mem0, Wq, Wk, Wv, Wo);
    launch_pdl(proj2_kernel, 68, 384, P2_SMEM, s1, pdl, P2);
    launch_pdl(attn_kernel, FA_GRID, 384, FA_SMEM, s1, pdl, AP, 1000);
    launch_pdl(out2_kernel, 128, 352, O2_SMEM, s1, pdl, OP, x, gate_w, out);
}
```

```cpp
#include <cuda_runtime.h>
#include <cuda_bf16.h>
#include <cuda.h>
#include <stdint.h>

constexpr int SEQ = 2048;
constexpr int DM = 512;
constexpr int NH = 32;
constexpr int HD = 128;
constexpr int NQ = NH * HD;
constexpr int SEGL = 32;
constexpr int NMEM = 8;
constexpr int NSEG = SEQ / SEGL;

typedef __nv_bfloat16 bf16;

__device__ bf16 g_QA[SEQ * NQ];
__device__ bf16 g_KA[SEQ * NQ];
__device__ bf16 g_VA[SEQ * NQ];
__device__ bf16 g_ctxA[SEQ * NQ];
__device__ bf16 g_ctxB[SEQ * NQ];
constexpr int CT_PROJ = 0, CT_ATTN = 1, CT_FIN = 5;
constexpr int CT_AP = 64;
#define O2_HE 18
constexpr int CT_CA = 128;
constexpr int CT_CB = 160;
constexpr int CT_OP = 192;
constexpr int CT_N = 224;
__device__ unsigned int g_ctr[CT_N];
__device__ uint2 g_xbuf[2 * 8 * 8 * 128];

#define FA_GRID 84

#define TS_BEGIN(id)
#define TS_END(id)
__device__ __forceinline__ void pdl_launch_dependents() { asm volatile("griddepcontrol.launch_dependents;" ::: "memory"); }
__device__ __forceinline__ void wait_ctr(int idx, unsigned int n) {
    unsigned int v; int it = 0;
    do { asm volatile("ld.acquire.gpu.global.u32 %0, [%1];" : "=r"(v) : "l"(&g_ctr[idx]) : "memory"); } while (v < n && ++it < (1 << 22));
    asm volatile("fence.proxy.async;" ::: "memory");
}
__device__ __forceinline__ void signal_ctr(int idx) {
    asm volatile("fence.proxy.async;" ::: "memory");
    __threadfence();
    atomicAdd(&g_ctr[idx], 1u);
}
__device__ __forceinline__ uint32_t smem_u32(const void* p) {
    return (uint32_t)__cvta_generic_to_shared(p);
}
__device__ __forceinline__ void mbar_init(uint32_t bar, uint32_t count) {
    asm volatile("mbarrier.init.shared::cta.b64 [%0], %1;" :: "r"(bar), "r"(count));
}
__device__ __forceinline__ void mbar_expect_tx(uint32_t bar, uint32_t bytes) {
    asm volatile("mbarrier.arrive.expect_tx.shared::cta.b64 _, [%0], %1;" :: "r"(bar), "r"(bytes) : "memory");
}
__device__ __forceinline__ void mbar_arrive(uint32_t bar) {
    asm volatile("mbarrier.arrive.shared::cta.b64 _, [%0];" :: "r"(bar) : "memory");
}
__device__ __forceinline__ void mbar_wait(uint32_t bar, uint32_t parity) {
    asm volatile(
        "{\n"
        ".reg .pred p, q;\n"
        ".reg .u32 c;\n"
        "mov.u32 c, 0;\n"
        "WAIT_LOOP:\n"
        "mbarrier.try_wait.parity.shared::cta.b64 p, [%0], %1;\n"
        "@p bra WAIT_DONE;\n"
        "add.u32 c, c, 1;\n"
        "setp.lt.u32 q, c, 4000000;\n"
        "@q bra WAIT_LOOP;\n"
        "WAIT_DONE:\n"
        "}\n" :: "r"(bar), "r"(parity) : "memory");
}
__device__ __forceinline__ void tma_load_2d(uint32_t dst, const CUtensorMap* map, uint32_t bar, int c0, int c1) {
    asm volatile(
        "cp.async.bulk.tensor.2d.shared::cluster.global.mbarrier::complete_tx::bytes [%0], [%1, {%3, %4}], [%2];"
        :: "r"(dst), "l"((uint64_t)map), "r"(bar), "r"(c0), "r"(c1) : "memory");
}
__device__ __forceinline__ void wgmma_fence() { asm volatile("wgmma.fence.sync.aligned;" ::: "memory"); }
__device__ __forceinline__ void wgmma_commit() { asm volatile("wgmma.commit_group.sync.aligned;" ::: "memory"); }
template <int N> __device__ __forceinline__ void wgmma_wait() {
    asm volatile("wgmma.wait_group.sync.aligned %0;" :: "n"(N) : "memory");
}
__device__ __forceinline__ uint64_t make_desc(uint32_t addr, uint32_t lbo, uint32_t sbo) {
    uint64_t d = 0;
    d |= (uint64_t)((addr & 0x3FFFF) >> 4);
    d |= (uint64_t)((lbo >> 4) & 0x3FFF) << 16;
    d |= (uint64_t)((sbo >> 4) & 0x3FFF) << 32;
    d |= (uint64_t)1 << 62;
    return d;
}

#define ACC64(d) \
    "+f"(d[0]), "+f"(d[1]), "+f"(d[2]), "+f"(d[3]), "+f"(d[4]), "+f"(d[5]), "+f"(d[6]), "+f"(d[7]), \
    "+f"(d[8]), "+f"(d[9]), "+f"(d[10]), "+f"(d[11]), "+f"(d[12]), "+f"(d[13]), "+f"(d[14]), "+f"(d[15]), \
    "+f"(d[16]), "+f"(d[17]), "+f"(d[18]), "+f"(d[19]), "+f"(d[20]), "+f"(d[21]), "+f"(d[22]), "+f"(d[23]), \
    "+f"(d[24]), "+f"(d[25]), "+f"(d[26]), "+f"(d[27]), "+f"(d[28]), "+f"(d[29]), "+f"(d[30]), "+f"(d[31]), \
    "+f"(d[32]), "+f"(d[33]), "+f"(d[34]), "+f"(d[35]), "+f"(d[36]), "+f"(d[37]), "+f"(d[38]), "+f"(d[39]), \
    "+f"(d[40]), "+f"(d[41]), "+f"(d[42]), "+f"(d[43]), "+f"(d[44]), "+f"(d[45]), "+f"(d[46]), "+f"(d[47]), \
    "+f"(d[48]), "+f"(d[49]), "+f"(d[50]), "+f"(d[51]), "+f"(d[52]), "+f"(d[53]), "+f"(d[54]), "+f"(d[55]), \
    "+f"(d[56]), "+f"(d[57]), "+f"(d[58]), "+f"(d[59]), "+f"(d[60]), "+f"(d[61]), "+f"(d[62]), "+f"(d[63])
#define ACC64_STR \
    "{%0, %1, %2, %3, %4, %5, %6, %7, %8, %9, %10, %11, %12, %13, %14, %15, " \
    "%16, %17, %18, %19, %20, %21, %22, %23, %24, %25, %26, %27, %28, %29, %30, %31, " \
    "%32, %33, %34, %35, %36, %37, %38, %39, %40, %41, %42, %43, %44, %45, %46, %47, " \
    "%48, %49, %50, %51, %52, %53, %54, %55, %56, %57, %58, %59, %60, %61, %62, %63}"

template <int TB>
__device__ __forceinline__ void wgmma_ss_n128(float (&d)[64], uint64_t da, uint64_t db, int scale_d) {
    asm volatile(
        "{\n.reg .pred p;\nsetp.ne.b32 p, %66, 0;\n"
        "wgmma.mma_async.sync.aligned.m64n128k16.f32.bf16.bf16 " ACC64_STR ", %64, %65, p, 1, 1, 0, %67;\n}\n"
        : ACC64(d) : "l"(da), "l"(db), "r"(scale_d), "n"(TB));
}
__device__ __forceinline__ uint32_t desc_lo(uint32_t addr, uint32_t lbo) { return ((addr & 0x3FFFF) >> 4) | ((lbo >> 4) << 16); }
template <int TB>
__device__ __forceinline__ void wgmma_ss_n128_lo(float (&d)[64], uint32_t da_lo, uint32_t db_lo, int scale_d) {
    asm volatile(
        "{\n.reg .pred p;\n.reg .b64 da, db;\nsetp.ne.b32 p, %66, 0;\n"
        "mov.b64 da, {%64, 0x40000040};\nmov.b64 db, {%65, 0x40000040};\n"
        "wgmma.mma_async.sync.aligned.m64n128k16.f32.bf16.bf16 " ACC64_STR ", da, db, p, 1, 1, 0, %67;\n}\n"
        : ACC64(d) : "r"(da_lo), "r"(db_lo), "r"(scale_d), "n"(TB));
}
__device__ __forceinline__ void wgmma_rs_n128_tb(float (&d)[64], uint32_t a0, uint32_t a1, uint32_t a2, uint32_t a3,
                                                 uint64_t db, int scale_d) {
    asm volatile(
        "{\n.reg .pred p;\nsetp.ne.b32 p, %69, 0;\n"
        "wgmma.mma_async.sync.aligned.m64n128k16.f32.bf16.bf16 " ACC64_STR ", {%64, %65, %66, %67}, %68, p, 1, 1, 1;\n}\n"
        : ACC64(d) : "r"(a0), "r"(a1), "r"(a2), "r"(a3), "l"(db), "r"(scale_d));
}
__device__ __forceinline__ void wgmma_rs_n80(float (&d)[40], const uint32_t (&a)[4], uint32_t db_lo, int scale_d) {
    asm volatile(
        "{\n.reg .pred p;\n.reg .b64 db;\nsetp.ne.b32 p, %45, 0;\nmov.b64 db, {%44, 0x40000040};\n"
        "wgmma.mma_async.sync.aligned.m64n80k16.f32.bf16.bf16 "
        "{%0, %1, %2, %3, %4, %5, %6, %7, %8, %9, %10, %11, %12, %13, %14, %15, %16, %17, %18, %19, %20, %21, %22, %23, %24, %25, %26, %27, %28, %29, %30, %31, %32, %33, %34, %35, %36, %37, %38, %39}, "
        "{%40, %41, %42, %43}, db, p, 1, 1, 0;\n}\n"
        : "+f"(d[0]), "+f"(d[1]), "+f"(d[2]), "+f"(d[3]), "+f"(d[4]), "+f"(d[5]), "+f"(d[6]), "+f"(d[7]), "+f"(d[8]), "+f"(d[9]), "+f"(d[10]), "+f"(d[11]), "+f"(d[12]), "+f"(d[13]), "+f"(d[14]), "+f"(d[15]), "+f"(d[16]), "+f"(d[17]), "+f"(d[18]), "+f"(d[19]), "+f"(d[20]), "+f"(d[21]), "+f"(d[22]), "+f"(d[23]), "+f"(d[24]), "+f"(d[25]), "+f"(d[26]), "+f"(d[27]), "+f"(d[28]), "+f"(d[29]), "+f"(d[30]), "+f"(d[31]), "+f"(d[32]), "+f"(d[33]), "+f"(d[34]), "+f"(d[35]), "+f"(d[36]), "+f"(d[37]), "+f"(d[38]), "+f"(d[39])
        : "r"(a[0]), "r"(a[1]), "r"(a[2]), "r"(a[3]), "r"(db_lo), "r"(scale_d));
}
__device__ __forceinline__ void wgmma_ss_n256_tb(float (&d)[128], uint64_t da, uint64_t db, int scale_d) {
    asm volatile(
        "{\n.reg .pred p;\nsetp.ne.b32 p, %130, 0;\n"
        "wgmma.mma_async.sync.aligned.m64n256k16.f32.bf16.bf16 {%0, %1, %2, %3, %4, %5, %6, %7, %8, %9, %10, %11, %12, %13, %14, %15, %16, %17, %18, %19, %20, %21, %22, %23, %24, %25, %26, %27, %28, %29, %30, %31, %32, %33, %34, %35, %36, %37, %38, %39, %40, %41, %42, %43, %44, %45, %46, %47, %48, %49, %50, %51, %52, %53, %54, %55, %56, %57, %58, %59, %60, %61, %62, %63, %64, %65, %66, %67, %68, %69, %70, %71, %72, %73, %74, %75, %76, %77, %78, %79, %80, %81, %82, %83, %84, %85, %86, %87, %88, %89, %90, %91, %92, %93, %94, %95, %96, %97, %98, %99, %100, %101, %102, %103, %104, %105, %106, %107, %108, %109, %110, %111, %112, %113, %114, %115, %116, %117, %118, %119, %120, %121, %122, %123, %124, %125, %126, %127}, %128, %129, p, 1, 1, 0, 1;\n}\n"
        : "+f"(d[0]), "+f"(d[1]), "+f"(d[2]), "+f"(d[3]), "+f"(d[4]), "+f"(d[5]), "+f"(d[6]), "+f"(d[7]), "+f"(d[8]), "+f"(d[9]), "+f"(d[10]), "+f"(d[11]), "+f"(d[12]), "+f"(d[13]), "+f"(d[14]), "+f"(d[15]), "+f"(d[16]), "+f"(d[17]), "+f"(d[18]), "+f"(d[19]), "+f"(d[20]), "+f"(d[21]), "+f"(d[22]), "+f"(d[23]), "+f"(d[24]), "+f"(d[25]), "+f"(d[26]), "+f"(d[27]), "+f"(d[28]), "+f"(d[29]), "+f"(d[30]), "+f"(d[31]), "+f"(d[32]), "+f"(d[33]), "+f"(d[34]), "+f"(d[35]), "+f"(d[36]), "+f"(d[37]), "+f"(d[38]), "+f"(d[39]), "+f"(d[40]), "+f"(d[41]), "+f"(d[42]), "+f"(d[43]), "+f"(d[44]), "+f"(d[45]), "+f"(d[46]), "+f"(d[47]), "+f"(d[48]), "+f"(d[49]), "+f"(d[50]), "+f"(d[51]), "+f"(d[52]), "+f"(d[53]), "+f"(d[54]), "+f"(d[55]), "+f"(d[56]), "+f"(d[57]), "+f"(d[58]), "+f"(d[59]), "+f"(d[60]), "+f"(d[61]), "+f"(d[62]), "+f"(d[63]), "+f"(d[64]), "+f"(d[65]), "+f"(d[66]), "+f"(d[67]), "+f"(d[68]), "+f"(d[69]), "+f"(d[70]), "+f"(d[71]), "+f"(d[72]), "+f"(d[73]), "+f"(d[74]), "+f"(d[75]), "+f"(d[76]), "+f"(d[77]), "+f"(d[78]), "+f"(d[79]), "+f"(d[80]), "+f"(d[81]), "+f"(d[82]), "+f"(d[83]), "+f"(d[84]), "+f"(d[85]), "+f"(d[86]), "+f"(d[87]), "+f"(d[88]), "+f"(d[89]), "+f"(d[90]), "+f"(d[91]), "+f"(d[92]), "+f"(d[93]), "+f"(d[94]), "+f"(d[95]), "+f"(d[96]), "+f"(d[97]), "+f"(d[98]), "+f"(d[99]), "+f"(d[100]), "+f"(d[101]), "+f"(d[102]), "+f"(d[103]), "+f"(d[104]), "+f"(d[105]), "+f"(d[106]), "+f"(d[107]), "+f"(d[108]), "+f"(d[109]), "+f"(d[110]), "+f"(d[111]), "+f"(d[112]), "+f"(d[113]), "+f"(d[114]), "+f"(d[115]), "+f"(d[116]), "+f"(d[117]), "+f"(d[118]), "+f"(d[119]), "+f"(d[120]), "+f"(d[121]), "+f"(d[122]), "+f"(d[123]), "+f"(d[124]), "+f"(d[125]), "+f"(d[126]), "+f"(d[127])
        : "l"(da), "l"(db), "r"(scale_d));
}
__device__ __forceinline__ void stmatrix_x4(uint32_t addr, uint32_t r0, uint32_t r1, uint32_t r2, uint32_t r3) {
    asm volatile("stmatrix.sync.aligned.m8n8.x4.shared.b16 [%0], {%1, %2, %3, %4};" :: "r"(addr), "r"(r0), "r"(r1), "r"(r2), "r"(r3) : "memory");
}
__device__ __forceinline__ void tma_store_2d(const CUtensorMap* map, uint32_t src, int c0, int c1) {
    asm volatile("cp.async.bulk.tensor.2d.global.shared::cta.bulk_group [%0, {%2, %3}], [%1];"
                 :: "l"((uint64_t)map), "r"(src), "r"(c0), "r"(c1) : "memory");
}
__device__ __forceinline__ float ex2f(float x) { float y; asm("ex2.approx.ftz.f32 %0, %1;" : "=f"(y) : "f"(x)); return y; }
__device__ __forceinline__ uint32_t pack_bf16(float lo, float hi) {
    __nv_bfloat162 v = __floats2bfloat162_rn(lo, hi);
    return *reinterpret_cast<uint32_t*>(&v);
}
__device__ __forceinline__ void mma_16816(float (&c)[4], uint32_t a0, uint32_t a1, uint32_t a2, uint32_t a3,
                                          uint32_t b0, uint32_t b1) {
    asm volatile(
        "mma.sync.aligned.m16n8k16.row.col.f32.bf16.bf16.f32 {%0,%1,%2,%3}, {%4,%5,%6,%7}, {%8,%9}, {%0,%1,%2,%3};"
        : "+f"(c[0]), "+f"(c[1]), "+f"(c[2]), "+f"(c[3])
        : "r"(a0), "r"(a1), "r"(a2), "r"(a3), "r"(b0), "r"(b1));
}
__device__ __forceinline__ void ldmatrix_x4_trans(uint32_t& r0, uint32_t& r1, uint32_t& r2, uint32_t& r3, uint32_t addr) {
    asm volatile("ldmatrix.sync.aligned.m8n8.x4.trans.shared.b16 {%0,%1,%2,%3}, [%4];"
                 : "=r"(r0), "=r"(r1), "=r"(r2), "=r"(r3) : "r"(addr));
}

struct AttnParams {
    CUtensorMap mapQ, mapK, mapV;
    CUtensorMap mapO;
};
constexpr int FA_STAGES = 2;
constexpr int FA_SMEM = 32768 + FA_STAGES * 65536 + 32768 + 1024 + 256;
constexpr int FA_ITEMS = 16 * NH;
#define FA_RETIRE 100000
#define FA_LASTG 8
__device__ __forceinline__ int fa_qt(int t) {
    constexpr int T0 = (32 - FA_LASTG) * 16;
    return t < T0 ? 15 - ((t & 127) >> 3) : 15 - (t - T0) / FA_LASTG;
}
__device__ __forceinline__ int fa_head(int t) {
    constexpr int T0 = (32 - FA_LASTG) * 16;
    return t < T0 ? (t >> 7) * 8 + (t & 7) : (32 - FA_LASTG) + (t - T0) % FA_LASTG;
}

__global__ void __launch_bounds__(384, 1) attn_kernel(const __grid_constant__ AttnParams P, int retire_cta) {
    extern __shared__ uint8_t smem_raw[];
    uint32_t sbase = (smem_u32(smem_raw) + 1023) & ~1023u;
    const uint32_t sQ = sbase;
    const uint32_t sKV = sbase + 32768;
    const uint32_t sO = sKV + FA_STAGES * 65536;
    const uint32_t bars = sO + 32768;
    const uint32_t bar_q = bars, bar_qe = bars + 8, bar_kf = bars + 16, bar_vf = bar_kf + 8 * FA_STAGES, bar_e = bar_vf + 8 * FA_STAGES,
                   bar_ek = bar_e + 8 * FA_STAGES, slot = bar_ek + 8 * FA_STAGES, bar_of = slot + 16, bar_oe = bar_of + 16, oslot = bar_oe + 16;
    const int warp = threadIdx.x >> 5;
    TS_BEGIN(1);
    int tfirst = 0;
    if (threadIdx.x == 256) tfirst = (int)atomicAdd(&g_ctr[CT_ATTN], 1u);
    if (threadIdx.x == 0) {
        mbar_init(bar_q, 1); mbar_init(bar_qe, 8);
        for (int i = 0; i < FA_STAGES; i++) { mbar_init(bar_kf + 8 * i, 1); mbar_init(bar_vf + 8 * i, 1); mbar_init(bar_e + 8 * i, 8); mbar_init(bar_ek + 8 * i, 8); }
        for (int i = 0; i < 2; i++) { mbar_init(bar_of + 8 * i, 1); mbar_init(bar_oe + 8 * i, 1); }
        asm volatile("fence.mbarrier_init.release.cluster;" ::: "memory");
    }
    if (threadIdx.x == 256) asm volatile("st.shared.s32 [%0], %1;" :: "r"(slot + 8), "r"(tfirst) : "memory");
    __syncthreads();
    pdl_launch_dependents();
    if (warp >= 8) {
        asm volatile("setmaxnreg.dec.sync.aligned.u32 40;");
        if (threadIdx.x == 288 || threadIdx.x == 320) {
            const int wg = threadIdx.x == 288 ? 0 : 1;
            const uint32_t stg = sO + wg * 16384;
            for (int n = 0;; n++) {
                mbar_wait(bar_of + 8 * wg, n & 1);
                int t;
                asm volatile("ld.shared.s32 %0, [%1];" : "=r"(t) : "r"(oslot + wg * 4) : "memory");
                if (t < 0) break;
                const int qt = fa_qt(t), h = fa_head(t);
                tma_store_2d(&P.mapO, stg, 0, h * SEQ + qt * 128 + wg * 64);
                tma_store_2d(&P.mapO, stg + 8192, 64, h * SEQ + qt * 128 + wg * 64);
                asm volatile("cp.async.bulk.commit_group;" ::: "memory");
                asm volatile("cp.async.bulk.wait_group.read 0;" ::: "memory");
                mbar_arrive(bar_oe + 8 * wg);
                asm volatile("cp.async.bulk.wait_group 0;" ::: "memory");
                signal_ctr(CT_CA + qt * 2 + (h >= O2_HE));
            }
        }
        if (threadIdx.x == 256) {
            int it = 0, hp_ready = 0;
            for (int item = 0;; item++) {
                int t = tfirst;
                if (item > 0) {
                    bool quit = false;
                    if ((int)blockIdx.x >= retire_cta) {
                        unsigned int v;
                        asm volatile("ld.relaxed.gpu.global.u32 %0, [%1];" : "=r"(v) : "l"(&g_ctr[CT_ATTN]) : "memory");
                        quit = v >= FA_RETIRE;
                    }
                    t = quit ? FA_ITEMS : (int)atomicAdd(&g_ctr[CT_ATTN], 1u);
                }
                const bool valid = t < FA_ITEMS;
                const int qt = fa_qt(t), h = fa_head(t);
                if (valid && !((hp_ready >> (h >> 1)) & 1)) { wait_ctr(CT_AP + (h >> 1), 96u); hp_ready |= 1 << (h >> 1); }
                mbar_wait(bar_qe, (item & 1) ^ 1);
                asm volatile("st.shared.s32 [%0], %1;" :: "r"(slot + (item & 1) * 4), "r"(valid ? t : -1) : "memory");
                if (!valid) { mbar_arrive(bar_q); break; }
                mbar_expect_tx(bar_q, 32768);
                tma_load_2d(sQ, &P.mapQ, bar_q, 0, h * SEQ + qt * 128);
                tma_load_2d(sQ + 16384, &P.mapQ, bar_q, 64, h * SEQ + qt * 128);
                for (int j = 0; j <= qt; j++, it++) {
                    const int s = it % FA_STAGES;
                    mbar_wait(bar_ek + 8 * s, ((it / FA_STAGES) & 1) ^ 1);
                    const uint32_t sk = sKV + s * 65536, sv = sk + 32768;
                    mbar_expect_tx(bar_kf + 8 * s, 32768);
                    tma_load_2d(sk, &P.mapK, bar_kf + 8 * s, 0, h * SEQ + j * 128);
                    tma_load_2d(sk + 16384, &P.mapK, bar_kf + 8 * s, 64, h * SEQ + j * 128);
                    mbar_wait(bar_e + 8 * s, ((it / FA_STAGES) & 1) ^ 1);
                    mbar_expect_tx(bar_vf + 8 * s, 32768);
                    tma_load_2d(sv, &P.mapV, bar_vf + 8 * s, 0, h * SEQ + j * 128);
                    tma_load_2d(sv + 16384, &P.mapV, bar_vf + 8 * s, 64, h * SEQ + j * 128);
                }
            }
        }
    } else {
        asm volatile("setmaxnreg.inc.sync.aligned.u32 232;");
        const int wg = warp >> 2;
        const int lane = threadIdx.x & 31;
        float o[64];
        float mrow0, mrow1, lrow0, lrow1;
        const float sc = 0.08838834764831845f * 1.4426950408889634f;
        const int r0 = wg * 64 + (warp & 3) * 16 + (lane >> 2);
        float sacc[64];
        uint32_t pa[32];
        float a0 = 1.f, a1 = 1.f;
        auto issue_qk = [&](int it) {
            const int s = it % FA_STAGES;
            const uint32_t sk = sKV + s * 65536;
            mbar_wait(bar_kf + 8 * s, (it / FA_STAGES) & 1);
            wgmma_fence();
#pragma unroll
            for (int kk = 0; kk < 8; kk++) {
                uint64_t da = make_desc(sQ + (kk >> 2) * 16384 + wg * 8192 + (kk & 3) * 32, 16, 1024);
                uint64_t db = make_desc(sk + (kk >> 2) * 16384 + (kk & 3) * 32, 16, 1024);
                wgmma_ss_n128<0>(sacc, da, db, kk != 0);
            }
            wgmma_commit();
        };
        auto issue_pv = [&](int it) {
            const int s = it % FA_STAGES;
            const uint32_t sv = sKV + s * 65536 + 32768;
            mbar_wait(bar_vf + 8 * s, (it / FA_STAGES) & 1);
            wgmma_fence();
#pragma unroll
            for (int kk = 0; kk < 8; kk++) {
                uint64_t db = make_desc(sv + kk * 2048, 16384, 1024);
                wgmma_rs_n128_tb(o, pa[kk * 4 + 0], pa[kk * 4 + 1], pa[kk * 4 + 2], pa[kk * 4 + 3], db, 1);
            }
            wgmma_commit();
        };
        auto softmax_stats = [&](bool diag) {
            if (diag) {
#pragma unroll
                for (int i = 0; i < 64; i++) {
                    int col = (i >> 2) * 8 + (lane & 3) * 2 + (i & 1);
                    int row = r0 + ((i & 2) ? 8 : 0);
                    if (col > row) sacc[i] = -INFINITY;
                }
            }
            float mx0 = -INFINITY, mx1 = -INFINITY;
#pragma unroll
            for (int i = 0; i < 16; i++) {
                mx0 = fmaxf(mx0, fmaxf(sacc[i * 4 + 0], sacc[i * 4 + 1]));
                mx1 = fmaxf(mx1, fmaxf(sacc[i * 4 + 2], sacc[i * 4 + 3]));
            }
            mx0 = fmaxf(mx0, __shfl_xor_sync(0xffffffff, mx0, 1));
            mx0 = fmaxf(mx0, __shfl_xor_sync(0xffffffff, mx0, 2));
            mx1 = fmaxf(mx1, __shfl_xor_sync(0xffffffff, mx1, 1));
            mx1 = fmaxf(mx1, __shfl_xor_sync(0xffffffff, mx1, 2));
            const float mn0 = fmaxf(mrow0, mx0), mn1 = fmaxf(mrow1, mx1);
            a0 = ex2f((mrow0 - mn0) * sc); a1 = ex2f((mrow1 - mn1) * sc);
            mrow0 = mn0; mrow1 = mn1;
            const float ms0 = mn0 * sc, ms1 = mn1 * sc;
            float sum0 = 0.f, sum1 = 0.f;
#pragma unroll
            for (int i = 0; i < 16; i++) {
                sacc[i * 4 + 0] = ex2f(fmaf(sacc[i * 4 + 0], sc, -ms0));
                sacc[i * 4 + 1] = ex2f(fmaf(sacc[i * 4 + 1], sc, -ms0));
                sacc[i * 4 + 2] = ex2f(fmaf(sacc[i * 4 + 2], sc, -ms1));
                sacc[i * 4 + 3] = ex2f(fmaf(sacc[i * 4 + 3], sc, -ms1));
                sum0 += sacc[i * 4 + 0] + sacc[i * 4 + 1];
                sum1 += sacc[i * 4 + 2] + sacc[i * 4 + 3];
            }
            lrow0 = lrow0 * a0 + sum0;
            lrow1 = lrow1 * a1 + sum1;
        };
        auto pack_p = [&]() {
#pragma unroll
            for (int i = 0; i < 16; i++) {
                pa[i * 2 + 0] = pack_bf16(sacc[i * 4 + 0], sacc[i * 4 + 1]);
                pa[i * 2 + 1] = pack_bf16(sacc[i * 4 + 2], sacc[i * 4 + 3]);
            }
        };
        int it = 0;
        if (wg == 1) asm volatile("bar.arrive 1, 256;" ::: "memory");
        for (int item = 0;; item++) {
            mbar_wait(bar_q, item & 1);
            int t;
            asm volatile("ld.shared.s32 %0, [%1];" : "=r"(t) : "r"(slot + (item & 1) * 4) : "memory");
            if (t < 0) {
                if ((threadIdx.x & 127) == 0) {
                    mbar_wait(bar_oe + 8 * wg, (item & 1) ^ 1);
                    asm volatile("st.shared.s32 [%0], %1;" :: "r"(oslot + wg * 4), "r"(-1) : "memory");
                    mbar_arrive(bar_of + 8 * wg);
                }
                break;
            }
            const int qt = fa_qt(t);
            const int nkv = qt + 1;
#pragma unroll
            for (int i = 0; i < 64; i++) o[i] = 0.f;
            mrow0 = -INFINITY; mrow1 = -INFINITY; lrow0 = 0.f; lrow1 = 0.f;
            asm volatile("bar.sync %0, 256;" :: "r"(1 + wg) : "memory");
            issue_qk(it);
            asm volatile("bar.arrive %0, 256;" :: "r"(2 - wg) : "memory");
            wgmma_wait<0>();
            if (lane == 0) { mbar_arrive(bar_ek + 8 * (it % FA_STAGES)); if (nkv == 1) mbar_arrive(bar_qe); }
            softmax_stats(nkv == 1);
            pack_p();
#pragma unroll 1
            for (int j = 1; j < nkv; j++) {
                asm volatile("bar.sync %0, 256;" :: "r"(1 + wg) : "memory");
                issue_qk(it + j);
                issue_pv(it + j - 1);
                asm volatile("bar.arrive %0, 256;" :: "r"(2 - wg) : "memory");
                wgmma_wait<1>();
                if (lane == 0) { mbar_arrive(bar_ek + 8 * ((it + j) % FA_STAGES)); if (j == nkv - 1) mbar_arrive(bar_qe); }
                softmax_stats(j == nkv - 1);
                wgmma_wait<0>();
                if (lane == 0) mbar_arrive(bar_e + 8 * ((it + j - 1) % FA_STAGES));
#pragma unroll
                for (int i = 0; i < 16; i++) {
                    o[i * 4 + 0] *= a0; o[i * 4 + 1] *= a0; o[i * 4 + 2] *= a1; o[i * 4 + 3] *= a1;
                }
                pack_p();
            }
            issue_pv(it + nkv - 1);
            wgmma_wait<0>();
            if (lane == 0) mbar_arrive(bar_e + 8 * ((it + nkv - 1) % FA_STAGES));
            it += nkv;
            lrow0 += __shfl_xor_sync(0xffffffff, lrow0, 1);
            lrow0 += __shfl_xor_sync(0xffffffff, lrow0, 2);
            lrow1 += __shfl_xor_sync(0xffffffff, lrow1, 1);
            lrow1 += __shfl_xor_sync(0xffffffff, lrow1, 2);
            const float i0 = 1.f / lrow0, i1 = 1.f / lrow1;
            const uint32_t stg = sO + wg * 16384;
            mbar_wait(bar_oe + 8 * wg, (item & 1) ^ 1);
            {
                const int row = (warp & 3) * 16 + (lane >> 2);
#pragma unroll
                for (int i = 0; i < 4; i++) {
                    const int ch = i * 4 + (lane & 3);
                    const uint32_t a = stg + (ch >> 3) * 8192 + row * 128 + (((ch & 7) ^ (row & 7)) << 4);
                    const float* q = &o[i * 16];
                    asm volatile("st.shared.v4.b32 [%0], {%1, %2, %3, %4};" :: "r"(a), "r"(pack_bf16(q[0] * i0, q[1] * i0)), "r"(pack_bf16(q[4] * i0, q[5] * i0)),
                                 "r"(pack_bf16(q[8] * i0, q[9] * i0)), "r"(pack_bf16(q[12] * i0, q[13] * i0)) : "memory");
                    asm volatile("st.shared.v4.b32 [%0], {%1, %2, %3, %4};" :: "r"(a + 1024), "r"(pack_bf16(q[2] * i1, q[3] * i1)), "r"(pack_bf16(q[6] * i1, q[7] * i1)),
                                 "r"(pack_bf16(q[10] * i1, q[11] * i1)), "r"(pack_bf16(q[14] * i1, q[15] * i1)) : "memory");
                }
            }
            asm volatile("fence.proxy.async.shared::cta;" ::: "memory");
            asm volatile("bar.sync %0, 128;" :: "r"(3 + wg) : "memory");
            if ((threadIdx.x & 127) == 0) {
                asm volatile("st.shared.s32 [%0], %1;" :: "r"(oslot + wg * 4), "r"(t) : "memory");
                mbar_arrive(bar_of + 8 * wg);
            }
        }
        TS_END(1);
    }
}

__device__ __forceinline__ uint32_t cluster_ctarank() {
    uint32_t r; asm volatile("mov.u32 %0, %%cluster_ctarank;" : "=r"(r)); return r;
}
__device__ __forceinline__ uint32_t mapa_u32(uint32_t addr, uint32_t rank) {
    uint32_t r; asm volatile("mapa.shared::cluster.u32 %0, %1, %2;" : "=r"(r) : "r"(addr), "r"(rank)); return r;
}
__device__ __forceinline__ void cluster_sync_all() {
    asm volatile("barrier.cluster.arrive.release.aligned;\nbarrier.cluster.wait.acquire.aligned;" ::: "memory");
}
__device__ __forceinline__ void st_async_v4(uint32_t addr, uint32_t a, uint32_t b, uint32_t c, uint32_t d, uint32_t mbar) {
    asm volatile("st.async.weak.shared::cluster.mbarrier::complete_tx::bytes.v4.b32 [%0], {%1, %2, %3, %4}, [%5];"
                 :: "r"(addr), "r"(a), "r"(b), "r"(c), "r"(d), "r"(mbar) : "memory");
}
__device__ __forceinline__ void st_async_v2(uint32_t addr, uint32_t a, uint32_t b, uint32_t mbar) {
    asm volatile("st.async.weak.shared::cluster.mbarrier::complete_tx::bytes.v2.b32 [%0], {%1, %2}, [%3];"
                 :: "r"(addr), "r"(a), "r"(b), "r"(mbar) : "memory");
}
__device__ __forceinline__ void st_async_b32(uint32_t addr, uint32_t a, uint32_t mbar) {
    asm volatile("st.async.weak.shared::cluster.mbarrier::complete_tx::bytes.b32 [%0], %1, [%2];" :: "r"(addr), "r"(a), "r"(mbar) : "memory");
}
__device__ __forceinline__ void pace(int cycles) {
    if (cycles > 0) {
        uint32_t t0, t;
        asm volatile("mov.u32 %0, %%clock;" : "=r"(t0));
        do { asm volatile("mov.u32 %0, %%clock;" : "=r"(t)); } while (t - t0 < (uint32_t)cycles);
    }
}
__device__ __forceinline__ void mbar_wait_cl(uint32_t bar, uint32_t parity) {
    uint32_t done = 0;
    for (int it = 0; it < (1 << 22) && !done; it++) {
        asm volatile(
            "{\n.reg .pred p;\n"
            "mbarrier.try_wait.parity.shared::cta.b64 p, [%1], %2;\n"
            "selp.u32 %0, 1, 0, p;\n}\n" : "=r"(done) : "r"(bar), "r"(parity) : "memory");
    }
}
__device__ __forceinline__ uint32_t mbar_test(uint32_t bar, uint32_t parity) {
    uint32_t done;
    asm volatile(
        "{\n.reg .pred p;\n"
        "mbarrier.test_wait.parity.shared::cta.b64 p, [%1], %2;\n"
        "selp.u32 %0, 1, 0, p;\n}\n" : "=r"(done) : "r"(bar), "r"(parity) : "memory");
    return done;
}
__device__ __forceinline__ void ldmatrix_x4(uint32_t& r0, uint32_t& r1, uint32_t& r2, uint32_t& r3, uint32_t addr) {
    asm volatile("ldmatrix.sync.aligned.m8n8.x4.shared.b16 {%0,%1,%2,%3}, [%4];"
                 : "=r"(r0), "=r"(r1), "=r"(r2), "=r"(r3) : "r"(addr));
}
__device__ __forceinline__ void cp_async16(uint32_t dst, const void* src) {
    asm volatile("cp.async.cg.shared.global [%0], [%1], 16;" :: "r"(dst), "l"(src) : "memory");
}
__device__ __forceinline__ float bf16r(float x) { return __uint_as_float(pack_bf16(0.f, x) & 0xffff0000u); }

#define DBG(i)
#define DBGW(i, w)
__device__ __forceinline__ void tma_load_2d_mc(uint32_t dst, const CUtensorMap* map, uint32_t bar, int c0, int c1, uint16_t mask) {
    asm volatile(
        "cp.async.bulk.tensor.2d.shared::cluster.global.mbarrier::complete_tx::bytes.multicast::cluster [%0], [%1, {%3, %4}], [%2], %5;"
        :: "r"(dst), "l"((uint64_t)map), "r"(bar), "r"(c0), "r"(c1), "h"(mask) : "memory");
}
__device__ __forceinline__ void bulk_s2s(uint32_t dst_cl, uint32_t src, uint32_t bytes, uint32_t bar_cl) {
    asm volatile("cp.async.bulk.shared::cluster.shared::cta.mbarrier::complete_tx::bytes [%0], [%1], %2, [%3];"
                 :: "r"(dst_cl), "r"(src), "r"(bytes), "r"(bar_cl) : "memory");
}
__device__ __forceinline__ bool elect_one() {
    uint32_t p;
    asm volatile("{\n.reg .pred p;\nelect.sync _|p, 0xffffffff;\nselp.u32 %0, 1, 0, p;\n}" : "=r"(p));
    return p;
}
__device__ __forceinline__ void fence_async_smem() { asm volatile("fence.proxy.async.shared::cta;" ::: "memory"); }
template <int ID, int N> __device__ __forceinline__ void bar_sync() { asm volatile("bar.sync %0, %1;" :: "n"(ID), "n"(N) : "memory"); }
template <int ID, int N> __device__ __forceinline__ void bar_arrive() { asm volatile("bar.arrive %0, %1;" :: "n"(ID), "n"(N) : "memory"); }
__device__ __forceinline__ void sts32(uint32_t a, uint32_t v) { asm volatile("st.shared.u32 [%0], %1;" :: "r"(a), "r"(v) : "memory"); }
__device__ __forceinline__ void ldsm_x4(uint32_t* r, uint32_t addr) {
    asm volatile("ldmatrix.sync.aligned.m8n8.x4.shared.b16 {%0,%1,%2,%3}, [%4];" : "=r"(r[0]), "=r"(r[1]), "=r"(r[2]), "=r"(r[3]) : "r"(addr) : "memory");
}
__device__ __forceinline__ uint32_t pin(uint32_t v) { asm volatile("" : "+r"(v)); return v; }
constexpr uint32_t DHI128 = 0x40000040u, DHI32 = 0xC0000010u;
#define ACC16(d) "+f"(d[0]), "+f"(d[1]), "+f"(d[2]), "+f"(d[3]), "+f"(d[4]), "+f"(d[5]), "+f"(d[6]), "+f"(d[7]), "+f"(d[8]), "+f"(d[9]), "+f"(d[10]), \
    "+f"(d[11]), "+f"(d[12]), "+f"(d[13]), "+f"(d[14]), "+f"(d[15])
#define ACC20(d) ACC16(d), "+f"(d[16]), "+f"(d[17]), "+f"(d[18]), "+f"(d[19])
__device__ __forceinline__ void wgmma_rs(float (&d)[16], const uint32_t (&a)[4], uint32_t db_lo) {
    asm volatile(
        "{\n.reg .b64 db;\nmov.b64 db, {%20, %21};\n"
        "wgmma.mma_async.sync.aligned.m64n32k16.f32.bf16.bf16 {%0,%1,%2,%3,%4,%5,%6,%7,%8,%9,%10,%11,%12,%13,%14,%15}, {%16,%17,%18,%19}, db, 1, 1, 1, 0;\n}\n"
        : ACC16(d) : "r"(a[0]), "r"(a[1]), "r"(a[2]), "r"(a[3]), "r"(db_lo), "n"(DHI128));
}
__device__ __forceinline__ void wgmma_rs(float (&d)[20], const uint32_t (&a)[4], uint32_t db_lo) {
    asm volatile(
        "{\n.reg .b64 db;\nmov.b64 db, {%24, %25};\n"
        "wgmma.mma_async.sync.aligned.m64n40k16.f32.bf16.bf16 {%0,%1,%2,%3,%4,%5,%6,%7,%8,%9,%10,%11,%12,%13,%14,%15,%16,%17,%18,%19}, {%20,%21,%22,%23}, db, 1, 1, 1, 0;\n}\n"
        : ACC20(d) : "r"(a[0]), "r"(a[1]), "r"(a[2]), "r"(a[3]), "r"(db_lo), "n"(DHI128));
}
template <uint32_t AHI, uint32_t BHI>
__device__ __forceinline__ void wgmma_ss(float (&d)[16], uint32_t da_lo, uint32_t db_lo) {
    asm volatile(
        "{\n.reg .b64 da, db;\nmov.b64 da, {%16, %18};\nmov.b64 db, {%17, %19};\n"
        "wgmma.mma_async.sync.aligned.m64n32k16.f32.bf16.bf16 {%0,%1,%2,%3,%4,%5,%6,%7,%8,%9,%10,%11,%12,%13,%14,%15}, da, db, 1, 1, 1, 0, 0;\n}\n"
        : ACC16(d) : "r"(da_lo), "r"(db_lo), "n"(AHI), "n"(BHI));
}
template <uint32_t AHI, uint32_t BHI>
__device__ __forceinline__ void wgmma_ss(float (&d)[20], uint32_t da_lo, uint32_t db_lo) {
    asm volatile(
        "{\n.reg .b64 da, db;\nmov.b64 da, {%20, %22};\nmov.b64 db, {%21, %23};\n"
        "wgmma.mma_async.sync.aligned.m64n40k16.f32.bf16.bf16 {%0,%1,%2,%3,%4,%5,%6,%7,%8,%9,%10,%11,%12,%13,%14,%15,%16,%17,%18,%19}, da, db, 1, 1, 1, 0, 0;\n}\n"
        : ACC20(d) : "r"(da_lo), "r"(db_lo), "n"(AHI), "n"(BHI));
}
__device__ __forceinline__ void wgmma_ss_n8(float (&d)[4], uint32_t da_lo, uint32_t db_lo) {
    asm volatile(
        "{\n.reg .b64 da, db;\nmov.b64 da, {%4, %6};\nmov.b64 db, {%5, %7};\n"
        "wgmma.mma_async.sync.aligned.m64n8k16.f32.bf16.bf16 {%0,%1,%2,%3}, da, db, 1, 1, 1, 1, 0;\n}\n"
        : "+f"(d[0]), "+f"(d[1]), "+f"(d[2]), "+f"(d[3]) : "r"(da_lo), "r"(db_lo), "n"(DHI128), "n"(DHI32));
}

constexpr uint32_t C2_WO = 0;
constexpr uint32_t C2_XB = 65536;
constexpr uint32_t C2_XS = 40960;
constexpr uint32_t C2_QX = C2_XB + 2 * C2_XS;
constexpr uint32_t C2_KX = C2_QX + 4096;
constexpr uint32_t C2_VT = C2_KX + 5120;
constexpr uint32_t C2_OB = C2_VT + 12288;
constexpr uint32_t C2_QM = C2_OB + 8192;
constexpr uint32_t C2_SC = C2_QM + 1024;
constexpr uint32_t C2_PB = C2_SC + 2560;
constexpr uint32_t C2_BAR = C2_PB + 768;
constexpr uint32_t C2_PX = C2_BAR + 256;
constexpr uint32_t C2_SX = C2_PX + 3072;
#define C2_NS 4
constexpr uint32_t C2_WS = C2_SX + 20480;
constexpr int C2_SMEM = C2_WS + 3 * C2_NS * 2048;
static_assert(C2_PX % 256 == 0 && C2_WS % 256 == 0 && C2_SMEM <= 232448, "smem map");
#define CH_POLL_DELAY 200

__device__ __forceinline__ void c2_load_w(uint32_t (&w)[32][4], const bf16* __restrict__ W, int rank, int col, uint32_t ws) {
#pragma unroll
    for (int e = 0; e < 32; e++) {
        const bf16* p = W + (size_t)((((rank - (e >> 2)) & 7) * 64) + (e & 3) * 16) * NQ + col;
        w[e][0] = __ldg(reinterpret_cast<const uint32_t*>(p));
        w[e][1] = __ldg(reinterpret_cast<const uint32_t*>(p + NQ));
        w[e][2] = __ldg(reinterpret_cast<const uint32_t*>(p + 8 * NQ));
        w[e][3] = __ldg(reinterpret_cast<const uint32_t*>(p + 9 * NQ));
    }
#pragma unroll
    for (int e = 0; e < 32; e++) {
        const uint32_t w0 = w[e][0], w1 = w[e][1], w2 = w[e][2], w3 = w[e][3];
        w[e][0] = __byte_perm(w0, w1, 0x5410); w[e][1] = __byte_perm(w0, w1, 0x7632);
        w[e][2] = __byte_perm(w2, w3, 0x5410); w[e][3] = __byte_perm(w2, w3, 0x7632);
        if (e < C2_NS) stmatrix_x4(ws + e * 2048, w[e][0], w[e][1], w[e][2], w[e][3]);
    }
    fence_async_smem();
    asm volatile("bar.sync %0, 128;" :: "r"(8 + (threadIdx.x >> 7)) : "memory");
}
template <int NA>
__device__ __forceinline__ void c2_xstream(float (&acc)[NA], const uint32_t (&w)[32][4], uint32_t xlo, uint32_t rank, uint32_t wslo) {
#pragma unroll
    for (int i = 0; i < NA; i++) acc[i] = 0.f;
    wgmma_fence();
#pragma unroll
    for (int e = 0; e < 32; e++) {
        if (e < C2_NS) wgmma_ss<DHI32, DHI128>(acc, wslo + e * 128, xlo + ((rank - (e >> 2)) & 7) * 320 + (e & 3) * 2);
        else wgmma_rs(acc, w[e], xlo + ((rank - (e >> 2)) & 7) * 320 + (e & 3) * 2);
    }
    wgmma_commit();
    wgmma_wait<0>();
}
__device__ __forceinline__ void c2_mma_slot(float (&a)[4][4], const uint32_t (&w)[32][4], int slot, const uint32_t* b, uint32_t ws) {
#pragma unroll
    for (int kk = 0; kk < 4; kk++) {
        const int e = slot * 4 + kk;
        if (e < C2_NS) {
            uint32_t t[4];
            ldsm_x4(t, ws + e * 2048);
            mma_16816(a[kk], t[0], t[1], t[2], t[3], b[2 * kk], b[2 * kk + 1]);
        } else mma_16816(a[kk], w[e][0], w[e][1], w[e][2], w[e][3], b[2 * kk], b[2 * kk + 1]);
    }
}
__device__ __forceinline__ constexpr int c2_grp(int i) { return i < 2 ? i : 1 + (i >> 1); }

__global__ void __cluster_dims__(8, 1, 1) __launch_bounds__(384, 1)
chain_kernel(const __grid_constant__ CUtensorMap mapX, const bf16* __restrict__ mem0, const bf16* __restrict__ Wq, const bf16* __restrict__ Wk,
             const bf16* __restrict__ Wv, const bf16* __restrict__ Wo) {
    extern __shared__ __align__(1024) uint8_t smem_chain[];
    const uint32_t sb = smem_u32(smem_chain);
    const uint32_t dlo = ((sb & 0x3FFFF) >> 4) | (1u << 16);
    const int tid = threadIdx.x, lane = tid & 31;
    const int warp = __shfl_sync(0xffffffff, tid >> 5, 0), wg = warp >> 2, w4 = warp & 3;
    const uint32_t rank = cluster_ctarank();
    const int C = blockIdx.x >> 3;
    const int h = C * 4 + (rank >> 1);
    const int g = lane >> 2, qc = lane & 3;
    pdl_launch_dependents();
    TS_BEGIN(2);
    const uint32_t bar_m = sb + C2_BAR, bar_o = bar_m + 64, bar_sc = bar_m + 128, bar_x = bar_m + 136, bar_sx = bar_m + 152;
    if (tid == 0) {
        for (int j = 0; j < 5; j++) { mbar_init(bar_m + 8 * j, j ? 1 : 4); mbar_init(bar_o + 8 * j, j ? 1 : 4); }
        for (int j = 0; j < 5; j++) mbar_init(bar_sc + 8 * j, 1);
        asm volatile("fence.mbarrier_init.release.cluster;" ::: "memory");
    }
    __syncthreads();
    cluster_sync_all();
    if (tid == 0) {
        mbar_expect_tx(bar_x, 32768);
        tma_load_2d_mc(sb + C2_XB + rank * 5120, &mapX, bar_x, rank * 64, 0, (uint16_t)0xff);
    }
    for (int i = tid; i < 2048; i += 384) {
        const int k = i >> 2, b = i & 3;
        const uint4* p = reinterpret_cast<const uint4*>(Wo + (size_t)(C * 512 + ((rank - (k >> 6)) & 7) * 64 + (k & 63)) * DM + rank * 64 + b * 16);
        const uint4 u = __ldg(p), v = __ldg(p + 1);
        const uint32_t a = sb + C2_WO + k * 128;
        asm volatile("st.shared.v4.b32 [%0], {%1, %2, %3, %4};" :: "r"(a + (((2 * b) ^ (k & 7)) << 4)), "r"(__byte_perm(u.x, u.y, 0x5410)),
                     "r"(__byte_perm(u.z, u.w, 0x5410)), "r"(__byte_perm(v.x, v.y, 0x5410)), "r"(__byte_perm(v.z, v.w, 0x5410)) : "memory");
        asm volatile("st.shared.v4.b32 [%0], {%1, %2, %3, %4};" :: "r"(a + (((2 * b + 1) ^ (k & 7)) << 4)), "r"(__byte_perm(u.x, u.y, 0x7632)),
                     "r"(__byte_perm(u.z, u.w, 0x7632)), "r"(__byte_perm(v.x, v.y, 0x7632)), "r"(__byte_perm(v.z, v.w, 0x7632)) : "memory");
    }
    for (int i = tid; i < 512; i += 384) {
        const int row = i >> 6, c = (i >> 3) & 7, j = i & 7;
        const uint4 u = __ldg(reinterpret_cast<const uint4*>(mem0) + i);
        asm volatile("st.shared.v4.b32 [%0], {%1, %2, %3, %4};" :: "r"(sb + C2_XB + c * 5120 + 4096 + row * 128 + ((j ^ row) << 4)),
                     "r"(u.x), "r"(u.y), "r"(u.z), "r"(u.w) : "memory");
    }
    for (int i = tid; i < 2 * 512 + 256; i += 384)
        sts32(sb + (i < 1024 ? C2_VT + (i >> 9) * 6144 + 4096 + (i & 511) * 4 : C2_PX + 2048 + (i - 1024) * 4), 0u);
    fence_async_smem();
    __syncthreads();

    const uint32_t t32 = w4 * 256 + qc * 64 + (((g >> 2) ^ (qc >> 1)) << 4) + (g & 3) * 4;
    const uint32_t t128 = qc * 256 + (((2 * w4 + (g >> 2)) ^ (2 * qc)) << 4) + (g & 3) * 4;
    const uint32_t a32 = (w4 * 16 + (lane & 15)) * 32 + (((lane >> 4) ^ ((lane >> 2) & 1)) << 4);
    const uint32_t ws = sb + C2_WS + wg * (C2_NS * 2048) + a32;
    uint32_t w[32][4];
    const int wcol = h * HD + (rank & 1) * 64 + w4 * 16 + 2 * g + 2 * qc * NQ;
    auto proj_mem = [&](float (&a)[4][4], int s) {
        uint32_t b[16];
#pragma unroll
        for (int i = 0; i < 16; i++) a[i >> 2][i & 3] = 0.f;
        const uint32_t par = (s & 1) ^ 1;
        const uint32_t l128 = (lane & 7) * 128 + (((lane >> 3) ^ (lane & 7)) << 4);
        const uint32_t mb = sb + C2_XB + (s & 1) * C2_XS + 4096;
        auto ldb = [&](uint32_t* bb, int i) {
            ldsm_x4(bb, mb + ((rank - i) & 7) * 5120 + l128);
            ldsm_x4(bb + 4, mb + ((rank - i) & 7) * 5120 + (l128 ^ 64));
        };
        mbar_wait(bar_m, par);
        ldb(b, 0);
        c2_mma_slot(a, w, 0, b, ws);
        mbar_wait(bar_m + 8, par);
        DBGW(1 + 16 * wg, 0);
        ldb(b, 1);
        uint32_t nxt = mbar_test(bar_m + 16, par);
        c2_mma_slot(a, w, 1, b, ws);
#pragma unroll
        for (int i = 2; i < 8; i += 2) {
            if (__builtin_expect(!nxt, 0)) mbar_wait(bar_m + 8 * c2_grp(i), par);
            if (i == 6) DBGW(2 + 16 * wg, 0);
            ldb(b, i);
            ldb(b + 8, i + 1);
            if (i < 6) nxt = mbar_test(bar_m + 8 * c2_grp(i + 2), par);
            c2_mma_slot(a, w, i, b, ws);
            c2_mma_slot(a, w, i + 1, b + 8, ws);
        }
#pragma unroll
        for (int i = 0; i < 4; i++) a[0][i] = (a[0][i] + a[1][i]) + (a[2][i] + a[3][i]);
    };
    auto store_x = [&](const float (&acc)[16], uint32_t base) {
#pragma unroll
        for (int j = 0; j < 4; j++) {
            sts32(base + t128 + j * 1024, pack_bf16(acc[4 * j], acc[4 * j + 2]));
            sts32(base + (t128 ^ 16) + 128 + j * 1024, pack_bf16(acc[4 * j + 1], acc[4 * j + 3]));
        }
    };
    const float scale = 0.08838834764831845f, l2e = 1.4426950408889634f;

    if (wg == 0) {
        c2_load_w(w, Wq, rank, wcol, ws);
        TS_END(6);
        TS_BEGIN(5);
#pragma unroll 1
        for (int s = -1;;) {
            uint32_t xok = 0;
            if (s >= 0) {
                float acc[4] = {0.f, 0.f, 0.f, 0.f};
                const uint32_t tag = ((s >> 1) & 1) ^ 1;
                uint32_t* dst = reinterpret_cast<uint32_t*>(g_xbuf + (((s & 1) * 8 + rank) * 8 + C) * 128) + qc * 64 + w4 * 8 + g;
                asm volatile("" : "+l"(dst));
#pragma unroll
                for (int i = 0; i < 8; i++) {
                    if (i < 2 || !(i & 1)) {
                        mbar_wait(bar_o + 8 * c2_grp(i), s & 1);
                        if (i == 0) DBGW(7, 0);
                        if (i == 1) DBGW(8, 0);
                        if (i == 6) DBGW(9, 0);
                        wgmma_fence();
                    }
#pragma unroll
                    for (int kk = 0; kk < 4; kk++)
                        wgmma_ss_n8(acc, dlo + ((C2_WO + i * 8192 + kk * 2048) >> 4), dlo + ((C2_OB + i * 1024 + kk * 256) >> 4));
                }
                wgmma_commit();
                xok = mbar_test(bar_x + 8 * ((s + 1) & 1), ((s + 1) >> 1) & 1);
                wgmma_wait<0>();
                asm volatile("st.relaxed.gpu.global.u32 [%0], %1;" :: "l"(dst), "r"((pack_bf16(acc[0], acc[2]) & ~1u) | tag) : "memory");
                asm volatile("st.relaxed.gpu.global.u32 [%0 + 128], %1;" :: "l"(dst), "r"((pack_bf16(acc[1], acc[3]) & ~1u) | tag) : "memory");
                bar_arrive<4, 384>();
                DBGW(10, 0);
            }
            s++;
            if (__builtin_expect(!xok, 0)) mbar_wait(bar_x + 8 * (s & 1), (s >> 1) & 1);
            {
                float acc[16];
                c2_xstream(acc, w, dlo + ((C2_XB + (s & 1) * C2_XS) >> 4), rank, dlo + (C2_WS >> 4));
                if (s > 0) bar_sync<5, 256>();
                store_x(acc, sb + C2_QX);
            }
            DBGW(0, 0);
            if (s == NSEG - 1) break;
            const uint32_t sca = w4 < 2 ? sb + C2_SC + w4 * 512 + lane * 16 : sb + C2_SC + 1024 + lane * 8;
            const uint32_t sc_peer = pin(mapa_u32(sca + 1280, rank ^ 1)), sc_own = pin(mapa_u32(sca, rank));
            const uint32_t krow = w4 * 16 + (lane & 15);
            const uint32_t ka0 = pin(sb + C2_KX + krow * 128 + (((lane >> 4) ^ (krow & 7)) << 4));
            const uint32_t l32 = pin(sb + C2_QM + (lane >> 4) * 256 + (lane & 7) * 32 + ((((lane >> 3) & 1) ^ ((lane >> 2) & 1)) << 4));
            const uint32_t qst = pin(sb + C2_QM + t32);
            {
                float a[4][4];
                proj_mem(a, s);
                sts32(qst, pack_bf16(a[0][0], a[0][2]));
                sts32(qst + 32, pack_bf16(a[0][1], a[0][3]));
            }
            DBGW(3, 0);
            if (w4 < 3) {
                uint32_t ka[4][4], qb[8];
                float c[4] = {0.f, 0.f, 0.f, 0.f}, c2[4] = {0.f, 0.f, 0.f, 0.f};
                bar_sync<1, 384>();
                ldsm_x4(qb, l32);
                ldsm_x4(ka[0], ka0);
                ldsm_x4(ka[1], ka0 ^ 32);
                ldsm_x4(qb + 4, l32 + 512);
                ldsm_x4(ka[2], ka0 ^ 64);
                ldsm_x4(ka[3], ka0 ^ 96);
                mma_16816(c, ka[0][0], ka[0][1], ka[0][2], ka[0][3], qb[0], qb[1]);
                mma_16816(c2, ka[1][0], ka[1][1], ka[1][2], ka[1][3], qb[2], qb[3]);
                mma_16816(c, ka[2][0], ka[2][1], ka[2][2], ka[2][3], qb[4], qb[5]);
                mma_16816(c2, ka[3][0], ka[3][1], ka[3][2], ka[3][3], qb[6], qb[7]);
                const uint32_t u0 = __float_as_uint(c[0] + c2[0]), u1 = __float_as_uint(c[1] + c2[1]);
                const uint32_t u2 = __float_as_uint(c[2] + c2[2]), u3 = __float_as_uint(c[3] + c2[3]);
                asm volatile(
                    "{\n.reg .pred p;\nsetp.lt.u32 p, %8, 2;\n"
                    "@p st.async.weak.shared::cluster.mbarrier::complete_tx::bytes.v4.b32 [%0], {%4, %5, %6, %7}, [%1];\n"
                    "@!p st.async.weak.shared::cluster.mbarrier::complete_tx::bytes.v2.b32 [%0], {%4, %5}, [%1];\n"
                    "@p st.async.weak.shared::cluster.mbarrier::complete_tx::bytes.v4.b32 [%2], {%4, %5, %6, %7}, [%3];\n"
                    "@!p st.async.weak.shared::cluster.mbarrier::complete_tx::bytes.v2.b32 [%2], {%4, %5}, [%3];\n}"
                    :: "r"(sc_peer), "r"(mapa_u32(bar_sc, rank ^ 1)), "r"(sc_own), "r"(mapa_u32(bar_sc, rank)), "r"(u0), "r"(u1), "r"(u2), "r"(u3), "r"(w4) : "memory");
                bar_arrive<2, 224>();
                DBGW(4, 2);
            } else {
                bar_arrive<1, 384>();
                const uint32_t a = pin(sb + C2_SC + lane * 16), a2 = pin(sb + C2_SC + 1024 + lane * 8), pa = pin(sb + C2_PB + lane * 4);
                mbar_wait(bar_sc, s & 1);
                DBG(5);
                float v[10];
                {
                    float4 x0, x1, y0, y1; float2 x2, y2;
                    asm volatile("ld.shared.v4.f32 {%0, %1, %2, %3}, [%4];" : "=f"(x0.x), "=f"(x0.y), "=f"(x0.z), "=f"(x0.w) : "r"(a) : "memory");
                    asm volatile("ld.shared.v4.f32 {%0, %1, %2, %3}, [%4];" : "=f"(y0.x), "=f"(y0.y), "=f"(y0.z), "=f"(y0.w) : "r"(a + 1280) : "memory");
                    asm volatile("ld.shared.v4.f32 {%0, %1, %2, %3}, [%4];" : "=f"(x1.x), "=f"(x1.y), "=f"(x1.z), "=f"(x1.w) : "r"(a + 512) : "memory");
                    asm volatile("ld.shared.v4.f32 {%0, %1, %2, %3}, [%4];" : "=f"(y1.x), "=f"(y1.y), "=f"(y1.z), "=f"(y1.w) : "r"(a + 1792) : "memory");
                    asm volatile("ld.shared.v2.f32 {%0, %1}, [%2];" : "=f"(x2.x), "=f"(x2.y) : "r"(a2) : "memory");
                    asm volatile("ld.shared.v2.f32 {%0, %1}, [%2];" : "=f"(y2.x), "=f"(y2.y) : "r"(a2 + 1280) : "memory");
                    v[0] = x0.x + y0.x; v[1] = x0.y + y0.y; v[2] = x0.z + y0.z; v[3] = x0.w + y0.w;
                    v[4] = x1.x + y1.x; v[5] = x1.y + y1.y; v[6] = x1.z + y1.z; v[7] = x1.w + y1.w;
                    v[8] = x2.x + y2.x; v[9] = x2.y + y2.y;
                }
                float m0 = fmaxf(fmaxf(fmaxf(v[0], v[2]), fmaxf(v[4], v[6])), v[8]);
                float m1 = fmaxf(fmaxf(fmaxf(v[1], v[3]), fmaxf(v[5], v[7])), v[9]);
#pragma unroll
                for (int o = 4; o < 32; o <<= 1) {
                    m0 = fmaxf(m0, __shfl_xor_sync(0xffffffff, m0, o));
                    m1 = fmaxf(m1, __shfl_xor_sync(0xffffffff, m1, o));
                }
                const float sl = scale * l2e;
                m0 *= sl; m1 *= sl;
#pragma unroll
                for (int j = 0; j < 5; j++)
                    sts32(pa + j * 128, pack_bf16(ex2f(fmaf(v[2 * j], sl, -m0)), ex2f(fmaf(v[2 * j + 1], sl, -m1))));
                bar_arrive<3, 160>();
                DBG(6);
            }
            fence_async_smem();
            bar_arrive<6, 256>();
        }
        bar_sync<1, 384>();
        fence_async_smem();
        bar_arrive<6, 256>();
        bar_arrive<4, 384>();
    } else if (wg == 1) {
        c2_load_w(w, Wk, rank, wcol, ws);
#pragma unroll 1
        for (int s = -1;;) {
            if (s > 0) {
                mbar_wait(bar_sx + 8 * ((s - 1) & 1), ((s - 1) >> 1) & 1);
                const uint32_t a = sb + C2_SX + ((s - 1) & 1) * 10240 + w4 * 1280 + lane * 8;
                float v[10];
                const int lim = 8 * w4 + g - 2 * qc;
#pragma unroll
                for (int j = 0; j < 5; j++) {
                    float2 x, y;
                    asm volatile("ld.shared.v2.f32 {%0, %1}, [%2];" : "=f"(x.x), "=f"(x.y) : "r"(a + j * 256) : "memory");
                    asm volatile("ld.shared.v2.f32 {%0, %1}, [%2];" : "=f"(y.x), "=f"(y.y) : "r"(a + 5120 + j * 256) : "memory");
                    v[2 * j] = (j < 4 && 8 * j > lim) ? -INFINITY : x.x + y.x;
                    v[2 * j + 1] = (j < 4 && 8 * j + 1 > lim) ? -INFINITY : x.y + y.y;
                }
                float mx = fmaxf(fmaxf(fmaxf(v[0], v[1]), fmaxf(v[2], v[3])), fmaxf(fmaxf(v[4], v[5]), fmaxf(v[6], v[7])));
                mx = fmaxf(mx, fmaxf(v[8], v[9]));
                mx = fmaxf(mx, __shfl_xor_sync(0xffffffff, mx, 1));
                mx = fmaxf(mx, __shfl_xor_sync(0xffffffff, mx, 2));
                const float sl = scale * l2e;
                mx *= sl;
#pragma unroll
                for (int j = 0; j < 10; j++) v[j] = ex2f(fmaf(v[j], sl, -mx));
                float sm = ((v[0] + v[1]) + (v[2] + v[3])) + ((v[4] + v[5]) + (v[6] + v[7])) + (v[8] + v[9]);
                sm += __shfl_xor_sync(0xffffffff, sm, 1);
                sm += __shfl_xor_sync(0xffffffff, sm, 2);
                float inv;
                asm("rcp.approx.ftz.f32 %0, %1;" : "=f"(inv) : "f"(sm));
                const uint32_t pa = sb + C2_PX + w4 * 256 + g * 32 + ((g >> 2) << 4) + qc * 4;
#pragma unroll
                for (int j = 0; j < 5; j++) sts32((pa ^ ((j & 1) << 4)) + (j >> 1) * 1024, pack_bf16(v[2 * j] * inv, v[2 * j + 1] * inv));
            }
            if (s >= 0) {
                fence_async_smem();
                if (s < NSEG) bar_sync<6, 256>(); else bar_sync<7, 128>();
                DBGW(20, 0);
                if (s < NSEG - 1) mbar_wait(bar_o, s & 1);
                if (s < NSEG) {
                    float sx[20];
#pragma unroll
                    for (int i = 0; i < 20; i++) sx[i] = 0.f;
                    wgmma_fence();
#pragma unroll
                    for (int kk = 0; kk < 4; kk++) wgmma_ss<DHI128, DHI128>(sx, dlo + (C2_QX >> 4) + kk * 2, dlo + (C2_KX >> 4) + kk * 2);
                    wgmma_commit();
                    wgmma_wait<0>();
                    if (s < NSEG - 1) bar_arrive<5, 256>();
                    if (w4 < 2) {
                        const uint32_t a = sb + C2_SX + (s & 1) * 10240 + w4 * 2560 + lane * 8;
#pragma unroll
                        for (int j = 0; j < 5; j++) {
                            asm volatile("st.shared.v2.f32 [%0], {%1, %2};" :: "r"(a + j * 256), "f"(sx[4 * j]), "f"(sx[4 * j + 1]) : "memory");
                            asm volatile("st.shared.v2.f32 [%0], {%1, %2};" :: "r"(a + 1280 + j * 256), "f"(sx[4 * j + 2]), "f"(sx[4 * j + 3]) : "memory");
                        }
                    }
                }
                DBGW(21, 0);
                if (s > 0) {
                    float cx[16];
#pragma unroll
                    for (int i = 0; i < 16; i++) cx[i] = 0.f;
                    wgmma_fence();
#pragma unroll
                    for (int kk = 0; kk < 3; kk++)
                        wgmma_ss<DHI32, DHI32>(cx, dlo + ((C2_VT + ((s - 1) & 1) * 6144 + kk * 2048) >> 4), dlo + ((C2_PX + kk * 1024) >> 4));
                    wgmma_commit();
                    wgmma_wait<0>();
                    uint32_t* dst = reinterpret_cast<uint32_t*>(g_ctxB + ((size_t)h * SEQ + (s - 1) * SEGL + 2 * qc) * HD + (rank & 1) * 64 + w4 * 16 + 2 * g);
#pragma unroll
                    for (int j = 0; j < 4; j++) {
                        dst[j * 8 * (HD / 2)] = pack_bf16(cx[4 * j], cx[4 * j + 2]);
                        dst[(j * 8 + 1) * (HD / 2)] = pack_bf16(cx[4 * j + 1], cx[4 * j + 3]);
                    }
                }
                DBGW(22, 0);
                if (s == NSEG) break;
                fence_async_smem();
            }
            if (s < NSEG - 1) mbar_wait(bar_x + 8 * ((s + 1) & 1), ((s + 1) >> 1) & 1);
            if (s >= 0) bar_sync<4, 384>();
            s++;
            if (s < NSEG) {
                {
                    float acc[16];
                    c2_xstream(acc, w, dlo + ((C2_XB + (s & 1) * C2_XS) >> 4), rank, dlo + ((C2_WS + C2_NS * 2048) >> 4));
                    store_x(acc, sb + C2_KX);
                }
                DBGW(16, 0);
                const uint32_t kst = pin(sb + C2_KX + 4096 + t128);
                float a[4][4];
                proj_mem(a, s);
                sts32(kst, pack_bf16(a[0][0], a[0][2]));
                sts32((kst ^ 16) + 128, pack_bf16(a[0][1], a[0][3]));
                bar_arrive<1, 384>();
                DBGW(19, 0);
                if (w4 == 0) {
                    if (s < NSEG - 1) {
                        if (lane == 0) mbar_expect_tx(bar_sc, 2560);
                        if (lane < 16 && (lane & 7) >= 1 && (lane & 7) < 5) mbar_expect_tx(bar_m + 8 * lane, (lane & 7) == 1 ? 1024 : 2048);
                        if (lane == 8) {
                            mbar_expect_tx(bar_x + 8 * ((s + 1) & 1), 32768);
                            tma_load_2d_mc(sb + C2_XB + ((s + 1) & 1) * C2_XS + rank * 5120, &mapX, bar_x + 8 * ((s + 1) & 1), rank * 64, (s + 1) * SEGL, (uint16_t)0xff);
                            if (s + 2 < NSEG)
                                asm volatile("cp.async.bulk.prefetch.tensor.2d.L2.global [%0, {%1, %2}];" :: "l"((uint64_t)&mapX), "r"(rank * 64), "r"((s + 2) * SEGL) : "memory");
                        }
                    }
                    if (lane == 16) mbar_expect_tx(bar_sx + 8 * (s & 1), 5120);
                    __syncwarp();
                }
            }
        }
        bar_sync<7, 128>();
        if (tid == 128) signal_ctr(CT_CB);
    } else {
        c2_load_w(w, Wv, rank, wcol, ws);
#pragma unroll 1
        for (int s = -1;;) {
            if (s >= 0) {
                const int t = tid - 256;
                const uint2* src = g_xbuf + ((s & 1) * 8 + rank) * 1024 + t;
                asm volatile("" : "+l"(src));
                const uint32_t ma = sb + C2_XB + ((s + 1) & 1) * C2_XS + rank * 5120 + 4096 + (t >> 4) * 128 + ((((t >> 1) & 7) ^ (t >> 4)) << 4) + (t & 1) * 8;
                uint32_t ra[8], rb[8];
#pragma unroll
                for (int i = 1; i < 8; i++) {
                    const uint32_t d = (rank + i) & 7;
                    ra[i] = pin(mapa_u32(ma, d)); rb[i] = pin(mapa_u32(bar_m + 8 * c2_grp(i), d));
                }
                bar_sync<4, 384>();
                DBGW(29, 0);
                if (tid == 256) {
                    const uint32_t a = sb + C2_SX + (s & 1) * 10240;
                    bulk_s2s(mapa_u32(a + 5120, rank ^ 1), a, 5120, mapa_u32(bar_sx + 8 * (s & 1), rank ^ 1));
                }
                if (s == NSEG - 1) break;
                pace(CH_POLL_DELAY);
                const uint32_t tag = ((s >> 1) & 1) ^ 1;
                uint32_t p[8][2];
                for (int it = 0; it < (1 << 20); it++) {
#pragma unroll
                    for (int k = 0; k < 8; k++)
                        asm volatile("ld.relaxed.gpu.global.v2.u32 {%0, %1}, [%2];" : "=r"(p[k][0]), "=r"(p[k][1]) : "l"(src + k * 128) : "memory");
                    uint32_t bad[8];
#pragma unroll
                    for (int k = 0; k < 8; k++) asm("lop3.b32 %0, %1, %2, %3, 0x7e;" : "=r"(bad[k]) : "r"(p[k][0]), "r"(p[k][1]), "r"(tag));
                    asm("lop3.b32 %0, %0, %1, %2, 0xfe;" : "+r"(bad[0]) : "r"(bad[1]), "r"(bad[2]));
                    asm("lop3.b32 %0, %0, %1, %2, 0xfe;" : "+r"(bad[3]) : "r"(bad[4]), "r"(bad[5]));
                    asm("lop3.b32 %0, %0, %1, %2, 0xfe;" : "+r"(bad[0]) : "r"(bad[3]), "r"(bad[6]));
                    asm("lop3.b32 %0, %0, %1, 1, 0xa8;" : "+r"(bad[0]) : "r"(bad[7]));
                    if (__all_sync(0xffffffff, bad[0] == 0u)) break;
                }
                DBGW(30, 0);
                float r[4];
#pragma unroll
                for (int e = 0; e < 2; e++) {
                    float lo[8], hi[8];
#pragma unroll
                    for (int k = 0; k < 8; k++) { lo[k] = __uint_as_float(p[k][e] << 16); hi[k] = __uint_as_float(p[k][e] & 0xffff0000u); }
                    r[2 * e] = ((lo[0] + lo[1]) + (lo[2] + lo[3])) + ((lo[4] + lo[5]) + (lo[6] + lo[7]));
                    r[2 * e + 1] = ((hi[0] + hi[1]) + (hi[2] + hi[3])) + ((hi[4] + hi[5]) + (hi[6] + hi[7]));
                }
                const uint32_t m0 = pack_bf16(r[0], r[1]), m1 = pack_bf16(r[2], r[3]);
                st_async_v2(ra[1], m0, m1, rb[1]);
                asm volatile("st.shared.v2.b32 [%0], {%1, %2};" :: "r"(ma), "r"(m0), "r"(m1) : "memory");
                __syncwarp();
                if (lane == 0) mbar_arrive(bar_m);
#pragma unroll
                for (int i = 2; i < 8; i++) st_async_v2(ra[i], m0, m1, rb[i]);
                DBGW(31, 0);
            }
            s++;
            const uint32_t ost = pin(sb + C2_OB + t32), pla = pin(sb + C2_PB + lane * 16), plb = pin(sb + C2_PB + 512 + (lane & 7) * 16);
            bar_sync<1, 384>();
            fence_async_smem();
            DBGW(24, 0);
            if (s < NSEG - 1) bar_sync<2, 224>();
            uint32_t va[5][2];
            {
                float acc[20];
                c2_xstream(acc, w, dlo + ((C2_XB + (s & 1) * C2_XS) >> 4), rank, dlo + ((C2_WS + 2 * C2_NS * 2048) >> 4));
#pragma unroll
                for (int j = 0; j < 5; j++) { va[j][0] = pack_bf16(acc[4 * j], acc[4 * j + 1]); va[j][1] = pack_bf16(acc[4 * j + 2], acc[4 * j + 3]); }
            }
            DBGW(26, 0);
            if (s < NSEG - 1) {
                uint32_t p[5];
                bar_sync<3, 160>();
                DBGW(27, 0);
                ldmatrix_x4_trans(p[0], p[1], p[2], p[3], pla);
                asm volatile("ldmatrix.sync.aligned.m8n8.x1.trans.shared.b16 {%0}, [%1];" : "=r"(p[4]) : "r"(plb) : "memory");
                float oa[4] = {0.f, 0.f, 0.f, 0.f}, ob[4] = {0.f, 0.f, 0.f, 0.f}, sa[4] = {0.f, 0.f, 0.f, 0.f}, sc[4] = {0.f, 0.f, 0.f, 0.f};
                const uint32_t one = 0x3f803f80u;
                mma_16816(sa, one, one, one, one, p[0], p[1]);
                mma_16816(oa, va[0][0], va[0][1], va[1][0], va[1][1], p[0], p[1]);
                mma_16816(sc, one, one, one, one, p[2], p[3]);
                mma_16816(ob, va[2][0], va[2][1], va[3][0], va[3][1], p[2], p[3]);
                mma_16816(sa, one, one, one, one, p[4], 0u);
                mma_16816(oa, va[4][0], va[4][1], 0u, 0u, p[4], 0u);
                float i0, i1;
                asm("rcp.approx.ftz.f32 %0, %1;" : "=f"(i0) : "f"(sa[0] + sc[0]));
                asm("rcp.approx.ftz.f32 %0, %1;" : "=f"(i1) : "f"(sa[1] + sc[1]));
                sts32(ost, pack_bf16((oa[0] + ob[0]) * i0, (oa[2] + ob[2]) * i0));
                sts32(ost + 32, pack_bf16((oa[1] + ob[1]) * i1, (oa[3] + ob[3]) * i1));
                fence_async_smem();
                __syncwarp();
                if (elect_one()) {
#pragma unroll
                    for (int i = 1; i < 8; i++) {
                        const uint32_t d = (rank + i) & 7;
                        bulk_s2s(mapa_u32(sb + C2_OB + i * 1024 + w4 * 256, d), sb + C2_OB + w4 * 256, 256, mapa_u32(bar_o + 8 * c2_grp(i), d));
                        if (i == 1) mbar_arrive(bar_o);
                    }
                }
                __syncwarp();
                DBGW(28, 0);
            }
            {
                const uint32_t a = sb + C2_VT + (s & 1) * 6144 + a32;
                stmatrix_x4(a, va[0][0], va[0][1], va[1][0], va[1][1]);
                stmatrix_x4(a + 2048, va[2][0], va[2][1], va[3][0], va[3][1]);
                asm volatile("stmatrix.sync.aligned.m8n8.x2.shared.b16 [%0], {%1, %2};" :: "r"(a + 4096), "r"(va[4][0]), "r"(va[4][1]) : "memory");
            }
            fence_async_smem();
        }
        g_xbuf[((8 + rank) * 8 + C) * 128 + (tid - 256)] = make_uint2(0u, 0u);
    }
    __syncthreads();
    cluster_sync_all();
    TS_END(2);
}

struct Proj2Params {
    CUtensorMap mapA[2];
    CUtensorMap mapW[3];
    bf16* out[3];
};
#define P2T(i)
#define P2_NOMMA 0
#define P2_NOLOAD 0
constexpr int P2_STAGES = 6;
constexpr int P2_SMEM = 131072 + P2_STAGES * 16384 + 1024 + 1024;
constexpr int P2_ITEMS = 168 + 48;
__device__ __forceinline__ int p2_reps(int t) { return t >= 168 ? 1 : 2; }
__device__ __forceinline__ void p2_tile(int t, int w, int& z, int& mp, int& head) {
    if (t >= 168) { w += ((t - 168) & 1) * 2; t = 168 + ((t - 168) >> 1); }
    const int hq = t / 24, v = t % 24;
    mp = v & 7;
    if (v < 16) { head = hq * 4 + (v >> 3) * 2 + (w >> 1); z = 1 + (w & 1); }
    else { head = hq * 4 + w; z = 0; }
}
__device__ __forceinline__ void mbar_arrive_remote(uint32_t bar_cluster_addr) {
    asm volatile("mbarrier.arrive.release.cluster.shared::cluster.b64 _, [%0];" :: "r"(bar_cluster_addr) : "memory");
}
__device__ __forceinline__ void mbar_arrive_cl(uint32_t bar_cluster_addr) {
    asm volatile("mbarrier.arrive.shared::cluster.b64 _, [%0];" :: "r"(bar_cluster_addr) : "memory");
}
__device__ __forceinline__ void mbar_wait_acq_cluster(uint32_t bar, uint32_t parity) {
    asm volatile(
        "{\n"
        ".reg .pred p, q;\n"
        ".reg .u32 c;\n"
        "mov.u32 c, 0;\n"
        "WAIT_LOOP_C:\n"
        "mbarrier.try_wait.parity.acquire.cluster.shared::cta.b64 p, [%0], %1;\n"
        "@p bra WAIT_DONE_C;\n"
        "add.u32 c, c, 1;\n"
        "setp.lt.u32 q, c, 4000000;\n"
        "@q bra WAIT_LOOP_C;\n"
        "WAIT_DONE_C:\n"
        "}\n" :: "r"(bar), "r"(parity) : "memory");
}
__device__ __forceinline__ uint4 quad_transpose(uint32_t p0, uint32_t p1, uint32_t p2, uint32_t p3, int lane) {
    const bool o1 = lane & 1, o2 = lane & 2;
    uint32_t s0 = o1 ? p0 : p1, s1 = o1 ? p2 : p3;
    s0 = __shfl_xor_sync(0xffffffff, s0, 1); s1 = __shfl_xor_sync(0xffffffff, s1, 1);
    const uint32_t a_lo = o1 ? s0 : p0, a_hi = o1 ? p1 : s0, b_lo = o1 ? s1 : p2, b_hi = o1 ? p3 : s1;
    uint32_t t0 = o2 ? a_lo : b_lo, t1 = o2 ? a_hi : b_hi;
    t0 = __shfl_xor_sync(0xffffffff, t0, 2); t1 = __shfl_xor_sync(0xffffffff, t1, 2);
    return o2 ? make_uint4(t0, t1, b_lo, b_hi) : make_uint4(a_lo, a_hi, t0, t1);
}
#define P2_PACE 35
#define P2_PACE2 0
template <bool PERM, int PACE = 0>
__device__ __forceinline__ void store_frag_128(const float (&acc)[64], bf16* obase, int lane) {
#pragma unroll
    for (int rr = 0; rr < 2; rr++)
#pragma unroll
        for (int g = 0; g < 4; g++) {
            const float* a = &acc[g * 16 + rr * 2];
            const uint32_t p0 = pack_bf16(a[0], a[1]), p1 = pack_bf16(a[4], a[5]), p2 = pack_bf16(a[8], a[9]), p3 = pack_bf16(a[12], a[13]);
            *reinterpret_cast<uint4*>(obase + (size_t)(rr * 8) * HD + g * 32) = PERM ? make_uint4(p0, p1, p2, p3) : quad_transpose(p0, p1, p2, p3, lane);
            pace(PACE);
        }
}
__global__ void __cluster_dims__(2, 1, 1) __launch_bounds__(384, 1) proj2_kernel(const __grid_constant__ Proj2Params P) {
    extern __shared__ uint8_t smem_raw[];
    const uint32_t sbase = (smem_u32(smem_raw) + 1023) & ~1023u;
    const uint32_t sA = sbase, sB = sbase + 131072, sC = sB + P2_STAGES * 16384;
    const uint32_t bars = sC;
    const uint32_t a_full = bars, a_empty = bars + 64, b_full = bars + 128, b_empty = b_full + 8 * P2_STAGES;
    const uint32_t item_bar = b_empty + 8 * P2_STAGES, item_in = item_bar + 16, slot = item_in + 16;
    const uint32_t note_bar = slot + 16, note_free = note_bar + 64, note = note_free + 64;
    const int warp = threadIdx.x >> 5, lane = threadIdx.x & 31;
    const uint32_t rank = cluster_ctarank();
    TS_BEGIN(0);
    if (threadIdx.x == 0) {
        for (int i = 0; i < 8; i++) { mbar_init(a_full + 8 * i, 1); mbar_init(a_empty + 8 * i, 2); }
        for (int i = 0; i < P2_STAGES; i++) { mbar_init(b_full + 8 * i, 1); mbar_init(b_empty + 8 * i, 2); }
        mbar_init(item_bar, 1); mbar_init(item_bar + 8, 1); mbar_init(item_in, 2); mbar_init(item_in + 8, 2);
        for (int i = 0; i < 8; i++) { mbar_init(note_bar + 8 * i, 1); mbar_init(note_free + 8 * i, 1); }
        asm volatile("fence.mbarrier_init.release.cluster;" ::: "memory");
    }
    __syncthreads();
    cluster_sync_all();
    pdl_launch_dependents();
    if (warp == 9) {
        if (lane == 0) {
            for (int n = 0;; n++) {
                const int e = (n & 1) * 4 + ((n >> 1) & 3);
                mbar_wait(note_bar + 8 * e, (n >> 3) & 1);
                int m;
                asm volatile("ld.shared.s32 %0, [%1];" : "=r"(m) : "r"(note + e * 4) : "memory");
                mbar_arrive(note_free + 8 * e);
                if (m < 0) break;
                signal_ctr(m);
            }
        }
    } else if (warp == 10) {
        if (lane == 0) {
            auto publish = [&](int ic, int tq) {
                const int t = tq < P2_ITEMS ? tq : -1;
                asm volatile("st.shared.s32 [%0], %1;" :: "r"(slot + (ic & 3) * 4), "r"(t) : "memory");
                mbar_arrive(item_bar + 8 * (ic & 1));
                st_async_b32(mapa_u32(slot + (ic & 3) * 4, 1), (uint32_t)t, mapa_u32(item_bar + 8 * (ic & 1), 1));
            };
            const int npair = (int)(gridDim.x >> 1), pair = (int)(blockIdx.x >> 1);
            if (rank == 0) publish(0, pair);
            for (int ic = 0;; ic++) {
                if (rank == 1) mbar_expect_tx(item_bar + 8 * (ic & 1), 4);
                mbar_wait(item_bar + 8 * (ic & 1), (ic >> 1) & 1);
                int t;
                asm volatile("ld.shared.s32 %0, [%1];" : "=r"(t) : "r"(slot + (ic & 3) * 4) : "memory");
                if (t < 0) break;
                int z0, mp, h0;
                p2_tile(t, 0, z0, mp, h0);
                const int aidx = z0 >= 1 ? 1 : 0;
                const int m0 = (2 * mp + (int)rank) * 128;
                for (int k = 0; k < 8; k++) {
                    mbar_wait(a_empty + 8 * k, (ic & 1) ^ 1);
                    if (P2_NOLOAD) mbar_arrive(a_full + 8 * k); else {
                    mbar_expect_tx(a_full + 8 * k, 16384);
                    tma_load_2d(sA + k * 16384, &P.mapA[aidx], a_full + 8 * k, k * 64, m0); }
                }
                if (rank == 0) {
                    mbar_wait(item_in + 8 * (ic & 1), (ic >> 1) & 1);
                    publish(ic + 1, ic == 0 ? npair + pair : 2 * npair + (int)atomicAdd(&g_ctr[CT_PROJ], 1u));
                }
            }
        }
    } else if (warp == 8 || warp == 11) {
        if (lane == 0) {
            const int par2 = warp == 8 ? 0 : 1;
            int it = 0; uint32_t bph = 0;
            for (int ic = 0;; ic++) {
                mbar_wait(item_bar + 8 * (ic & 1), (ic >> 1) & 1);
                int t;
                asm volatile("ld.shared.s32 %0, [%1];" : "=r"(t) : "r"(slot + (ic & 3) * 4) : "memory");
                if (t < 0) break;
                const int nt = 2 * p2_reps(t);
                for (int w = 0; w < nt; w++) {
                    int z, mp, hd;
                    p2_tile(t, w, z, mp, hd);
                    for (int k = 0; k < 8; k++) {
                        const int s = it; const uint32_t phb = bph;
                        if (++it == P2_STAGES) { it = 0; bph ^= 1; }
                        if ((k & 1) != par2) continue;
                        mbar_wait(b_empty + 8 * s, phb ^ 1);
                        if (P2_NOLOAD) { mbar_arrive(b_full + 8 * s); continue; }
                        mbar_expect_tx(b_full + 8 * s, 16384);
                        tma_load_2d_mc(sB + s * 16384 + rank * 8192, &P.mapW[z], b_full + 8 * s, hd * 128 + (int)rank * 64, k * 64, (uint16_t)3);
                    }
                }
            }
        }
    } else {
        const int wg = warp >> 2;
        float acc[2][64];
        const uint32_t a_lo = desc_lo(sA, 16), b_lo0 = desc_lo(sB, 8192);
        const bool elected = (threadIdx.x & 127) == 0;
        int s = (wg * 8) % P2_STAGES;
        uint32_t ph = ((wg * 8) / P2_STAGES) & 1;
        int nnote = 0;
        if (wg == 1) asm volatile("bar.arrive 3, 256;" ::: "memory");
        for (int ic = 0;; ic++) {
            mbar_wait(item_bar + 8 * (ic & 1), (ic >> 1) & 1);
            int t;
            asm volatile("ld.shared.s32 %0, [%1];" : "=r"(t) : "r"(slot + (ic & 3) * 4) : "memory");
            P2T(7);
            if (wg == 0 && t < 0) {
                if (elected) {
                    const int e = nnote & 3;
                    mbar_wait(note_free + 8 * e, ((nnote >> 2) & 1) ^ 1);
                    asm volatile("st.shared.s32 [%0], %1;" :: "r"(note + e * 4), "r"(-1) : "memory");
                    mbar_arrive(note_bar + 8 * e);
                }
            }
            if (t < 0) break;
            const int reps = p2_reps(t);
#pragma unroll 1
            for (int rp = 0; rp < reps; rp++) {
            const bool first = rp == 0, last = rp == reps - 1;
            int z, mp, head;
            p2_tile(t, rp * 2 + wg, z, mp, head);
            asm volatile("bar.sync %0, 256;" :: "r"(3 + wg) : "memory");
            P2T(0);
            if (wg == 1 && last && elected) mbar_arrive_cl(mapa_u32(item_in + 8 * (ic & 1), 0));
            int sprev = 0;
#pragma unroll
            for (int k = 0; k < 8; k++) {
                if (k == 0) P2T(5);
                if (wg == 0 && first) mbar_wait(a_full + 8 * k, ic & 1);
                if (k == 0) P2T(6);
                mbar_wait(b_full + 8 * s, ph);
                if (k == 7) asm volatile("bar.arrive %0, 256;" :: "r"(4 - wg) : "memory");
                if (k == 0) P2T(1);
                if (k == 7) P2T(2);
                const uint32_t b_lo = b_lo0 + s * 1024;
                wgmma_fence();
#pragma unroll
                for (int kk = 0; kk < (P2_NOMMA ? 1 : 4); kk++) {
                    wgmma_ss_n128_lo<1>(acc[0], a_lo + k * 1024 + kk * 2, b_lo + kk * 128, (k | kk) != 0);
                    wgmma_ss_n128_lo<1>(acc[1], a_lo + k * 1024 + 512 + kk * 2, b_lo + kk * 128, (k | kk) != 0);
                }
                wgmma_commit();
                if (k > 0) {
                    wgmma_wait<1>();
                    if (elected) {
                        const uint32_t e = b_empty + 8 * sprev;
                        mbar_arrive_cl(mapa_u32(e, 0)); mbar_arrive_cl(mapa_u32(e, 1));
                        if (last) mbar_arrive(a_empty + 8 * (k - 1));
                    }
                }
                sprev = s;
                if (++s == P2_STAGES) { s = 0; ph ^= 1; }
            }
            wgmma_wait<0>();
            P2T(3);
            if (elected) {
                const uint32_t e = b_empty + 8 * sprev;
                mbar_arrive_cl(mapa_u32(e, 0)); mbar_arrive_cl(mapa_u32(e, 1));
                if (last) mbar_arrive(a_empty + 8 * 7);
            }
            s += 8 % P2_STAGES; ph ^= (8 / P2_STAGES) & 1;
            if (s >= P2_STAGES) { s -= P2_STAGES; ph ^= 1; }
            const int m0 = (2 * mp + (int)rank) * 128;
            bf16* obase = P.out[z] + ((size_t)head * SEQ + m0 + (warp & 3) * 16 + (lane >> 2)) * HD + (lane & 3) * 8;
            store_frag_128<true, P2_PACE>(acc[0], obase, lane); store_frag_128<true, P2_PACE>(acc[1], obase + (size_t)64 * HD, lane);
            P2T(4);
            {
                asm volatile("bar.sync %0, 128;" :: "r"(1 + wg) : "memory");
                if (elected) {
                    const int e = wg * 4 + (nnote & 3);
                    mbar_wait(note_free + 8 * e, ((nnote >> 2) & 1) ^ 1);
                    asm volatile("st.shared.s32 [%0], %1;" :: "r"(note + e * 4), "r"(CT_AP + (head >> 1)) : "memory");
                    mbar_arrive(note_bar + 8 * e);
                }
                nnote++;
            }
            }
        }
        TS_END(0);
    }
    __syncthreads();
    cluster_sync_all();
}

struct OutParams {
    CUtensorMap mapCtx[2];
    CUtensorMap mapWo[2];
    CUtensorMap mapPart;
};
__device__ float g_part[4 * SEQ * DM];

#define OT(i)
constexpr int O2_STAGES = 4;
constexpr int O2_SMEM = O2_STAGES * 49152 + 1024 + 256;

__global__ void __cluster_dims__(2, 1, 1) __launch_bounds__(352, 1)
out2_kernel(const __grid_constant__ OutParams P, const bf16* __restrict__ x, const bf16* __restrict__ gate_w, bf16* __restrict__ out) {
    extern __shared__ uint8_t smem_raw[];
    const uint32_t sbase = (smem_u32(smem_raw) + 1023) & ~1023u;
    const uint32_t bar_full = sbase + O2_STAGES * 49152, bar_empty = bar_full + 8 * O2_STAGES;
    __shared__ float s_gate[32];
    const int warp = threadIdx.x >> 5, lane = threadIdx.x & 31;
    const uint32_t rank = cluster_ctarank();
    const int cid = blockIdx.x >> 1;
    const int late = cid >> 5, mp = (cid >> 1) & 7, nh = cid & 1;
    const int b = late ? 1 - ((cid >> 4) & 1) : (cid >> 4) & 1, kq = b * 2 + late;
    const int h0 = late ? O2_HE : 0;
    const int KT = late ? 2 * (NH - O2_HE) : 2 * O2_HE;
    const int m0 = (2 * mp + (int)rank) * 128, n0 = nh * 256;
    TS_BEGIN(4);
    OT(0);
    if (threadIdx.x == 0) {
        for (int i = 0; i < O2_STAGES; i++) { mbar_init(bar_full + 8 * i, 1); mbar_init(bar_empty + 8 * i, 4); }
        asm volatile("fence.mbarrier_init.release.cluster;" ::: "memory");
    }
    __syncthreads();
    asm volatile("barrier.cluster.arrive.release.aligned;" ::: "memory");
    if (threadIdx.x == 256) wait_ctr(b == 0 ? CT_CA + (m0 >> 7) * 2 + late : CT_CB, (unsigned)(b == 0 ? KT : 64));
    __syncwarp();
    asm volatile("barrier.cluster.wait.acquire.aligned;" ::: "memory");
    if (warp >= 8) {
        if (lane == 0) {
            int s = 0; uint32_t ph = 0;
            for (int i = 0; i < KT; i++) {
                mbar_wait(bar_empty + 8 * s, ph ^ 1);
                const uint32_t sa = sbase + s * 49152;
                const int head = h0 + (i >> 1), dk = (i & 1) * 64;
                if (warp == 8) {
                    mbar_expect_tx(bar_full + 8 * s, 49152);
                    tma_load_2d(sa, &P.mapCtx[b], bar_full + 8 * s, dk, head * SEQ + m0);
                } else {
                    const int j = (int)rank * 2 + (warp - 9);
                    tma_load_2d_mc(sa + 16384 + j * 8192, &P.mapWo[b], bar_full + 8 * s, n0 + j * 64, head * HD + dk, (uint16_t)3);
                }
                if (++s == O2_STAGES) { s = 0; ph ^= 1; }
            }
        }
    } else {
        const int wg = warp >> 2;
        const bool elected = (threadIdx.x & 127) == 0;
        float acc[128];
        {
            const int r = m0 + kq * 32 + (threadIdx.x >> 3);
            float sum = 0.f;
#pragma unroll
            for (int c = 0; c < 8; c++) {
                const int col = c * 64 + (threadIdx.x & 7) * 8;
                const uint4 xv = __ldg(reinterpret_cast<const uint4*>(x + (size_t)r * DM + col));
                const uint4 gv = __ldg(reinterpret_cast<const uint4*>(gate_w + col));
                const bf16* xp = reinterpret_cast<const bf16*>(&xv);
                const bf16* gp = reinterpret_cast<const bf16*>(&gv);
#pragma unroll
                for (int e = 0; e < 8; e++)
                    sum += __bfloat162float(__float2bfloat16(__bfloat162float(xp[e]) * __bfloat162float(gp[e])));
            }
            sum += __shfl_xor_sync(0xffffffff, sum, 1);
            sum += __shfl_xor_sync(0xffffffff, sum, 2);
            sum += __shfl_xor_sync(0xffffffff, sum, 4);
            sum = __bfloat162float(__float2bfloat16(sum));
            if ((threadIdx.x & 7) == 0) s_gate[threadIdx.x >> 3] = __bfloat162float(__float2bfloat16(1.f / (1.f + __expf(-sum))));
        }
        int s = 0, sprev = 0; uint32_t ph = 0;
#pragma unroll 1
        for (int i = 0; i < KT; i++) {
            mbar_wait(bar_full + 8 * s, ph);
            if (i == 0) OT(1);
            if (i == 8) OT(2);
            const uint32_t sa = sbase + s * 49152 + wg * 8192, sb = sbase + s * 49152 + 16384;
            wgmma_fence();
#pragma unroll
            for (int kk = 0; kk < 4; kk++)
                wgmma_ss_n256_tb(acc, make_desc(sa + kk * 32, 16, 1024), make_desc(sb + kk * 2048, 8192, 1024), (i | kk) != 0);
            wgmma_commit();
            if (i > 0) {
                wgmma_wait<1>();
                if (elected) { const uint32_t e = bar_empty + 8 * sprev; mbar_arrive_cl(mapa_u32(e, 0)); mbar_arrive_cl(mapa_u32(e, 1)); }
            }
            sprev = s;
            if (++s == O2_STAGES) { s = 0; ph ^= 1; }
        }
        wgmma_wait<0>();
        OT(3);
        {
            const int r = wg * 64 + (warp & 3) * 16 + (lane >> 2);
            if ((warp >> 1) == kq) {
#pragma unroll
                for (int j = 0; j < 32; j++) {
                    const uint32_t a = sbase + (j >> 2) * 16384 + r * 128 + ((((j & 3) * 2 + ((lane & 3) >> 1)) ^ (r & 7)) << 4) + (lane & 1) * 8;
                    asm volatile("st.shared.v2.f32 [%0], {%1, %2};" :: "r"(a), "f"(acc[j * 4 + 0]), "f"(acc[j * 4 + 1]) : "memory");
                    asm volatile("st.shared.v2.f32 [%0], {%1, %2};" :: "r"(a + 1024), "f"(acc[j * 4 + 2]), "f"(acc[j * 4 + 3]) : "memory");
                }
            } else {
                float* pp = g_part + ((size_t)kq * SEQ + m0 + r) * DM + n0 + (lane & 3) * 2;
#pragma unroll
                for (int j = 0; j < 32; j++) {
                    *reinterpret_cast<float2*>(pp + j * 8) = make_float2(acc[j * 4 + 0], acc[j * 4 + 1]);
                    *reinterpret_cast<float2*>(pp + 8 * DM + j * 8) = make_float2(acc[j * 4 + 2], acc[j * 4 + 3]);
                }
            }
        }
        asm volatile("bar.sync 1, 256;" ::: "memory");
        OT(4);
        unsigned int* ctr = &g_ctr[CT_OP + (2 * mp + (int)rank) * 2 + nh];
        if (threadIdx.x == 0) {
            asm volatile("fence.proxy.async;" ::: "memory");
            __threadfence();
            atomicAdd(ctr, 1u);
            unsigned int v; int it = 0;
            do { asm volatile("ld.acquire.gpu.global.u32 %0, [%1];" : "=r"(v) : "l"(ctr) : "memory"); } while (v < 4u && ++it < (1 << 22));
        }
        asm volatile("bar.sync 1, 256;" ::: "memory");
        OT(5);
        {
            const int c8 = threadIdx.x & 31, r0 = threadIdx.x >> 5;
            float4 u[4][3][2];
#pragma unroll
            for (int i = 0; i < 4; i++)
#pragma unroll
                for (int q = 1; q < 4; q++) {
                    const float4* p4 = reinterpret_cast<const float4*>(g_part + ((size_t)((kq + q) & 3) * SEQ + m0 + kq * 32 + r0 + i * 8) * DM + n0 + c8 * 8);
                    asm volatile("ld.relaxed.gpu.global.v4.f32 {%0, %1, %2, %3}, [%4];"
                                 : "=f"(u[i][q - 1][0].x), "=f"(u[i][q - 1][0].y), "=f"(u[i][q - 1][0].z), "=f"(u[i][q - 1][0].w) : "l"(p4) : "memory");
                    asm volatile("ld.relaxed.gpu.global.v4.f32 {%0, %1, %2, %3}, [%4];"
                                 : "=f"(u[i][q - 1][1].x), "=f"(u[i][q - 1][1].y), "=f"(u[i][q - 1][1].z), "=f"(u[i][q - 1][1].w) : "l"(p4 + 1) : "memory");
                }
#pragma unroll
            for (int i = 0; i < 4; i++) {
                const int rl = kq * 32 + r0 + i * 8;
                const float ga = s_gate[r0 + i * 8], gb = 1.f - ga;
                float o8[8];
#pragma unroll
                for (int hf = 0; hf < 2; hf++) {
                    float4 own;
                    const uint32_t a = sbase + (c8 >> 2) * 16384 + rl * 128 + ((((c8 & 3) * 2 + hf) ^ (rl & 7)) << 4);
                    asm volatile("ld.shared.v4.f32 {%0, %1, %2, %3}, [%4];" : "=f"(own.x), "=f"(own.y), "=f"(own.z), "=f"(own.w) : "r"(a) : "memory");
                    const int qp = ((kq ^ 1) - kq) & 3;
                    const float4 pa = qp == 1 ? u[i][0][hf] : u[i][2][hf];
                    const float4 o1 = u[i][1][hf];
                    const float4 o2 = qp == 1 ? u[i][2][hf] : u[i][0][hf];
                    const float gm = b == 0 ? ga : gb, go = b == 0 ? gb : ga;
                    o8[hf * 4 + 0] = gm * (own.x + pa.x) + go * (o1.x + o2.x);
                    o8[hf * 4 + 1] = gm * (own.y + pa.y) + go * (o1.y + o2.y);
                    o8[hf * 4 + 2] = gm * (own.z + pa.z) + go * (o1.z + o2.z);
                    o8[hf * 4 + 3] = gm * (own.w + pa.w) + go * (o1.w + o2.w);
                }
                *reinterpret_cast<uint4*>(out + (size_t)(m0 + rl) * DM + n0 + c8 * 8) =
                    make_uint4(pack_bf16(o8[0], o8[1]), pack_bf16(o8[2], o8[3]), pack_bf16(o8[4], o8[5]), pack_bf16(o8[6], o8[7]));
            }
        }
        OT(6);
        if (threadIdx.x == 0) {
            const unsigned int tk = atomicAdd(&g_ctr[CT_FIN], 1u);
            asm volatile("st.shared.u32 [%0], %1;" :: "r"(bar_empty + 8 * O2_STAGES), "r"(tk) : "memory");
        }
        asm volatile("bar.sync 1, 256;" ::: "memory");
        unsigned int tk;
        asm volatile("ld.shared.u32 %0, [%1];" : "=r"(tk) : "r"(bar_empty + 8 * O2_STAGES) : "memory");
        if (tk == gridDim.x - 1 && threadIdx.x < CT_N) g_ctr[threadIdx.x] = 0u;
    }
    __syncthreads();
    cluster_sync_all();
    TS_END(4);
}

typedef CUresult (*PFN_encodeTiled)(CUtensorMap*, CUtensorMapDataType, cuuint32_t, void*, const cuuint64_t*,
                                    const cuuint64_t*, const cuuint32_t*, const cuuint32_t*, CUtensorMapInterleave,
                                    CUtensorMapSwizzle, CUtensorMapL2promotion, CUtensorMapFloatOOBfill);
static PFN_encodeTiled g_encode = nullptr;

static void make_map(CUtensorMap* m, const void* ptr, uint64_t rows, uint64_t cols, uint32_t box_rows, bool sw64 = false) {
    cuuint64_t dims[2] = {cols, rows};
    cuuint64_t strides[1] = {cols * 2};
    cuuint32_t box[2] = {sw64 ? 32u : 64u, box_rows};
    cuuint32_t es[2] = {1, 1};
    g_encode(m, CU_TENSOR_MAP_DATA_TYPE_BFLOAT16, 2, const_cast<void*>(ptr), dims, strides, box, es,
             CU_TENSOR_MAP_INTERLEAVE_NONE, sw64 ? CU_TENSOR_MAP_SWIZZLE_64B : CU_TENSOR_MAP_SWIZZLE_128B, CU_TENSOR_MAP_L2_PROMOTION_L2_256B,
             CU_TENSOR_MAP_FLOAT_OOB_FILL_NONE);
}

template <typename... KArgs, typename... Args>
static void launch_pdl(void (*kernel)(KArgs...), int grid, int block, size_t smem, cudaStream_t st, bool pdl, Args... args) {
    cudaLaunchConfig_t cfg = {};
    cfg.gridDim = dim3(grid); cfg.blockDim = dim3(block); cfg.dynamicSmemBytes = smem; cfg.stream = st;
    cudaLaunchAttribute at[1];
    at[0].id = cudaLaunchAttributeProgrammaticStreamSerialization;
    at[0].val.programmaticStreamSerializationAllowed = 1;
    cfg.attrs = at; cfg.numAttrs = pdl ? 1 : 0;
    cudaLaunchKernelEx(&cfg, kernel, KArgs(args)...);
}

extern "C" void kernel_launch(void* const* d_in, const int* in_sizes, int n_in, void* d_out, int out_size) {
    const bf16* x = (const bf16*)d_in[0];
    const bf16* ckv = (const bf16*)d_in[1];
    const bf16* wq = (const bf16*)d_in[2];
    const bf16* wuk = (const bf16*)d_in[3];
    const bf16* wuv = (const bf16*)d_in[4];
    const bf16* wo = (const bf16*)d_in[5];
    const bf16* mem0 = (const bf16*)d_in[7];
    const bf16* Wq = (const bf16*)d_in[8];
    const bf16* Wk = (const bf16*)d_in[9];
    const bf16* Wv = (const bf16*)d_in[10];
    const bf16* Wo = (const bf16*)d_in[11];
    const bf16* gate_w = (const bf16*)d_in[13];
    bf16* out = (bf16*)d_out;

    static Proj2Params P2;
    static CUtensorMap mapX;
    static AttnParams AP;
    static OutParams OP;
    static bool init = false;
    static const void* last_in[14];
    bool same = init;
    for (int i = 0; i < 14 && same; i++) same = last_in[i] == d_in[i];
    if (!init) {
        cudaDriverEntryPointQueryResult qr;
        cudaGetDriverEntryPoint("cuTensorMapEncodeTiled", (void**)&g_encode, cudaEnableDefault, &qr);
        cudaFuncSetAttribute(proj2_kernel, cudaFuncAttributeMaxDynamicSharedMemorySize, P2_SMEM);
        cudaFuncSetAttribute(attn_kernel, cudaFuncAttributeMaxDynamicSharedMemorySize, FA_SMEM);
        cudaFuncSetAttribute(chain_kernel, cudaFuncAttributeMaxDynamicSharedMemorySize, C2_SMEM);
        cudaFuncSetAttribute(out2_kernel, cudaFuncAttributeMaxDynamicSharedMemorySize, O2_SMEM);
        init = true;
    }
    if (!same) {
        for (int i = 0; i < 14; i++) last_in[i] = d_in[i];
        void *pQA, *pKA, *pVA, *pCA, *pCB;
        cudaGetSymbolAddress(&pQA, g_QA); cudaGetSymbolAddress(&pKA, g_KA); cudaGetSymbolAddress(&pVA, g_VA);
        cudaGetSymbolAddress(&pCA, g_ctxA); cudaGetSymbolAddress(&pCB, g_ctxB);
        make_map(&P2.mapA[0], x, SEQ, DM, 128);
        make_map(&P2.mapA[1], ckv, SEQ, DM, 128);
        const void* ws[3] = {wq, wuk, wuv};
        void* cs[3] = {pQA, pKA, pVA};
        for (int i = 0; i < 3; i++) { make_map(&P2.mapW[i], ws[i], DM, NQ, 64); P2.out[i] = (bf16*)cs[i]; }
        make_map(&mapX, x, SEQ, DM, SEGL);
        make_map(&AP.mapQ, pQA, NH * SEQ, HD, 128);
        make_map(&AP.mapK, pKA, NH * SEQ, HD, 128);
        make_map(&AP.mapV, pVA, NH * SEQ, HD, 128);
        make_map(&AP.mapO, pCA, NH * SEQ, HD, 64);
        make_map(&OP.mapCtx[0], pCA, NH * SEQ, HD, 128);
        make_map(&OP.mapCtx[1], pCB, NH * SEQ, HD, 128);
        make_map(&OP.mapWo[0], wo, NQ, DM, 64);
        make_map(&OP.mapWo[1], Wo, NQ, DM, 64);
        {
            void* pP; cudaGetSymbolAddress(&pP, g_part);
            cuuint64_t dims[2] = {DM, 4 * SEQ}; cuuint64_t strides[1] = {DM * 4}; cuuint32_t box[2] = {32, 32}; cuuint32_t es[2] = {1, 1};
            g_encode(&OP.mapPart, CU_TENSOR_MAP_DATA_TYPE_FLOAT32, 2, pP, dims, strides, box, es, CU_TENSOR_MAP_INTERLEAVE_NONE,
                     CU_TENSOR_MAP_SWIZZLE_128B, CU_TENSOR_MAP_L2_PROMOTION_NONE, CU_TENSOR_MAP_FLOAT_OOB_FILL_NONE);
        }
    }
    cudaStream_t s1 = cudaStreamPerThread;
    const bool pdl = true;
    launch_pdl(chain_kernel, 64, 384, C2_SMEM, s1, false, mapX, mem0, Wq, Wk, Wv, Wo);
    launch_pdl(proj2_kernel, 68, 384, P2_SMEM, s1, pdl, P2);
    launch_pdl(attn_kernel, FA_GRID, 384, FA_SMEM, s1, pdl, AP, 1000);
    launch_pdl(out2_kernel, 128, 352, O2_SMEM, s1, pdl, OP, x, gate_w, out);
}
```

```cpp
#include <cuda_runtime.h>
#include <cuda_bf16.h>
#include <cuda.h>
#include <stdint.h>
#include <type_traits>

constexpr int SEQ = 2048;
constexpr int DM = 512;
constexpr int NH = 32;
constexpr int HD = 128;
constexpr int NQ = NH * HD;
constexpr int SEGL = 32;
constexpr int NMEM = 8;
constexpr int NSEG = SEQ / SEGL;

typedef __nv_bfloat16 bf16;

__device__ bf16 g_QA[SEQ * NQ];
__device__ bf16 g_KA[SEQ * NQ];
__device__ bf16 g_VA[SEQ * NQ];
__device__ bf16 g_ctxA[SEQ * NQ];
__device__ bf16 g_ctxB[SEQ * NQ];
constexpr int CT_PROJ = 0, CT_ATTN = 1, CT_FIN = 5;
constexpr int CT_G = 32;
constexpr int CT_AP = 64;
#define O2_HE 24
constexpr int CT_CA = 128;
constexpr int CT_CB = 160;
constexpr int CT_OP = 192;
constexpr int CT_N = 224;
__device__ unsigned int g_ctr[CT_N];
__device__ float g_gate[SEQ];
__device__ uint2 g_xbuf[2 * 8 * 8 * 128];

#define FA_GRID 68

#define TS_BEGIN(id)
#define TS_END(id)
__device__ __forceinline__ void pdl_launch_dependents() { asm volatile("griddepcontrol.launch_dependents;" ::: "memory"); }
__device__ __forceinline__ void wait_ctr(int idx, unsigned int n) {
    unsigned int v; int it = 0;
    do { asm volatile("ld.acquire.gpu.global.u32 %0, [%1];" : "=r"(v) : "l"(&g_ctr[idx]) : "memory"); } while (v < n && ++it < (1 << 22));
    asm volatile("fence.proxy.async;" ::: "memory");
}
__device__ __forceinline__ void signal_ctr(int idx) {
    asm volatile("fence.proxy.async;" ::: "memory");
    __threadfence();
    atomicAdd(&g_ctr[idx], 1u);
}
__device__ __forceinline__ uint32_t smem_u32(const void* p) {
    return (uint32_t)__cvta_generic_to_shared(p);
}
__device__ __forceinline__ void mbar_init(uint32_t bar, uint32_t count) {
    asm volatile("mbarrier.init.shared::cta.b64 [%0], %1;" :: "r"(bar), "r"(count));
}
__device__ __forceinline__ void mbar_expect_tx(uint32_t bar, uint32_t bytes) {
    asm volatile("mbarrier.arrive.expect_tx.shared::cta.b64 _, [%0], %1;" :: "r"(bar), "r"(bytes) : "memory");
}
__device__ __forceinline__ void mbar_arrive(uint32_t bar) {
    asm volatile("mbarrier.arrive.shared::cta.b64 _, [%0];" :: "r"(bar) : "memory");
}
__device__ __forceinline__ void mbar_wait(uint32_t bar, uint32_t parity) {
    asm volatile(
        "{\n"
        ".reg .pred p, q;\n"
        ".reg .u32 c;\n"
        "mov.u32 c, 0;\n"
        "WAIT_LOOP:\n"
        "mbarrier.try_wait.parity.shared::cta.b64 p, [%0], %1;\n"
        "@p bra WAIT_DONE;\n"
        "add.u32 c, c, 1;\n"
        "setp.lt.u32 q, c, 4000000;\n"
        "@q bra WAIT_LOOP;\n"
        "WAIT_DONE:\n"
        "}\n" :: "r"(bar), "r"(parity) : "memory");
}
__device__ __forceinline__ void tma_load_2d(uint32_t dst, const CUtensorMap* map, uint32_t bar, int c0, int c1) {
    asm volatile(
        "cp.async.bulk.tensor.2d.shared::cluster.global.mbarrier::complete_tx::bytes [%0], [%1, {%3, %4}], [%2];"
        :: "r"(dst), "l"((uint64_t)map), "r"(bar), "r"(c0), "r"(c1) : "memory");
}
__device__ __forceinline__ void wgmma_fence() { asm volatile("wgmma.fence.sync.aligned;" ::: "memory"); }
__device__ __forceinline__ void wgmma_commit() { asm volatile("wgmma.commit_group.sync.aligned;" ::: "memory"); }
template <int N> __device__ __forceinline__ void wgmma_wait() {
    asm volatile("wgmma.wait_group.sync.aligned %0;" :: "n"(N) : "memory");
}
__device__ __forceinline__ uint64_t make_desc(uint32_t addr, uint32_t lbo, uint32_t sbo) {
    uint64_t d = 0;
    d |= (uint64_t)((addr & 0x3FFFF) >> 4);
    d |= (uint64_t)((lbo >> 4) & 0x3FFF) << 16;
    d |= (uint64_t)((sbo >> 4) & 0x3FFF) << 32;
    d |= (uint64_t)1 << 62;
    return d;
}

#define ACC64(d) \
    "+f"(d[0]), "+f"(d[1]), "+f"(d[2]), "+f"(d[3]), "+f"(d[4]), "+f"(d[5]), "+f"(d[6]), "+f"(d[7]), \
    "+f"(d[8]), "+f"(d[9]), "+f"(d[10]), "+f"(d[11]), "+f"(d[12]), "+f"(d[13]), "+f"(d[14]), "+f"(d[15]), \
    "+f"(d[16]), "+f"(d[17]), "+f"(d[18]), "+f"(d[19]), "+f"(d[20]), "+f"(d[21]), "+f"(d[22]), "+f"(d[23]), \
    "+f"(d[24]), "+f"(d[25]), "+f"(d[26]), "+f"(d[27]), "+f"(d[28]), "+f"(d[29]), "+f"(d[30]), "+f"(d[31]), \
    "+f"(d[32]), "+f"(d[33]), "+f"(d[34]), "+f"(d[35]), "+f"(d[36]), "+f"(d[37]), "+f"(d[38]), "+f"(d[39]), \
    "+f"(d[40]), "+f"(d[41]), "+f"(d[42]), "+f"(d[43]), "+f"(d[44]), "+f"(d[45]), "+f"(d[46]), "+f"(d[47]), \
    "+f"(d[48]), "+f"(d[49]), "+f"(d[50]), "+f"(d[51]), "+f"(d[52]), "+f"(d[53]), "+f"(d[54]), "+f"(d[55]), \
    "+f"(d[56]), "+f"(d[57]), "+f"(d[58]), "+f"(d[59]), "+f"(d[60]), "+f"(d[61]), "+f"(d[62]), "+f"(d[63])
#define ACC64_STR \
    "{%0, %1, %2, %3, %4, %5, %6, %7, %8, %9, %10, %11, %12, %13, %14, %15, " \
    "%16, %17, %18, %19, %20, %21, %22, %23, %24, %25, %26, %27, %28, %29, %30, %31, " \
    "%32, %33, %34, %35, %36, %37, %38, %39, %40, %41, %42, %43, %44, %45, %46, %47, " \
    "%48, %49, %50, %51, %52, %53, %54, %55, %56, %57, %58, %59, %60, %61, %62, %63}"

template <int TB>
__device__ __forceinline__ void wgmma_ss_n128(float (&d)[64], uint64_t da, uint64_t db, int scale_d) {
    asm volatile(
        "{\n.reg .pred p;\nsetp.ne.b32 p, %66, 0;\n"
        "wgmma.mma_async.sync.aligned.m64n128k16.f32.bf16.bf16 " ACC64_STR ", %64, %65, p, 1, 1, 0, %67;\n}\n"
        : ACC64(d) : "l"(da), "l"(db), "r"(scale_d), "n"(TB));
}
__device__ __forceinline__ uint32_t desc_lo(uint32_t addr, uint32_t lbo) { return ((addr & 0x3FFFF) >> 4) | ((lbo >> 4) << 16); }
template <int TB>
__device__ __forceinline__ void wgmma_ss_n128_lo(float (&d)[64], uint32_t da_lo, uint32_t db_lo, int scale_d) {
    asm volatile(
        "{\n.reg .pred p;\n.reg .b64 da, db;\nsetp.ne.b32 p, %66, 0;\n"
        "mov.b64 da, {%64, 0x40000040};\nmov.b64 db, {%65, 0x40000040};\n"
        "wgmma.mma_async.sync.aligned.m64n128k16.f32.bf16.bf16 " ACC64_STR ", da, db, p, 1, 1, 0, %67;\n}\n"
        : ACC64(d) : "r"(da_lo), "r"(db_lo), "r"(scale_d), "n"(TB));
}
__device__ __forceinline__ void wgmma_rs_n128_tb(float (&d)[64], uint32_t a0, uint32_t a1, uint32_t a2, uint32_t a3,
                                                 uint64_t db, int scale_d) {
    asm volatile(
        "{\n.reg .pred p;\nsetp.ne.b32 p, %69, 0;\n"
        "wgmma.mma_async.sync.aligned.m64n128k16.f32.bf16.bf16 " ACC64_STR ", {%64, %65, %66, %67}, %68, p, 1, 1, 1;\n}\n"
        : ACC64(d) : "r"(a0), "r"(a1), "r"(a2), "r"(a3), "l"(db), "r"(scale_d));
}
__device__ __forceinline__ void wgmma_rs_n80(float (&d)[40], const uint32_t (&a)[4], uint32_t db_lo, int scale_d) {
    asm volatile(
        "{\n.reg .pred p;\n.reg .b64 db;\nsetp.ne.b32 p, %45, 0;\nmov.b64 db, {%44, 0x40000040};\n"
        "wgmma.mma_async.sync.aligned.m64n80k16.f32.bf16.bf16 "
        "{%0, %1, %2, %3, %4, %5, %6, %7, %8, %9, %10, %11, %12, %13, %14, %15, %16, %17, %18, %19, %20, %21, %22, %23, %24, %25, %26, %27, %28, %29, %30, %31, %32, %33, %34, %35, %36, %37, %38, %39}, "
        "{%40, %41, %42, %43}, db, p, 1, 1, 0;\n}\n"
        : "+f"(d[0]), "+f"(d[1]), "+f"(d[2]), "+f"(d[3]), "+f"(d[4]), "+f"(d[5]), "+f"(d[6]), "+f"(d[7]), "+f"(d[8]), "+f"(d[9]), "+f"(d[10]), "+f"(d[11]), "+f"(d[12]), "+f"(d[13]), "+f"(d[14]), "+f"(d[15]), "+f"(d[16]), "+f"(d[17]), "+f"(d[18]), "+f"(d[19]), "+f"(d[20]), "+f"(d[21]), "+f"(d[22]), "+f"(d[23]), "+f"(d[24]), "+f"(d[25]), "+f"(d[26]), "+f"(d[27]), "+f"(d[28]), "+f"(d[29]), "+f"(d[30]), "+f"(d[31]), "+f"(d[32]), "+f"(d[33]), "+f"(d[34]), "+f"(d[35]), "+f"(d[36]), "+f"(d[37]), "+f"(d[38]), "+f"(d[39])
        : "r"(a[0]), "r"(a[1]), "r"(a[2]), "r"(a[3]), "r"(db_lo), "r"(scale_d));
}
__device__ __forceinline__ void wgmma_ss_n256_tb(float (&d)[128], uint64_t da, uint64_t db, int scale_d) {
    asm volatile(
        "{\n.reg .pred p;\nsetp.ne.b32 p, %130, 0;\n"
        "wgmma.mma_async.sync.aligned.m64n256k16.f32.bf16.bf16 {%0, %1, %2, %3, %4, %5, %6, %7, %8, %9, %10, %11, %12, %13, %14, %15, %16, %17, %18, %19, %20, %21, %22, %23, %24, %25, %26, %27, %28, %29, %30, %31, %32, %33, %34, %35, %36, %37, %38, %39, %40, %41, %42, %43, %44, %45, %46, %47, %48, %49, %50, %51, %52, %53, %54, %55, %56, %57, %58, %59, %60, %61, %62, %63, %64, %65, %66, %67, %68, %69, %70, %71, %72, %73, %74, %75, %76, %77, %78, %79, %80, %81, %82, %83, %84, %85, %86, %87, %88, %89, %90, %91, %92, %93, %94, %95, %96, %97, %98, %99, %100, %101, %102, %103, %104, %105, %106, %107, %108, %109, %110, %111, %112, %113, %114, %115, %116, %117, %118, %119, %120, %121, %122, %123, %124, %125, %126, %127}, %128, %129, p, 1, 1, 0, 1;\n}\n"
        : "+f"(d[0]), "+f"(d[1]), "+f"(d[2]), "+f"(d[3]), "+f"(d[4]), "+f"(d[5]), "+f"(d[6]), "+f"(d[7]), "+f"(d[8]), "+f"(d[9]), "+f"(d[10]), "+f"(d[11]), "+f"(d[12]), "+f"(d[13]), "+f"(d[14]), "+f"(d[15]), "+f"(d[16]), "+f"(d[17]), "+f"(d[18]), "+f"(d[19]), "+f"(d[20]), "+f"(d[21]), "+f"(d[22]), "+f"(d[23]), "+f"(d[24]), "+f"(d[25]), "+f"(d[26]), "+f"(d[27]), "+f"(d[28]), "+f"(d[29]), "+f"(d[30]), "+f"(d[31]), "+f"(d[32]), "+f"(d[33]), "+f"(d[34]), "+f"(d[35]), "+f"(d[36]), "+f"(d[37]), "+f"(d[38]), "+f"(d[39]), "+f"(d[40]), "+f"(d[41]), "+f"(d[42]), "+f"(d[43]), "+f"(d[44]), "+f"(d[45]), "+f"(d[46]), "+f"(d[47]), "+f"(d[48]), "+f"(d[49]), "+f"(d[50]), "+f"(d[51]), "+f"(d[52]), "+f"(d[53]), "+f"(d[54]), "+f"(d[55]), "+f"(d[56]), "+f"(d[57]), "+f"(d[58]), "+f"(d[59]), "+f"(d[60]), "+f"(d[61]), "+f"(d[62]), "+f"(d[63]), "+f"(d[64]), "+f"(d[65]), "+f"(d[66]), "+f"(d[67]), "+f"(d[68]), "+f"(d[69]), "+f"(d[70]), "+f"(d[71]), "+f"(d[72]), "+f"(d[73]), "+f"(d[74]), "+f"(d[75]), "+f"(d[76]), "+f"(d[77]), "+f"(d[78]), "+f"(d[79]), "+f"(d[80]), "+f"(d[81]), "+f"(d[82]), "+f"(d[83]), "+f"(d[84]), "+f"(d[85]), "+f"(d[86]), "+f"(d[87]), "+f"(d[88]), "+f"(d[89]), "+f"(d[90]), "+f"(d[91]), "+f"(d[92]), "+f"(d[93]), "+f"(d[94]), "+f"(d[95]), "+f"(d[96]), "+f"(d[97]), "+f"(d[98]), "+f"(d[99]), "+f"(d[100]), "+f"(d[101]), "+f"(d[102]), "+f"(d[103]), "+f"(d[104]), "+f"(d[105]), "+f"(d[106]), "+f"(d[107]), "+f"(d[108]), "+f"(d[109]), "+f"(d[110]), "+f"(d[111]), "+f"(d[112]), "+f"(d[113]), "+f"(d[114]), "+f"(d[115]), "+f"(d[116]), "+f"(d[117]), "+f"(d[118]), "+f"(d[119]), "+f"(d[120]), "+f"(d[121]), "+f"(d[122]), "+f"(d[123]), "+f"(d[124]), "+f"(d[125]), "+f"(d[126]), "+f"(d[127])
        : "l"(da), "l"(db), "r"(scale_d));
}
__device__ __forceinline__ void stmatrix_x4(uint32_t addr, uint32_t r0, uint32_t r1, uint32_t r2, uint32_t r3) {
    asm volatile("stmatrix.sync.aligned.m8n8.x4.shared.b16 [%0], {%1, %2, %3, %4};" :: "r"(addr), "r"(r0), "r"(r1), "r"(r2), "r"(r3) : "memory");
}
__device__ __forceinline__ void tma_store_2d(const CUtensorMap* map, uint32_t src, int c0, int c1) {
    asm volatile("cp.async.bulk.tensor.2d.global.shared::cta.bulk_group [%0, {%2, %3}], [%1];"
                 :: "l"((uint64_t)map), "r"(src), "r"(c0), "r"(c1) : "memory");
}
__device__ __forceinline__ float ex2f(float x) { float y; asm("ex2.approx.ftz.f32 %0, %1;" : "=f"(y) : "f"(x)); return y; }
__device__ __forceinline__ uint32_t pack_bf16(float lo, float hi) {
    __nv_bfloat162 v = __floats2bfloat162_rn(lo, hi);
    return *reinterpret_cast<uint32_t*>(&v);
}
__device__ __forceinline__ float bf16r(float x) { return __uint_as_float(pack_bf16(0.f, x) & 0xffff0000u); }
__device__ __forceinline__ void mma_16816(float (&c)[4], uint32_t a0, uint32_t a1, uint32_t a2, uint32_t a3,
                                          uint32_t b0, uint32_t b1) {
    asm volatile(
        "mma.sync.aligned.m16n8k16.row.col.f32.bf16.bf16.f32 {%0,%1,%2,%3}, {%4,%5,%6,%7}, {%8,%9}, {%0,%1,%2,%3};"
        : "+f"(c[0]), "+f"(c[1]), "+f"(c[2]), "+f"(c[3])
        : "r"(a0), "r"(a1), "r"(a2), "r"(a3), "r"(b0), "r"(b1));
}
__device__ __forceinline__ void ldmatrix_x4_trans(uint32_t& r0, uint32_t& r1, uint32_t& r2, uint32_t& r3, uint32_t addr) {
    asm volatile("ldmatrix.sync.aligned.m8n8.x4.trans.shared.b16 {%0,%1,%2,%3}, [%4];"
                 : "=r"(r0), "=r"(r1), "=r"(r2), "=r"(r3) : "r"(addr));
}

struct AttnParams {
    CUtensorMap mapQ, mapK, mapV;
    CUtensorMap mapO;
    const bf16 *x, *gate_w;
};
constexpr int FA_STAGES = 2;
constexpr int FA_SMEM = 32768 + FA_STAGES * 65536 + 32768 + 1024 + 256;
constexpr int FA_ITEMS = 16 * NH;
#define FA_RETIRE 100000
#define FA_LASTG 8
__device__ __forceinline__ int fa_qt(int t) {
    constexpr int T0 = (32 - FA_LASTG) * 16;
    return t < T0 ? 15 - ((t & 127) >> 3) : 15 - (t - T0) / FA_LASTG;
}
__device__ __forceinline__ int fa_head(int t) {
    constexpr int T0 = (32 - FA_LASTG) * 16;
    return t < T0 ? (t >> 7) * 8 + (t & 7) : (32 - FA_LASTG) + (t - T0) % FA_LASTG;
}

__global__ void __launch_bounds__(384, 1) attn_kernel(const __grid_constant__ AttnParams P, int retire_cta) {
    extern __shared__ uint8_t smem_raw[];
    uint32_t sbase = (smem_u32(smem_raw) + 1023) & ~1023u;
    const uint32_t sQ = sbase;
    const uint32_t sKV = sbase + 32768;
    const uint32_t sO = sKV + FA_STAGES * 65536;
    const uint32_t bars = sO + 32768;
    const uint32_t bar_q = bars, bar_qe = bars + 8, bar_kf = bars + 16, bar_vf = bar_kf + 8 * FA_STAGES, bar_e = bar_vf + 8 * FA_STAGES,
                   bar_ek = bar_e + 8 * FA_STAGES, slot = bar_ek + 8 * FA_STAGES, bar_of = slot + 16, bar_oe = bar_of + 16, oslot = bar_oe + 16;
    const int warp = threadIdx.x >> 5;
    TS_BEGIN(1);
    int tfirst = 0;
    if (threadIdx.x == 256) tfirst = (int)atomicAdd(&g_ctr[CT_ATTN], 1u);
    if (threadIdx.x == 0) {
        mbar_init(bar_q, 1); mbar_init(bar_qe, 8);
        for (int i = 0; i < FA_STAGES; i++) { mbar_init(bar_kf + 8 * i, 1); mbar_init(bar_vf + 8 * i, 1); mbar_init(bar_e + 8 * i, 8); mbar_init(bar_ek + 8 * i, 8); }
        for (int i = 0; i < 2; i++) { mbar_init(bar_of + 8 * i, 1); mbar_init(bar_oe + 8 * i, 1); }
        asm volatile("fence.mbarrier_init.release.cluster;" ::: "memory");
    }
    if (threadIdx.x == 256) asm volatile("st.shared.s32 [%0], %1;" :: "r"(slot + 8), "r"(tfirst) : "memory");
    __syncthreads();
    pdl_launch_dependents();
    if (warp >= 8) {
        asm volatile("setmaxnreg.dec.sync.aligned.u32 40;");
        if (warp == 11) {
            const int lane = threadIdx.x & 31;
            const uint4 gv0 = __ldg(reinterpret_cast<const uint4*>(P.gate_w) + lane), gv1 = __ldg(reinterpret_cast<const uint4*>(P.gate_w) + 32 + lane);
            const uint32_t gw[8] = {gv0.x, gv0.y, gv0.z, gv0.w, gv1.x, gv1.y, gv1.z, gv1.w};
#pragma unroll 1
            for (int r = blockIdx.x; r < SEQ; r += gridDim.x) {
                const uint4 x0 = __ldg(reinterpret_cast<const uint4*>(P.x + (size_t)r * DM) + lane), x1 = __ldg(reinterpret_cast<const uint4*>(P.x + (size_t)r * DM) + 32 + lane);
                const uint32_t xw[8] = {x0.x, x0.y, x0.z, x0.w, x1.x, x1.y, x1.z, x1.w};
                float sum = 0.f;
#pragma unroll
                for (int e = 0; e < 8; e++) {
                    const uint32_t pr = pack_bf16(__uint_as_float(xw[e] << 16) * __uint_as_float(gw[e] << 16), __uint_as_float(xw[e] & 0xffff0000u) * __uint_as_float(gw[e] & 0xffff0000u));
                    sum += __uint_as_float(pr << 16) + __uint_as_float(pr & 0xffff0000u);
                }
#pragma unroll
                for (int o = 16; o; o >>= 1) sum += __shfl_xor_sync(0xffffffff, sum, o);
                if (lane == 0) g_gate[r] = bf16r(1.f / (1.f + __expf(-bf16r(sum))));
            }
            if (lane == 0) signal_ctr(CT_G);
        }
        if (threadIdx.x == 288 || threadIdx.x == 320) {
            const int wg = threadIdx.x == 288 ? 0 : 1;
            const uint32_t stg = sO + wg * 16384;
            for (int n = 0;; n++) {
                mbar_wait(bar_of + 8 * wg, n & 1);
                int t;
                asm volatile("ld.shared.s32 %0, [%1];" : "=r"(t) : "r"(oslot + wg * 4) : "memory");
                if (t < 0) break;
                const int qt = fa_qt(t), h = fa_head(t);
                tma_store_2d(&P.mapO, stg, 0, h * SEQ + qt * 128 + wg * 64);
                tma_store_2d(&P.mapO, stg + 8192, 64, h * SEQ + qt * 128 + wg * 64);
                asm volatile("cp.async.bulk.commit_group;" ::: "memory");
                asm volatile("cp.async.bulk.wait_group.read 0;" ::: "memory");
                mbar_arrive(bar_oe + 8 * wg);
                asm volatile("cp.async.bulk.wait_group 0;" ::: "memory");
                signal_ctr(CT_CA + qt * 2 + (h >= O2_HE));
            }
        }
        if (threadIdx.x == 256) {
            int it = 0, hp_ready = 0;
            for (int item = 0;; item++) {
                int t = tfirst;
                if (item > 0) {
                    bool quit = false;
                    if ((int)blockIdx.x >= retire_cta) {
                        unsigned int v;
                        asm volatile("ld.relaxed.gpu.global.u32 %0, [%1];" : "=r"(v) : "l"(&g_ctr[CT_ATTN]) : "memory");
                        quit = v >= FA_RETIRE;
                    }
                    t = quit ? FA_ITEMS : (int)atomicAdd(&g_ctr[CT_ATTN], 1u);
                }
                const bool valid = t < FA_ITEMS;
                const int qt = fa_qt(t), h = fa_head(t);
                if (valid && !((hp_ready >> (h >> 1)) & 1)) { wait_ctr(CT_AP + (h >> 1), 96u); hp_ready |= 1 << (h >> 1); }
                mbar_wait(bar_qe, (item & 1) ^ 1);
                asm volatile("st.shared.s32 [%0], %1;" :: "r"(slot + (item & 1) * 4), "r"(valid ? t : -1) : "memory");
                if (!valid) { mbar_arrive(bar_q); break; }
                mbar_expect_tx(bar_q, 32768);
                tma_load_2d(sQ, &P.mapQ, bar_q, 0, h * SEQ + qt * 128);
                tma_load_2d(sQ + 16384, &P.mapQ, bar_q, 64, h * SEQ + qt * 128);
                for (int j = 0; j <= qt; j++, it++) {
                    const int s = it % FA_STAGES;
                    mbar_wait(bar_ek + 8 * s, ((it / FA_STAGES) & 1) ^ 1);
                    const uint32_t sk = sKV + s * 65536, sv = sk + 32768;
                    mbar_expect_tx(bar_kf + 8 * s, 32768);
                    tma_load_2d(sk, &P.mapK, bar_kf + 8 * s, 0, h * SEQ + j * 128);
                    tma_load_2d(sk + 16384, &P.mapK, bar_kf + 8 * s, 64, h * SEQ + j * 128);
                    mbar_wait(bar_e + 8 * s, ((it / FA_STAGES) & 1) ^ 1);
                    mbar_expect_tx(bar_vf + 8 * s, 32768);
                    tma_load_2d(sv, &P.mapV, bar_vf + 8 * s, 0, h * SEQ + j * 128);
                    tma_load_2d(sv + 16384, &P.mapV, bar_vf + 8 * s, 64, h * SEQ + j * 128);
                }
            }
        }
    } else {
        asm volatile("setmaxnreg.inc.sync.aligned.u32 232;");
        const int wg = warp >> 2;
        const int lane = threadIdx.x & 31;
        float o[64];
        float mrow0, mrow1, lrow0, lrow1;
        const float sc = 0.08838834764831845f * 1.4426950408889634f;
        const int r0 = wg * 64 + (warp & 3) * 16 + (lane >> 2);
        float sacc[64];
        uint32_t pa[32];
        float a0 = 1.f, a1 = 1.f;
        auto issue_qk = [&](int it) {
            const int s = it % FA_STAGES;
            const uint32_t sk = sKV + s * 65536;
            mbar_wait(bar_kf + 8 * s, (it / FA_STAGES) & 1);
            wgmma_fence();
#pragma unroll
            for (int kk = 0; kk < 8; kk++) {
                uint64_t da = make_desc(sQ + (kk >> 2) * 16384 + wg * 8192 + (kk & 3) * 32, 16, 1024);
                uint64_t db = make_desc(sk + (kk >> 2) * 16384 + (kk & 3) * 32, 16, 1024);
                wgmma_ss_n128<0>(sacc, da, db, kk != 0);
            }
            wgmma_commit();
        };
        auto issue_pv = [&](int it) {
            const int s = it % FA_STAGES;
            const uint32_t sv = sKV + s * 65536 + 32768;
            mbar_wait(bar_vf + 8 * s, (it / FA_STAGES) & 1);
            wgmma_fence();
#pragma unroll
            for (int kk = 0; kk < 8; kk++) {
                uint64_t db = make_desc(sv + kk * 2048, 16384, 1024);
                wgmma_rs_n128_tb(o, pa[kk * 4 + 0], pa[kk * 4 + 1], pa[kk * 4 + 2], pa[kk * 4 + 3], db, 1);
            }
            wgmma_commit();
        };
        auto softmax_stats = [&](bool diag) {
            if (diag) {
#pragma unroll
                for (int i = 0; i < 64; i++) {
                    int col = (i >> 2) * 8 + (lane & 3) * 2 + (i & 1);
                    int row = r0 + ((i & 2) ? 8 : 0);
                    if (col > row) sacc[i] = -INFINITY;
                }
            }
            float mx0 = -INFINITY, mx1 = -INFINITY;
#pragma unroll
            for (int i = 0; i < 16; i++) {
                mx0 = fmaxf(mx0, fmaxf(sacc[i * 4 + 0], sacc[i * 4 + 1]));
                mx1 = fmaxf(mx1, fmaxf(sacc[i * 4 + 2], sacc[i * 4 + 3]));
            }
            mx0 = fmaxf(mx0, __shfl_xor_sync(0xffffffff, mx0, 1));
            mx0 = fmaxf(mx0, __shfl_xor_sync(0xffffffff, mx0, 2));
            mx1 = fmaxf(mx1, __shfl_xor_sync(0xffffffff, mx1, 1));
            mx1 = fmaxf(mx1, __shfl_xor_sync(0xffffffff, mx1, 2));
            const float mn0 = fmaxf(mrow0, mx0), mn1 = fmaxf(mrow1, mx1);
            a0 = ex2f((mrow0 - mn0) * sc); a1 = ex2f((mrow1 - mn1) * sc);
            mrow0 = mn0; mrow1 = mn1;
            const float ms0 = mn0 * sc, ms1 = mn1 * sc;
            float sum0 = 0.f, sum1 = 0.f;
#pragma unroll
            for (int i = 0; i < 16; i++) {
                sacc[i * 4 + 0] = ex2f(fmaf(sacc[i * 4 + 0], sc, -ms0));
                sacc[i * 4 + 1] = ex2f(fmaf(sacc[i * 4 + 1], sc, -ms0));
                sacc[i * 4 + 2] = ex2f(fmaf(sacc[i * 4 + 2], sc, -ms1));
                sacc[i * 4 + 3] = ex2f(fmaf(sacc[i * 4 + 3], sc, -ms1));
                sum0 += sacc[i * 4 + 0] + sacc[i * 4 + 1];
                sum1 += sacc[i * 4 + 2] + sacc[i * 4 + 3];
            }
            lrow0 = lrow0 * a0 + sum0;
            lrow1 = lrow1 * a1 + sum1;
        };
        auto pack_p = [&]() {
#pragma unroll
            for (int i = 0; i < 16; i++) {
                pa[i * 2 + 0] = pack_bf16(sacc[i * 4 + 0], sacc[i * 4 + 1]);
                pa[i * 2 + 1] = pack_bf16(sacc[i * 4 + 2], sacc[i * 4 + 3]);
            }
        };
        int it = 0;
        if (wg == 1) asm volatile("bar.arrive 1, 256;" ::: "memory");
        for (int item = 0;; item++) {
            mbar_wait(bar_q, item & 1);
            int t;
            asm volatile("ld.shared.s32 %0, [%1];" : "=r"(t) : "r"(slot + (item & 1) * 4) : "memory");
            if (t < 0) {
                if ((threadIdx.x & 127) == 0) {
                    mbar_wait(bar_oe + 8 * wg, (item & 1) ^ 1);
                    asm volatile("st.shared.s32 [%0], %1;" :: "r"(oslot + wg * 4), "r"(-1) : "memory");
                    mbar_arrive(bar_of + 8 * wg);
                }
                break;
            }
            const int qt = fa_qt(t);
            const int nkv = qt + 1;
#pragma unroll
            for (int i = 0; i < 64; i++) o[i] = 0.f;
            mrow0 = -INFINITY; mrow1 = -INFINITY; lrow0 = 0.f; lrow1 = 0.f;
            asm volatile("bar.sync %0, 256;" :: "r"(1 + wg) : "memory");
            issue_qk(it);
            asm volatile("bar.arrive %0, 256;" :: "r"(2 - wg) : "memory");
            wgmma_wait<0>();
            if (lane == 0) { mbar_arrive(bar_ek + 8 * (it % FA_STAGES)); if (nkv == 1) mbar_arrive(bar_qe); }
            softmax_stats(nkv == 1);
            pack_p();
#pragma unroll 1
            for (int j = 1; j < nkv; j++) {
                asm volatile("bar.sync %0, 256;" :: "r"(1 + wg) : "memory");
                issue_qk(it + j);
                issue_pv(it + j - 1);
                asm volatile("bar.arrive %0, 256;" :: "r"(2 - wg) : "memory");
                wgmma_wait<1>();
                if (lane == 0) { mbar_arrive(bar_ek + 8 * ((it + j) % FA_STAGES)); if (j == nkv - 1) mbar_arrive(bar_qe); }
                softmax_stats(j == nkv - 1);
                wgmma_wait<0>();
                if (lane == 0) mbar_arrive(bar_e + 8 * ((it + j - 1) % FA_STAGES));
#pragma unroll
                for (int i = 0; i < 16; i++) {
                    o[i * 4 + 0] *= a0; o[i * 4 + 1] *= a0; o[i * 4 + 2] *= a1; o[i * 4 + 3] *= a1;
                }
                pack_p();
            }
            issue_pv(it + nkv - 1);
            wgmma_wait<0>();
            if (lane == 0) mbar_arrive(bar_e + 8 * ((it + nkv - 1) % FA_STAGES));
            it += nkv;
            lrow0 += __shfl_xor_sync(0xffffffff, lrow0, 1);
            lrow0 += __shfl_xor_sync(0xffffffff, lrow0, 2);
            lrow1 += __shfl_xor_sync(0xffffffff, lrow1, 1);
            lrow1 += __shfl_xor_sync(0xffffffff, lrow1, 2);
            const float i0 = 1.f / lrow0, i1 = 1.f / lrow1;
            const uint32_t stg = sO + wg * 16384;
            mbar_wait(bar_oe + 8 * wg, (item & 1) ^ 1);
            {
                const int row = (warp & 3) * 16 + (lane >> 2);
#pragma unroll
                for (int i = 0; i < 4; i++) {
                    const int ch = i * 4 + (lane & 3);
                    const uint32_t a = stg + (ch >> 3) * 8192 + row * 128 + (((ch & 7) ^ (row & 7)) << 4);
                    const float* q = &o[i * 16];
                    asm volatile("st.shared.v4.b32 [%0], {%1, %2, %3, %4};" :: "r"(a), "r"(pack_bf16(q[0] * i0, q[1] * i0)), "r"(pack_bf16(q[4] * i0, q[5] * i0)),
                                 "r"(pack_bf16(q[8] * i0, q[9] * i0)), "r"(pack_bf16(q[12] * i0, q[13] * i0)) : "memory");
                    asm volatile("st.shared.v4.b32 [%0], {%1, %2, %3, %4};" :: "r"(a + 1024), "r"(pack_bf16(q[2] * i1, q[3] * i1)), "r"(pack_bf16(q[6] * i1, q[7] * i1)),
                                 "r"(pack_bf16(q[10] * i1, q[11] * i1)), "r"(pack_bf16(q[14] * i1, q[15] * i1)) : "memory");
                }
            }
            asm volatile("fence.proxy.async.shared::cta;" ::: "memory");
            asm volatile("bar.sync %0, 128;" :: "r"(3 + wg) : "memory");
            if ((threadIdx.x & 127) == 0) {
                asm volatile("st.shared.s32 [%0], %1;" :: "r"(oslot + wg * 4), "r"(t) : "memory");
                mbar_arrive(bar_of + 8 * wg);
            }
        }
        TS_END(1);
    }
}

__device__ __forceinline__ uint32_t cluster_ctarank() {
    uint32_t r; asm volatile("mov.u32 %0, %%cluster_ctarank;" : "=r"(r)); return r;
}
__device__ __forceinline__ uint32_t mapa_u32(uint32_t addr, uint32_t rank) {
    uint32_t r; asm volatile("mapa.shared::cluster.u32 %0, %1, %2;" : "=r"(r) : "r"(addr), "r"(rank)); return r;
}
__device__ __forceinline__ void cluster_sync_all() {
    asm volatile("barrier.cluster.arrive.release.aligned;\nbarrier.cluster.wait.acquire.aligned;" ::: "memory");
}
__device__ __forceinline__ void st_async_v4(uint32_t addr, uint32_t a, uint32_t b, uint32_t c, uint32_t d, uint32_t mbar) {
    asm volatile("st.async.weak.shared::cluster.mbarrier::complete_tx::bytes.v4.b32 [%0], {%1, %2, %3, %4}, [%5];"
                 :: "r"(addr), "r"(a), "r"(b), "r"(c), "r"(d), "r"(mbar) : "memory");
}
__device__ __forceinline__ void st_async_v2(uint32_t addr, uint32_t a, uint32_t b, uint32_t mbar) {
    asm volatile("st.async.weak.shared::cluster.mbarrier::complete_tx::bytes.v2.b32 [%0], {%1, %2}, [%3];"
                 :: "r"(addr), "r"(a), "r"(b), "r"(mbar) : "memory");
}
__device__ __forceinline__ void st_async_b32(uint32_t addr, uint32_t a, uint32_t mbar) {
    asm volatile("st.async.weak.shared::cluster.mbarrier::complete_tx::bytes.b32 [%0], %1, [%2];" :: "r"(addr), "r"(a), "r"(mbar) : "memory");
}
__device__ __forceinline__ void pace(int cycles) {
    if (cycles > 0) {
        uint32_t t0, t;
        asm volatile("mov.u32 %0, %%clock;" : "=r"(t0));
        do { asm volatile("mov.u32 %0, %%clock;" : "=r"(t)); } while (t - t0 < (uint32_t)cycles);
    }
}
__device__ __forceinline__ void mbar_wait_cl(uint32_t bar, uint32_t parity) {
    uint32_t done = 0;
    for (int it = 0; it < (1 << 22) && !done; it++) {
        asm volatile(
            "{\n.reg .pred p;\n"
            "mbarrier.try_wait.parity.shared::cta.b64 p, [%1], %2;\n"
            "selp.u32 %0, 1, 0, p;\n}\n" : "=r"(done) : "r"(bar), "r"(parity) : "memory");
    }
}
__device__ __forceinline__ uint32_t mbar_test(uint32_t bar, uint32_t parity) {
    uint32_t done;
    asm volatile(
        "{\n.reg .pred p;\n"
        "mbarrier.test_wait.parity.shared::cta.b64 p, [%1], %2;\n"
        "selp.u32 %0, 1, 0, p;\n}\n" : "=r"(done) : "r"(bar), "r"(parity) : "memory");
    return done;
}
__device__ __forceinline__ void ldmatrix_x4(uint32_t& r0, uint32_t& r1, uint32_t& r2, uint32_t& r3, uint32_t addr) {
    asm volatile("ldmatrix.sync.aligned.m8n8.x4.shared.b16 {%0,%1,%2,%3}, [%4];"
                 : "=r"(r0), "=r"(r1), "=r"(r2), "=r"(r3) : "r"(addr));
}
__device__ __forceinline__ void cp_async16(uint32_t dst, const void* src) {
    asm volatile("cp.async.cg.shared.global [%0], [%1], 16;" :: "r"(dst), "l"(src) : "memory");
}

#define DBG(i)
#define DBGW(i, w)
__device__ __forceinline__ void tma_load_2d_mc(uint32_t dst, const CUtensorMap* map, uint32_t bar, int c0, int c1, uint16_t mask) {
    asm volatile(
        "cp.async.bulk.tensor.2d.shared::cluster.global.mbarrier::complete_tx::bytes.multicast::cluster [%0], [%1, {%3, %4}], [%2], %5;"
        :: "r"(dst), "l"((uint64_t)map), "r"(bar), "r"(c0), "r"(c1), "h"(mask) : "memory");
}
__device__ __forceinline__ void bulk_s2s(uint32_t dst_cl, uint32_t src, uint32_t bytes, uint32_t bar_cl) {
    asm volatile("cp.async.bulk.shared::cluster.shared::cta.mbarrier::complete_tx::bytes [%0], [%1], %2, [%3];"
                 :: "r"(dst_cl), "r"(src), "r"(bytes), "r"(bar_cl) : "memory");
}
__device__ __forceinline__ bool elect_one() {
    uint32_t p;
    asm volatile("{\n.reg .pred p;\nelect.sync _|p, 0xffffffff;\nselp.u32 %0, 1, 0, p;\n}" : "=r"(p));
    return p;
}
__device__ __forceinline__ void fence_async_smem() { asm volatile("fence.proxy.async.shared::cta;" ::: "memory"); }
template <int ID, int N> __device__ __forceinline__ void bar_sync() { asm volatile("bar.sync %0, %1;" :: "n"(ID), "n"(N) : "memory"); }
template <int ID, int N> __device__ __forceinline__ void bar_arrive() { asm volatile("bar.arrive %0, %1;" :: "n"(ID), "n"(N) : "memory"); }
__device__ __forceinline__ void sts32(uint32_t a, uint32_t v) { asm volatile("st.shared.u32 [%0], %1;" :: "r"(a), "r"(v) : "memory"); }
__device__ __forceinline__ void ldsm_x4(uint32_t* r, uint32_t addr) {
    asm volatile("ldmatrix.sync.aligned.m8n8.x4.shared.b16 {%0,%1,%2,%3}, [%4];" : "=r"(r[0]), "=r"(r[1]), "=r"(r[2]), "=r"(r[3]) : "r"(addr) : "memory");
}
__device__ __forceinline__ uint32_t pin(uint32_t v) { asm volatile("" : "+r"(v)); return v; }
constexpr uint32_t DHI128 = 0x40000040u, DHI32 = 0xC0000010u;
#define ACC16(d) "+f"(d[0]), "+f"(d[1]), "+f"(d[2]), "+f"(d[3]), "+f"(d[4]), "+f"(d[5]), "+f"(d[6]), "+f"(d[7]), "+f"(d[8]), "+f"(d[9]), "+f"(d[10]), \
    "+f"(d[11]), "+f"(d[12]), "+f"(d[13]), "+f"(d[14]), "+f"(d[15])
#define ACC20(d) ACC16(d), "+f"(d[16]), "+f"(d[17]), "+f"(d[18]), "+f"(d[19])
__device__ __forceinline__ void wgmma_rs(float (&d)[16], const uint32_t (&a)[4], uint32_t db_lo) {
    asm volatile(
        "{\n.reg .b64 db;\nmov.b64 db, {%20, %21};\n"
        "wgmma.mma_async.sync.aligned.m64n32k16.f32.bf16.bf16 {%0,%1,%2,%3,%4,%5,%6,%7,%8,%9,%10,%11,%12,%13,%14,%15}, {%16,%17,%18,%19}, db, 1, 1, 1, 0;\n}\n"
        : ACC16(d) : "r"(a[0]), "r"(a[1]), "r"(a[2]), "r"(a[3]), "r"(db_lo), "n"(DHI128));
}
__device__ __forceinline__ void wgmma_rs(float (&d)[20], const uint32_t (&a)[4], uint32_t db_lo) {
    asm volatile(
        "{\n.reg .b64 db;\nmov.b64 db, {%24, %25};\n"
        "wgmma.mma_async.sync.aligned.m64n40k16.f32.bf16.bf16 {%0,%1,%2,%3,%4,%5,%6,%7,%8,%9,%10,%11,%12,%13,%14,%15,%16,%17,%18,%19}, {%20,%21,%22,%23}, db, 1, 1, 1, 0;\n}\n"
        : ACC20(d) : "r"(a[0]), "r"(a[1]), "r"(a[2]), "r"(a[3]), "r"(db_lo), "n"(DHI128));
}
template <uint32_t AHI, uint32_t BHI>
__device__ __forceinline__ void wgmma_ss(float (&d)[16], uint32_t da_lo, uint32_t db_lo) {
    asm volatile(
        "{\n.reg .b64 da, db;\nmov.b64 da, {%16, %18};\nmov.b64 db, {%17, %19};\n"
        "wgmma.mma_async.sync.aligned.m64n32k16.f32.bf16.bf16 {%0,%1,%2,%3,%4,%5,%6,%7,%8,%9,%10,%11,%12,%13,%14,%15}, da, db, 1, 1, 1, 0, 0;\n}\n"
        : ACC16(d) : "r"(da_lo), "r"(db_lo), "n"(AHI), "n"(BHI));
}
template <uint32_t AHI, uint32_t BHI>
__device__ __forceinline__ void wgmma_ss(float (&d)[20], uint32_t da_lo, uint32_t db_lo) {
    asm volatile(
        "{\n.reg .b64 da, db;\nmov.b64 da, {%20, %22};\nmov.b64 db, {%21, %23};\n"
        "wgmma.mma_async.sync.aligned.m64n40k16.f32.bf16.bf16 {%0,%1,%2,%3,%4,%5,%6,%7,%8,%9,%10,%11,%12,%13,%14,%15,%16,%17,%18,%19}, da, db, 1, 1, 1, 0, 0;\n}\n"
        : ACC20(d) : "r"(da_lo), "r"(db_lo), "n"(AHI), "n"(BHI));
}
__device__ __forceinline__ void wgmma_ss_n8(float (&d)[4], uint32_t da_lo, uint32_t db_lo) {
    asm volatile(
        "{\n.reg .b64 da, db;\nmov.b64 da, {%4, %6};\nmov.b64 db, {%5, %7};\n"
        "wgmma.mma_async.sync.aligned.m64n8k16.f32.bf16.bf16 {%0,%1,%2,%3}, da, db, 1, 1, 1, 1, 0;\n}\n"
        : "+f"(d[0]), "+f"(d[1]), "+f"(d[2]), "+f"(d[3]) : "r"(da_lo), "r"(db_lo), "n"(DHI128), "n"(DHI32));
}

constexpr uint32_t C2_WO = 0;
constexpr uint32_t C2_XB = 65536;
constexpr uint32_t C2_XS = 40960;
constexpr uint32_t C2_QX = C2_XB + 2 * C2_XS;
constexpr uint32_t C2_KX = C2_QX + 4096;
constexpr uint32_t C2_VT = C2_KX + 5120;
constexpr uint32_t C2_OB = C2_VT + 12288;
constexpr uint32_t C2_QM = C2_OB + 8192;
constexpr uint32_t C2_SC = C2_QM + 1024;
constexpr uint32_t C2_PB = C2_SC + 2560;
constexpr uint32_t C2_BAR = C2_PB + 768;
constexpr uint32_t C2_PX = C2_BAR + 256;
constexpr uint32_t C2_SX = C2_PX + 3072;
#define C2_NS 4
constexpr uint32_t C2_WS = C2_SX + 20480;
constexpr int C2_SMEM = C2_WS + 3 * C2_NS * 2048;
static_assert(C2_PX % 256 == 0 && C2_WS % 256 == 0 && C2_SMEM <= 232448, "smem map");
#define CH_POLL_DELAY 200

__device__ __forceinline__ void c2_load_w(uint32_t (&w)[32][4], const bf16* __restrict__ W, int rank, int col, uint32_t ws) {
#pragma unroll
    for (int e = 0; e < 32; e++) {
        const bf16* p = W + (size_t)((((rank - (e >> 2)) & 7) * 64) + (e & 3) * 16) * NQ + col;
        w[e][0] = __ldg(reinterpret_cast<const uint32_t*>(p));
        w[e][1] = __ldg(reinterpret_cast<const uint32_t*>(p + NQ));
        w[e][2] = __ldg(reinterpret_cast<const uint32_t*>(p + 8 * NQ));
        w[e][3] = __ldg(reinterpret_cast<const uint32_t*>(p + 9 * NQ));
    }
#pragma unroll
    for (int e = 0; e < 32; e++) {
        const uint32_t w0 = w[e][0], w1 = w[e][1], w2 = w[e][2], w3 = w[e][3];
        w[e][0] = __byte_perm(w0, w1, 0x5410); w[e][1] = __byte_perm(w0, w1, 0x7632);
        w[e][2] = __byte_perm(w2, w3, 0x5410); w[e][3] = __byte_perm(w2, w3, 0x7632);
        if (e < C2_NS) stmatrix_x4(ws + e * 2048, w[e][0], w[e][1], w[e][2], w[e][3]);
    }
    fence_async_smem();
    asm volatile("bar.sync %0, 128;" :: "r"(8 + (threadIdx.x >> 7)) : "memory");
}
template <int NA>
__device__ __forceinline__ void c2_xstream(float (&acc)[NA], const uint32_t (&w)[32][4], uint32_t xlo, uint32_t rank, uint32_t wslo) {
#pragma unroll
    for (int i = 0; i < NA; i++) acc[i] = 0.f;
    wgmma_fence();
#pragma unroll
    for (int e = 0; e < 32; e++) {
        if (e < C2_NS) wgmma_ss<DHI32, DHI128>(acc, wslo + e * 128, xlo + ((rank - (e >> 2)) & 7) * 320 + (e & 3) * 2);
        else wgmma_rs(acc, w[e], xlo + ((rank - (e >> 2)) & 7) * 320 + (e & 3) * 2);
    }
    wgmma_commit();
    wgmma_wait<0>();
}
__device__ __forceinline__ void c2_mma_slot(float (&a)[4][4], const uint32_t (&w)[32][4], int slot, const uint32_t* b, uint32_t ws) {
#pragma unroll
    for (int kk = 0; kk < 4; kk++) {
        const int e = slot * 4 + kk;
        if (e < C2_NS) {
            uint32_t t[4];
            ldsm_x4(t, ws + e * 2048);
            mma_16816(a[kk], t[0], t[1], t[2], t[3], b[2 * kk], b[2 * kk + 1]);
        } else mma_16816(a[kk], w[e][0], w[e][1], w[e][2], w[e][3], b[2 * kk], b[2 * kk + 1]);
    }
}
__device__ __forceinline__ constexpr int c2_grp(int i) { return i < 2 ? i : 1 + (i >> 1); }

__global__ void __cluster_dims__(8, 1, 1) __launch_bounds__(384, 1)
chain_kernel(const __grid_constant__ CUtensorMap mapX, const bf16* __restrict__ mem0, const bf16* __restrict__ Wq, const bf16* __restrict__ Wk,
             const bf16* __restrict__ Wv, const bf16* __restrict__ Wo) {
    extern __shared__ __align__(1024) uint8_t smem_chain[];
    const uint32_t sb = smem_u32(smem_chain);
    const uint32_t dlo = ((sb & 0x3FFFF) >> 4) | (1u << 16);
    const int tid = threadIdx.x, lane = tid & 31;
    const int warp = __shfl_sync(0xffffffff, tid >> 5, 0), wg = warp >> 2, w4 = warp & 3;
    const uint32_t rank = cluster_ctarank();
    const int C = blockIdx.x >> 3;
    const int h = C * 4 + (rank >> 1);
    const int g = lane >> 2, qc = lane & 3;
    pdl_launch_dependents();
    TS_BEGIN(2);
    const uint32_t bar_m = sb + C2_BAR, bar_o = bar_m + 64, bar_sc = bar_m + 128, bar_x = bar_m + 136, bar_sx = bar_m + 152;
    if (tid == 0) {
        for (int j = 0; j < 5; j++) { mbar_init(bar_m + 8 * j, j ? 1 : 4); mbar_init(bar_o + 8 * j, j ? 1 : 4); }
        for (int j = 0; j < 5; j++) mbar_init(bar_sc + 8 * j, 1);
        asm volatile("fence.mbarrier_init.release.cluster;" ::: "memory");
    }
    __syncthreads();
    cluster_sync_all();
    if (tid == 0) {
        mbar_expect_tx(bar_x, 32768);
        tma_load_2d_mc(sb + C2_XB + rank * 5120, &mapX, bar_x, rank * 64, 0, (uint16_t)0xff);
    }
    for (int i = tid; i < 2048; i += 384) {
        const int k = i >> 2, b = i & 3;
        const uint4* p = reinterpret_cast<const uint4*>(Wo + (size_t)(C * 512 + ((rank - (k >> 6)) & 7) * 64 + (k & 63)) * DM + rank * 64 + b * 16);
        const uint4 u = __ldg(p), v = __ldg(p + 1);
        const uint32_t a = sb + C2_WO + k * 128;
        asm volatile("st.shared.v4.b32 [%0], {%1, %2, %3, %4};" :: "r"(a + (((2 * b) ^ (k & 7)) << 4)), "r"(__byte_perm(u.x, u.y, 0x5410)),
                     "r"(__byte_perm(u.z, u.w, 0x5410)), "r"(__byte_perm(v.x, v.y, 0x5410)), "r"(__byte_perm(v.z, v.w, 0x5410)) : "memory");
        asm volatile("st.shared.v4.b32 [%0], {%1, %2, %3, %4};" :: "r"(a + (((2 * b + 1) ^ (k & 7)) << 4)), "r"(__byte_perm(u.x, u.y, 0x7632)),
                     "r"(__byte_perm(u.z, u.w, 0x7632)), "r"(__byte_perm(v.x, v.y, 0x7632)), "r"(__byte_perm(v.z, v.w, 0x7632)) : "memory");
    }
    for (int i = tid; i < 512; i += 384) {
        const int row = i >> 6, c = (i >> 3) & 7, j = i & 7;
        const uint4 u = __ldg(reinterpret_cast<const uint4*>(mem0) + i);
        asm volatile("st.shared.v4.b32 [%0], {%1, %2, %3, %4};" :: "r"(sb + C2_XB + c * 5120 + 4096 + row * 128 + ((j ^ row) << 4)),
                     "r"(u.x), "r"(u.y), "r"(u.z), "r"(u.w) : "memory");
    }
    for (int i = tid; i < 2 * 512 + 256; i += 384)
        sts32(sb + (i < 1024 ? C2_VT + (i >> 9) * 6144 + 4096 + (i & 511) * 4 : C2_PX + 2048 + (i - 1024) * 4), 0u);
    fence_async_smem();
    __syncthreads();

    const uint32_t t32 = w4 * 256 + qc * 64 + (((g >> 2) ^ (qc >> 1)) << 4) + (g & 3) * 4;
    const uint32_t t128 = qc * 256 + (((2 * w4 + (g >> 2)) ^ (2 * qc)) << 4) + (g & 3) * 4;
    const uint32_t a32 = (w4 * 16 + (lane & 15)) * 32 + (((lane >> 4) ^ ((lane >> 2) & 1)) << 4);
    const uint32_t ws = sb + C2_WS + wg * (C2_NS * 2048) + a32;
    uint32_t w[32][4];
    const int wcol = h * HD + (rank & 1) * 64 + w4 * 16 + 2 * g + 2 * qc * NQ;
    auto proj_mem = [&](float (&a)[4][4], int s) {
        uint32_t b[16];
#pragma unroll
        for (int i = 0; i < 16; i++) a[i >> 2][i & 3] = 0.f;
        const uint32_t par = (s & 1) ^ 1;
        const uint32_t l128 = (lane & 7) * 128 + (((lane >> 3) ^ (lane & 7)) << 4);
        const uint32_t mb = sb + C2_XB + (s & 1) * C2_XS + 4096;
        auto ldb = [&](uint32_t* bb, int i) {
            ldsm_x4(bb, mb + ((rank - i) & 7) * 5120 + l128);
            ldsm_x4(bb + 4, mb + ((rank - i) & 7) * 5120 + (l128 ^ 64));
        };
        mbar_wait(bar_m, par);
        ldb(b, 0);
        c2_mma_slot(a, w, 0, b, ws);
        mbar_wait(bar_m + 8, par);
        DBGW(1 + 16 * wg, 0);
        ldb(b, 1);
        uint32_t nxt = mbar_test(bar_m + 16, par);
        c2_mma_slot(a, w, 1, b, ws);
#pragma unroll
        for (int i = 2; i < 8; i += 2) {
            if (__builtin_expect(!nxt, 0)) mbar_wait(bar_m + 8 * c2_grp(i), par);
            if (i == 6) DBGW(2 + 16 * wg, 0);
            ldb(b, i);
            ldb(b + 8, i + 1);
            if (i < 6) nxt = mbar_test(bar_m + 8 * c2_grp(i + 2), par);
            c2_mma_slot(a, w, i, b, ws);
            c2_mma_slot(a, w, i + 1, b + 8, ws);
        }
#pragma unroll
        for (int i = 0; i < 4; i++) a[0][i] = (a[0][i] + a[1][i]) + (a[2][i] + a[3][i]);
    };
    auto store_x = [&](const float (&acc)[16], uint32_t base) {
#pragma unroll
        for (int j = 0; j < 4; j++) {
            sts32(base + t128 + j * 1024, pack_bf16(acc[4 * j], acc[4 * j + 2]));
            sts32(base + (t128 ^ 16) + 128 + j * 1024, pack_bf16(acc[4 * j + 1], acc[4 * j + 3]));
        }
    };
    const float scale = 0.08838834764831845f, l2e = 1.4426950408889634f;

    if (wg == 0) {
        c2_load_w(w, Wq, rank, wcol, ws);
        TS_END(6);
        TS_BEGIN(5);
#pragma unroll 1
        for (int s = -1;;) {
            uint32_t xok = 0;
            if (s >= 0) {
                float acc[4] = {0.f, 0.f, 0.f, 0.f};
                const uint32_t tag = ((s >> 1) & 1) ^ 1;
                uint32_t* dst = reinterpret_cast<uint32_t*>(g_xbuf + (((s & 1) * 8 + rank) * 8 + C) * 128) + qc * 64 + w4 * 8 + g;
                asm volatile("" : "+l"(dst));
#pragma unroll
                for (int i = 0; i < 8; i++) {
                    if (i < 2 || !(i & 1)) {
                        mbar_wait(bar_o + 8 * c2_grp(i), s & 1);
                        if (i == 0) DBGW(7, 0);
                        if (i == 1) DBGW(8, 0);
                        if (i == 6) DBGW(9, 0);
                        wgmma_fence();
                    }
#pragma unroll
                    for (int kk = 0; kk < 4; kk++)
                        wgmma_ss_n8(acc, dlo + ((C2_WO + i * 8192 + kk * 2048) >> 4), dlo + ((C2_OB + i * 1024 + kk * 256) >> 4));
                }
                wgmma_commit();
                xok = mbar_test(bar_x + 8 * ((s + 1) & 1), ((s + 1) >> 1) & 1);
                wgmma_wait<0>();
                asm volatile("st.relaxed.gpu.global.u32 [%0], %1;" :: "l"(dst), "r"((pack_bf16(acc[0], acc[2]) & ~1u) | tag) : "memory");
                asm volatile("st.relaxed.gpu.global.u32 [%0 + 128], %1;" :: "l"(dst), "r"((pack_bf16(acc[1], acc[3]) & ~1u) | tag) : "memory");
                bar_arrive<4, 384>();
                DBGW(10, 0);
            }
            s++;
            if (__builtin_expect(!xok, 0)) mbar_wait(bar_x + 8 * (s & 1), (s >> 1) & 1);
            {
                float acc[16];
                c2_xstream(acc, w, dlo + ((C2_XB + (s & 1) * C2_XS) >> 4), rank, dlo + (C2_WS >> 4));
                if (s > 0) bar_sync<5, 256>();
                store_x(acc, sb + C2_QX);
            }
            DBGW(0, 0);
            if (s == NSEG - 1) break;
            const uint32_t sca = w4 < 2 ? sb + C2_SC + w4 * 512 + lane * 16 : sb + C2_SC + 1024 + lane * 8;
            const uint32_t sc_peer = pin(mapa_u32(sca + 1280, rank ^ 1)), sc_own = pin(mapa_u32(sca, rank));
            const uint32_t krow = w4 * 16 + (lane & 15);
            const uint32_t ka0 = pin(sb + C2_KX + krow * 128 + (((lane >> 4) ^ (krow & 7)) << 4));
            const uint32_t l32 = pin(sb + C2_QM + (lane >> 4) * 256 + (lane & 7) * 32 + ((((lane >> 3) & 1) ^ ((lane >> 2) & 1)) << 4));
            const uint32_t qst = pin(sb + C2_QM + t32);
            {
                float a[4][4];
                proj_mem(a, s);
                sts32(qst, pack_bf16(a[0][0], a[0][2]));
                sts32(qst + 32, pack_bf16(a[0][1], a[0][3]));
            }
            DBGW(3, 0);
            if (w4 < 3) {
                uint32_t ka[4][4], qb[8];
                float c[4] = {0.f, 0.f, 0.f, 0.f}, c2[4] = {0.f, 0.f, 0.f, 0.f};
                bar_sync<1, 384>();
                ldsm_x4(qb, l32);
                ldsm_x4(ka[0], ka0);
                ldsm_x4(ka[1], ka0 ^ 32);
                ldsm_x4(qb + 4, l32 + 512);
                ldsm_x4(ka[2], ka0 ^ 64);
                ldsm_x4(ka[3], ka0 ^ 96);
                mma_16816(c, ka[0][0], ka[0][1], ka[0][2], ka[0][3], qb[0], qb[1]);
                mma_16816(c2, ka[1][0], ka[1][1], ka[1][2], ka[1][3], qb[2], qb[3]);
                mma_16816(c, ka[2][0], ka[2][1], ka[2][2], ka[2][3], qb[4], qb[5]);
                mma_16816(c2, ka[3][0], ka[3][1], ka[3][2], ka[3][3], qb[6], qb[7]);
                const uint32_t u0 = __float_as_uint(c[0] + c2[0]), u1 = __float_as_uint(c[1] + c2[1]);
                const uint32_t u2 = __float_as_uint(c[2] + c2[2]), u3 = __float_as_uint(c[3] + c2[3]);
                asm volatile(
                    "{\n.reg .pred p;\nsetp.lt.u32 p, %8, 2;\n"
                    "@p st.async.weak.shared::cluster.mbarrier::complete_tx::bytes.v4.b32 [%0], {%4, %5, %6, %7}, [%1];\n"
                    "@!p st.async.weak.shared::cluster.mbarrier::complete_tx::bytes.v2.b32 [%0], {%4, %5}, [%1];\n"
                    "@p st.async.weak.shared::cluster.mbarrier::complete_tx::bytes.v4.b32 [%2], {%4, %5, %6, %7}, [%3];\n"
                    "@!p st.async.weak.shared::cluster.mbarrier::complete_tx::bytes.v2.b32 [%2], {%4, %5}, [%3];\n}"
                    :: "r"(sc_peer), "r"(mapa_u32(bar_sc, rank ^ 1)), "r"(sc_own), "r"(mapa_u32(bar_sc, rank)), "r"(u0), "r"(u1), "r"(u2), "r"(u3), "r"(w4) : "memory");
                bar_arrive<2, 224>();
                if (s == NSEG - 3 && tid == 0) signal_ctr(CT_CB + 1);
                __syncwarp();
                DBGW(4, 2);
            } else {
                bar_arrive<1, 384>();
                const uint32_t a = pin(sb + C2_SC + lane * 16), a2 = pin(sb + C2_SC + 1024 + lane * 8), pa = pin(sb + C2_PB + lane * 4);
                mbar_wait(bar_sc, s & 1);
                DBG(5);
                float v[10];
                {
                    float4 x0, x1, y0, y1; float2 x2, y2;
                    asm volatile("ld.shared.v4.f32 {%0, %1, %2, %3}, [%4];" : "=f"(x0.x), "=f"(x0.y), "=f"(x0.z), "=f"(x0.w) : "r"(a) : "memory");
                    asm volatile("ld.shared.v4.f32 {%0, %1, %2, %3}, [%4];" : "=f"(y0.x), "=f"(y0.y), "=f"(y0.z), "=f"(y0.w) : "r"(a + 1280) : "memory");
                    asm volatile("ld.shared.v4.f32 {%0, %1, %2, %3}, [%4];" : "=f"(x1.x), "=f"(x1.y), "=f"(x1.z), "=f"(x1.w) : "r"(a + 512) : "memory");
                    asm volatile("ld.shared.v4.f32 {%0, %1, %2, %3}, [%4];" : "=f"(y1.x), "=f"(y1.y), "=f"(y1.z), "=f"(y1.w) : "r"(a + 1792) : "memory");
                    asm volatile("ld.shared.v2.f32 {%0, %1}, [%2];" : "=f"(x2.x), "=f"(x2.y) : "r"(a2) : "memory");
                    asm volatile("ld.shared.v2.f32 {%0, %1}, [%2];" : "=f"(y2.x), "=f"(y2.y) : "r"(a2 + 1280) : "memory");
                    v[0] = x0.x + y0.x; v[1] = x0.y + y0.y; v[2] = x0.z + y0.z; v[3] = x0.w + y0.w;
                    v[4] = x1.x + y1.x; v[5] = x1.y + y1.y; v[6] = x1.z + y1.z; v[7] = x1.w + y1.w;
                    v[8] = x2.x + y2.x; v[9] = x2.y + y2.y;
                }
                float m0 = fmaxf(fmaxf(fmaxf(v[0], v[2]), fmaxf(v[4], v[6])), v[8]);
                float m1 = fmaxf(fmaxf(fmaxf(v[1], v[3]), fmaxf(v[5], v[7])), v[9]);
#pragma unroll
                for (int o = 4; o < 32; o <<= 1) {
                    m0 = fmaxf(m0, __shfl_xor_sync(0xffffffff, m0, o));
                    m1 = fmaxf(m1, __shfl_xor_sync(0xffffffff, m1, o));
                }
                const float sl = scale * l2e;
                m0 *= sl; m1 *= sl;
#pragma unroll
                for (int j = 0; j < 5; j++)
                    sts32(pa + j * 128, pack_bf16(ex2f(fmaf(v[2 * j], sl, -m0)), ex2f(fmaf(v[2 * j + 1], sl, -m1))));
                bar_arrive<3, 160>();
                DBG(6);
            }
            fence_async_smem();
            bar_arrive<6, 256>();
        }
        bar_sync<1, 384>();
        fence_async_smem();
        bar_arrive<6, 256>();
        bar_arrive<4, 384>();
    } else if (wg == 1) {
        c2_load_w(w, Wk, rank, wcol, ws);
#pragma unroll 1
        for (int s = -1;;) {
            if (s > 0) {
                mbar_wait(bar_sx + 8 * ((s - 1) & 1), ((s - 1) >> 1) & 1);
                const uint32_t a = sb + C2_SX + ((s - 1) & 1) * 10240 + w4 * 1280 + lane * 8;
                float v[10];
                const int lim = 8 * w4 + g - 2 * qc;
#pragma unroll
                for (int j = 0; j < 5; j++) {
                    float2 x, y;
                    asm volatile("ld.shared.v2.f32 {%0, %1}, [%2];" : "=f"(x.x), "=f"(x.y) : "r"(a + j * 256) : "memory");
                    asm volatile("ld.shared.v2.f32 {%0, %1}, [%2];" : "=f"(y.x), "=f"(y.y) : "r"(a + 5120 + j * 256) : "memory");
                    v[2 * j] = (j < 4 && 8 * j > lim) ? -INFINITY : x.x + y.x;
                    v[2 * j + 1] = (j < 4 && 8 * j + 1 > lim) ? -INFINITY : x.y + y.y;
                }
                float mx = fmaxf(fmaxf(fmaxf(v[0], v[1]), fmaxf(v[2], v[3])), fmaxf(fmaxf(v[4], v[5]), fmaxf(v[6], v[7])));
                mx = fmaxf(mx, fmaxf(v[8], v[9]));
                mx = fmaxf(mx, __shfl_xor_sync(0xffffffff, mx, 1));
                mx = fmaxf(mx, __shfl_xor_sync(0xffffffff, mx, 2));
                const float sl = scale * l2e;
                mx *= sl;
#pragma unroll
                for (int j = 0; j < 10; j++) v[j] = ex2f(fmaf(v[j], sl, -mx));
                float sm = ((v[0] + v[1]) + (v[2] + v[3])) + ((v[4] + v[5]) + (v[6] + v[7])) + (v[8] + v[9]);
                sm += __shfl_xor_sync(0xffffffff, sm, 1);
                sm += __shfl_xor_sync(0xffffffff, sm, 2);
                float inv;
                asm("rcp.approx.ftz.f32 %0, %1;" : "=f"(inv) : "f"(sm));
                const uint32_t pa = sb + C2_PX + w4 * 256 + g * 32 + ((g >> 2) << 4) + qc * 4;
#pragma unroll
                for (int j = 0; j < 5; j++) sts32((pa ^ ((j & 1) << 4)) + (j >> 1) * 1024, pack_bf16(v[2 * j] * inv, v[2 * j + 1] * inv));
            }
            if (s >= 0) {
                fence_async_smem();
                if (s < NSEG) bar_sync<6, 256>(); else bar_sync<7, 128>();
                DBGW(20, 0);
                if (s < NSEG - 1) mbar_wait(bar_o, s & 1);
                if (s < NSEG) {
                    float sx[20];
#pragma unroll
                    for (int i = 0; i < 20; i++) sx[i] = 0.f;
                    wgmma_fence();
#pragma unroll
                    for (int kk = 0; kk < 4; kk++) wgmma_ss<DHI128, DHI128>(sx, dlo + (C2_QX >> 4) + kk * 2, dlo + (C2_KX >> 4) + kk * 2);
                    wgmma_commit();
                    wgmma_wait<0>();
                    if (s < NSEG - 1) bar_arrive<5, 256>();
                    if (w4 < 2) {
                        const uint32_t a = sb + C2_SX + (s & 1) * 10240 + w4 * 2560 + lane * 8;
#pragma unroll
                        for (int j = 0; j < 5; j++) {
                            asm volatile("st.shared.v2.f32 [%0], {%1, %2};" :: "r"(a + j * 256), "f"(sx[4 * j]), "f"(sx[4 * j + 1]) : "memory");
                            asm volatile("st.shared.v2.f32 [%0], {%1, %2};" :: "r"(a + 1280 + j * 256), "f"(sx[4 * j + 2]), "f"(sx[4 * j + 3]) : "memory");
                        }
                    }
                }
                DBGW(21, 0);
                if (s > 0) {
                    float cx[16];
#pragma unroll
                    for (int i = 0; i < 16; i++) cx[i] = 0.f;
                    wgmma_fence();
#pragma unroll
                    for (int kk = 0; kk < 3; kk++)
                        wgmma_ss<DHI32, DHI32>(cx, dlo + ((C2_VT + ((s - 1) & 1) * 6144 + kk * 2048) >> 4), dlo + ((C2_PX + kk * 1024) >> 4));
                    wgmma_commit();
                    wgmma_wait<0>();
                    uint32_t* dst = reinterpret_cast<uint32_t*>(g_ctxB + ((size_t)h * SEQ + (s - 1) * SEGL + 2 * qc) * HD + (rank & 1) * 64 + w4 * 16 + 2 * g);
#pragma unroll
                    for (int j = 0; j < 4; j++) {
                        dst[j * 8 * (HD / 2)] = pack_bf16(cx[4 * j], cx[4 * j + 2]);
                        dst[(j * 8 + 1) * (HD / 2)] = pack_bf16(cx[4 * j + 1], cx[4 * j + 3]);
                    }
                }
                DBGW(22, 0);
                if (s == NSEG) break;
                fence_async_smem();
            }
            if (s < NSEG - 1) mbar_wait(bar_x + 8 * ((s + 1) & 1), ((s + 1) >> 1) & 1);
            if (s >= 0) bar_sync<4, 384>();
            s++;
            if (s < NSEG) {
                {
                    float acc[16];
                    c2_xstream(acc, w, dlo + ((C2_XB + (s & 1) * C2_XS) >> 4), rank, dlo + ((C2_WS + C2_NS * 2048) >> 4));
                    store_x(acc, sb + C2_KX);
                }
                DBGW(16, 0);
                const uint32_t kst = pin(sb + C2_KX + 4096 + t128);
                float a[4][4];
                proj_mem(a, s);
                sts32(kst, pack_bf16(a[0][0], a[0][2]));
                sts32((kst ^ 16) + 128, pack_bf16(a[0][1], a[0][3]));
                bar_arrive<1, 384>();
                DBGW(19, 0);
                if (w4 == 0) {
                    if (s < NSEG - 1) {
                        if (lane == 0) mbar_expect_tx(bar_sc, 2560);
                        if (lane < 16 && (lane & 7) >= 1 && (lane & 7) < 5) mbar_expect_tx(bar_m + 8 * lane, (lane & 7) == 1 ? 1024 : 2048);
                        if (lane == 8) {
                            mbar_expect_tx(bar_x + 8 * ((s + 1) & 1), 32768);
                            tma_load_2d_mc(sb + C2_XB + ((s + 1) & 1) * C2_XS + rank * 5120, &mapX, bar_x + 8 * ((s + 1) & 1), rank * 64, (s + 1) * SEGL, (uint16_t)0xff);
                            if (s + 2 < NSEG)
                                asm volatile("cp.async.bulk.prefetch.tensor.2d.L2.global [%0, {%1, %2}];" :: "l"((uint64_t)&mapX), "r"(rank * 64), "r"((s + 2) * SEGL) : "memory");
                        }
                    }
                    if (lane == 16) mbar_expect_tx(bar_sx + 8 * (s & 1), 5120);
                    __syncwarp();
                }
            }
        }
        bar_sync<7, 128>();
        if (tid == 128) signal_ctr(CT_CB);
    } else {
        c2_load_w(w, Wv, rank, wcol, ws);
#pragma unroll 1
        for (int s = -1;;) {
            if (s >= 0) {
                const int t = tid - 256;
                const uint2* src = g_xbuf + ((s & 1) * 8 + rank) * 1024 + t;
                asm volatile("" : "+l"(src));
                const uint32_t ma = sb + C2_XB + ((s + 1) & 1) * C2_XS + rank * 5120 + 4096 + (t >> 4) * 128 + ((((t >> 1) & 7) ^ (t >> 4)) << 4) + (t & 1) * 8;
                uint32_t ra[8], rb[8];
#pragma unroll
                for (int i = 1; i < 8; i++) {
                    const uint32_t d = (rank + i) & 7;
                    ra[i] = pin(mapa_u32(ma, d)); rb[i] = pin(mapa_u32(bar_m + 8 * c2_grp(i), d));
                }
                bar_sync<4, 384>();
                DBGW(29, 0);
                if (tid == 256) {
                    const uint32_t a = sb + C2_SX + (s & 1) * 10240;
                    bulk_s2s(mapa_u32(a + 5120, rank ^ 1), a, 5120, mapa_u32(bar_sx + 8 * (s & 1), rank ^ 1));
                }
                if (s == NSEG - 1) break;
                pace(CH_POLL_DELAY);
                const uint32_t tag = ((s >> 1) & 1) ^ 1;
                uint32_t p[8][2];
                for (int it = 0; it < (1 << 20); it++) {
#pragma unroll
                    for (int k = 0; k < 8; k++)
                        asm volatile("ld.relaxed.gpu.global.v2.u32 {%0, %1}, [%2];" : "=r"(p[k][0]), "=r"(p[k][1]) : "l"(src + k * 128) : "memory");
                    uint32_t bad[8];
#pragma unroll
                    for (int k = 0; k < 8; k++) asm("lop3.b32 %0, %1, %2, %3, 0x7e;" : "=r"(bad[k]) : "r"(p[k][0]), "r"(p[k][1]), "r"(tag));
                    asm("lop3.b32 %0, %0, %1, %2, 0xfe;" : "+r"(bad[0]) : "r"(bad[1]), "r"(bad[2]));
                    asm("lop3.b32 %0, %0, %1, %2, 0xfe;" : "+r"(bad[3]) : "r"(bad[4]), "r"(bad[5]));
                    asm("lop3.b32 %0, %0, %1, %2, 0xfe;" : "+r"(bad[0]) : "r"(bad[3]), "r"(bad[6]));
                    asm("lop3.b32 %0, %0, %1, 1, 0xa8;" : "+r"(bad[0]) : "r"(bad[7]));
                    if (__all_sync(0xffffffff, bad[0] == 0u)) break;
                }
                DBGW(30, 0);
                float r[4];
#pragma unroll
                for (int e = 0; e < 2; e++) {
                    float lo[8], hi[8];
#pragma unroll
                    for (int k = 0; k < 8; k++) { lo[k] = __uint_as_float(p[k][e] << 16); hi[k] = __uint_as_float(p[k][e] & 0xffff0000u); }
                    r[2 * e] = ((lo[0] + lo[1]) + (lo[2] + lo[3])) + ((lo[4] + lo[5]) + (lo[6] + lo[7]));
                    r[2 * e + 1] = ((hi[0] + hi[1]) + (hi[2] + hi[3])) + ((hi[4] + hi[5]) + (hi[6] + hi[7]));
                }
                const uint32_t m0 = pack_bf16(r[0], r[1]), m1 = pack_bf16(r[2], r[3]);
                st_async_v2(ra[1], m0, m1, rb[1]);
                asm volatile("st.shared.v2.b32 [%0], {%1, %2};" :: "r"(ma), "r"(m0), "r"(m1) : "memory");
                __syncwarp();
                if (lane == 0) mbar_arrive(bar_m);
#pragma unroll
                for (int i = 2; i < 8; i++) st_async_v2(ra[i], m0, m1, rb[i]);
                DBGW(31, 0);
            }
            s++;
            const uint32_t ost = pin(sb + C2_OB + t32), pla = pin(sb + C2_PB + lane * 16), plb = pin(sb + C2_PB + 512 + (lane & 7) * 16);
            bar_sync<1, 384>();
            fence_async_smem();
            DBGW(24, 0);
            if (s < NSEG - 1) bar_sync<2, 224>();
            uint32_t va[5][2];
            {
                float acc[20];
                c2_xstream(acc, w, dlo + ((C2_XB + (s & 1) * C2_XS) >> 4), rank, dlo + ((C2_WS + 2 * C2_NS * 2048) >> 4));
#pragma unroll
                for (int j = 0; j < 5; j++) { va[j][0] = pack_bf16(acc[4 * j], acc[4 * j + 1]); va[j][1] = pack_bf16(acc[4 * j + 2], acc[4 * j + 3]); }
            }
            DBGW(26, 0);
            if (s < NSEG - 1) {
                uint32_t p[5];
                bar_sync<3, 160>();
                DBGW(27, 0);
                ldmatrix_x4_trans(p[0], p[1], p[2], p[3], pla);
                asm volatile("ldmatrix.sync.aligned.m8n8.x1.trans.shared.b16 {%0}, [%1];" : "=r"(p[4]) : "r"(plb) : "memory");
                float oa[4] = {0.f, 0.f, 0.f, 0.f}, ob[4] = {0.f, 0.f, 0.f, 0.f}, sa[4] = {0.f, 0.f, 0.f, 0.f}, sc[4] = {0.f, 0.f, 0.f, 0.f};
                const uint32_t one = 0x3f803f80u;
                mma_16816(sa, one, one, one, one, p[0], p[1]);
                mma_16816(oa, va[0][0], va[0][1], va[1][0], va[1][1], p[0], p[1]);
                mma_16816(sc, one, one, one, one, p[2], p[3]);
                mma_16816(ob, va[2][0], va[2][1], va[3][0], va[3][1], p[2], p[3]);
                mma_16816(sa, one, one, one, one, p[4], 0u);
                mma_16816(oa, va[4][0], va[4][1], 0u, 0u, p[4], 0u);
                float i0, i1;
                asm("rcp.approx.ftz.f32 %0, %1;" : "=f"(i0) : "f"(sa[0] + sc[0]));
                asm("rcp.approx.ftz.f32 %0, %1;" : "=f"(i1) : "f"(sa[1] + sc[1]));
                sts32(ost, pack_bf16((oa[0] + ob[0]) * i0, (oa[2] + ob[2]) * i0));
                sts32(ost + 32, pack_bf16((oa[1] + ob[1]) * i1, (oa[3] + ob[3]) * i1));
                fence_async_smem();
                __syncwarp();
                if (elect_one()) {
#pragma unroll
                    for (int i = 1; i < 8; i++) {
                        const uint32_t d = (rank + i) & 7;
                        bulk_s2s(mapa_u32(sb + C2_OB + i * 1024 + w4 * 256, d), sb + C2_OB + w4 * 256, 256, mapa_u32(bar_o + 8 * c2_grp(i), d));
                        if (i == 1) mbar_arrive(bar_o);
                    }
                }
                __syncwarp();
                DBGW(28, 0);
            }
            {
                const uint32_t a = sb + C2_VT + (s & 1) * 6144 + a32;
                stmatrix_x4(a, va[0][0], va[0][1], va[1][0], va[1][1]);
                stmatrix_x4(a + 2048, va[2][0], va[2][1], va[3][0], va[3][1]);
                asm volatile("stmatrix.sync.aligned.m8n8.x2.shared.b16 [%0], {%1, %2};" :: "r"(a + 4096), "r"(va[4][0]), "r"(va[4][1]) : "memory");
            }
            fence_async_smem();
        }
        g_xbuf[((8 + rank) * 8 + C) * 128 + (tid - 256)] = make_uint2(0u, 0u);
    }
    __syncthreads();
    cluster_sync_all();
    TS_END(2);
}

struct Proj2Params {
    CUtensorMap mapA[2];
    CUtensorMap mapW[3];
    bf16* out[3];
};
#define P2T(i)
#define P2_NOMMA 0
#define P2_NOLOAD 0
constexpr int P2_STAGES = 6;
constexpr int P2_SMEM = 131072 + P2_STAGES * 16384 + 1024 + 1024;
constexpr int P2_ITEMS = 168 + 48;
__device__ __forceinline__ int p2_reps(int t) { return t >= 168 ? 1 : 2; }
__device__ __forceinline__ void p2_tile(int t, int w, int& z, int& mp, int& head) {
    if (t >= 168) { w += ((t - 168) & 1) * 2; t = 168 + ((t - 168) >> 1); }
    const int hq = t / 24, v = t % 24;
    mp = v & 7;
    if (v < 16) { head = hq * 4 + (v >> 3) * 2 + (w >> 1); z = 1 + (w & 1); }
    else { head = hq * 4 + w; z = 0; }
}
__device__ __forceinline__ void mbar_arrive_remote(uint32_t bar_cluster_addr) {
    asm volatile("mbarrier.arrive.release.cluster.shared::cluster.b64 _, [%0];" :: "r"(bar_cluster_addr) : "memory");
}
__device__ __forceinline__ void mbar_arrive_cl(uint32_t bar_cluster_addr) {
    asm volatile("mbarrier.arrive.shared::cluster.b64 _, [%0];" :: "r"(bar_cluster_addr) : "memory");
}
__device__ __forceinline__ void mbar_wait_acq_cluster(uint32_t bar, uint32_t parity) {
    asm volatile(
        "{\n"
        ".reg .pred p, q;\n"
        ".reg .u32 c;\n"
        "mov.u32 c, 0;\n"
        "WAIT_LOOP_C:\n"
        "mbarrier.try_wait.parity.acquire.cluster.shared::cta.b64 p, [%0], %1;\n"
        "@p bra WAIT_DONE_C;\n"
        "add.u32 c, c, 1;\n"
        "setp.lt.u32 q, c, 4000000;\n"
        "@q bra WAIT_LOOP_C;\n"
        "WAIT_DONE_C:\n"
        "}\n" :: "r"(bar), "r"(parity) : "memory");
}
__device__ __forceinline__ uint4 quad_transpose(uint32_t p0, uint32_t p1, uint32_t p2, uint32_t p3, int lane) {
    const bool o1 = lane & 1, o2 = lane & 2;
    uint32_t s0 = o1 ? p0 : p1, s1 = o1 ? p2 : p3;
    s0 = __shfl_xor_sync(0xffffffff, s0, 1); s1 = __shfl_xor_sync(0xffffffff, s1, 1);
    const uint32_t a_lo = o1 ? s0 : p0, a_hi = o1 ? p1 : s0, b_lo = o1 ? s1 : p2, b_hi = o1 ? p3 : s1;
    uint32_t t0 = o2 ? a_lo : b_lo, t1 = o2 ? a_hi : b_hi;
    t0 = __shfl_xor_sync(0xffffffff, t0, 2); t1 = __shfl_xor_sync(0xffffffff, t1, 2);
    return o2 ? make_uint4(t0, t1, b_lo, b_hi) : make_uint4(a_lo, a_hi, t0, t1);
}
#define P2_PACE 35
#define P2_PACE2 0
template <bool PERM, int PACE = 0>
__device__ __forceinline__ void store_frag_128(const float (&acc)[64], bf16* obase, int lane) {
#pragma unroll
    for (int rr = 0; rr < 2; rr++)
#pragma unroll
        for (int g = 0; g < 4; g++) {
            const float* a = &acc[g * 16 + rr * 2];
            const uint32_t p0 = pack_bf16(a[0], a[1]), p1 = pack_bf16(a[4], a[5]), p2 = pack_bf16(a[8], a[9]), p3 = pack_bf16(a[12], a[13]);
            *reinterpret_cast<uint4*>(obase + (size_t)(rr * 8) * HD + g * 32) = PERM ? make_uint4(p0, p1, p2, p3) : quad_transpose(p0, p1, p2, p3, lane);
            pace(PACE);
        }
}
__global__ void __cluster_dims__(2, 1, 1) __launch_bounds__(384, 1) proj2_kernel(const __grid_constant__ Proj2Params P) {
    extern __shared__ uint8_t smem_raw[];
    const uint32_t sbase = (smem_u32(smem_raw) + 1023) & ~1023u;
    const uint32_t sA = sbase, sB = sbase + 131072, sC = sB + P2_STAGES * 16384;
    const uint32_t bars = sC;
    const uint32_t a_full = bars, a_empty = bars + 64, b_full = bars + 128, b_empty = b_full + 8 * P2_STAGES;
    const uint32_t item_bar = b_empty + 8 * P2_STAGES, item_in = item_bar + 16, slot = item_in + 16;
    const uint32_t note_bar = slot + 16, note_free = note_bar + 64, note = note_free + 64;
    const int warp = threadIdx.x >> 5, lane = threadIdx.x & 31;
    const uint32_t rank = cluster_ctarank();
    TS_BEGIN(0);
    if (threadIdx.x == 0) {
        for (int i = 0; i < 8; i++) { mbar_init(a_full + 8 * i, 1); mbar_init(a_empty + 8 * i, 2); }
        for (int i = 0; i < P2_STAGES; i++) { mbar_init(b_full + 8 * i, 1); mbar_init(b_empty + 8 * i, 2); }
        mbar_init(item_bar, 1); mbar_init(item_bar + 8, 1); mbar_init(item_in, 2); mbar_init(item_in + 8, 2);
        for (int i = 0; i < 8; i++) { mbar_init(note_bar + 8 * i, 1); mbar_init(note_free + 8 * i, 1); }
        asm volatile("fence.mbarrier_init.release.cluster;" ::: "memory");
    }
    __syncthreads();
    cluster_sync_all();
    pdl_launch_dependents();
    if (warp == 9) {
        if (lane == 0) {
            for (int n = 0;; n++) {
                const int e = (n & 1) * 4 + ((n >> 1) & 3);
                mbar_wait(note_bar + 8 * e, (n >> 3) & 1);
                int m;
                asm volatile("ld.shared.s32 %0, [%1];" : "=r"(m) : "r"(note + e * 4) : "memory");
                mbar_arrive(note_free + 8 * e);
                if (m < 0) break;
                signal_ctr(m);
            }
        }
    } else if (warp == 10) {
        if (lane == 0) {
            auto publish = [&](int ic, int tq) {
                const int t = tq < P2_ITEMS ? tq : -1;
                asm volatile("st.shared.s32 [%0], %1;" :: "r"(slot + (ic & 3) * 4), "r"(t) : "memory");
                mbar_arrive(item_bar + 8 * (ic & 1));
                st_async_b32(mapa_u32(slot + (ic & 3) * 4, 1), (uint32_t)t, mapa_u32(item_bar + 8 * (ic & 1), 1));
            };
            const int npair = (int)(gridDim.x >> 1), pair = (int)(blockIdx.x >> 1);
            if (rank == 0) publish(0, pair);
            for (int ic = 0;; ic++) {
                if (rank == 1) mbar_expect_tx(item_bar + 8 * (ic & 1), 4);
                mbar_wait(item_bar + 8 * (ic & 1), (ic >> 1) & 1);
                int t;
                asm volatile("ld.shared.s32 %0, [%1];" : "=r"(t) : "r"(slot + (ic & 3) * 4) : "memory");
                if (t < 0) break;
                int z0, mp, h0;
                p2_tile(t, 0, z0, mp, h0);
                const int aidx = z0 >= 1 ? 1 : 0;
                const int m0 = (2 * mp + (int)rank) * 128;
                for (int k = 0; k < 8; k++) {
                    mbar_wait(a_empty + 8 * k, (ic & 1) ^ 1);
                    if (P2_NOLOAD) mbar_arrive(a_full + 8 * k); else {
                    mbar_expect_tx(a_full + 8 * k, 16384);
                    tma_load_2d(sA + k * 16384, &P.mapA[aidx], a_full + 8 * k, k * 64, m0); }
                }
                if (rank == 0) {
                    mbar_wait(item_in + 8 * (ic & 1), (ic >> 1) & 1);
                    publish(ic + 1, ic == 0 ? npair + pair : 2 * npair + (int)atomicAdd(&g_ctr[CT_PROJ], 1u));
                }
            }
        }
    } else if (warp == 8 || warp == 11) {
        if (lane == 0) {
            const int par2 = warp == 8 ? 0 : 1;
            int it = 0; uint32_t bph = 0;
            for (int ic = 0;; ic++) {
                mbar_wait(item_bar + 8 * (ic & 1), (ic >> 1) & 1);
                int t;
                asm volatile("ld.shared.s32 %0, [%1];" : "=r"(t) : "r"(slot + (ic & 3) * 4) : "memory");
                if (t < 0) break;
                const int nt = 2 * p2_reps(t);
                for (int w = 0; w < nt; w++) {
                    int z, mp, hd;
                    p2_tile(t, w, z, mp, hd);
                    for (int k = 0; k < 8; k++) {
                        const int s = it; const uint32_t phb = bph;
                        if (++it == P2_STAGES) { it = 0; bph ^= 1; }
                        if ((k & 1) != par2) continue;
                        mbar_wait(b_empty + 8 * s, phb ^ 1);
                        if (P2_NOLOAD) { mbar_arrive(b_full + 8 * s); continue; }
                        mbar_expect_tx(b_full + 8 * s, 16384);
                        tma_load_2d_mc(sB + s * 16384 + rank * 8192, &P.mapW[z], b_full + 8 * s, hd * 128 + (int)rank * 64, k * 64, (uint16_t)3);
                    }
                }
            }
        }
    } else {
        const int wg = warp >> 2;
        float acc[2][64];
        const uint32_t a_lo = desc_lo(sA, 16), b_lo0 = desc_lo(sB, 8192);
        const bool elected = (threadIdx.x & 127) == 0;
        int s = (wg * 8) % P2_STAGES;
        uint32_t ph = ((wg * 8) / P2_STAGES) & 1;
        int nnote = 0;
        if (wg == 1) asm volatile("bar.arrive 3, 256;" ::: "memory");
        for (int ic = 0;; ic++) {
            mbar_wait(item_bar + 8 * (ic & 1), (ic >> 1) & 1);
            int t;
            asm volatile("ld.shared.s32 %0, [%1];" : "=r"(t) : "r"(slot + (ic & 3) * 4) : "memory");
            P2T(7);
            if (wg == 0 && t < 0) {
                if (elected) {
                    const int e = nnote & 3;
                    mbar_wait(note_free + 8 * e, ((nnote >> 2) & 1) ^ 1);
                    asm volatile("st.shared.s32 [%0], %1;" :: "r"(note + e * 4), "r"(-1) : "memory");
                    mbar_arrive(note_bar + 8 * e);
                }
            }
            if (t < 0) break;
            const int reps = p2_reps(t);
#pragma unroll 1
            for (int rp = 0; rp < reps; rp++) {
            const bool first = rp == 0, last = rp == reps - 1;
            int z, mp, head;
            p2_tile(t, rp * 2 + wg, z, mp, head);
            asm volatile("bar.sync %0, 256;" :: "r"(3 + wg) : "memory");
            P2T(0);
            if (wg == 1 && last && elected) mbar_arrive_cl(mapa_u32(item_in + 8 * (ic & 1), 0));
            int sprev = 0;
#pragma unroll
            for (int k = 0; k < 8; k++) {
                if (k == 0) P2T(5);
                if (wg == 0 && first) mbar_wait(a_full + 8 * k, ic & 1);
                if (k == 0) P2T(6);
                mbar_wait(b_full + 8 * s, ph);
                if (k == 7) asm volatile("bar.arrive %0, 256;" :: "r"(4 - wg) : "memory");
                if (k == 0) P2T(1);
                if (k == 7) P2T(2);
                const uint32_t b_lo = b_lo0 + s * 1024;
                wgmma_fence();
#pragma unroll
                for (int kk = 0; kk < (P2_NOMMA ? 1 : 4); kk++) {
                    wgmma_ss_n128_lo<1>(acc[0], a_lo + k * 1024 + kk * 2, b_lo + kk * 128, (k | kk) != 0);
                    wgmma_ss_n128_lo<1>(acc[1], a_lo + k * 1024 + 512 + kk * 2, b_lo + kk * 128, (k | kk) != 0);
                }
                wgmma_commit();
                if (k > 0) {
                    wgmma_wait<1>();
                    if (elected) {
                        const uint32_t e = b_empty + 8 * sprev;
                        mbar_arrive_cl(mapa_u32(e, 0)); mbar_arrive_cl(mapa_u32(e, 1));
                        if (last) mbar_arrive(a_empty + 8 * (k - 1));
                    }
                }
                sprev = s;
                if (++s == P2_STAGES) { s = 0; ph ^= 1; }
            }
            wgmma_wait<0>();
            P2T(3);
            if (elected) {
                const uint32_t e = b_empty + 8 * sprev;
                mbar_arrive_cl(mapa_u32(e, 0)); mbar_arrive_cl(mapa_u32(e, 1));
                if (last) mbar_arrive(a_empty + 8 * 7);
            }
            s += 8 % P2_STAGES; ph ^= (8 / P2_STAGES) & 1;
            if (s >= P2_STAGES) { s -= P2_STAGES; ph ^= 1; }
            const int m0 = (2 * mp + (int)rank) * 128;
            bf16* obase = P.out[z] + ((size_t)head * SEQ + m0 + (warp & 3) * 16 + (lane >> 2)) * HD + (lane & 3) * 8;
            store_frag_128<true, P2_PACE>(acc[0], obase, lane); store_frag_128<true, P2_PACE>(acc[1], obase + (size_t)64 * HD, lane);
            P2T(4);
            {
                asm volatile("bar.sync %0, 128;" :: "r"(1 + wg) : "memory");
                if (elected) {
                    const int e = wg * 4 + (nnote & 3);
                    mbar_wait(note_free + 8 * e, ((nnote >> 2) & 1) ^ 1);
                    asm volatile("st.shared.s32 [%0], %1;" :: "r"(note + e * 4), "r"(CT_AP + (head >> 1)) : "memory");
                    mbar_arrive(note_bar + 8 * e);
                }
                nnote++;
            }
            }
        }
        TS_END(0);
    }
    __syncthreads();
    cluster_sync_all();
}

struct OutParams {
    CUtensorMap mapCtx[2];
    CUtensorMap mapWo[2];
    CUtensorMap mapPart;
    CUtensorMap mapOut;
};
__device__ bf16 g_part[4 * SEQ * DM];

#define OT(i)
#define OTP(i)
#define O3_LK 26
#define O3_D 3
constexpr int O3_E = 68, O3_GRID = O3_E + 64;
constexpr int O2_SMEM = 196608 + 1024 + 256;

__global__ void __cluster_dims__(2, 1, 1) __launch_bounds__(352, 1) out3_kernel(const __grid_constant__ OutParams P) {
    extern __shared__ uint8_t smem_raw[];
    const uint32_t sbase = (smem_u32(smem_raw) + 1023) & ~1023u;
    const uint32_t bar_full = sbase + 196608, bar_empty = bar_full + 64;
    const int warp = threadIdx.x >> 5, lane = threadIdx.x & 31;
    const uint32_t rank = cluster_ctarank();
    const int pair = blockIdx.x >> 1;
    const bool early = pair < O3_E / 2;
    constexpr int EB = 64 - O3_LK;
    int mt, part, a0, na, b0, nb;
    if (pair < 30) {
        part = pair >= 15; mt = part ? 29 - pair : pair;
        a0 = part ? 32 + O3_D : 0; na = part ? 32 - O3_D : 32 + O3_D;
        b0 = part ? EB / 2 : 0; nb = part ? EB - EB / 2 : EB / 2;
    } else if (early) {
        part = pair - 30; mt = 15;
        a0 = part * 16; na = 16;
        b0 = part * EB / 4; nb = (part + 1) * EB / 4 - b0;
    } else {
        part = (pair - O3_E / 2) & 1; mt = (pair - O3_E / 2) >> 1;
        a0 = 0; na = 0; b0 = EB; nb = O3_LK;
    }
    const int m0 = mt * 128, nk = na + nb;
    const int n0 = early ? (int)rank * 256 : part * 256 + (int)rank * 128;
    const int nst = early ? 4 : 6;
    const uint32_t ssz = early ? 49152 : 32768;
    TS_BEGIN(4);
    OT(0);
    if (threadIdx.x == 0) {
        for (int i = 0; i < 6; i++) { mbar_init(bar_full + 8 * i, 1); mbar_init(bar_empty + 8 * i, 4); }
        asm volatile("fence.mbarrier_init.release.cluster;" ::: "memory");
    }
    if (threadIdx.x == 256) {
        asm volatile("prefetch.tensormap [%0];" :: "l"((uint64_t)&P.mapCtx[early ? 0 : 1]) : "memory");
        asm volatile("prefetch.tensormap [%0];" :: "l"((uint64_t)&P.mapWo[early ? 0 : 1]) : "memory");
    }
    __syncthreads();
    asm volatile("barrier.cluster.arrive.release.aligned;" ::: "memory");
    if (warp > 8) {
        if (lane == 0) {
            int s = 0; uint32_t ph = 0;
            for (int i = 0; i < nk; i++) {
                if (i >= nst) mbar_wait(bar_empty + 8 * s, ph ^ 1);
                const uint32_t sa = sbase + s * ssz + 16384;
                const int b = i >= na, k = b ? b0 + i - na : a0 + i;
                if (early) {
                    tma_load_2d(sa + (warp - 9) * 16384, &P.mapWo[b], bar_full + 8 * s, n0 + (warp - 9) * 128, k * 64);
                    tma_load_2d(sa + (warp - 9) * 16384 + 8192, &P.mapWo[b], bar_full + 8 * s, n0 + (warp - 9) * 128 + 64, k * 64);
                } else tma_load_2d(sa + (warp - 9) * 8192, &P.mapWo[1], bar_full + 8 * s, n0 + (warp - 9) * 64, k * 64);
                if (++s == nst) { s = 0; ph ^= 1; }
            }
        }
        __syncwarp();
        asm volatile("barrier.cluster.wait.acquire.aligned;" ::: "memory");
    } else if (warp == 8) {
        if (lane == 0) {
            if (early) wait_ctr(CT_CA + mt * 2, 2u * O2_HE); else wait_ctr(mt == 15 ? CT_CB : CT_CB + 1, 64u);
            OTP(3);
        }
        __syncwarp();
        asm volatile("barrier.cluster.wait.acquire.aligned;" ::: "memory");
        if (lane == 0) {
            OTP(7);
            int s = 0; uint32_t ph = 0;
            bool late_a = false;
            for (int i = 0; i < nk; i++) {
                const int b = i >= na, k = b ? b0 + i - na : a0 + i;
                if (!b && k >= 2 * O2_HE && !late_a) { wait_ctr(CT_CA + mt * 2 + 1, 2u * (NH - O2_HE)); late_a = true; }
                if (i == na && early) wait_ctr(mt == 15 ? CT_CB : CT_CB + 1, 64u);
                if (i >= nst) mbar_wait(bar_empty + 8 * s, ph ^ 1);
                mbar_expect_tx(bar_full + 8 * s, ssz);
                tma_load_2d_mc(sbase + s * ssz + rank * 8192, &P.mapCtx[b], bar_full + 8 * s, (k & 1) * 64, (k >> 1) * SEQ + m0 + (int)rank * 64, (uint16_t)3);
                if (++s == nst) { s = 0; ph ^= 1; }
            }
            if (!early) {
                const int np = mt == 15 ? 4 : 2;
                wait_ctr(CT_OP + mt * 2 + part, 2u * np);
                for (int i = 0; i < np; i++) {
                    mbar_wait(bar_empty + 8 * s, ph ^ 1);
                    mbar_expect_tx(bar_full + 8 * s, 32768);
                    for (int j = 0; j < 4; j++)
                        tma_load_2d(sbase + s * ssz + j * 8192, &P.mapPart, bar_full + 8 * s, n0 + (j & 1) * 64, i * SEQ + m0 + (j >> 1) * 64);
                    if (++s == nst) { s = 0; ph ^= 1; }
                }
            }
        }
    } else {
        asm volatile("barrier.cluster.wait.acquire.aligned;" ::: "memory");
        const int wg = warp >> 2;
        const bool elected = (threadIdx.x & 127) == 0;
        const int row = (warp & 3) * 16 + (lane >> 2);
        const int mrow = (warp & 3) * 16 + (lane & 15);
        const uint32_t moff = mrow * 128, mx = (lane >> 4) ^ (mrow & 7);
        float g0, g1;
        int s = 0, sprev = 0; uint32_t ph = 0;
        {
            unsigned int v; int it = 0;
            do { asm volatile("ld.acquire.gpu.global.u32 %0, [%1];" : "=r"(v) : "l"(&g_ctr[CT_G]) : "memory"); } while (v < FA_GRID && ++it < (1 << 22));
        }
        asm volatile("ld.relaxed.gpu.global.f32 %0, [%1];" : "=f"(g0) : "l"(g_gate + m0 + wg * 64 + row) : "memory");
        asm volatile("ld.relaxed.gpu.global.f32 %0, [%1];" : "=f"(g1) : "l"(g_gate + m0 + wg * 64 + row + 8) : "memory");
        auto release = [&](int st) {
            if (elected) { const uint32_t e = bar_empty + 8 * st; mbar_arrive_cl(mapa_u32(e, 0)); mbar_arrive_cl(mapa_u32(e, 1)); }
        };
        if (early) {
            float acc[128];
#pragma unroll 1
            for (int i = 0; i < nk; i++) {
                mbar_wait(bar_full + 8 * s, ph);
                if (i == 8) OT(2);
                if (i == na) {
                    wgmma_wait<0>();
                    const float r0 = g0 / fmaxf(1.f - g0, 0x1p-40f), r1 = g1 / fmaxf(1.f - g1, 0x1p-40f);
#pragma unroll
                    for (int j = 0; j < 32; j++) { acc[4 * j] *= r0; acc[4 * j + 1] *= r0; acc[4 * j + 2] *= r1; acc[4 * j + 3] *= r1; }
                }
                const uint32_t sa = sbase + s * 49152 + wg * 8192, sb = sbase + s * 49152 + 16384;
                wgmma_fence();
#pragma unroll
                for (int kk = 0; kk < 4; kk++)
                    wgmma_ss_n256_tb(acc, make_desc(sa + kk * 32, 16, 1024), make_desc(sb + kk * 2048, 8192, 1024), (i | kk) != 0);
                wgmma_commit();
                if (i > 0) { wgmma_wait<1>(); release(sprev); }
                sprev = s;
                if (++s == 4) { s = 0; ph ^= 1; }
            }
            wgmma_wait<0>();
            OT(4);
            const float w0 = fmaxf(1.f - g0, 0x1p-40f), w1 = fmaxf(1.f - g1, 0x1p-40f);
            const uint32_t stg = sbase + ((sprev + 1 + wg) & 3) * 49152;
            asm volatile("bar.sync 1, 256;" ::: "memory");
#pragma unroll
            for (int j = 0; j < 16; j++) {
                const float* a = &acc[8 * j];
                stmatrix_x4(stg + (j >> 2) * 8192 + moff + ((mx ^ ((j & 3) * 2)) << 4), pack_bf16(a[0] * w0, a[1] * w0), pack_bf16(a[2] * w1, a[3] * w1),
                            pack_bf16(a[4] * w0, a[5] * w0), pack_bf16(a[6] * w1, a[7] * w1));
            }
            fence_async_smem();
            asm volatile("bar.sync %0, 128;" :: "r"(2 + wg) : "memory");
            if (elected) {
                for (int j = 0; j < 4; j++) tma_store_2d(&P.mapPart, stg + j * 8192, n0 + j * 64, part * SEQ + m0 + wg * 64);
                asm volatile("cp.async.bulk.commit_group;" ::: "memory");
                asm volatile("cp.async.bulk.wait_group 0;" ::: "memory");
                OT(5);
                signal_ctr(CT_OP + mt * 2 + (int)rank);
            }
            OT(6);
        } else {
            float acc[64];
            const uint32_t a_lo = desc_lo(sbase + wg * 8192, 16), b_lo = desc_lo(sbase + 16384, 8192);
#pragma unroll 1
            for (int i = 0; i < nk; i++) {
                mbar_wait(bar_full + 8 * s, ph);
                if (i == 8) OT(2);
                wgmma_fence();
#pragma unroll
                for (int kk = 0; kk < 4; kk++) wgmma_ss_n128_lo<1>(acc, a_lo + s * 2048 + kk * 2, b_lo + s * 2048 + kk * 128, (i | kk) != 0);
                wgmma_commit();
                if (i > 0) { wgmma_wait<1>(); release(sprev); }
                sprev = s;
                if (++s == 6) { s = 0; ph ^= 1; }
            }
            wgmma_wait<0>();
            OT(4);
            const float w0 = 1.f - g0, w1 = 1.f - g1;
#pragma unroll
            for (int j = 0; j < 16; j++) { acc[4 * j] *= w0; acc[4 * j + 1] *= w0; acc[4 * j + 2] *= w1; acc[4 * j + 3] *= w1; }
            const int np = mt == 15 ? 4 : 2;
#pragma unroll 1
            for (int i = 0; i < np; i++) {
                mbar_wait(bar_full + 8 * s, ph);
                sprev = s;
#pragma unroll
                for (int j = 0; j < 8; j++) {
                    uint32_t u[4];
                    ldsm_x4(u, sbase + s * 32768 + wg * 16384 + (j >> 2) * 8192 + moff + ((mx ^ ((j & 3) * 2)) << 4));
#pragma unroll
                    for (int e = 0; e < 4; e++) {
                        acc[8 * j + 2 * e] += __uint_as_float(u[e] << 16);
                        acc[8 * j + 2 * e + 1] += __uint_as_float(u[e] & 0xffff0000u);
                    }
                }
                if (++s == 6) { s = 0; ph ^= 1; }
            }
            OT(5);
            const uint32_t stg = sbase + sprev * 32768 + wg * 16384;
#pragma unroll
            for (int j = 0; j < 8; j++) {
                const float* a = &acc[8 * j];
                stmatrix_x4(stg + (j >> 2) * 8192 + moff + ((mx ^ ((j & 3) * 2)) << 4), pack_bf16(a[0], a[1]), pack_bf16(a[2], a[3]), pack_bf16(a[4], a[5]), pack_bf16(a[6], a[7]));
            }
            fence_async_smem();
            asm volatile("bar.sync %0, 128;" :: "r"(2 + wg) : "memory");
            if (elected) {
                tma_store_2d(&P.mapOut, stg, n0, m0 + wg * 64);
                tma_store_2d(&P.mapOut, stg + 8192, n0 + 64, m0 + wg * 64);
                asm volatile("cp.async.bulk.commit_group;" ::: "memory");
                asm volatile("cp.async.bulk.wait_group 0;" ::: "memory");
            }
            OT(6);
        }
    }
    __syncthreads();
    asm volatile("barrier.cluster.arrive.release.aligned;" ::: "memory");
    if (warp == 0) {
        unsigned int tk = 0;
        if (lane == 0) tk = atomicAdd(&g_ctr[CT_FIN], 1u);
        tk = __shfl_sync(0xffffffff, tk, 0);
        if (tk == gridDim.x - 1)
            for (int i = lane; i < CT_N; i += 32) g_ctr[i] = 0u;
    }
    asm volatile("barrier.cluster.wait.acquire.aligned;" ::: "memory");
    TS_END(4);
}

typedef CUresult (*PFN_encodeTiled)(CUtensorMap*, CUtensorMapDataType, cuuint32_t, void*, const cuuint64_t*,
                                    const cuuint64_t*, const cuuint32_t*, const cuuint32_t*, CUtensorMapInterleave,
                                    CUtensorMapSwizzle, CUtensorMapL2promotion, CUtensorMapFloatOOBfill);
static PFN_encodeTiled g_encode = nullptr;

static void make_map(CUtensorMap* m, const void* ptr, uint64_t rows, uint64_t cols, uint32_t box_rows, bool sw64 = false) {
    cuuint64_t dims[2] = {cols, rows};
    cuuint64_t strides[1] = {cols * 2};
    cuuint32_t box[2] = {sw64 ? 32u : 64u, box_rows};
    cuuint32_t es[2] = {1, 1};
    g_encode(m, CU_TENSOR_MAP_DATA_TYPE_BFLOAT16, 2, const_cast<void*>(ptr), dims, strides, box, es,
             CU_TENSOR_MAP_INTERLEAVE_NONE, sw64 ? CU_TENSOR_MAP_SWIZZLE_64B : CU_TENSOR_MAP_SWIZZLE_128B, CU_TENSOR_MAP_L2_PROMOTION_L2_256B,
             CU_TENSOR_MAP_FLOAT_OOB_FILL_NONE);
}

template <typename... KArgs, typename... Args>
static void launch_pdl(void (*kernel)(KArgs...), int grid, int block, size_t smem, cudaStream_t st, bool pdl, Args... args) {
    cudaLaunchConfig_t cfg = {};
    cfg.gridDim = dim3(grid); cfg.blockDim = dim3(block); cfg.dynamicSmemBytes = smem; cfg.stream = st;
    cudaLaunchAttribute at[1];
    at[0].id = cudaLaunchAttributeProgrammaticStreamSerialization;
    at[0].val.programmaticStreamSerializationAllowed = 1;
    cfg.attrs = at; cfg.numAttrs = pdl ? 1 : 0;
    cudaLaunchKernelEx(&cfg, kernel, KArgs(args)...);
}

extern "C" void kernel_launch(void* const* d_in, const int* in_sizes, int n_in, void* d_out, int out_size) {
    const bf16* x = (const bf16*)d_in[0];
    const bf16* ckv = (const bf16*)d_in[1];
    const bf16* wq = (const bf16*)d_in[2];
    const bf16* wuk = (const bf16*)d_in[3];
    const bf16* wuv = (const bf16*)d_in[4];
    const bf16* wo = (const bf16*)d_in[5];
    const bf16* mem0 = (const bf16*)d_in[7];
    const bf16* Wq = (const bf16*)d_in[8];
    const bf16* Wk = (const bf16*)d_in[9];
    const bf16* Wv = (const bf16*)d_in[10];
    const bf16* Wo = (const bf16*)d_in[11];
    const bf16* gate_w = (const bf16*)d_in[13];
    bf16* out = (bf16*)d_out;

    static Proj2Params P2;
    static CUtensorMap mapX;
    static AttnParams AP;
    static OutParams OP;
    static bool init = false;
    static const void* last_in[15];
    bool same = init;
    for (int i = 0; i < 14 && same; i++) same = last_in[i] == d_in[i];
    same = same && last_in[14] == d_out;
    if (!init) {
        cudaDriverEntryPointQueryResult qr;
        cudaGetDriverEntryPoint("cuTensorMapEncodeTiled", (void**)&g_encode, cudaEnableDefault, &qr);
        cudaFuncSetAttribute(proj2_kernel, cudaFuncAttributeMaxDynamicSharedMemorySize, P2_SMEM);
        cudaFuncSetAttribute(attn_kernel, cudaFuncAttributeMaxDynamicSharedMemorySize, FA_SMEM);
        cudaFuncSetAttribute(chain_kernel, cudaFuncAttributeMaxDynamicSharedMemorySize, C2_SMEM);
        cudaFuncSetAttribute(out3_kernel, cudaFuncAttributeMaxDynamicSharedMemorySize, O2_SMEM);
        init = true;
    }
    if (!same) {
        for (int i = 0; i < 14; i++) last_in[i] = d_in[i];
        last_in[14] = d_out;
        void *pQA, *pKA, *pVA, *pCA, *pCB;
        cudaGetSymbolAddress(&pQA, g_QA); cudaGetSymbolAddress(&pKA, g_KA); cudaGetSymbolAddress(&pVA, g_VA);
        cudaGetSymbolAddress(&pCA, g_ctxA); cudaGetSymbolAddress(&pCB, g_ctxB);
        make_map(&P2.mapA[0], x, SEQ, DM, 128);
        make_map(&P2.mapA[1], ckv, SEQ, DM, 128);
        const void* ws[3] = {wq, wuk, wuv};
        void* cs[3] = {pQA, pKA, pVA};
        for (int i = 0; i < 3; i++) { make_map(&P2.mapW[i], ws[i], DM, NQ, 64); P2.out[i] = (bf16*)cs[i]; }
        make_map(&mapX, x, SEQ, DM, SEGL);
        make_map(&AP.mapQ, pQA, NH * SEQ, HD, 128);
        make_map(&AP.mapK, pKA, NH * SEQ, HD, 128);
        make_map(&AP.mapV, pVA, NH * SEQ, HD, 128);
        make_map(&AP.mapO, pCA, NH * SEQ, HD, 64);
        make_map(&OP.mapCtx[0], pCA, NH * SEQ, HD, 64);
        make_map(&OP.mapCtx[1], pCB, NH * SEQ, HD, 64);
        make_map(&OP.mapWo[0], wo, NQ, DM, 64);
        make_map(&OP.mapWo[1], Wo, NQ, DM, 64);
        void* pP; cudaGetSymbolAddress(&pP, g_part);
        make_map(&OP.mapPart, pP, 4 * SEQ, DM, 64);
        make_map(&OP.mapOut, out, SEQ, DM, 64);
        AP.x = x; AP.gate_w = gate_w;
    }
    cudaStream_t s1 = cudaStreamPerThread;
    const bool pdl = true;
    launch_pdl(chain_kernel, 64, 384, C2_SMEM, s1, false, mapX, mem0, Wq, Wk, Wv, Wo);
    launch_pdl(proj2_kernel, 68, 384, P2_SMEM, s1, pdl, P2);
    launch_pdl(attn_kernel, FA_GRID, 384, FA_SMEM, s1, pdl, AP, 1000);
    launch_pdl(out3_kernel, O3_GRID, 352, O2_SMEM, s1, pdl, OP);
}
```

```cpp
#include <cuda_runtime.h>
#include <cuda_bf16.h>
#include <cuda.h>
#include <stdint.h>
#include <type_traits>

constexpr int SEQ = 2048;
constexpr int DM = 512;
constexpr int NH = 32;
constexpr int HD = 128;
constexpr int NQ = NH * HD;
constexpr int SEGL = 32;
constexpr int NMEM = 8;
constexpr int NSEG = SEQ / SEGL;

typedef __nv_bfloat16 bf16;

__device__ bf16 g_QA[SEQ * NQ];
__device__ bf16 g_KA[SEQ * NQ];
__device__ bf16 g_VA[SEQ * NQ];
__device__ bf16 g_ctxA[SEQ * NQ];
__device__ bf16 g_ctxB[SEQ * NQ];
constexpr int CT_PROJ = 0, CT_ATTN = 1, CT_FIN = 5;
constexpr int CT_G = 32;
constexpr int CT_AP = 64;
#define O2_HE 24
constexpr int CT_CA = 128;
constexpr int CT_CB = 160;
constexpr int CT_OP = 192;
constexpr int CT_N = 448;
__device__ unsigned int g_ctr[CT_N];
__device__ float g_gate[SEQ];
__device__ uint2 g_xbuf[2 * 8 * 8 * 128];

#define FA_GRID 68

#define TS_BEGIN(id)
#define TS_END(id)
__device__ __forceinline__ void pdl_launch_dependents() { asm volatile("griddepcontrol.launch_dependents;" ::: "memory"); }
__device__ __forceinline__ void wait_ctr(int idx, unsigned int n) {
    unsigned int v; int it = 0;
    do { asm volatile("ld.acquire.gpu.global.u32 %0, [%1];" : "=r"(v) : "l"(&g_ctr[idx]) : "memory"); } while (v < n && ++it < (1 << 22));
}
__device__ __forceinline__ void signal_ctr(int idx) {
    asm volatile("fence.proxy.async.global;" ::: "memory");
    asm volatile("red.release.gpu.global.add.u32 [%0], 1;" :: "l"(&g_ctr[idx]) : "memory");
}
__device__ __forceinline__ void signal_ctr_generic(int idx) {
    asm volatile("red.release.gpu.global.add.u32 [%0], 1;" :: "l"(&g_ctr[idx]) : "memory");
}
__device__ __forceinline__ uint32_t smem_u32(const void* p) {
    return (uint32_t)__cvta_generic_to_shared(p);
}
__device__ __forceinline__ void mbar_init(uint32_t bar, uint32_t count) {
    asm volatile("mbarrier.init.shared::cta.b64 [%0], %1;" :: "r"(bar), "r"(count));
}
__device__ __forceinline__ void mbar_expect_tx(uint32_t bar, uint32_t bytes) {
    asm volatile("mbarrier.arrive.expect_tx.shared::cta.b64 _, [%0], %1;" :: "r"(bar), "r"(bytes) : "memory");
}
__device__ __forceinline__ void mbar_arrive(uint32_t bar) {
    asm volatile("mbarrier.arrive.shared::cta.b64 _, [%0];" :: "r"(bar) : "memory");
}
__device__ __forceinline__ void mbar_wait(uint32_t bar, uint32_t parity) {
    asm volatile(
        "{\n"
        ".reg .pred p, q;\n"
        ".reg .u32 c;\n"
        "mov.u32 c, 0;\n"
        "WAIT_LOOP:\n"
        "mbarrier.try_wait.parity.shared::cta.b64 p, [%0], %1;\n"
        "@p bra WAIT_DONE;\n"
        "add.u32 c, c, 1;\n"
        "setp.lt.u32 q, c, 4000000;\n"
        "@q bra WAIT_LOOP;\n"
        "WAIT_DONE:\n"
        "}\n" :: "r"(bar), "r"(parity) : "memory");
}
__device__ __forceinline__ void tma_load_2d(uint32_t dst, const CUtensorMap* map, uint32_t bar, int c0, int c1) {
    asm volatile(
        "cp.async.bulk.tensor.2d.shared::cluster.global.mbarrier::complete_tx::bytes [%0], [%1, {%3, %4}], [%2];"
        :: "r"(dst), "l"((uint64_t)map), "r"(bar), "r"(c0), "r"(c1) : "memory");
}
__device__ __forceinline__ void wgmma_fence() { asm volatile("wgmma.fence.sync.aligned;" ::: "memory"); }
__device__ __forceinline__ void wgmma_commit() { asm volatile("wgmma.commit_group.sync.aligned;" ::: "memory"); }
template <int N> __device__ __forceinline__ void wgmma_wait() {
    asm volatile("wgmma.wait_group.sync.aligned %0;" :: "n"(N) : "memory");
}
__device__ __forceinline__ uint64_t make_desc(uint32_t addr, uint32_t lbo, uint32_t sbo) {
    uint64_t d = 0;
    d |= (uint64_t)((addr & 0x3FFFF) >> 4);
    d |= (uint64_t)((lbo >> 4) & 0x3FFF) << 16;
    d |= (uint64_t)((sbo >> 4) & 0x3FFF) << 32;
    d |= (uint64_t)1 << 62;
    return d;
}

#define ACC64(d) \
    "+f"(d[0]), "+f"(d[1]), "+f"(d[2]), "+f"(d[3]), "+f"(d[4]), "+f"(d[5]), "+f"(d[6]), "+f"(d[7]), \
    "+f"(d[8]), "+f"(d[9]), "+f"(d[10]), "+f"(d[11]), "+f"(d[12]), "+f"(d[13]), "+f"(d[14]), "+f"(d[15]), \
    "+f"(d[16]), "+f"(d[17]), "+f"(d[18]), "+f"(d[19]), "+f"(d[20]), "+f"(d[21]), "+f"(d[22]), "+f"(d[23]), \
    "+f"(d[24]), "+f"(d[25]), "+f"(d[26]), "+f"(d[27]), "+f"(d[28]), "+f"(d[29]), "+f"(d[30]), "+f"(d[31]), \
    "+f"(d[32]), "+f"(d[33]), "+f"(d[34]), "+f"(d[35]), "+f"(d[36]), "+f"(d[37]), "+f"(d[38]), "+f"(d[39]), \
    "+f"(d[40]), "+f"(d[41]), "+f"(d[42]), "+f"(d[43]), "+f"(d[44]), "+f"(d[45]), "+f"(d[46]), "+f"(d[47]), \
    "+f"(d[48]), "+f"(d[49]), "+f"(d[50]), "+f"(d[51]), "+f"(d[52]), "+f"(d[53]), "+f"(d[54]), "+f"(d[55]), \
    "+f"(d[56]), "+f"(d[57]), "+f"(d[58]), "+f"(d[59]), "+f"(d[60]), "+f"(d[61]), "+f"(d[62]), "+f"(d[63])
#define ACC64_STR \
    "{%0, %1, %2, %3, %4, %5, %6, %7, %8, %9, %10, %11, %12, %13, %14, %15, " \
    "%16, %17, %18, %19, %20, %21, %22, %23, %24, %25, %26, %27, %28, %29, %30, %31, " \
    "%32, %33, %34, %35, %36, %37, %38, %39, %40, %41, %42, %43, %44, %45, %46, %47, " \
    "%48, %49, %50, %51, %52, %53, %54, %55, %56, %57, %58, %59, %60, %61, %62, %63}"

template <int TB>
__device__ __forceinline__ void wgmma_ss_n128(float (&d)[64], uint64_t da, uint64_t db, int scale_d) {
    asm volatile(
        "{\n.reg .pred p;\nsetp.ne.b32 p, %66, 0;\n"
        "wgmma.mma_async.sync.aligned.m64n128k16.f32.bf16.bf16 " ACC64_STR ", %64, %65, p, 1, 1, 0, %67;\n}\n"
        : ACC64(d) : "l"(da), "l"(db), "r"(scale_d), "n"(TB));
}
__device__ __forceinline__ uint32_t desc_lo(uint32_t addr, uint32_t lbo) { return ((addr & 0x3FFFF) >> 4) | ((lbo >> 4) << 16); }
template <int TB>
__device__ __forceinline__ void wgmma_ss_n128_lo(float (&d)[64], uint32_t da_lo, uint32_t db_lo, int scale_d) {
    asm volatile(
        "{\n.reg .pred p;\n.reg .b64 da, db;\nsetp.ne.b32 p, %66, 0;\n"
        "mov.b64 da, {%64, 0x40000040};\nmov.b64 db, {%65, 0x40000040};\n"
        "wgmma.mma_async.sync.aligned.m64n128k16.f32.bf16.bf16 " ACC64_STR ", da, db, p, 1, 1, 0, %67;\n}\n"
        : ACC64(d) : "r"(da_lo), "r"(db_lo), "r"(scale_d), "n"(TB));
}
__device__ __forceinline__ void wgmma_rs_n128_tb(float (&d)[64], uint32_t a0, uint32_t a1, uint32_t a2, uint32_t a3,
                                                 uint64_t db, int scale_d) {
    asm volatile(
        "{\n.reg .pred p;\nsetp.ne.b32 p, %69, 0;\n"
        "wgmma.mma_async.sync.aligned.m64n128k16.f32.bf16.bf16 " ACC64_STR ", {%64, %65, %66, %67}, %68, p, 1, 1, 1;\n}\n"
        : ACC64(d) : "r"(a0), "r"(a1), "r"(a2), "r"(a3), "l"(db), "r"(scale_d));
}
__device__ __forceinline__ void wgmma_rs_n80(float (&d)[40], const uint32_t (&a)[4], uint32_t db_lo, int scale_d) {
    asm volatile(
        "{\n.reg .pred p;\n.reg .b64 db;\nsetp.ne.b32 p, %45, 0;\nmov.b64 db, {%44, 0x40000040};\n"
        "wgmma.mma_async.sync.aligned.m64n80k16.f32.bf16.bf16 "
        "{%0, %1, %2, %3, %4, %5, %6, %7, %8, %9, %10, %11, %12, %13, %14, %15, %16, %17, %18, %19, %20, %21, %22, %23, %24, %25, %26, %27, %28, %29, %30, %31, %32, %33, %34, %35, %36, %37, %38, %39}, "
        "{%40, %41, %42, %43}, db, p, 1, 1, 0;\n}\n"
        : "+f"(d[0]), "+f"(d[1]), "+f"(d[2]), "+f"(d[3]), "+f"(d[4]), "+f"(d[5]), "+f"(d[6]), "+f"(d[7]), "+f"(d[8]), "+f"(d[9]), "+f"(d[10]), "+f"(d[11]), "+f"(d[12]), "+f"(d[13]), "+f"(d[14]), "+f"(d[15]), "+f"(d[16]), "+f"(d[17]), "+f"(d[18]), "+f"(d[19]), "+f"(d[20]), "+f"(d[21]), "+f"(d[22]), "+f"(d[23]), "+f"(d[24]), "+f"(d[25]), "+f"(d[26]), "+f"(d[27]), "+f"(d[28]), "+f"(d[29]), "+f"(d[30]), "+f"(d[31]), "+f"(d[32]), "+f"(d[33]), "+f"(d[34]), "+f"(d[35]), "+f"(d[36]), "+f"(d[37]), "+f"(d[38]), "+f"(d[39])
        : "r"(a[0]), "r"(a[1]), "r"(a[2]), "r"(a[3]), "r"(db_lo), "r"(scale_d));
}
__device__ __forceinline__ void wgmma_ss_n256_tb(float (&d)[128], uint64_t da, uint64_t db, int scale_d) {
    asm volatile(
        "{\n.reg .pred p;\nsetp.ne.b32 p, %130, 0;\n"
        "wgmma.mma_async.sync.aligned.m64n256k16.f32.bf16.bf16 {%0, %1, %2, %3, %4, %5, %6, %7, %8, %9, %10, %11, %12, %13, %14, %15, %16, %17, %18, %19, %20, %21, %22, %23, %24, %25, %26, %27, %28, %29, %30, %31, %32, %33, %34, %35, %36, %37, %38, %39, %40, %41, %42, %43, %44, %45, %46, %47, %48, %49, %50, %51, %52, %53, %54, %55, %56, %57, %58, %59, %60, %61, %62, %63, %64, %65, %66, %67, %68, %69, %70, %71, %72, %73, %74, %75, %76, %77, %78, %79, %80, %81, %82, %83, %84, %85, %86, %87, %88, %89, %90, %91, %92, %93, %94, %95, %96, %97, %98, %99, %100, %101, %102, %103, %104, %105, %106, %107, %108, %109, %110, %111, %112, %113, %114, %115, %116, %117, %118, %119, %120, %121, %122, %123, %124, %125, %126, %127}, %128, %129, p, 1, 1, 0, 1;\n}\n"
        : "+f"(d[0]), "+f"(d[1]), "+f"(d[2]), "+f"(d[3]), "+f"(d[4]), "+f"(d[5]), "+f"(d[6]), "+f"(d[7]), "+f"(d[8]), "+f"(d[9]), "+f"(d[10]), "+f"(d[11]), "+f"(d[12]), "+f"(d[13]), "+f"(d[14]), "+f"(d[15]), "+f"(d[16]), "+f"(d[17]), "+f"(d[18]), "+f"(d[19]), "+f"(d[20]), "+f"(d[21]), "+f"(d[22]), "+f"(d[23]), "+f"(d[24]), "+f"(d[25]), "+f"(d[26]), "+f"(d[27]), "+f"(d[28]), "+f"(d[29]), "+f"(d[30]), "+f"(d[31]), "+f"(d[32]), "+f"(d[33]), "+f"(d[34]), "+f"(d[35]), "+f"(d[36]), "+f"(d[37]), "+f"(d[38]), "+f"(d[39]), "+f"(d[40]), "+f"(d[41]), "+f"(d[42]), "+f"(d[43]), "+f"(d[44]), "+f"(d[45]), "+f"(d[46]), "+f"(d[47]), "+f"(d[48]), "+f"(d[49]), "+f"(d[50]), "+f"(d[51]), "+f"(d[52]), "+f"(d[53]), "+f"(d[54]), "+f"(d[55]), "+f"(d[56]), "+f"(d[57]), "+f"(d[58]), "+f"(d[59]), "+f"(d[60]), "+f"(d[61]), "+f"(d[62]), "+f"(d[63]), "+f"(d[64]), "+f"(d[65]), "+f"(d[66]), "+f"(d[67]), "+f"(d[68]), "+f"(d[69]), "+f"(d[70]), "+f"(d[71]), "+f"(d[72]), "+f"(d[73]), "+f"(d[74]), "+f"(d[75]), "+f"(d[76]), "+f"(d[77]), "+f"(d[78]), "+f"(d[79]), "+f"(d[80]), "+f"(d[81]), "+f"(d[82]), "+f"(d[83]), "+f"(d[84]), "+f"(d[85]), "+f"(d[86]), "+f"(d[87]), "+f"(d[88]), "+f"(d[89]), "+f"(d[90]), "+f"(d[91]), "+f"(d[92]), "+f"(d[93]), "+f"(d[94]), "+f"(d[95]), "+f"(d[96]), "+f"(d[97]), "+f"(d[98]), "+f"(d[99]), "+f"(d[100]), "+f"(d[101]), "+f"(d[102]), "+f"(d[103]), "+f"(d[104]), "+f"(d[105]), "+f"(d[106]), "+f"(d[107]), "+f"(d[108]), "+f"(d[109]), "+f"(d[110]), "+f"(d[111]), "+f"(d[112]), "+f"(d[113]), "+f"(d[114]), "+f"(d[115]), "+f"(d[116]), "+f"(d[117]), "+f"(d[118]), "+f"(d[119]), "+f"(d[120]), "+f"(d[121]), "+f"(d[122]), "+f"(d[123]), "+f"(d[124]), "+f"(d[125]), "+f"(d[126]), "+f"(d[127])
        : "l"(da), "l"(db), "r"(scale_d));
}
__device__ __forceinline__ void stmatrix_x4(uint32_t addr, uint32_t r0, uint32_t r1, uint32_t r2, uint32_t r3) {
    asm volatile("stmatrix.sync.aligned.m8n8.x4.shared.b16 [%0], {%1, %2, %3, %4};" :: "r"(addr), "r"(r0), "r"(r1), "r"(r2), "r"(r3) : "memory");
}
__device__ __forceinline__ void tma_store_2d(const CUtensorMap* map, uint32_t src, int c0, int c1) {
    asm volatile("cp.async.bulk.tensor.2d.global.shared::cta.bulk_group [%0, {%2, %3}], [%1];"
                 :: "l"((uint64_t)map), "r"(src), "r"(c0), "r"(c1) : "memory");
}
__device__ __forceinline__ float ex2f(float x) { float y; asm("ex2.approx.ftz.f32 %0, %1;" : "=f"(y) : "f"(x)); return y; }
__device__ __forceinline__ uint32_t pack_bf16(float lo, float hi) {
    __nv_bfloat162 v = __floats2bfloat162_rn(lo, hi);
    return *reinterpret_cast<uint32_t*>(&v);
}
__device__ __forceinline__ float bf16r(float x) { return __uint_as_float(pack_bf16(0.f, x) & 0xffff0000u); }
__device__ __forceinline__ void mma_16816(float (&c)[4], uint32_t a0, uint32_t a1, uint32_t a2, uint32_t a3,
                                          uint32_t b0, uint32_t b1) {
    asm volatile(
        "mma.sync.aligned.m16n8k16.row.col.f32.bf16.bf16.f32 {%0,%1,%2,%3}, {%4,%5,%6,%7}, {%8,%9}, {%0,%1,%2,%3};"
        : "+f"(c[0]), "+f"(c[1]), "+f"(c[2]), "+f"(c[3])
        : "r"(a0), "r"(a1), "r"(a2), "r"(a3), "r"(b0), "r"(b1));
}
__device__ __forceinline__ void ldmatrix_x4_trans(uint32_t& r0, uint32_t& r1, uint32_t& r2, uint32_t& r3, uint32_t addr) {
    asm volatile("ldmatrix.sync.aligned.m8n8.x4.trans.shared.b16 {%0,%1,%2,%3}, [%4];"
                 : "=r"(r0), "=r"(r1), "=r"(r2), "=r"(r3) : "r"(addr));
}

struct AttnParams {
    CUtensorMap mapQ, mapK, mapV;
    CUtensorMap mapO;
    const bf16 *x, *gate_w;
};
constexpr int FA_STAGES = 2;
constexpr int FA_SMEM = 32768 + FA_STAGES * 65536 + 32768 + 1024 + 256;
constexpr int FA_ITEMS = 16 * NH;
#define FA_RETIRE 100000
#define FA_LASTG 8
__device__ __forceinline__ int fa_qt(int t) {
    constexpr int T0 = (32 - FA_LASTG) * 16;
    return t < T0 ? 15 - ((t & 127) >> 3) : 15 - (t - T0) / FA_LASTG;
}
__device__ __forceinline__ int fa_head(int t) {
    constexpr int T0 = (32 - FA_LASTG) * 16;
    return t < T0 ? (t >> 7) * 8 + (t & 7) : (32 - FA_LASTG) + (t - T0) % FA_LASTG;
}

__global__ void __launch_bounds__(384, 1) attn_kernel(const __grid_constant__ AttnParams P, int retire_cta) {
    extern __shared__ uint8_t smem_raw[];
    uint32_t sbase = (smem_u32(smem_raw) + 1023) & ~1023u;
    const uint32_t sQ = sbase;
    const uint32_t sKV = sbase + 32768;
    const uint32_t sO = sKV + FA_STAGES * 65536;
    const uint32_t bars = sO + 32768;
    const uint32_t bar_q = bars, bar_qe = bars + 8, bar_kf = bars + 16, bar_vf = bar_kf + 8 * FA_STAGES, bar_e = bar_vf + 8 * FA_STAGES,
                   bar_ek = bar_e + 8 * FA_STAGES, slot = bar_ek + 8 * FA_STAGES, bar_of = slot + 16, bar_oe = bar_of + 16, oslot = bar_oe + 16;
    const int warp = threadIdx.x >> 5;
    TS_BEGIN(1);
    int tfirst = 0;
    if (threadIdx.x == 256) tfirst = (int)atomicAdd(&g_ctr[CT_ATTN], 1u);
    if (threadIdx.x == 0) {
        mbar_init(bar_q, 1); mbar_init(bar_qe, 8);
        for (int i = 0; i < FA_STAGES; i++) { mbar_init(bar_kf + 8 * i, 1); mbar_init(bar_vf + 8 * i, 1); mbar_init(bar_e + 8 * i, 8); mbar_init(bar_ek + 8 * i, 8); }
        for (int i = 0; i < 2; i++) { mbar_init(bar_of + 8 * i, 1); mbar_init(bar_oe + 8 * i, 1); }
        asm volatile("fence.mbarrier_init.release.cluster;" ::: "memory");
    }
    if (threadIdx.x == 256) asm volatile("st.shared.s32 [%0], %1;" :: "r"(slot + 8), "r"(tfirst) : "memory");
    __syncthreads();
    pdl_launch_dependents();
    if (warp >= 8) {
        asm volatile("setmaxnreg.dec.sync.aligned.u32 40;");
        if (warp == 11) {
            const int lane = threadIdx.x & 31;
            const uint4 gv0 = __ldg(reinterpret_cast<const uint4*>(P.gate_w) + lane), gv1 = __ldg(reinterpret_cast<const uint4*>(P.gate_w) + 32 + lane);
            const uint32_t gw[8] = {gv0.x, gv0.y, gv0.z, gv0.w, gv1.x, gv1.y, gv1.z, gv1.w};
#pragma unroll 1
            for (int r = blockIdx.x; r < SEQ; r += gridDim.x) {
                const uint4 x0 = __ldg(reinterpret_cast<const uint4*>(P.x + (size_t)r * DM) + lane), x1 = __ldg(reinterpret_cast<const uint4*>(P.x + (size_t)r * DM) + 32 + lane);
                const uint32_t xw[8] = {x0.x, x0.y, x0.z, x0.w, x1.x, x1.y, x1.z, x1.w};
                float sum = 0.f;
#pragma unroll
                for (int e = 0; e < 8; e++) {
                    const uint32_t pr = pack_bf16(__uint_as_float(xw[e] << 16) * __uint_as_float(gw[e] << 16), __uint_as_float(xw[e] & 0xffff0000u) * __uint_as_float(gw[e] & 0xffff0000u));
                    sum += __uint_as_float(pr << 16) + __uint_as_float(pr & 0xffff0000u);
                }
#pragma unroll
                for (int o = 16; o; o >>= 1) sum += __shfl_xor_sync(0xffffffff, sum, o);
                if (lane == 0) g_gate[r] = bf16r(1.f / (1.f + __expf(-bf16r(sum))));
            }
            if (lane == 0) signal_ctr_generic(CT_G);
        }
        if (threadIdx.x == 288 || threadIdx.x == 320) {
            const int wg = threadIdx.x == 288 ? 0 : 1;
            const uint32_t stg = sO + wg * 16384;
            for (int n = 0;; n++) {
                mbar_wait(bar_of + 8 * wg, n & 1);
                int t;
                asm volatile("ld.shared.s32 %0, [%1];" : "=r"(t) : "r"(oslot + wg * 4) : "memory");
                if (t < 0) break;
                const int qt = fa_qt(t), h = fa_head(t);
                tma_store_2d(&P.mapO, stg, 0, h * SEQ + qt * 128 + wg * 64);
                tma_store_2d(&P.mapO, stg + 8192, 64, h * SEQ + qt * 128 + wg * 64);
                asm volatile("cp.async.bulk.commit_group;" ::: "memory");
                asm volatile("cp.async.bulk.wait_group.read 0;" ::: "memory");
                mbar_arrive(bar_oe + 8 * wg);
                asm volatile("cp.async.bulk.wait_group 0;" ::: "memory");
                signal_ctr(CT_CA + qt * 2 + (h >= O2_HE));
            }
        }
        if (threadIdx.x == 256) {
            int it = 0, hp_ready = 0;
            for (int item = 0;; item++) {
                int t = tfirst;
                if (item > 0) {
                    bool quit = false;
                    if ((int)blockIdx.x >= retire_cta) {
                        unsigned int v;
                        asm volatile("ld.relaxed.gpu.global.u32 %0, [%1];" : "=r"(v) : "l"(&g_ctr[CT_ATTN]) : "memory");
                        quit = v >= FA_RETIRE;
                    }
                    t = quit ? FA_ITEMS : (int)atomicAdd(&g_ctr[CT_ATTN], 1u);
                }
                const bool valid = t < FA_ITEMS;
                const int qt = fa_qt(t), h = fa_head(t);
                if (valid && !((hp_ready >> (h >> 1)) & 1)) { wait_ctr(CT_AP + (h >> 1), 96u); hp_ready |= 1 << (h >> 1); }
                mbar_wait(bar_qe, (item & 1) ^ 1);
                asm volatile("st.shared.s32 [%0], %1;" :: "r"(slot + (item & 1) * 4), "r"(valid ? t : -1) : "memory");
                if (!valid) { mbar_arrive(bar_q); break; }
                mbar_expect_tx(bar_q, 32768);
                tma_load_2d(sQ, &P.mapQ, bar_q, 0, h * SEQ + qt * 128);
                tma_load_2d(sQ + 16384, &P.mapQ, bar_q, 64, h * SEQ + qt * 128);
                for (int j = 0; j <= qt; j++, it++) {
                    const int s = it % FA_STAGES;
                    mbar_wait(bar_ek + 8 * s, ((it / FA_STAGES) & 1) ^ 1);
                    const uint32_t sk = sKV + s * 65536, sv = sk + 32768;
                    mbar_expect_tx(bar_kf + 8 * s, 32768);
                    tma_load_2d(sk, &P.mapK, bar_kf + 8 * s, 0, h * SEQ + j * 128);
                    tma_load_2d(sk + 16384, &P.mapK, bar_kf + 8 * s, 64, h * SEQ + j * 128);
                    mbar_wait(bar_e + 8 * s, ((it / FA_STAGES) & 1) ^ 1);
                    mbar_expect_tx(bar_vf + 8 * s, 32768);
                    tma_load_2d(sv, &P.mapV, bar_vf + 8 * s, 0, h * SEQ + j * 128);
                    tma_load_2d(sv + 16384, &P.mapV, bar_vf + 8 * s, 64, h * SEQ + j * 128);
                }
            }
        }
    } else {
        asm volatile("setmaxnreg.inc.sync.aligned.u32 232;");
        const int wg = warp >> 2;
        const int lane = threadIdx.x & 31;
        float o[64];
        float mrow0, mrow1, lrow0, lrow1;
        const float sc = 0.08838834764831845f * 1.4426950408889634f;
        const int r0 = wg * 64 + (warp & 3) * 16 + (lane >> 2);
        float sacc[64];
        uint32_t pa[32];
        float a0 = 1.f, a1 = 1.f;
        auto issue_qk = [&](int it) {
            const int s = it % FA_STAGES;
            const uint32_t sk = sKV + s * 65536;
            mbar_wait(bar_kf + 8 * s, (it / FA_STAGES) & 1);
            wgmma_fence();
#pragma unroll
            for (int kk = 0; kk < 8; kk++) {
                uint64_t da = make_desc(sQ + (kk >> 2) * 16384 + wg * 8192 + (kk & 3) * 32, 16, 1024);
                uint64_t db = make_desc(sk + (kk >> 2) * 16384 + (kk & 3) * 32, 16, 1024);
                wgmma_ss_n128<0>(sacc, da, db, kk != 0);
            }
            wgmma_commit();
        };
        auto issue_pv = [&](int it) {
            const int s = it % FA_STAGES;
            const uint32_t sv = sKV + s * 65536 + 32768;
            mbar_wait(bar_vf + 8 * s, (it / FA_STAGES) & 1);
            wgmma_fence();
#pragma unroll
            for (int kk = 0; kk < 8; kk++) {
                uint64_t db = make_desc(sv + kk * 2048, 16384, 1024);
                wgmma_rs_n128_tb(o, pa[kk * 4 + 0], pa[kk * 4 + 1], pa[kk * 4 + 2], pa[kk * 4 + 3], db, 1);
            }
            wgmma_commit();
        };
        auto softmax_stats = [&](bool diag) {
            if (diag) {
#pragma unroll
                for (int i = 0; i < 64; i++) {
                    int col = (i >> 2) * 8 + (lane & 3) * 2 + (i & 1);
                    int row = r0 + ((i & 2) ? 8 : 0);
                    if (col > row) sacc[i] = -INFINITY;
                }
            }
            float mx0 = -INFINITY, mx1 = -INFINITY;
#pragma unroll
            for (int i = 0; i < 16; i++) {
                mx0 = fmaxf(mx0, fmaxf(sacc[i * 4 + 0], sacc[i * 4 + 1]));
                mx1 = fmaxf(mx1, fmaxf(sacc[i * 4 + 2], sacc[i * 4 + 3]));
            }
            mx0 = fmaxf(mx0, __shfl_xor_sync(0xffffffff, mx0, 1));
            mx0 = fmaxf(mx0, __shfl_xor_sync(0xffffffff, mx0, 2));
            mx1 = fmaxf(mx1, __shfl_xor_sync(0xffffffff, mx1, 1));
            mx1 = fmaxf(mx1, __shfl_xor_sync(0xffffffff, mx1, 2));
            const float mn0 = fmaxf(mrow0, mx0), mn1 = fmaxf(mrow1, mx1);
            a0 = ex2f((mrow0 - mn0) * sc); a1 = ex2f((mrow1 - mn1) * sc);
            mrow0 = mn0; mrow1 = mn1;
            const float ms0 = mn0 * sc, ms1 = mn1 * sc;
            float sum0 = 0.f, sum1 = 0.f;
#pragma unroll
            for (int i = 0; i < 16; i++) {
                sacc[i * 4 + 0] = ex2f(fmaf(sacc[i * 4 + 0], sc, -ms0));
                sacc[i * 4 + 1] = ex2f(fmaf(sacc[i * 4 + 1], sc, -ms0));
                sacc[i * 4 + 2] = ex2f(fmaf(sacc[i * 4 + 2], sc, -ms1));
                sacc[i * 4 + 3] = ex2f(fmaf(sacc[i * 4 + 3], sc, -ms1));
                sum0 += sacc[i * 4 + 0] + sacc[i * 4 + 1];
                sum1 += sacc[i * 4 + 2] + sacc[i * 4 + 3];
            }
            lrow0 = lrow0 * a0 + sum0;
            lrow1 = lrow1 * a1 + sum1;
        };
        auto pack_p = [&]() {
#pragma unroll
            for (int i = 0; i < 16; i++) {
                pa[i * 2 + 0] = pack_bf16(sacc[i * 4 + 0], sacc[i * 4 + 1]);
                pa[i * 2 + 1] = pack_bf16(sacc[i * 4 + 2], sacc[i * 4 + 3]);
            }
        };
        int it = 0;
        if (wg == 1) asm volatile("bar.arrive 1, 256;" ::: "memory");
        for (int item = 0;; item++) {
            mbar_wait(bar_q, item & 1);
            int t;
            asm volatile("ld.shared.s32 %0, [%1];" : "=r"(t) : "r"(slot + (item & 1) * 4) : "memory");
            if (t < 0) {
                if ((threadIdx.x & 127) == 0) {
                    mbar_wait(bar_oe + 8 * wg, (item & 1) ^ 1);
                    asm volatile("st.shared.s32 [%0], %1;" :: "r"(oslot + wg * 4), "r"(-1) : "memory");
                    mbar_arrive(bar_of + 8 * wg);
                }
                break;
            }
            const int qt = fa_qt(t);
            const int nkv = qt + 1;
#pragma unroll
            for (int i = 0; i < 64; i++) o[i] = 0.f;
            mrow0 = -INFINITY; mrow1 = -INFINITY; lrow0 = 0.f; lrow1 = 0.f;
            asm volatile("bar.sync %0, 256;" :: "r"(1 + wg) : "memory");
            issue_qk(it);
            asm volatile("bar.arrive %0, 256;" :: "r"(2 - wg) : "memory");
            wgmma_wait<0>();
            if (lane == 0) { mbar_arrive(bar_ek + 8 * (it % FA_STAGES)); if (nkv == 1) mbar_arrive(bar_qe); }
            softmax_stats(nkv == 1);
            pack_p();
#pragma unroll 1
            for (int j = 1; j < nkv; j++) {
                asm volatile("bar.sync %0, 256;" :: "r"(1 + wg) : "memory");
                issue_qk(it + j);
                issue_pv(it + j - 1);
                asm volatile("bar.arrive %0, 256;" :: "r"(2 - wg) : "memory");
                wgmma_wait<1>();
                if (lane == 0) { mbar_arrive(bar_ek + 8 * ((it + j) % FA_STAGES)); if (j == nkv - 1) mbar_arrive(bar_qe); }
                softmax_stats(j == nkv - 1);
                wgmma_wait<0>();
                if (lane == 0) mbar_arrive(bar_e + 8 * ((it + j - 1) % FA_STAGES));
#pragma unroll
                for (int i = 0; i < 16; i++) {
                    o[i * 4 + 0] *= a0; o[i * 4 + 1] *= a0; o[i * 4 + 2] *= a1; o[i * 4 + 3] *= a1;
                }
                pack_p();
            }
            issue_pv(it + nkv - 1);
            wgmma_wait<0>();
            if (lane == 0) mbar_arrive(bar_e + 8 * ((it + nkv - 1) % FA_STAGES));
            it += nkv;
            lrow0 += __shfl_xor_sync(0xffffffff, lrow0, 1);
            lrow0 += __shfl_xor_sync(0xffffffff, lrow0, 2);
            lrow1 += __shfl_xor_sync(0xffffffff, lrow1, 1);
            lrow1 += __shfl_xor_sync(0xffffffff, lrow1, 2);
            const float i0 = 1.f / lrow0, i1 = 1.f / lrow1;
            const uint32_t stg = sO + wg * 16384;
            mbar_wait(bar_oe + 8 * wg, (item & 1) ^ 1);
            {
                const int row = (warp & 3) * 16 + (lane >> 2);
#pragma unroll
                for (int i = 0; i < 4; i++) {
                    const int ch = i * 4 + (lane & 3);
                    const uint32_t a = stg + (ch >> 3) * 8192 + row * 128 + (((ch & 7) ^ (row & 7)) << 4);
                    const float* q = &o[i * 16];
                    asm volatile("st.shared.v4.b32 [%0], {%1, %2, %3, %4};" :: "r"(a), "r"(pack_bf16(q[0] * i0, q[1] * i0)), "r"(pack_bf16(q[4] * i0, q[5] * i0)),
                                 "r"(pack_bf16(q[8] * i0, q[9] * i0)), "r"(pack_bf16(q[12] * i0, q[13] * i0)) : "memory");
                    asm volatile("st.shared.v4.b32 [%0], {%1, %2, %3, %4};" :: "r"(a + 1024), "r"(pack_bf16(q[2] * i1, q[3] * i1)), "r"(pack_bf16(q[6] * i1, q[7] * i1)),
                                 "r"(pack_bf16(q[10] * i1, q[11] * i1)), "r"(pack_bf16(q[14] * i1, q[15] * i1)) : "memory");
                }
            }
            asm volatile("fence.proxy.async.shared::cta;" ::: "memory");
            asm volatile("bar.sync %0, 128;" :: "r"(3 + wg) : "memory");
            if ((threadIdx.x & 127) == 0) {
                asm volatile("st.shared.s32 [%0], %1;" :: "r"(oslot + wg * 4), "r"(t) : "memory");
                mbar_arrive(bar_of + 8 * wg);
            }
        }
        TS_END(1);
    }
}

__device__ __forceinline__ uint32_t cluster_ctarank() {
    uint32_t r; asm volatile("mov.u32 %0, %%cluster_ctarank;" : "=r"(r)); return r;
}
__device__ __forceinline__ uint32_t mapa_u32(uint32_t addr, uint32_t rank) {
    uint32_t r; asm volatile("mapa.shared::cluster.u32 %0, %1, %2;" : "=r"(r) : "r"(addr), "r"(rank)); return r;
}
__device__ __forceinline__ void cluster_sync_all() {
    asm volatile("barrier.cluster.arrive.release.aligned;\nbarrier.cluster.wait.acquire.aligned;" ::: "memory");
}
__device__ __forceinline__ void cluster_sync_relaxed() {
    asm volatile("barrier.cluster.arrive.relaxed.aligned;\nbarrier.cluster.wait.aligned;" ::: "memory");
}
__device__ __forceinline__ void st_async_v4(uint32_t addr, uint32_t a, uint32_t b, uint32_t c, uint32_t d, uint32_t mbar) {
    asm volatile("st.async.weak.shared::cluster.mbarrier::complete_tx::bytes.v4.b32 [%0], {%1, %2, %3, %4}, [%5];"
                 :: "r"(addr), "r"(a), "r"(b), "r"(c), "r"(d), "r"(mbar) : "memory");
}
__device__ __forceinline__ void st_async_v2(uint32_t addr, uint32_t a, uint32_t b, uint32_t mbar) {
    asm volatile("st.async.weak.shared::cluster.mbarrier::complete_tx::bytes.v2.b32 [%0], {%1, %2}, [%3];"
                 :: "r"(addr), "r"(a), "r"(b), "r"(mbar) : "memory");
}
__device__ __forceinline__ void st_async_b32(uint32_t addr, uint32_t a, uint32_t mbar) {
    asm volatile("st.async.weak.shared::cluster.mbarrier::complete_tx::bytes.b32 [%0], %1, [%2];" :: "r"(addr), "r"(a), "r"(mbar) : "memory");
}
__device__ __forceinline__ void pace(int cycles) {
    if (cycles > 0) {
        uint32_t t0, t;
        asm volatile("mov.u32 %0, %%clock;" : "=r"(t0));
        do { asm volatile("mov.u32 %0, %%clock;" : "=r"(t)); } while (t - t0 < (uint32_t)cycles);
    }
}
__device__ __forceinline__ void mbar_wait_cl(uint32_t bar, uint32_t parity) {
    uint32_t done = 0;
    for (int it = 0; it < (1 << 22) && !done; it++) {
        asm volatile(
            "{\n.reg .pred p;\n"
            "mbarrier.try_wait.parity.shared::cta.b64 p, [%1], %2;\n"
            "selp.u32 %0, 1, 0, p;\n}\n" : "=r"(done) : "r"(bar), "r"(parity) : "memory");
    }
}
__device__ __forceinline__ uint32_t mbar_test(uint32_t bar, uint32_t parity) {
    uint32_t done;
    asm volatile(
        "{\n.reg .pred p;\n"
        "mbarrier.test_wait.parity.shared::cta.b64 p, [%1], %2;\n"
        "selp.u32 %0, 1, 0, p;\n}\n" : "=r"(done) : "r"(bar), "r"(parity) : "memory");
    return done;
}
__device__ __forceinline__ void ldmatrix_x4(uint32_t& r0, uint32_t& r1, uint32_t& r2, uint32_t& r3, uint32_t addr) {
    asm volatile("ldmatrix.sync.aligned.m8n8.x4.shared.b16 {%0,%1,%2,%3}, [%4];"
                 : "=r"(r0), "=r"(r1), "=r"(r2), "=r"(r3) : "r"(addr));
}
__device__ __forceinline__ void cp_async16(uint32_t dst, const void* src) {
    asm volatile("cp.async.cg.shared.global [%0], [%1], 16;" :: "r"(dst), "l"(src) : "memory");
}

#define DBG(i)
#define DBGW(i, w)
__device__ __forceinline__ void tma_load_2d_mc(uint32_t dst, const CUtensorMap* map, uint32_t bar, int c0, int c1, uint16_t mask) {
    asm volatile(
        "cp.async.bulk.tensor.2d.shared::cluster.global.mbarrier::complete_tx::bytes.multicast::cluster [%0], [%1, {%3, %4}], [%2], %5;"
        :: "r"(dst), "l"((uint64_t)map), "r"(bar), "r"(c0), "r"(c1), "h"(mask) : "memory");
}
__device__ __forceinline__ void bulk_s2s(uint32_t dst_cl, uint32_t src, uint32_t bytes, uint32_t bar_cl) {
    asm volatile("cp.async.bulk.shared::cluster.shared::cta.mbarrier::complete_tx::bytes [%0], [%1], %2, [%3];"
                 :: "r"(dst_cl), "r"(src), "r"(bytes), "r"(bar_cl) : "memory");
}
__device__ __forceinline__ bool elect_one() {
    uint32_t p;
    asm volatile("{\n.reg .pred p;\nelect.sync _|p, 0xffffffff;\nselp.u32 %0, 1, 0, p;\n}" : "=r"(p));
    return p;
}
__device__ __forceinline__ void fence_async_smem() { asm volatile("fence.proxy.async.shared::cta;" ::: "memory"); }
template <int ID, int N> __device__ __forceinline__ void bar_sync() { asm volatile("bar.sync %0, %1;" :: "n"(ID), "n"(N) : "memory"); }
template <int ID, int N> __device__ __forceinline__ void bar_arrive() { asm volatile("bar.arrive %0, %1;" :: "n"(ID), "n"(N) : "memory"); }
__device__ __forceinline__ void sts32(uint32_t a, uint32_t v) { asm volatile("st.shared.u32 [%0], %1;" :: "r"(a), "r"(v) : "memory"); }
__device__ __forceinline__ void ldsm_x4(uint32_t* r, uint32_t addr) {
    asm volatile("ldmatrix.sync.aligned.m8n8.x4.shared.b16 {%0,%1,%2,%3}, [%4];" : "=r"(r[0]), "=r"(r[1]), "=r"(r[2]), "=r"(r[3]) : "r"(addr) : "memory");
}
__device__ __forceinline__ uint32_t pin(uint32_t v) { asm volatile("" : "+r"(v)); return v; }
constexpr uint32_t DHI128 = 0x40000040u, DHI32 = 0xC0000010u;
#define ACC16(d) "+f"(d[0]), "+f"(d[1]), "+f"(d[2]), "+f"(d[3]), "+f"(d[4]), "+f"(d[5]), "+f"(d[6]), "+f"(d[7]), "+f"(d[8]), "+f"(d[9]), "+f"(d[10]), \
    "+f"(d[11]), "+f"(d[12]), "+f"(d[13]), "+f"(d[14]), "+f"(d[15])
#define ACC20(d) ACC16(d), "+f"(d[16]), "+f"(d[17]), "+f"(d[18]), "+f"(d[19])
__device__ __forceinline__ void wgmma_rs(float (&d)[16], const uint32_t (&a)[4], uint32_t db_lo) {
    asm volatile(
        "{\n.reg .b64 db;\nmov.b64 db, {%20, %21};\n"
        "wgmma.mma_async.sync.aligned.m64n32k16.f32.bf16.bf16 {%0,%1,%2,%3,%4,%5,%6,%7,%8,%9,%10,%11,%12,%13,%14,%15}, {%16,%17,%18,%19}, db, 1, 1, 1, 0;\n}\n"
        : ACC16(d) : "r"(a[0]), "r"(a[1]), "r"(a[2]), "r"(a[3]), "r"(db_lo), "n"(DHI128));
}
__device__ __forceinline__ void wgmma_rs(float (&d)[20], const uint32_t (&a)[4], uint32_t db_lo) {
    asm volatile(
        "{\n.reg .b64 db;\nmov.b64 db, {%24, %25};\n"
        "wgmma.mma_async.sync.aligned.m64n40k16.f32.bf16.bf16 {%0,%1,%2,%3,%4,%5,%6,%7,%8,%9,%10,%11,%12,%13,%14,%15,%16,%17,%18,%19}, {%20,%21,%22,%23}, db, 1, 1, 1, 0;\n}\n"
        : ACC20(d) : "r"(a[0]), "r"(a[1]), "r"(a[2]), "r"(a[3]), "r"(db_lo), "n"(DHI128));
}
template <uint32_t AHI, uint32_t BHI>
__device__ __forceinline__ void wgmma_ss(float (&d)[16], uint32_t da_lo, uint32_t db_lo) {
    asm volatile(
        "{\n.reg .b64 da, db;\nmov.b64 da, {%16, %18};\nmov.b64 db, {%17, %19};\n"
        "wgmma.mma_async.sync.aligned.m64n32k16.f32.bf16.bf16 {%0,%1,%2,%3,%4,%5,%6,%7,%8,%9,%10,%11,%12,%13,%14,%15}, da, db, 1, 1, 1, 0, 0;\n}\n"
        : ACC16(d) : "r"(da_lo), "r"(db_lo), "n"(AHI), "n"(BHI));
}
template <uint32_t AHI, uint32_t BHI>
__device__ __forceinline__ void wgmma_ss(float (&d)[20], uint32_t da_lo, uint32_t db_lo) {
    asm volatile(
        "{\n.reg .b64 da, db;\nmov.b64 da, {%20, %22};\nmov.b64 db, {%21, %23};\n"
        "wgmma.mma_async.sync.aligned.m64n40k16.f32.bf16.bf16 {%0,%1,%2,%3,%4,%5,%6,%7,%8,%9,%10,%11,%12,%13,%14,%15,%16,%17,%18,%19}, da, db, 1, 1, 1, 0, 0;\n}\n"
        : ACC20(d) : "r"(da_lo), "r"(db_lo), "n"(AHI), "n"(BHI));
}
__device__ __forceinline__ void wgmma_ss_n8(float (&d)[4], uint32_t da_lo, uint32_t db_lo) {
    asm volatile(
        "{\n.reg .b64 da, db;\nmov.b64 da, {%4, %6};\nmov.b64 db, {%5, %7};\n"
        "wgmma.mma_async.sync.aligned.m64n8k16.f32.bf16.bf16 {%0,%1,%2,%3}, da, db, 1, 1, 1, 1, 0;\n}\n"
        : "+f"(d[0]), "+f"(d[1]), "+f"(d[2]), "+f"(d[3]) : "r"(da_lo), "r"(db_lo), "n"(DHI128), "n"(DHI32));
}

constexpr uint32_t C2_WO = 0;
constexpr uint32_t C2_XB = 65536;
constexpr uint32_t C2_XS = 40960;
constexpr uint32_t C2_QX = C2_XB + 2 * C2_XS;
constexpr uint32_t C2_KX = C2_QX + 4096;
constexpr uint32_t C2_VT = C2_KX + 5120;
constexpr uint32_t C2_OB = C2_VT + 12288;
constexpr uint32_t C2_QM = C2_OB + 8192;
constexpr uint32_t C2_SC = C2_QM + 1024;
constexpr uint32_t C2_PB = C2_SC + 2560;
constexpr uint32_t C2_BAR = C2_PB + 768;
constexpr uint32_t C2_PX = C2_BAR + 256;
constexpr uint32_t C2_SX = C2_PX + 3072;
#define C2_NS 4
constexpr uint32_t C2_WS = C2_SX + 20480;
constexpr int C2_SMEM = C2_WS + 3 * C2_NS * 2048;
static_assert(C2_PX % 256 == 0 && C2_WS % 256 == 0 && C2_SMEM <= 232448, "smem map");
#define CH_PF 0
#define CH_PFD 3000
#define CH_POLL_DELAY 200

__device__ __forceinline__ uint32_t c2_stage(int wg, int i) { return wg < 2 ? C2_XB + C2_XS + (wg * 4 + i) * 8192 : ((C2_PX + 1023) & ~1023u) + i * 8192; }
static_assert(C2_XB + C2_XS + 8 * 8192 <= C2_BAR && ((C2_PX + 1023) & ~1023u) + 4 * 8192 <= C2_SMEM && (C2_XB + C2_XS) % 1024 == 0, "staging");
__device__ __forceinline__ void c2_stage_load(const CUtensorMap* map, uint32_t sb, int wg, int rank, int col0, int round) {
    const uint32_t bar = sb + C2_BAR + 176 + (wg * 2 + round) * 8;
    mbar_expect_tx(bar, 32768);
    for (int i = 0; i < 4; i++) tma_load_2d(sb + c2_stage(wg, i), map, bar, col0, ((rank - round * 4 - i) & 7) * 64);
}
__device__ __forceinline__ void c2_load_w(uint32_t (&w)[32][4], const CUtensorMap* map, int wg, int rank, int col0, uint32_t t128, uint32_t ws, uint32_t sb) {
#pragma unroll
    for (int r = 0; r < 2; r++) {
        mbar_wait(sb + C2_BAR + 176 + (wg * 2 + r) * 8, 0);
#pragma unroll
        for (int e = 0; e < 16; e++) {
            const uint32_t a = sb + c2_stage(wg, 0) + e * 2048;
            uint32_t w0, w1, w2, w3;
            asm volatile("ld.shared.b32 %0, [%1];" : "=r"(w0) : "r"(a + t128) : "memory");
            asm volatile("ld.shared.b32 %0, [%1];" : "=r"(w1) : "r"(a + (t128 ^ 16) + 128) : "memory");
            asm volatile("ld.shared.b32 %0, [%1];" : "=r"(w2) : "r"(a + t128 + 1024) : "memory");
            asm volatile("ld.shared.b32 %0, [%1];" : "=r"(w3) : "r"(a + (t128 ^ 16) + 1152) : "memory");
            uint32_t* d = w[r * 16 + e];
            d[0] = __byte_perm(w0, w1, 0x5410); d[1] = __byte_perm(w0, w1, 0x7632);
            d[2] = __byte_perm(w2, w3, 0x5410); d[3] = __byte_perm(w2, w3, 0x7632);
        }
        if (r == 0) {
            asm volatile("bar.sync %0, 128;" :: "r"(8 + wg) : "memory");
            if ((threadIdx.x & 127) == 32) c2_stage_load(map, sb, wg, rank, col0, 1);
            mbar_wait(sb + C2_BAR + 168, 0);
#pragma unroll 2
            for (int i = threadIdx.x; i < 2048; i += 384) {
                const int k = i >> 2, b = i & 3;
                const uint32_t a0 = sb + C2_WO + k * 128 + (((2 * b) ^ (k & 7)) << 4), a1 = a0 ^ 16;
                uint4 u, v;
                asm volatile("ld.shared.v4.b32 {%0, %1, %2, %3}, [%4];" : "=r"(u.x), "=r"(u.y), "=r"(u.z), "=r"(u.w) : "r"(a0) : "memory");
                asm volatile("ld.shared.v4.b32 {%0, %1, %2, %3}, [%4];" : "=r"(v.x), "=r"(v.y), "=r"(v.z), "=r"(v.w) : "r"(a1) : "memory");
                asm volatile("st.shared.v4.b32 [%0], {%1, %2, %3, %4};" :: "r"(a0), "r"(__byte_perm(u.x, u.y, 0x5410)),
                             "r"(__byte_perm(u.z, u.w, 0x5410)), "r"(__byte_perm(v.x, v.y, 0x5410)), "r"(__byte_perm(v.z, v.w, 0x5410)) : "memory");
                asm volatile("st.shared.v4.b32 [%0], {%1, %2, %3, %4};" :: "r"(a1), "r"(__byte_perm(u.x, u.y, 0x7632)),
                             "r"(__byte_perm(u.z, u.w, 0x7632)), "r"(__byte_perm(v.x, v.y, 0x7632)), "r"(__byte_perm(v.z, v.w, 0x7632)) : "memory");
            }
        }
    }
    cluster_sync_relaxed();
#pragma unroll
    for (int e = 0; e < C2_NS; e++) stmatrix_x4(ws + e * 2048, w[e][0], w[e][1], w[e][2], w[e][3]);
    for (int i = threadIdx.x; i < 2 * 512 + 256; i += 384)
        sts32(sb + (i < 1024 ? C2_VT + (i >> 9) * 6144 + 4096 + (i & 511) * 4 : C2_PX + 2048 + (i - 1024) * 4), 0u);
    fence_async_smem();
    asm volatile("bar.sync %0, 128;" :: "r"(8 + wg) : "memory");
}
template <int NA>
__device__ __forceinline__ void c2_xstream(float (&acc)[NA], const uint32_t (&w)[32][4], uint32_t xlo, uint32_t rank, uint32_t wslo) {
#pragma unroll
    for (int i = 0; i < NA; i++) acc[i] = 0.f;
    wgmma_fence();
#pragma unroll
    for (int e = 0; e < 32; e++) {
        if (e < C2_NS) wgmma_ss<DHI32, DHI128>(acc, wslo + e * 128, xlo + ((rank - (e >> 2)) & 7) * 320 + (e & 3) * 2);
        else wgmma_rs(acc, w[e], xlo + ((rank - (e >> 2)) & 7) * 320 + (e & 3) * 2);
    }
    wgmma_commit();
    wgmma_wait<0>();
}
__device__ __forceinline__ void c2_mma_slot(float (&a)[4][4], const uint32_t (&w)[32][4], int slot, const uint32_t* b, uint32_t ws) {
#pragma unroll
    for (int kk = 0; kk < 4; kk++) {
        const int e = slot * 4 + kk;
        if (e < C2_NS) {
            uint32_t t[4];
            ldsm_x4(t, ws + e * 2048);
            mma_16816(a[kk], t[0], t[1], t[2], t[3], b[2 * kk], b[2 * kk + 1]);
        } else mma_16816(a[kk], w[e][0], w[e][1], w[e][2], w[e][3], b[2 * kk], b[2 * kk + 1]);
    }
}
__device__ __forceinline__ constexpr int c2_grp(int i) { return i < 2 ? i : 1 + (i >> 1); }

struct ChainParams {
    CUtensorMap mapX;
    CUtensorMap mapM;
    CUtensorMap mapW[3];
    CUtensorMap mapWo;
};
__global__ void __cluster_dims__(8, 1, 1) __launch_bounds__(384, 1)
chain_kernel(const __grid_constant__ ChainParams P) {
    const CUtensorMap& mapX = P.mapX;
    extern __shared__ __align__(1024) uint8_t smem_chain[];
    const uint32_t sb = smem_u32(smem_chain);
    const uint32_t dlo = ((sb & 0x3FFFF) >> 4) | (1u << 16);
    const int tid = threadIdx.x, lane = tid & 31;
    const int warp = __shfl_sync(0xffffffff, tid >> 5, 0), wg = warp >> 2, w4 = warp & 3;
    const uint32_t rank = cluster_ctarank();
    const int C = blockIdx.x >> 3;
    const int h = C * 4 + (rank >> 1);
    const int g = lane >> 2, qc = lane & 3;
    pdl_launch_dependents();
    TS_BEGIN(2);
    const uint32_t bar_m = sb + C2_BAR, bar_o = bar_m + 64, bar_sc = bar_m + 128, bar_x = bar_m + 136, bar_sx = bar_m + 152;
    const uint32_t bar_w = bar_m + 168;
    const int col0 = h * HD + (rank & 1) * 64;
    if (tid == 0) {
        for (int j = 0; j < 5; j++) { mbar_init(bar_m + 8 * j, j ? 1 : 4); mbar_init(bar_o + 8 * j, j ? 1 : 4); }
        for (int j = 0; j < 12; j++) mbar_init(bar_sc + 8 * j, 1);
        asm volatile("fence.mbarrier_init.release.cluster;" ::: "memory");
    }
    __syncwarp();
    cluster_sync_relaxed();
    if (tid == 0) {
        mbar_expect_tx(bar_x, 32768 + 8192);
        tma_load_2d_mc(sb + C2_XB + rank * 5120, &mapX, bar_x, rank * 64, 0, (uint16_t)0xff);
        for (int j = 0; j < 8; j++) tma_load_2d(sb + C2_XB + j * 5120 + 4096, &P.mapM, bar_x, j * 64, 0);
        pace(CH_PFD);
        mbar_expect_tx(bar_w, 65536);
        for (int j = 0; j < 8; j++) tma_load_2d(sb + C2_WO + j * 8192, &P.mapWo, bar_w, rank * 64, C * 512 + ((rank - j) & 7) * 64);
    }
    if ((tid & 127) == 32) {
        pace(CH_PFD);
        c2_stage_load(&P.mapW[wg], sb, wg, rank, col0, 0);
        if (CH_PF)
            for (int i = 4; i < 8; i++)
                asm volatile("cp.async.bulk.prefetch.tensor.2d.L2.global [%0, {%1, %2}];" :: "l"((uint64_t)&P.mapW[wg]), "r"(col0), "r"((int)((rank - i) & 7) * 64) : "memory");
    }
    __syncwarp();

    const uint32_t t32 = w4 * 256 + qc * 64 + (((g >> 2) ^ (qc >> 1)) << 4) + (g & 3) * 4;
    const uint32_t t128 = qc * 256 + (((2 * w4 + (g >> 2)) ^ (2 * qc)) << 4) + (g & 3) * 4;
    const uint32_t a32 = (w4 * 16 + (lane & 15)) * 32 + (((lane >> 4) ^ ((lane >> 2) & 1)) << 4);
    const uint32_t ws = sb + C2_WS + wg * (C2_NS * 2048) + a32;
    uint32_t w[32][4];
    auto proj_mem = [&](float (&a)[4][4], int s) {
        uint32_t b[16];
#pragma unroll
        for (int i = 0; i < 16; i++) a[i >> 2][i & 3] = 0.f;
        const uint32_t par = (s & 1) ^ 1;
        const uint32_t l128 = (lane & 7) * 128 + (((lane >> 3) ^ (lane & 7)) << 4);
        const uint32_t mb = sb + C2_XB + (s & 1) * C2_XS + 4096;
        auto ldb = [&](uint32_t* bb, int i) {
            ldsm_x4(bb, mb + ((rank - i) & 7) * 5120 + l128);
            ldsm_x4(bb + 4, mb + ((rank - i) & 7) * 5120 + (l128 ^ 64));
        };
        mbar_wait(bar_m, par);
        ldb(b, 0);
        c2_mma_slot(a, w, 0, b, ws);
        mbar_wait(bar_m + 8, par);
        DBGW(1 + 16 * wg, 0);
        ldb(b, 1);
        uint32_t nxt = mbar_test(bar_m + 16, par);
        c2_mma_slot(a, w, 1, b, ws);
#pragma unroll
        for (int i = 2; i < 8; i += 2) {
            if (__builtin_expect(!nxt, 0)) mbar_wait(bar_m + 8 * c2_grp(i), par);
            if (i == 6) DBGW(2 + 16 * wg, 0);
            ldb(b, i);
            ldb(b + 8, i + 1);
            if (i < 6) nxt = mbar_test(bar_m + 8 * c2_grp(i + 2), par);
            c2_mma_slot(a, w, i, b, ws);
            c2_mma_slot(a, w, i + 1, b + 8, ws);
        }
#pragma unroll
        for (int i = 0; i < 4; i++) a[0][i] = (a[0][i] + a[1][i]) + (a[2][i] + a[3][i]);
    };
    auto store_x = [&](const float (&acc)[16], uint32_t base) {
#pragma unroll
        for (int j = 0; j < 4; j++) {
            sts32(base + t128 + j * 1024, pack_bf16(acc[4 * j], acc[4 * j + 2]));
            sts32(base + (t128 ^ 16) + 128 + j * 1024, pack_bf16(acc[4 * j + 1], acc[4 * j + 3]));
        }
    };
    const float scale = 0.08838834764831845f, l2e = 1.4426950408889634f;

    if (wg == 0) {
        c2_load_w(w, &P.mapW[0], 0, rank, col0, t128, ws, sb);
        TS_END(6);
        TS_BEGIN(5);
#pragma unroll 1
        for (int s = -1;;) {
            uint32_t xok = 0;
            if (s >= 0) {
                float acc[4] = {0.f, 0.f, 0.f, 0.f};
                const uint32_t tag = ((s >> 1) & 1) ^ 1;
                uint32_t* dst = reinterpret_cast<uint32_t*>(g_xbuf + (((s & 1) * 8 + rank) * 8 + C) * 128) + qc * 64 + w4 * 8 + g;
                asm volatile("" : "+l"(dst));
#pragma unroll
                for (int i = 0; i < 8; i++) {
                    if (i < 2 || !(i & 1)) {
                        mbar_wait(bar_o + 8 * c2_grp(i), s & 1);
                        if (i == 0) DBGW(7, 0);
                        if (i == 1) DBGW(8, 0);
                        if (i == 6) DBGW(9, 0);
                        wgmma_fence();
                    }
#pragma unroll
                    for (int kk = 0; kk < 4; kk++)
                        wgmma_ss_n8(acc, dlo + ((C2_WO + i * 8192 + kk * 2048) >> 4), dlo + ((C2_OB + i * 1024 + kk * 256) >> 4));
                }
                wgmma_commit();
                xok = mbar_test(bar_x + 8 * ((s + 1) & 1), ((s + 1) >> 1) & 1);
                wgmma_wait<0>();
                asm volatile("st.relaxed.gpu.global.u32 [%0], %1;" :: "l"(dst), "r"((pack_bf16(acc[0], acc[2]) & ~1u) | tag) : "memory");
                asm volatile("st.relaxed.gpu.global.u32 [%0 + 128], %1;" :: "l"(dst), "r"((pack_bf16(acc[1], acc[3]) & ~1u) | tag) : "memory");
                bar_arrive<4, 384>();
                DBGW(10, 0);
            }
            s++;
            if (__builtin_expect(!xok, 0)) mbar_wait(bar_x + 8 * (s & 1), (s >> 1) & 1);
            {
                float acc[16];
                c2_xstream(acc, w, dlo + ((C2_XB + (s & 1) * C2_XS) >> 4), rank, dlo + (C2_WS >> 4));
                if (s > 0) bar_sync<5, 256>();
                store_x(acc, sb + C2_QX);
            }
            DBGW(0, 0);
            if (s == NSEG - 1) break;
            const uint32_t sca = w4 < 2 ? sb + C2_SC + w4 * 512 + lane * 16 : sb + C2_SC + 1024 + lane * 8;
            const uint32_t sc_peer = pin(mapa_u32(sca + 1280, rank ^ 1)), sc_own = pin(mapa_u32(sca, rank));
            const uint32_t krow = w4 * 16 + (lane & 15);
            const uint32_t ka0 = pin(sb + C2_KX + krow * 128 + (((lane >> 4) ^ (krow & 7)) << 4));
            const uint32_t l32 = pin(sb + C2_QM + (lane >> 4) * 256 + (lane & 7) * 32 + ((((lane >> 3) & 1) ^ ((lane >> 2) & 1)) << 4));
            const uint32_t qst = pin(sb + C2_QM + t32);
            {
                float a[4][4];
                proj_mem(a, s);
                sts32(qst, pack_bf16(a[0][0], a[0][2]));
                sts32(qst + 32, pack_bf16(a[0][1], a[0][3]));
            }
            DBGW(3, 0);
            if (w4 < 3) {
                uint32_t ka[4][4], qb[8];
                float c[4] = {0.f, 0.f, 0.f, 0.f}, c2[4] = {0.f, 0.f, 0.f, 0.f};
                bar_sync<1, 384>();
                ldsm_x4(qb, l32);
                ldsm_x4(ka[0], ka0);
                ldsm_x4(ka[1], ka0 ^ 32);
                ldsm_x4(qb + 4, l32 + 512);
                ldsm_x4(ka[2], ka0 ^ 64);
                ldsm_x4(ka[3], ka0 ^ 96);
                mma_16816(c, ka[0][0], ka[0][1], ka[0][2], ka[0][3], qb[0], qb[1]);
                mma_16816(c2, ka[1][0], ka[1][1], ka[1][2], ka[1][3], qb[2], qb[3]);
                mma_16816(c, ka[2][0], ka[2][1], ka[2][2], ka[2][3], qb[4], qb[5]);
                mma_16816(c2, ka[3][0], ka[3][1], ka[3][2], ka[3][3], qb[6], qb[7]);
                const uint32_t u0 = __float_as_uint(c[0] + c2[0]), u1 = __float_as_uint(c[1] + c2[1]);
                const uint32_t u2 = __float_as_uint(c[2] + c2[2]), u3 = __float_as_uint(c[3] + c2[3]);
                asm volatile(
                    "{\n.reg .pred p;\nsetp.lt.u32 p, %8, 2;\n"
                    "@p st.async.weak.shared::cluster.mbarrier::complete_tx::bytes.v4.b32 [%0], {%4, %5, %6, %7}, [%1];\n"
                    "@!p st.async.weak.shared::cluster.mbarrier::complete_tx::bytes.v2.b32 [%0], {%4, %5}, [%1];\n"
                    "@p st.async.weak.shared::cluster.mbarrier::complete_tx::bytes.v4.b32 [%2], {%4, %5, %6, %7}, [%3];\n"
                    "@!p st.async.weak.shared::cluster.mbarrier::complete_tx::bytes.v2.b32 [%2], {%4, %5}, [%3];\n}"
                    :: "r"(sc_peer), "r"(mapa_u32(bar_sc, rank ^ 1)), "r"(sc_own), "r"(mapa_u32(bar_sc, rank)), "r"(u0), "r"(u1), "r"(u2), "r"(u3), "r"(w4) : "memory");
                bar_arrive<2, 224>();
                if (s == NSEG - 3 && tid == 0) signal_ctr(CT_CB + 1);
                __syncwarp();
                DBGW(4, 2);
            } else {
                bar_arrive<1, 384>();
                const uint32_t a = pin(sb + C2_SC + lane * 16), a2 = pin(sb + C2_SC + 1024 + lane * 8), pa = pin(sb + C2_PB + lane * 4);
                mbar_wait(bar_sc, s & 1);
                DBG(5);
                float v[10];
                {
                    float4 x0, x1, y0, y1; float2 x2, y2;
                    asm volatile("ld.shared.v4.f32 {%0, %1, %2, %3}, [%4];" : "=f"(x0.x), "=f"(x0.y), "=f"(x0.z), "=f"(x0.w) : "r"(a) : "memory");
                    asm volatile("ld.shared.v4.f32 {%0, %1, %2, %3}, [%4];" : "=f"(y0.x), "=f"(y0.y), "=f"(y0.z), "=f"(y0.w) : "r"(a + 1280) : "memory");
                    asm volatile("ld.shared.v4.f32 {%0, %1, %2, %3}, [%4];" : "=f"(x1.x), "=f"(x1.y), "=f"(x1.z), "=f"(x1.w) : "r"(a + 512) : "memory");
                    asm volatile("ld.shared.v4.f32 {%0, %1, %2, %3}, [%4];" : "=f"(y1.x), "=f"(y1.y), "=f"(y1.z), "=f"(y1.w) : "r"(a + 1792) : "memory");
                    asm volatile("ld.shared.v2.f32 {%0, %1}, [%2];" : "=f"(x2.x), "=f"(x2.y) : "r"(a2) : "memory");
                    asm volatile("ld.shared.v2.f32 {%0, %1}, [%2];" : "=f"(y2.x), "=f"(y2.y) : "r"(a2 + 1280) : "memory");
                    v[0] = x0.x + y0.x; v[1] = x0.y + y0.y; v[2] = x0.z + y0.z; v[3] = x0.w + y0.w;
                    v[4] = x1.x + y1.x; v[5] = x1.y + y1.y; v[6] = x1.z + y1.z; v[7] = x1.w + y1.w;
                    v[8] = x2.x + y2.x; v[9] = x2.y + y2.y;
                }
                float m0 = fmaxf(fmaxf(fmaxf(v[0], v[2]), fmaxf(v[4], v[6])), v[8]);
                float m1 = fmaxf(fmaxf(fmaxf(v[1], v[3]), fmaxf(v[5], v[7])), v[9]);
#pragma unroll
                for (int o = 4; o < 32; o <<= 1) {
                    m0 = fmaxf(m0, __shfl_xor_sync(0xffffffff, m0, o));
                    m1 = fmaxf(m1, __shfl_xor_sync(0xffffffff, m1, o));
                }
                const float sl = scale * l2e;
                m0 *= sl; m1 *= sl;
#pragma unroll
                for (int j = 0; j < 5; j++)
                    sts32(pa + j * 128, pack_bf16(ex2f(fmaf(v[2 * j], sl, -m0)), ex2f(fmaf(v[2 * j + 1], sl, -m1))));
                bar_arrive<3, 160>();
                DBG(6);
            }
            fence_async_smem();
            bar_arrive<6, 256>();
        }
        bar_sync<1, 384>();
        fence_async_smem();
        bar_arrive<6, 256>();
        bar_arrive<4, 384>();
    } else if (wg == 1) {
        c2_load_w(w, &P.mapW[1], 1, rank, col0, t128, ws, sb);
#pragma unroll 1
        for (int s = -1;;) {
            if (s > 0) {
                mbar_wait(bar_sx + 8 * ((s - 1) & 1), ((s - 1) >> 1) & 1);
                const uint32_t a = sb + C2_SX + ((s - 1) & 1) * 10240 + w4 * 1280 + lane * 8;
                float v[10];
                const int lim = 8 * w4 + g - 2 * qc;
#pragma unroll
                for (int j = 0; j < 5; j++) {
                    float2 x, y;
                    asm volatile("ld.shared.v2.f32 {%0, %1}, [%2];" : "=f"(x.x), "=f"(x.y) : "r"(a + j * 256) : "memory");
                    asm volatile("ld.shared.v2.f32 {%0, %1}, [%2];" : "=f"(y.x), "=f"(y.y) : "r"(a + 5120 + j * 256) : "memory");
                    v[2 * j] = (j < 4 && 8 * j > lim) ? -INFINITY : x.x + y.x;
                    v[2 * j + 1] = (j < 4 && 8 * j + 1 > lim) ? -INFINITY : x.y + y.y;
                }
                float mx = fmaxf(fmaxf(fmaxf(v[0], v[1]), fmaxf(v[2], v[3])), fmaxf(fmaxf(v[4], v[5]), fmaxf(v[6], v[7])));
                mx = fmaxf(mx, fmaxf(v[8], v[9]));
                mx = fmaxf(mx, __shfl_xor_sync(0xffffffff, mx, 1));
                mx = fmaxf(mx, __shfl_xor_sync(0xffffffff, mx, 2));
                const float sl = scale * l2e;
                mx *= sl;
#pragma unroll
                for (int j = 0; j < 10; j++) v[j] = ex2f(fmaf(v[j], sl, -mx));
                float sm = ((v[0] + v[1]) + (v[2] + v[3])) + ((v[4] + v[5]) + (v[6] + v[7])) + (v[8] + v[9]);
                sm += __shfl_xor_sync(0xffffffff, sm, 1);
                sm += __shfl_xor_sync(0xffffffff, sm, 2);
                float inv;
                asm("rcp.approx.ftz.f32 %0, %1;" : "=f"(inv) : "f"(sm));
                const uint32_t pa = sb + C2_PX + w4 * 256 + g * 32 + ((g >> 2) << 4) + qc * 4;
#pragma unroll
                for (int j = 0; j < 5; j++) sts32((pa ^ ((j & 1) << 4)) + (j >> 1) * 1024, pack_bf16(v[2 * j] * inv, v[2 * j + 1] * inv));
            }
            if (s >= 0) {
                fence_async_smem();
                if (s < NSEG) bar_sync<6, 256>(); else bar_sync<7, 128>();
                DBGW(20, 0);
                if (s < NSEG - 1) mbar_wait(bar_o, s & 1);
                if (s < NSEG) {
                    float sx[20];
#pragma unroll
                    for (int i = 0; i < 20; i++) sx[i] = 0.f;
                    wgmma_fence();
#pragma unroll
                    for (int kk = 0; kk < 4; kk++) wgmma_ss<DHI128, DHI128>(sx, dlo + (C2_QX >> 4) + kk * 2, dlo + (C2_KX >> 4) + kk * 2);
                    wgmma_commit();
                    wgmma_wait<0>();
                    if (s < NSEG - 1) bar_arrive<5, 256>();
                    if (w4 < 2) {
                        const uint32_t a = sb + C2_SX + (s & 1) * 10240 + w4 * 2560 + lane * 8;
#pragma unroll
                        for (int j = 0; j < 5; j++) {
                            asm volatile("st.shared.v2.f32 [%0], {%1, %2};" :: "r"(a + j * 256), "f"(sx[4 * j]), "f"(sx[4 * j + 1]) : "memory");
                            asm volatile("st.shared.v2.f32 [%0], {%1, %2};" :: "r"(a + 1280 + j * 256), "f"(sx[4 * j + 2]), "f"(sx[4 * j + 3]) : "memory");
                        }
                    }
                }
                DBGW(21, 0);
                if (s > 0) {
                    float cx[16];
#pragma unroll
                    for (int i = 0; i < 16; i++) cx[i] = 0.f;
                    wgmma_fence();
#pragma unroll
                    for (int kk = 0; kk < 3; kk++)
                        wgmma_ss<DHI32, DHI32>(cx, dlo + ((C2_VT + ((s - 1) & 1) * 6144 + kk * 2048) >> 4), dlo + ((C2_PX + kk * 1024) >> 4));
                    wgmma_commit();
                    wgmma_wait<0>();
                    uint32_t* dst = reinterpret_cast<uint32_t*>(g_ctxB + ((size_t)h * SEQ + (s - 1) * SEGL + 2 * qc) * HD + (rank & 1) * 64 + w4 * 16 + 2 * g);
#pragma unroll
                    for (int j = 0; j < 4; j++) {
                        dst[j * 8 * (HD / 2)] = pack_bf16(cx[4 * j], cx[4 * j + 2]);
                        dst[(j * 8 + 1) * (HD / 2)] = pack_bf16(cx[4 * j + 1], cx[4 * j + 3]);
                    }
                }
                DBGW(22, 0);
                if (s == NSEG) break;
                fence_async_smem();
            }
            if (s < NSEG - 1) mbar_wait(bar_x + 8 * ((s + 1) & 1), ((s + 1) >> 1) & 1);
            if (s >= 0) bar_sync<4, 384>();
            s++;
            if (s < NSEG) {
                {
                    float acc[16];
                    c2_xstream(acc, w, dlo + ((C2_XB + (s & 1) * C2_XS) >> 4), rank, dlo + ((C2_WS + C2_NS * 2048) >> 4));
                    store_x(acc, sb + C2_KX);
                }
                DBGW(16, 0);
                const uint32_t kst = pin(sb + C2_KX + 4096 + t128);
                float a[4][4];
                proj_mem(a, s);
                sts32(kst, pack_bf16(a[0][0], a[0][2]));
                sts32((kst ^ 16) + 128, pack_bf16(a[0][1], a[0][3]));
                bar_arrive<1, 384>();
                DBGW(19, 0);
                if (w4 == 0) {
                    if (s < NSEG - 1) {
                        if (lane == 0) mbar_expect_tx(bar_sc, 2560);
                        if (lane < 16 && (lane & 7) >= 1 && (lane & 7) < 5) mbar_expect_tx(bar_m + 8 * lane, (lane & 7) == 1 ? 1024 : 2048);
                        if (lane == 8) {
                            mbar_expect_tx(bar_x + 8 * ((s + 1) & 1), 32768);
                            tma_load_2d_mc(sb + C2_XB + ((s + 1) & 1) * C2_XS + rank * 5120, &mapX, bar_x + 8 * ((s + 1) & 1), rank * 64, (s + 1) * SEGL, (uint16_t)0xff);
                            if (s + 2 < NSEG)
                                asm volatile("cp.async.bulk.prefetch.tensor.2d.L2.global [%0, {%1, %2}];" :: "l"((uint64_t)&mapX), "r"(rank * 64), "r"((s + 2) * SEGL) : "memory");
                        }
                    }
                    if (lane == 16) mbar_expect_tx(bar_sx + 8 * (s & 1), 5120);
                    __syncwarp();
                }
            }
        }
        bar_sync<7, 128>();
        if (tid == 128) signal_ctr(CT_CB);
    } else {
        c2_load_w(w, &P.mapW[2], 2, rank, col0, t128, ws, sb);
#pragma unroll 1
        for (int s = -1;;) {
            if (s >= 0) {
                const int t = tid - 256;
                const uint2* src = g_xbuf + ((s & 1) * 8 + rank) * 1024 + t;
                asm volatile("" : "+l"(src));
                const uint32_t ma = sb + C2_XB + ((s + 1) & 1) * C2_XS + rank * 5120 + 4096 + (t >> 4) * 128 + ((((t >> 1) & 7) ^ (t >> 4)) << 4) + (t & 1) * 8;
                uint32_t ra[8], rb[8];
#pragma unroll
                for (int i = 1; i < 8; i++) {
                    const uint32_t d = (rank + i) & 7;
                    ra[i] = pin(mapa_u32(ma, d)); rb[i] = pin(mapa_u32(bar_m + 8 * c2_grp(i), d));
                }
                bar_sync<4, 384>();
                DBGW(29, 0);
                if (tid == 256) {
                    const uint32_t a = sb + C2_SX + (s & 1) * 10240;
                    bulk_s2s(mapa_u32(a + 5120, rank ^ 1), a, 5120, mapa_u32(bar_sx + 8 * (s & 1), rank ^ 1));
                }
                if (s == NSEG - 1) break;
                pace(CH_POLL_DELAY);
                const uint32_t tag = ((s >> 1) & 1) ^ 1;
                uint32_t p[8][2];
                for (int it = 0; it < (1 << 20); it++) {
#pragma unroll
                    for (int k = 0; k < 8; k++)
                        asm volatile("ld.relaxed.gpu.global.v2.u32 {%0, %1}, [%2];" : "=r"(p[k][0]), "=r"(p[k][1]) : "l"(src + k * 128) : "memory");
                    uint32_t bad[8];
#pragma unroll
                    for (int k = 0; k < 8; k++) asm("lop3.b32 %0, %1, %2, %3, 0x7e;" : "=r"(bad[k]) : "r"(p[k][0]), "r"(p[k][1]), "r"(tag));
                    asm("lop3.b32 %0, %0, %1, %2, 0xfe;" : "+r"(bad[0]) : "r"(bad[1]), "r"(bad[2]));
                    asm("lop3.b32 %0, %0, %1, %2, 0xfe;" : "+r"(bad[3]) : "r"(bad[4]), "r"(bad[5]));
                    asm("lop3.b32 %0, %0, %1, %2, 0xfe;" : "+r"(bad[0]) : "r"(bad[3]), "r"(bad[6]));
                    asm("lop3.b32 %0, %0, %1, 1, 0xa8;" : "+r"(bad[0]) : "r"(bad[7]));
                    if (__all_sync(0xffffffff, bad[0] == 0u)) break;
                }
                DBGW(30, 0);
                float r[4];
#pragma unroll
                for (int e = 0; e < 2; e++) {
                    float lo[8], hi[8];
#pragma unroll
                    for (int k = 0; k < 8; k++) { lo[k] = __uint_as_float(p[k][e] << 16); hi[k] = __uint_as_float(p[k][e] & 0xffff0000u); }
                    r[2 * e] = ((lo[0] + lo[1]) + (lo[2] + lo[3])) + ((lo[4] + lo[5]) + (lo[6] + lo[7]));
                    r[2 * e + 1] = ((hi[0] + hi[1]) + (hi[2] + hi[3])) + ((hi[4] + hi[5]) + (hi[6] + hi[7]));
                }
                const uint32_t m0 = pack_bf16(r[0], r[1]), m1 = pack_bf16(r[2], r[3]);
                st_async_v2(ra[1], m0, m1, rb[1]);
                asm volatile("st.shared.v2.b32 [%0], {%1, %2};" :: "r"(ma), "r"(m0), "r"(m1) : "memory");
                __syncwarp();
                if (lane == 0) mbar_arrive(bar_m);
#pragma unroll
                for (int i = 2; i < 8; i++) st_async_v2(ra[i], m0, m1, rb[i]);
                DBGW(31, 0);
            }
            s++;
            const uint32_t ost = pin(sb + C2_OB + t32), pla = pin(sb + C2_PB + lane * 16), plb = pin(sb + C2_PB + 512 + (lane & 7) * 16);
            bar_sync<1, 384>();
            fence_async_smem();
            DBGW(24, 0);
            if (s < NSEG - 1) bar_sync<2, 224>();
            uint32_t va[5][2];
            {
                float acc[20];
                c2_xstream(acc, w, dlo + ((C2_XB + (s & 1) * C2_XS) >> 4), rank, dlo + ((C2_WS + 2 * C2_NS * 2048) >> 4));
#pragma unroll
                for (int j = 0; j < 5; j++) { va[j][0] = pack_bf16(acc[4 * j], acc[4 * j + 1]); va[j][1] = pack_bf16(acc[4 * j + 2], acc[4 * j + 3]); }
            }
            DBGW(26, 0);
            if (s < NSEG - 1) {
                uint32_t p[5];
                bar_sync<3, 160>();
                DBGW(27, 0);
                ldmatrix_x4_trans(p[0], p[1], p[2], p[3], pla);
                asm volatile("ldmatrix.sync.aligned.m8n8.x1.trans.shared.b16 {%0}, [%1];" : "=r"(p[4]) : "r"(plb) : "memory");
                float oa[4] = {0.f, 0.f, 0.f, 0.f}, ob[4] = {0.f, 0.f, 0.f, 0.f}, sa[4] = {0.f, 0.f, 0.f, 0.f}, sc[4] = {0.f, 0.f, 0.f, 0.f};
                const uint32_t one = 0x3f803f80u;
                mma_16816(sa, one, one, one, one, p[0], p[1]);
                mma_16816(oa, va[0][0], va[0][1], va[1][0], va[1][1], p[0], p[1]);
                mma_16816(sc, one, one, one, one, p[2], p[3]);
                mma_16816(ob, va[2][0], va[2][1], va[3][0], va[3][1], p[2], p[3]);
                mma_16816(sa, one, one, one, one, p[4], 0u);
                mma_16816(oa, va[4][0], va[4][1], 0u, 0u, p[4], 0u);
                float i0, i1;
                asm("rcp.approx.ftz.f32 %0, %1;" : "=f"(i0) : "f"(sa[0] + sc[0]));
                asm("rcp.approx.ftz.f32 %0, %1;" : "=f"(i1) : "f"(sa[1] + sc[1]));
                sts32(ost, pack_bf16((oa[0] + ob[0]) * i0, (oa[2] + ob[2]) * i0));
                sts32(ost + 32, pack_bf16((oa[1] + ob[1]) * i1, (oa[3] + ob[3]) * i1));
                fence_async_smem();
                __syncwarp();
                if (elect_one()) {
#pragma unroll
                    for (int i = 1; i < 8; i++) {
                        const uint32_t d = (rank + i) & 7;
                        bulk_s2s(mapa_u32(sb + C2_OB + i * 1024 + w4 * 256, d), sb + C2_OB + w4 * 256, 256, mapa_u32(bar_o + 8 * c2_grp(i), d));
                        if (i == 1) mbar_arrive(bar_o);
                    }
                }
                __syncwarp();
                DBGW(28, 0);
            }
            {
                const uint32_t a = sb + C2_VT + (s & 1) * 6144 + a32;
                stmatrix_x4(a, va[0][0], va[0][1], va[1][0], va[1][1]);
                stmatrix_x4(a + 2048, va[2][0], va[2][1], va[3][0], va[3][1]);
                asm volatile("stmatrix.sync.aligned.m8n8.x2.shared.b16 [%0], {%1, %2};" :: "r"(a + 4096), "r"(va[4][0]), "r"(va[4][1]) : "memory");
            }
            fence_async_smem();
        }
        g_xbuf[((8 + rank) * 8 + C) * 128 + (tid - 256)] = make_uint2(0u, 0u);
    }
    cluster_sync_relaxed();
    TS_END(2);
}

struct Proj2Params {
    CUtensorMap mapA[2];
    CUtensorMap mapW[3];
    bf16* out[3];
};
#define P2T(i)
#define P2_NOMMA 0
#define P2_NOLOAD 0
constexpr int P2_STAGES = 6;
constexpr int P2_SMEM = 131072 + P2_STAGES * 16384 + 1024 + 1024;
constexpr int P2_ITEMS = 168 + 48;
__device__ __forceinline__ int p2_reps(int t) { return t >= 168 ? 1 : 2; }
__device__ __forceinline__ void p2_tile(int t, int w, int& z, int& mp, int& head) {
    if (t >= 168) { w += ((t - 168) & 1) * 2; t = 168 + ((t - 168) >> 1); }
    const int hq = t / 24, v = t % 24;
    mp = v & 7;
    if (v < 16) { head = hq * 4 + (v >> 3) * 2 + (w >> 1); z = 1 + (w & 1); }
    else { head = hq * 4 + w; z = 0; }
}
__device__ __forceinline__ void mbar_arrive_remote(uint32_t bar_cluster_addr) {
    asm volatile("mbarrier.arrive.release.cluster.shared::cluster.b64 _, [%0];" :: "r"(bar_cluster_addr) : "memory");
}
__device__ __forceinline__ void mbar_arrive_cl(uint32_t bar_cluster_addr) {
    asm volatile("mbarrier.arrive.shared::cluster.b64 _, [%0];" :: "r"(bar_cluster_addr) : "memory");
}
__device__ __forceinline__ void mbar_wait_acq_cluster(uint32_t bar, uint32_t parity) {
    asm volatile(
        "{\n"
        ".reg .pred p, q;\n"
        ".reg .u32 c;\n"
        "mov.u32 c, 0;\n"
        "WAIT_LOOP_C:\n"
        "mbarrier.try_wait.parity.acquire.cluster.shared::cta.b64 p, [%0], %1;\n"
        "@p bra WAIT_DONE_C;\n"
        "add.u32 c, c, 1;\n"
        "setp.lt.u32 q, c, 4000000;\n"
        "@q bra WAIT_LOOP_C;\n"
        "WAIT_DONE_C:\n"
        "}\n" :: "r"(bar), "r"(parity) : "memory");
}
__device__ __forceinline__ uint4 quad_transpose(uint32_t p0, uint32_t p1, uint32_t p2, uint32_t p3, int lane) {
    const bool o1 = lane & 1, o2 = lane & 2;
    uint32_t s0 = o1 ? p0 : p1, s1 = o1 ? p2 : p3;
    s0 = __shfl_xor_sync(0xffffffff, s0, 1); s1 = __shfl_xor_sync(0xffffffff, s1, 1);
    const uint32_t a_lo = o1 ? s0 : p0, a_hi = o1 ? p1 : s0, b_lo = o1 ? s1 : p2, b_hi = o1 ? p3 : s1;
    uint32_t t0 = o2 ? a_lo : b_lo, t1 = o2 ? a_hi : b_hi;
    t0 = __shfl_xor_sync(0xffffffff, t0, 2); t1 = __shfl_xor_sync(0xffffffff, t1, 2);
    return o2 ? make_uint4(t0, t1, b_lo, b_hi) : make_uint4(a_lo, a_hi, t0, t1);
}
#define P2_PACE 35
#define P2_PACE2 0
template <bool PERM, int PACE = 0>
__device__ __forceinline__ void store_frag_128(const float (&acc)[64], bf16* obase, int lane) {
#pragma unroll
    for (int rr = 0; rr < 2; rr++)
#pragma unroll
        for (int g = 0; g < 4; g++) {
            const float* a = &acc[g * 16 + rr * 2];
            const uint32_t p0 = pack_bf16(a[0], a[1]), p1 = pack_bf16(a[4], a[5]), p2 = pack_bf16(a[8], a[9]), p3 = pack_bf16(a[12], a[13]);
            *reinterpret_cast<uint4*>(obase + (size_t)(rr * 8) * HD + g * 32) = PERM ? make_uint4(p0, p1, p2, p3) : quad_transpose(p0, p1, p2, p3, lane);
            pace(PACE);
        }
}
__global__ void __cluster_dims__(2, 1, 1) __launch_bounds__(384, 1) proj2_kernel(const __grid_constant__ Proj2Params P) {
    extern __shared__ uint8_t smem_raw[];
    const uint32_t sbase = (smem_u32(smem_raw) + 1023) & ~1023u;
    const uint32_t sA = sbase, sB = sbase + 131072, sC = sB + P2_STAGES * 16384;
    const uint32_t bars = sC;
    const uint32_t a_full = bars, a_empty = bars + 64, b_full = bars + 128, b_empty = b_full + 8 * P2_STAGES;
    const uint32_t item_bar = b_empty + 8 * P2_STAGES, item_in = item_bar + 16, slot = item_in + 16;
    const uint32_t note_bar = slot + 16, note_free = note_bar + 64, note = note_free + 64;
    const int warp = threadIdx.x >> 5, lane = threadIdx.x & 31;
    const uint32_t rank = cluster_ctarank();
    TS_BEGIN(0);
    if (threadIdx.x == 0) {
        for (int i = 0; i < 8; i++) { mbar_init(a_full + 8 * i, 1); mbar_init(a_empty + 8 * i, 2); }
        for (int i = 0; i < P2_STAGES; i++) { mbar_init(b_full + 8 * i, 1); mbar_init(b_empty + 8 * i, 2); }
        mbar_init(item_bar, 1); mbar_init(item_bar + 8, 1); mbar_init(item_in, 2); mbar_init(item_in + 8, 2);
        for (int i = 0; i < 8; i++) { mbar_init(note_bar + 8 * i, 1); mbar_init(note_free + 8 * i, 1); }
        asm volatile("fence.mbarrier_init.release.cluster;" ::: "memory");
    }
    __syncwarp();
    cluster_sync_relaxed();
    pdl_launch_dependents();
    if (warp == 9) {
        if (lane == 0) {
            for (int n = 0;; n++) {
                const int e = (n & 1) * 4 + ((n >> 1) & 3);
                mbar_wait(note_bar + 8 * e, (n >> 3) & 1);
                int m;
                asm volatile("ld.shared.s32 %0, [%1];" : "=r"(m) : "r"(note + e * 4) : "memory");
                mbar_arrive(note_free + 8 * e);
                if (m < 0) break;
                signal_ctr(m);
            }
        }
    } else if (warp == 10) {
        if (lane == 0) {
            auto publish = [&](int ic, int tq) {
                const int t = tq < P2_ITEMS ? tq : -1;
                asm volatile("st.shared.s32 [%0], %1;" :: "r"(slot + (ic & 3) * 4), "r"(t) : "memory");
                mbar_arrive(item_bar + 8 * (ic & 1));
                st_async_b32(mapa_u32(slot + (ic & 3) * 4, 1), (uint32_t)t, mapa_u32(item_bar + 8 * (ic & 1), 1));
            };
            const int npair = (int)(gridDim.x >> 1), pair = (int)(blockIdx.x >> 1);
            if (rank == 0) publish(0, pair);
            for (int ic = 0;; ic++) {
                if (rank == 1) mbar_expect_tx(item_bar + 8 * (ic & 1), 4);
                mbar_wait(item_bar + 8 * (ic & 1), (ic >> 1) & 1);
                int t;
                asm volatile("ld.shared.s32 %0, [%1];" : "=r"(t) : "r"(slot + (ic & 3) * 4) : "memory");
                if (t < 0) break;
                int z0, mp, h0;
                p2_tile(t, 0, z0, mp, h0);
                const int aidx = z0 >= 1 ? 1 : 0;
                const int m0 = (2 * mp + (int)rank) * 128;
                for (int k = 0; k < 8; k++) {
                    mbar_wait(a_empty + 8 * k, (ic & 1) ^ 1);
                    if (P2_NOLOAD) mbar_arrive(a_full + 8 * k); else {
                    mbar_expect_tx(a_full + 8 * k, 16384);
                    tma_load_2d(sA + k * 16384, &P.mapA[aidx], a_full + 8 * k, k * 64, m0); }
                }
                if (rank == 0) {
                    mbar_wait(item_in + 8 * (ic & 1), (ic >> 1) & 1);
                    publish(ic + 1, ic == 0 ? npair + pair : 2 * npair + (int)atomicAdd(&g_ctr[CT_PROJ], 1u));
                }
            }
        }
    } else if (warp == 8 || warp == 11) {
        if (lane == 0) {
            const int par2 = warp == 8 ? 0 : 1;
            int it = 0; uint32_t bph = 0;
            for (int ic = 0;; ic++) {
                mbar_wait(item_bar + 8 * (ic & 1), (ic >> 1) & 1);
                int t;
                asm volatile("ld.shared.s32 %0, [%1];" : "=r"(t) : "r"(slot + (ic & 3) * 4) : "memory");
                if (t < 0) break;
                const int nt = 2 * p2_reps(t);
                for (int w = 0; w < nt; w++) {
                    int z, mp, hd;
                    p2_tile(t, w, z, mp, hd);
                    for (int k = 0; k < 8; k++) {
                        const int s = it; const uint32_t phb = bph;
                        if (++it == P2_STAGES) { it = 0; bph ^= 1; }
                        if ((k & 1) != par2) continue;
                        mbar_wait(b_empty + 8 * s, phb ^ 1);
                        if (P2_NOLOAD) { mbar_arrive(b_full + 8 * s); continue; }
                        mbar_expect_tx(b_full + 8 * s, 16384);
                        tma_load_2d_mc(sB + s * 16384 + rank * 8192, &P.mapW[z], b_full + 8 * s, hd * 128 + (int)rank * 64, k * 64, (uint16_t)3);
                    }
                }
            }
        }
    } else {
        const int wg = warp >> 2;
        float acc[2][64];
        const uint32_t a_lo = desc_lo(sA, 16), b_lo0 = desc_lo(sB, 8192);
        const bool elected = (threadIdx.x & 127) == 0;
        int s = (wg * 8) % P2_STAGES;
        uint32_t ph = ((wg * 8) / P2_STAGES) & 1;
        int nnote = 0;
        if (wg == 1) asm volatile("bar.arrive 3, 256;" ::: "memory");
        for (int ic = 0;; ic++) {
            mbar_wait(item_bar + 8 * (ic & 1), (ic >> 1) & 1);
            int t;
            asm volatile("ld.shared.s32 %0, [%1];" : "=r"(t) : "r"(slot + (ic & 3) * 4) : "memory");
            P2T(7);
            if (wg == 0 && t < 0) {
                if (elected) {
                    const int e = nnote & 3;
                    mbar_wait(note_free + 8 * e, ((nnote >> 2) & 1) ^ 1);
                    asm volatile("st.shared.s32 [%0], %1;" :: "r"(note + e * 4), "r"(-1) : "memory");
                    mbar_arrive(note_bar + 8 * e);
                }
            }
            if (t < 0) break;
            const int reps = p2_reps(t);
#pragma unroll 1
            for (int rp = 0; rp < reps; rp++) {
            const bool first = rp == 0, last = rp == reps - 1;
            int z, mp, head;
            p2_tile(t, rp * 2 + wg, z, mp, head);
            asm volatile("bar.sync %0, 256;" :: "r"(3 + wg) : "memory");
            P2T(0);
            if (wg == 1 && last && elected) mbar_arrive_cl(mapa_u32(item_in + 8 * (ic & 1), 0));
            int sprev = 0;
#pragma unroll
            for (int k = 0; k < 8; k++) {
                if (k == 0) P2T(5);
                if (wg == 0 && first) mbar_wait(a_full + 8 * k, ic & 1);
                if (k == 0) P2T(6);
                mbar_wait(b_full + 8 * s, ph);
                if (k == 7) asm volatile("bar.arrive %0, 256;" :: "r"(4 - wg) : "memory");
                if (k == 0) P2T(1);
                if (k == 7) P2T(2);
                const uint32_t b_lo = b_lo0 + s * 1024;
                wgmma_fence();
#pragma unroll
                for (int kk = 0; kk < (P2_NOMMA ? 1 : 4); kk++) {
                    wgmma_ss_n128_lo<1>(acc[0], a_lo + k * 1024 + kk * 2, b_lo + kk * 128, (k | kk) != 0);
                    wgmma_ss_n128_lo<1>(acc[1], a_lo + k * 1024 + 512 + kk * 2, b_lo + kk * 128, (k | kk) != 0);
                }
                wgmma_commit();
                if (k > 0) {
                    wgmma_wait<1>();
                    if (elected) {
                        const uint32_t e = b_empty + 8 * sprev;
                        mbar_arrive_cl(mapa_u32(e, 0)); mbar_arrive_cl(mapa_u32(e, 1));
                        if (last) mbar_arrive(a_empty + 8 * (k - 1));
                    }
                }
                sprev = s;
                if (++s == P2_STAGES) { s = 0; ph ^= 1; }
            }
            wgmma_wait<0>();
            P2T(3);
            if (elected) {
                const uint32_t e = b_empty + 8 * sprev;
                mbar_arrive_cl(mapa_u32(e, 0)); mbar_arrive_cl(mapa_u32(e, 1));
                if (last) mbar_arrive(a_empty + 8 * 7);
            }
            s += 8 % P2_STAGES; ph ^= (8 / P2_STAGES) & 1;
            if (s >= P2_STAGES) { s -= P2_STAGES; ph ^= 1; }
            const int m0 = (2 * mp + (int)rank) * 128;
            bf16* obase = P.out[z] + ((size_t)head * SEQ + m0 + (warp & 3) * 16 + (lane >> 2)) * HD + (lane & 3) * 8;
            store_frag_128<true, P2_PACE>(acc[0], obase, lane); store_frag_128<true, P2_PACE>(acc[1], obase + (size_t)64 * HD, lane);
            P2T(4);
            {
                asm volatile("bar.sync %0, 128;" :: "r"(1 + wg) : "memory");
                if (elected) {
                    const int e = wg * 4 + (nnote & 3);
                    mbar_wait(note_free + 8 * e, ((nnote >> 2) & 1) ^ 1);
                    asm volatile("st.shared.s32 [%0], %1;" :: "r"(note + e * 4), "r"(CT_AP + (head >> 1)) : "memory");
                    mbar_arrive(note_bar + 8 * e);
                }
                nnote++;
            }
            }
        }
        TS_END(0);
    }
    __syncwarp();
    cluster_sync_relaxed();
}

struct OutParams {
    CUtensorMap mapCtx[2];
    CUtensorMap mapWo[2];
    CUtensorMap mapOut;
};
__device__ uint4 g_part[4 * 32 * 8 * 16 * 32];

#define OT(i)
#define OTP(i)
#define O3_LK 42
#define O3_D 5
constexpr int O3_E = 68, O3_GRID = O3_E + 64;
constexpr int O2_SMEM = 196608 + 1024 + 256;

__global__ void __cluster_dims__(2, 1, 1) __launch_bounds__(352, 1) out3_kernel(const __grid_constant__ OutParams P) {
    extern __shared__ uint8_t smem_raw[];
    const uint32_t sbase = (smem_u32(smem_raw) + 1023) & ~1023u;
    const uint32_t bar_full = sbase + 196608, bar_empty = bar_full + 64;
    const int warp = threadIdx.x >> 5, lane = threadIdx.x & 31;
    const uint32_t rank = cluster_ctarank();
    const int pair = blockIdx.x >> 1;
    const bool early = pair < O3_E / 2;
    constexpr int EB = 64 - O3_LK;
    int mt, part, a0, na, b0, nb;
    if (pair < 30) {
        part = pair >= 15; mt = part ? 29 - pair : pair;
        const int d = (14 - mt) * O3_D / 14;
        a0 = part ? 32 + d : 0; na = part ? 32 - d : 32 + d;
        b0 = part ? EB / 2 : 0; nb = part ? EB - EB / 2 : EB / 2;
    } else if (early) {
        part = pair - 30; mt = 15;
        a0 = part * 16; na = 16;
        b0 = part * EB / 4; nb = (part + 1) * EB / 4 - b0;
    } else {
        part = (pair - O3_E / 2) & 1; mt = (pair - O3_E / 2) >> 1;
        a0 = 0; na = 0; b0 = EB; nb = O3_LK;
    }
    const int m0 = mt * 128, nk = na + nb;
    const int n0 = early ? (int)rank * 256 : part * 256 + (int)rank * 128;
    const int nst = early ? 4 : 6;
    const uint32_t ssz = early ? 49152 : 32768;
    TS_BEGIN(4);
    OT(0);
    if (threadIdx.x == 0) {
        for (int i = 0; i < 6; i++) { mbar_init(bar_full + 8 * i, 1); mbar_init(bar_empty + 8 * i, 4); }
        asm volatile("fence.mbarrier_init.release.cluster;" ::: "memory");
    }
    if (threadIdx.x == 256) asm volatile("prefetch.tensormap [%0];" :: "l"((uint64_t)&P.mapCtx[early ? 0 : 1]) : "memory");
    if (threadIdx.x == 288) asm volatile("prefetch.tensormap [%0];" :: "l"((uint64_t)&P.mapWo[early ? 0 : 1]) : "memory");
    if (warp == 0 || warp > 8) asm volatile("bar.sync 1, 96;" ::: "memory");
    __syncwarp();
    asm volatile("barrier.cluster.arrive.relaxed.aligned;" ::: "memory");
    if (warp > 8) {
        if (lane == 0) {
            int s = 0; uint32_t ph = 0;
            for (int i = 0; i < nk; i++) {
                if (i >= nst) mbar_wait(bar_empty + 8 * s, ph ^ 1);
                const uint32_t sa = sbase + s * ssz + 16384;
                const int b = i >= na, k = b ? b0 + i - na : a0 + i;
                if (early) {
                    tma_load_2d(sa + (warp - 9) * 16384, &P.mapWo[b], bar_full + 8 * s, n0 + (warp - 9) * 128, k * 64);
                    tma_load_2d(sa + (warp - 9) * 16384 + 8192, &P.mapWo[b], bar_full + 8 * s, n0 + (warp - 9) * 128 + 64, k * 64);
                } else tma_load_2d(sa + (warp - 9) * 8192, &P.mapWo[1], bar_full + 8 * s, n0 + (warp - 9) * 64, k * 64);
                if (++s == nst) { s = 0; ph ^= 1; }
            }
        }
        __syncwarp();
        asm volatile("barrier.cluster.wait.acquire.aligned;" ::: "memory");
    } else if (warp == 8) {
        if (lane == 0) {
            if (early) wait_ctr(CT_CA + mt * 2, 2u * O2_HE); else wait_ctr(mt == 15 ? CT_CB : CT_CB + 1, 64u);
            OTP(3);
        }
        __syncwarp();
        asm volatile("barrier.cluster.wait.acquire.aligned;" ::: "memory");
        if (lane == 0) {
            OTP(7);
            int s = 0; uint32_t ph = 0;
            bool late_a = false;
            for (int i = 0; i < nk; i++) {
                const int b = i >= na, k = b ? b0 + i - na : a0 + i;
                if (!b && k >= 2 * O2_HE && !late_a) { wait_ctr(CT_CA + mt * 2 + 1, 2u * (NH - O2_HE)); late_a = true; }
                if (i == na && early) wait_ctr(mt == 15 ? CT_CB : CT_CB + 1, 64u);
                if (i >= nst) mbar_wait(bar_empty + 8 * s, ph ^ 1);
                mbar_expect_tx(bar_full + 8 * s, ssz);
                tma_load_2d_mc(sbase + s * ssz + rank * 8192, &P.mapCtx[b], bar_full + 8 * s, (k & 1) * 64, (k >> 1) * SEQ + m0 + (int)rank * 64, (uint16_t)3);
                if (++s == nst) { s = 0; ph ^= 1; }
            }
        }
    } else {
        asm volatile("barrier.cluster.wait.acquire.aligned;" ::: "memory");
        const int wg = warp >> 2;
        const bool elected = (threadIdx.x & 127) == 0;
        const int row = (warp & 3) * 16 + (lane >> 2);
        const int mrow = (warp & 3) * 16 + (lane & 15);
        const uint32_t moff = mrow * 128, mx = (lane >> 4) ^ (mrow & 7);
        float g0, g1;
        int s = 0, sprev = 0; uint32_t ph = 0;
        {
            unsigned int v; int it = 0;
            do { asm volatile("ld.acquire.gpu.global.u32 %0, [%1];" : "=r"(v) : "l"(&g_ctr[CT_G]) : "memory"); } while (v < FA_GRID && ++it < (1 << 22));
        }
        asm volatile("ld.relaxed.gpu.global.f32 %0, [%1];" : "=f"(g0) : "l"(g_gate + m0 + wg * 64 + row) : "memory");
        asm volatile("ld.relaxed.gpu.global.f32 %0, [%1];" : "=f"(g1) : "l"(g_gate + m0 + wg * 64 + row + 8) : "memory");
        auto release = [&](int st) {
            if (elected) { const uint32_t e = bar_empty + 8 * st; mbar_arrive_cl(mapa_u32(e, 0)); mbar_arrive_cl(mapa_u32(e, 1)); }
        };
        if (early) {
            float acc[128];
#pragma unroll 1
            for (int i = 0; i < nk; i++) {
                mbar_wait(bar_full + 8 * s, ph);
                if (i == 8) OT(2);
                if (i == na) {
                    wgmma_wait<0>();
                    const float r0 = g0 / fmaxf(1.f - g0, 0x1p-40f), r1 = g1 / fmaxf(1.f - g1, 0x1p-40f);
#pragma unroll
                    for (int j = 0; j < 32; j++) { acc[4 * j] *= r0; acc[4 * j + 1] *= r0; acc[4 * j + 2] *= r1; acc[4 * j + 3] *= r1; }
                }
                const uint32_t sa = sbase + s * 49152 + wg * 8192, sb = sbase + s * 49152 + 16384;
                wgmma_fence();
#pragma unroll
                for (int kk = 0; kk < 4; kk++)
                    wgmma_ss_n256_tb(acc, make_desc(sa + kk * 32, 16, 1024), make_desc(sb + kk * 2048, 8192, 1024), (i | kk) != 0);
                wgmma_commit();
                if (i > 0) { wgmma_wait<1>(); release(sprev); }
                sprev = s;
                if (++s == 4) { s = 0; ph ^= 1; }
            }
            wgmma_wait<0>();
            OT(4);
            const float w0 = fmaxf(1.f - g0, 0x1p-40f), w1 = fmaxf(1.f - g1, 0x1p-40f);
            uint4* dst = g_part + (((part * 32 + mt * 2 + (int)rank) * 8 + warp) * 16) * 32 + lane;
#pragma unroll
            for (int j = 0; j < 16; j++) {
                const float* a = &acc[8 * j];
                dst[j * 32] = make_uint4(pack_bf16(a[0] * w0, a[1] * w0), pack_bf16(a[2] * w1, a[3] * w1), pack_bf16(a[4] * w0, a[5] * w0), pack_bf16(a[6] * w1, a[7] * w1));
            }
            __syncwarp();
            OT(5);
            if (lane == 0) signal_ctr_generic(CT_OP + (mt * 2 + (int)rank) * 8 + warp);
            OT(6);
        } else {
            float acc[64];
            const uint32_t a_lo = desc_lo(sbase + wg * 8192, 16), b_lo = desc_lo(sbase + 16384, 8192);
#pragma unroll 1
            for (int i = 0; i < nk; i++) {
                mbar_wait(bar_full + 8 * s, ph);
                if (i == 8) OT(2);
                wgmma_fence();
#pragma unroll
                for (int kk = 0; kk < 4; kk++) wgmma_ss_n128_lo<1>(acc, a_lo + s * 2048 + kk * 2, b_lo + s * 2048 + kk * 128, (i | kk) != 0);
                wgmma_commit();
                if (i > 0) { wgmma_wait<1>(); release(sprev); }
                sprev = s;
                if (++s == 6) { s = 0; ph ^= 1; }
            }
            const int np = mt == 15 ? 4 : 2;
            wait_ctr(CT_OP + (mt * 2 + part) * 8 + warp, np);
            const uint4* src = g_part + (((mt * 2 + part) * 8 + warp) * 16 + (int)rank * 8) * 32 + lane;
            uint4 u[2][8];
            auto load_parts = [&](int p) {
#pragma unroll
                for (int i = 0; i < 16; i++)
                    asm volatile("ld.relaxed.gpu.global.v4.u32 {%0, %1, %2, %3}, [%4];" : "=r"(u[i >> 3][i & 7].x), "=r"(u[i >> 3][i & 7].y), "=r"(u[i >> 3][i & 7].z),
                                 "=r"(u[i >> 3][i & 7].w) : "l"(src + (p + (i >> 3)) * (32 * 8 * 16 * 32) + (i & 7) * 32) : "memory");
            };
            auto add_parts = [&]() {
#pragma unroll
                for (int i = 0; i < 16; i++) {
                    const uint32_t v[4] = {u[i >> 3][i & 7].x, u[i >> 3][i & 7].y, u[i >> 3][i & 7].z, u[i >> 3][i & 7].w};
#pragma unroll
                    for (int e = 0; e < 4; e++) {
                        acc[8 * (i & 7) + 2 * e] += __uint_as_float(v[e] << 16);
                        acc[8 * (i & 7) + 2 * e + 1] += __uint_as_float(v[e] & 0xffff0000u);
                    }
                }
            };
            load_parts(0);
            wgmma_wait<0>();
            OT(4);
            const float w0 = 1.f - g0, w1 = 1.f - g1;
#pragma unroll
            for (int j = 0; j < 16; j++) { acc[4 * j] *= w0; acc[4 * j + 1] *= w0; acc[4 * j + 2] *= w1; acc[4 * j + 3] *= w1; }
            add_parts();
            if (np == 4) { load_parts(2); add_parts(); }
            OT(5);
            mbar_wait(bar_empty + 8 * s, ph ^ 1);
            const uint32_t stg = sbase + s * 32768 + wg * 16384;
#pragma unroll
            for (int j = 0; j < 8; j++) {
                const float* a = &acc[8 * j];
                stmatrix_x4(stg + (j >> 2) * 8192 + moff + ((mx ^ ((j & 3) * 2)) << 4), pack_bf16(a[0], a[1]), pack_bf16(a[2], a[3]), pack_bf16(a[4], a[5]), pack_bf16(a[6], a[7]));
            }
            fence_async_smem();
            asm volatile("bar.sync %0, 128;" :: "r"(2 + wg) : "memory");
            if (elected) {
                tma_store_2d(&P.mapOut, stg, n0, m0 + wg * 64);
                tma_store_2d(&P.mapOut, stg + 8192, n0 + 64, m0 + wg * 64);
                asm volatile("cp.async.bulk.commit_group;" ::: "memory");
                asm volatile("cp.async.bulk.wait_group 0;" ::: "memory");
            }
            OT(6);
        }
    }
    __syncthreads();
    asm volatile("barrier.cluster.arrive.relaxed.aligned;" ::: "memory");
    if (warp == 0) {
        unsigned int tk = 0;
        if (lane == 0) tk = atomicAdd(&g_ctr[CT_FIN], 1u);
        tk = __shfl_sync(0xffffffff, tk, 0);
        if (tk == gridDim.x - 1)
            for (int i = lane; i < CT_N; i += 32) g_ctr[i] = 0u;
    }
    asm volatile("barrier.cluster.wait.acquire.aligned;" ::: "memory");
    TS_END(4);
}

typedef CUresult (*PFN_encodeTiled)(CUtensorMap*, CUtensorMapDataType, cuuint32_t, void*, const cuuint64_t*,
                                    const cuuint64_t*, const cuuint32_t*, const cuuint32_t*, CUtensorMapInterleave,
                                    CUtensorMapSwizzle, CUtensorMapL2promotion, CUtensorMapFloatOOBfill);
static PFN_encodeTiled g_encode = nullptr;

static void make_map(CUtensorMap* m, const void* ptr, uint64_t rows, uint64_t cols, uint32_t box_rows, bool sw64 = false) {
    cuuint64_t dims[2] = {cols, rows};
    cuuint64_t strides[1] = {cols * 2};
    cuuint32_t box[2] = {sw64 ? 32u : 64u, box_rows};
    cuuint32_t es[2] = {1, 1};
    g_encode(m, CU_TENSOR_MAP_DATA_TYPE_BFLOAT16, 2, const_cast<void*>(ptr), dims, strides, box, es,
             CU_TENSOR_MAP_INTERLEAVE_NONE, sw64 ? CU_TENSOR_MAP_SWIZZLE_64B : CU_TENSOR_MAP_SWIZZLE_128B, CU_TENSOR_MAP_L2_PROMOTION_L2_256B,
             CU_TENSOR_MAP_FLOAT_OOB_FILL_NONE);
}

template <typename... KArgs, typename... Args>
static void launch_pdl(void (*kernel)(KArgs...), int grid, int block, size_t smem, cudaStream_t st, bool pdl, Args... args) {
    cudaLaunchConfig_t cfg = {};
    cfg.gridDim = dim3(grid); cfg.blockDim = dim3(block); cfg.dynamicSmemBytes = smem; cfg.stream = st;
    cudaLaunchAttribute at[1];
    at[0].id = cudaLaunchAttributeProgrammaticStreamSerialization;
    at[0].val.programmaticStreamSerializationAllowed = 1;
    cfg.attrs = at; cfg.numAttrs = pdl ? 1 : 0;
    cudaLaunchKernelEx(&cfg, kernel, KArgs(args)...);
}

extern "C" void kernel_launch(void* const* d_in, const int* in_sizes, int n_in, void* d_out, int out_size) {
    const bf16* x = (const bf16*)d_in[0];
    const bf16* ckv = (const bf16*)d_in[1];
    const bf16* wq = (const bf16*)d_in[2];
    const bf16* wuk = (const bf16*)d_in[3];
    const bf16* wuv = (const bf16*)d_in[4];
    const bf16* wo = (const bf16*)d_in[5];
    const bf16* mem0 = (const bf16*)d_in[7];
    const bf16* Wq = (const bf16*)d_in[8];
    const bf16* Wk = (const bf16*)d_in[9];
    const bf16* Wv = (const bf16*)d_in[10];
    const bf16* Wo = (const bf16*)d_in[11];
    const bf16* gate_w = (const bf16*)d_in[13];
    bf16* out = (bf16*)d_out;

    static Proj2Params P2;
    static ChainParams CP;
    static AttnParams AP;
    static OutParams OP;
    static bool init = false;
    static const void* last_in[15];
    bool same = init;
    for (int i = 0; i < 14 && same; i++) same = last_in[i] == d_in[i];
    same = same && last_in[14] == d_out;
    if (!init) {
        cudaDriverEntryPointQueryResult qr;
        cudaGetDriverEntryPoint("cuTensorMapEncodeTiled", (void**)&g_encode, cudaEnableDefault, &qr);
        cudaFuncSetAttribute(proj2_kernel, cudaFuncAttributeMaxDynamicSharedMemorySize, P2_SMEM);
        cudaFuncSetAttribute(attn_kernel, cudaFuncAttributeMaxDynamicSharedMemorySize, FA_SMEM);
        cudaFuncSetAttribute(chain_kernel, cudaFuncAttributeMaxDynamicSharedMemorySize, C2_SMEM);
        cudaFuncSetAttribute(out3_kernel, cudaFuncAttributeMaxDynamicSharedMemorySize, O2_SMEM);
        init = true;
    }
    if (!same) {
        for (int i = 0; i < 14; i++) last_in[i] = d_in[i];
        last_in[14] = d_out;
        void *pQA, *pKA, *pVA, *pCA, *pCB;
        cudaGetSymbolAddress(&pQA, g_QA); cudaGetSymbolAddress(&pKA, g_KA); cudaGetSymbolAddress(&pVA, g_VA);
        cudaGetSymbolAddress(&pCA, g_ctxA); cudaGetSymbolAddress(&pCB, g_ctxB);
        make_map(&P2.mapA[0], x, SEQ, DM, 128);
        make_map(&P2.mapA[1], ckv, SEQ, DM, 128);
        const void* ws[3] = {wq, wuk, wuv};
        void* cs[3] = {pQA, pKA, pVA};
        for (int i = 0; i < 3; i++) { make_map(&P2.mapW[i], ws[i], DM, NQ, 64); P2.out[i] = (bf16*)cs[i]; }
        make_map(&CP.mapX, x, SEQ, DM, SEGL);
        make_map(&CP.mapM, mem0, NMEM, DM, NMEM);
        make_map(&CP.mapW[0], Wq, DM, NQ, 64);
        make_map(&CP.mapW[1], Wk, DM, NQ, 64);
        make_map(&CP.mapW[2], Wv, DM, NQ, 64);
        make_map(&CP.mapWo, Wo, NQ, DM, 64);
        make_map(&AP.mapQ, pQA, NH * SEQ, HD, 128);
        make_map(&AP.mapK, pKA, NH * SEQ, HD, 128);
        make_map(&AP.mapV, pVA, NH * SEQ, HD, 128);
        make_map(&AP.mapO, pCA, NH * SEQ, HD, 64);
        make_map(&OP.mapCtx[0], pCA, NH * SEQ, HD, 64);
        make_map(&OP.mapCtx[1], pCB, NH * SEQ, HD, 64);
        make_map(&OP.mapWo[0], wo, NQ, DM, 64);
        make_map(&OP.mapWo[1], Wo, NQ, DM, 64);
        make_map(&OP.mapOut, out, SEQ, DM, 64);
        AP.x = x; AP.gate_w = gate_w;
    }
    cudaStream_t s1 = cudaStreamPerThread;
    const bool pdl = true;
    launch_pdl(chain_kernel, 64, 384, C2_SMEM, s1, false, CP);
    launch_pdl(proj2_kernel, 68, 384, P2_SMEM, s1, pdl, P2);
    launch_pdl(attn_kernel, FA_GRID, 384, FA_SMEM, s1, pdl, AP, 1000);
    launch_pdl(out3_kernel, O3_GRID, 352, O2_SMEM, s1, pdl, OP);
}
```

```cpp
#include <cuda_runtime.h>
#include <cuda_bf16.h>
#include <cuda.h>
#include <stdint.h>
#include <type_traits>

constexpr int SEQ = 2048;
constexpr int DM = 512;
constexpr int NH = 32;
constexpr int HD = 128;
constexpr int NQ = NH * HD;
constexpr int SEGL = 32;
constexpr int NMEM = 8;
constexpr int NSEG = SEQ / SEGL;

typedef __nv_bfloat16 bf16;

__device__ bf16 g_QA[SEQ * NQ];
__device__ bf16 g_KA[SEQ * NQ];
__device__ bf16 g_VA[SEQ * NQ];
__device__ bf16 g_ctxA[SEQ * NQ];
__device__ bf16 g_ctxB[SEQ * NQ];
constexpr int CT_PROJ = 0, CT_ATTN = 1, CT_FIN = 5;
constexpr int CT_G = 32;
constexpr int CT_AP = 64;
#define O2_HE 24
constexpr int CT_CA = 128;
constexpr int CT_CB = 160;
constexpr int CT_OP = 192;
constexpr int CT_N = 448;
__device__ unsigned int g_ctr[CT_N];
__device__ float g_gate[SEQ];
__device__ uint2 g_xbuf[2 * 8 * 8 * 128];

#define FA_GRID 68

#define TS_BEGIN(id)
#define TS_END(id)
__device__ __forceinline__ void pdl_launch_dependents() { asm volatile("griddepcontrol.launch_dependents;" ::: "memory"); }
__device__ __forceinline__ void wait_ctr(int idx, unsigned int n) {
    unsigned int v; int it = 0;
    do { asm volatile("ld.acquire.gpu.global.u32 %0, [%1];" : "=r"(v) : "l"(&g_ctr[idx]) : "memory"); } while (v < n && ++it < (1 << 22));
}
__device__ __forceinline__ void signal_ctr(int idx) {
    asm volatile("fence.proxy.async.global;" ::: "memory");
    asm volatile("red.release.gpu.global.add.u32 [%0], 1;" :: "l"(&g_ctr[idx]) : "memory");
}
__device__ __forceinline__ void signal_ctr_generic(int idx) {
    asm volatile("red.release.gpu.global.add.u32 [%0], 1;" :: "l"(&g_ctr[idx]) : "memory");
}
__device__ __forceinline__ uint32_t smem_u32(const void* p) {
    return (uint32_t)__cvta_generic_to_shared(p);
}
__device__ __forceinline__ void mbar_init(uint32_t bar, uint32_t count) {
    asm volatile("mbarrier.init.shared::cta.b64 [%0], %1;" :: "r"(bar), "r"(count));
}
__device__ __forceinline__ void mbar_expect_tx(uint32_t bar, uint32_t bytes) {
    asm volatile("mbarrier.arrive.expect_tx.shared::cta.b64 _, [%0], %1;" :: "r"(bar), "r"(bytes) : "memory");
}
__device__ __forceinline__ void mbar_arrive(uint32_t bar) {
    asm volatile("mbarrier.arrive.shared::cta.b64 _, [%0];" :: "r"(bar) : "memory");
}
__device__ __forceinline__ void mbar_wait(uint32_t bar, uint32_t parity) {
    asm volatile(
        "{\n"
        ".reg .pred p, q;\n"
        ".reg .u32 c;\n"
        "mov.u32 c, 0;\n"
        "WAIT_LOOP:\n"
        "mbarrier.try_wait.parity.shared::cta.b64 p, [%0], %1;\n"
        "@p bra WAIT_DONE;\n"
        "add.u32 c, c, 1;\n"
        "setp.lt.u32 q, c, 4000000;\n"
        "@q bra WAIT_LOOP;\n"
        "WAIT_DONE:\n"
        "}\n" :: "r"(bar), "r"(parity) : "memory");
}
__device__ __forceinline__ void tma_load_2d(uint32_t dst, const CUtensorMap* map, uint32_t bar, int c0, int c1) {
    asm volatile(
        "cp.async.bulk.tensor.2d.shared::cluster.global.mbarrier::complete_tx::bytes [%0], [%1, {%3, %4}], [%2];"
        :: "r"(dst), "l"((uint64_t)map), "r"(bar), "r"(c0), "r"(c1) : "memory");
}
__device__ __forceinline__ void wgmma_fence() { asm volatile("wgmma.fence.sync.aligned;" ::: "memory"); }
__device__ __forceinline__ void wgmma_commit() { asm volatile("wgmma.commit_group.sync.aligned;" ::: "memory"); }
template <int N> __device__ __forceinline__ void wgmma_wait() {
    asm volatile("wgmma.wait_group.sync.aligned %0;" :: "n"(N) : "memory");
}
__device__ __forceinline__ uint64_t make_desc(uint32_t addr, uint32_t lbo, uint32_t sbo) {
    uint64_t d = 0;
    d |= (uint64_t)((addr & 0x3FFFF) >> 4);
    d |= (uint64_t)((lbo >> 4) & 0x3FFF) << 16;
    d |= (uint64_t)((sbo >> 4) & 0x3FFF) << 32;
    d |= (uint64_t)1 << 62;
    return d;
}

#define ACC64(d) \
    "+f"(d[0]), "+f"(d[1]), "+f"(d[2]), "+f"(d[3]), "+f"(d[4]), "+f"(d[5]), "+f"(d[6]), "+f"(d[7]), \
    "+f"(d[8]), "+f"(d[9]), "+f"(d[10]), "+f"(d[11]), "+f"(d[12]), "+f"(d[13]), "+f"(d[14]), "+f"(d[15]), \
    "+f"(d[16]), "+f"(d[17]), "+f"(d[18]), "+f"(d[19]), "+f"(d[20]), "+f"(d[21]), "+f"(d[22]), "+f"(d[23]), \
    "+f"(d[24]), "+f"(d[25]), "+f"(d[26]), "+f"(d[27]), "+f"(d[28]), "+f"(d[29]), "+f"(d[30]), "+f"(d[31]), \
    "+f"(d[32]), "+f"(d[33]), "+f"(d[34]), "+f"(d[35]), "+f"(d[36]), "+f"(d[37]), "+f"(d[38]), "+f"(d[39]), \
    "+f"(d[40]), "+f"(d[41]), "+f"(d[42]), "+f"(d[43]), "+f"(d[44]), "+f"(d[45]), "+f"(d[46]), "+f"(d[47]), \
    "+f"(d[48]), "+f"(d[49]), "+f"(d[50]), "+f"(d[51]), "+f"(d[52]), "+f"(d[53]), "+f"(d[54]), "+f"(d[55]), \
    "+f"(d[56]), "+f"(d[57]), "+f"(d[58]), "+f"(d[59]), "+f"(d[60]), "+f"(d[61]), "+f"(d[62]), "+f"(d[63])
#define ACC64_STR \
    "{%0, %1, %2, %3, %4, %5, %6, %7, %8, %9, %10, %11, %12, %13, %14, %15, " \
    "%16, %17, %18, %19, %20, %21, %22, %23, %24, %25, %26, %27, %28, %29, %30, %31, " \
    "%32, %33, %34, %35, %36, %37, %38, %39, %40, %41, %42, %43, %44, %45, %46, %47, " \
    "%48, %49, %50, %51, %52, %53, %54, %55, %56, %57, %58, %59, %60, %61, %62, %63}"

template <int TB>
__device__ __forceinline__ void wgmma_ss_n128(float (&d)[64], uint64_t da, uint64_t db, int scale_d) {
    asm volatile(
        "{\n.reg .pred p;\nsetp.ne.b32 p, %66, 0;\n"
        "wgmma.mma_async.sync.aligned.m64n128k16.f32.bf16.bf16 " ACC64_STR ", %64, %65, p, 1, 1, 0, %67;\n}\n"
        : ACC64(d) : "l"(da), "l"(db), "r"(scale_d), "n"(TB));
}
__device__ __forceinline__ uint32_t desc_lo(uint32_t addr, uint32_t lbo) { return ((addr & 0x3FFFF) >> 4) | ((lbo >> 4) << 16); }
template <int TB>
__device__ __forceinline__ void wgmma_ss_n128_lo(float (&d)[64], uint32_t da_lo, uint32_t db_lo, int scale_d) {
    asm volatile(
        "{\n.reg .pred p;\n.reg .b64 da, db;\nsetp.ne.b32 p, %66, 0;\n"
        "mov.b64 da, {%64, 0x40000040};\nmov.b64 db, {%65, 0x40000040};\n"
        "wgmma.mma_async.sync.aligned.m64n128k16.f32.bf16.bf16 " ACC64_STR ", da, db, p, 1, 1, 0, %67;\n}\n"
        : ACC64(d) : "r"(da_lo), "r"(db_lo), "r"(scale_d), "n"(TB));
}
__device__ __forceinline__ void wgmma_rs_n128_tb(float (&d)[64], uint32_t a0, uint32_t a1, uint32_t a2, uint32_t a3,
                                                 uint64_t db, int scale_d) {
    asm volatile(
        "{\n.reg .pred p;\nsetp.ne.b32 p, %69, 0;\n"
        "wgmma.mma_async.sync.aligned.m64n128k16.f32.bf16.bf16 " ACC64_STR ", {%64, %65, %66, %67}, %68, p, 1, 1, 1;\n}\n"
        : ACC64(d) : "r"(a0), "r"(a1), "r"(a2), "r"(a3), "l"(db), "r"(scale_d));
}
__device__ __forceinline__ void wgmma_rs_n80(float (&d)[40], const uint32_t (&a)[4], uint32_t db_lo, int scale_d) {
    asm volatile(
        "{\n.reg .pred p;\n.reg .b64 db;\nsetp.ne.b32 p, %45, 0;\nmov.b64 db, {%44, 0x40000040};\n"
        "wgmma.mma_async.sync.aligned.m64n80k16.f32.bf16.bf16 "
        "{%0, %1, %2, %3, %4, %5, %6, %7, %8, %9, %10, %11, %12, %13, %14, %15, %16, %17, %18, %19, %20, %21, %22, %23, %24, %25, %26, %27, %28, %29, %30, %31, %32, %33, %34, %35, %36, %37, %38, %39}, "
        "{%40, %41, %42, %43}, db, p, 1, 1, 0;\n}\n"
        : "+f"(d[0]), "+f"(d[1]), "+f"(d[2]), "+f"(d[3]), "+f"(d[4]), "+f"(d[5]), "+f"(d[6]), "+f"(d[7]), "+f"(d[8]), "+f"(d[9]), "+f"(d[10]), "+f"(d[11]), "+f"(d[12]), "+f"(d[13]), "+f"(d[14]), "+f"(d[15]), "+f"(d[16]), "+f"(d[17]), "+f"(d[18]), "+f"(d[19]), "+f"(d[20]), "+f"(d[21]), "+f"(d[22]), "+f"(d[23]), "+f"(d[24]), "+f"(d[25]), "+f"(d[26]), "+f"(d[27]), "+f"(d[28]), "+f"(d[29]), "+f"(d[30]), "+f"(d[31]), "+f"(d[32]), "+f"(d[33]), "+f"(d[34]), "+f"(d[35]), "+f"(d[36]), "+f"(d[37]), "+f"(d[38]), "+f"(d[39])
        : "r"(a[0]), "r"(a[1]), "r"(a[2]), "r"(a[3]), "r"(db_lo), "r"(scale_d));
}
__device__ __forceinline__ void wgmma_ss_n256_tb(float (&d)[128], uint64_t da, uint64_t db, int scale_d) {
    asm volatile(
        "{\n.reg .pred p;\nsetp.ne.b32 p, %130, 0;\n"
        "wgmma.mma_async.sync.aligned.m64n256k16.f32.bf16.bf16 {%0, %1, %2, %3, %4, %5, %6, %7, %8, %9, %10, %11, %12, %13, %14, %15, %16, %17, %18, %19, %20, %21, %22, %23, %24, %25, %26, %27, %28, %29, %30, %31, %32, %33, %34, %35, %36, %37, %38, %39, %40, %41, %42, %43, %44, %45, %46, %47, %48, %49, %50, %51, %52, %53, %54, %55, %56, %57, %58, %59, %60, %61, %62, %63, %64, %65, %66, %67, %68, %69, %70, %71, %72, %73, %74, %75, %76, %77, %78, %79, %80, %81, %82, %83, %84, %85, %86, %87, %88, %89, %90, %91, %92, %93, %94, %95, %96, %97, %98, %99, %100, %101, %102, %103, %104, %105, %106, %107, %108, %109, %110, %111, %112, %113, %114, %115, %116, %117, %118, %119, %120, %121, %122, %123, %124, %125, %126, %127}, %128, %129, p, 1, 1, 0, 1;\n}\n"
        : "+f"(d[0]), "+f"(d[1]), "+f"(d[2]), "+f"(d[3]), "+f"(d[4]), "+f"(d[5]), "+f"(d[6]), "+f"(d[7]), "+f"(d[8]), "+f"(d[9]), "+f"(d[10]), "+f"(d[11]), "+f"(d[12]), "+f"(d[13]), "+f"(d[14]), "+f"(d[15]), "+f"(d[16]), "+f"(d[17]), "+f"(d[18]), "+f"(d[19]), "+f"(d[20]), "+f"(d[21]), "+f"(d[22]), "+f"(d[23]), "+f"(d[24]), "+f"(d[25]), "+f"(d[26]), "+f"(d[27]), "+f"(d[28]), "+f"(d[29]), "+f"(d[30]), "+f"(d[31]), "+f"(d[32]), "+f"(d[33]), "+f"(d[34]), "+f"(d[35]), "+f"(d[36]), "+f"(d[37]), "+f"(d[38]), "+f"(d[39]), "+f"(d[40]), "+f"(d[41]), "+f"(d[42]), "+f"(d[43]), "+f"(d[44]), "+f"(d[45]), "+f"(d[46]), "+f"(d[47]), "+f"(d[48]), "+f"(d[49]), "+f"(d[50]), "+f"(d[51]), "+f"(d[52]), "+f"(d[53]), "+f"(d[54]), "+f"(d[55]), "+f"(d[56]), "+f"(d[57]), "+f"(d[58]), "+f"(d[59]), "+f"(d[60]), "+f"(d[61]), "+f"(d[62]), "+f"(d[63]), "+f"(d[64]), "+f"(d[65]), "+f"(d[66]), "+f"(d[67]), "+f"(d[68]), "+f"(d[69]), "+f"(d[70]), "+f"(d[71]), "+f"(d[72]), "+f"(d[73]), "+f"(d[74]), "+f"(d[75]), "+f"(d[76]), "+f"(d[77]), "+f"(d[78]), "+f"(d[79]), "+f"(d[80]), "+f"(d[81]), "+f"(d[82]), "+f"(d[83]), "+f"(d[84]), "+f"(d[85]), "+f"(d[86]), "+f"(d[87]), "+f"(d[88]), "+f"(d[89]), "+f"(d[90]), "+f"(d[91]), "+f"(d[92]), "+f"(d[93]), "+f"(d[94]), "+f"(d[95]), "+f"(d[96]), "+f"(d[97]), "+f"(d[98]), "+f"(d[99]), "+f"(d[100]), "+f"(d[101]), "+f"(d[102]), "+f"(d[103]), "+f"(d[104]), "+f"(d[105]), "+f"(d[106]), "+f"(d[107]), "+f"(d[108]), "+f"(d[109]), "+f"(d[110]), "+f"(d[111]), "+f"(d[112]), "+f"(d[113]), "+f"(d[114]), "+f"(d[115]), "+f"(d[116]), "+f"(d[117]), "+f"(d[118]), "+f"(d[119]), "+f"(d[120]), "+f"(d[121]), "+f"(d[122]), "+f"(d[123]), "+f"(d[124]), "+f"(d[125]), "+f"(d[126]), "+f"(d[127])
        : "l"(da), "l"(db), "r"(scale_d));
}
__device__ __forceinline__ void stmatrix_x4(uint32_t addr, uint32_t r0, uint32_t r1, uint32_t r2, uint32_t r3) {
    asm volatile("stmatrix.sync.aligned.m8n8.x4.shared.b16 [%0], {%1, %2, %3, %4};" :: "r"(addr), "r"(r0), "r"(r1), "r"(r2), "r"(r3) : "memory");
}
__device__ __forceinline__ void tma_store_2d(const CUtensorMap* map, uint32_t src, int c0, int c1) {
    asm volatile("cp.async.bulk.tensor.2d.global.shared::cta.bulk_group [%0, {%2, %3}], [%1];"
                 :: "l"((uint64_t)map), "r"(src), "r"(c0), "r"(c1) : "memory");
}
__device__ __forceinline__ float ex2f(float x) { float y; asm("ex2.approx.ftz.f32 %0, %1;" : "=f"(y) : "f"(x)); return y; }
__device__ __forceinline__ uint32_t pack_bf16(float lo, float hi) {
    __nv_bfloat162 v = __floats2bfloat162_rn(lo, hi);
    return *reinterpret_cast<uint32_t*>(&v);
}
__device__ __forceinline__ float bf16r(float x) { return __uint_as_float(pack_bf16(0.f, x) & 0xffff0000u); }
__device__ __forceinline__ void mma_16816(float (&c)[4], uint32_t a0, uint32_t a1, uint32_t a2, uint32_t a3,
                                          uint32_t b0, uint32_t b1) {
    asm volatile(
        "mma.sync.aligned.m16n8k16.row.col.f32.bf16.bf16.f32 {%0,%1,%2,%3}, {%4,%5,%6,%7}, {%8,%9}, {%0,%1,%2,%3};"
        : "+f"(c[0]), "+f"(c[1]), "+f"(c[2]), "+f"(c[3])
        : "r"(a0), "r"(a1), "r"(a2), "r"(a3), "r"(b0), "r"(b1));
}
__device__ __forceinline__ void ldmatrix_x4_trans(uint32_t& r0, uint32_t& r1, uint32_t& r2, uint32_t& r3, uint32_t addr) {
    asm volatile("ldmatrix.sync.aligned.m8n8.x4.trans.shared.b16 {%0,%1,%2,%3}, [%4];"
                 : "=r"(r0), "=r"(r1), "=r"(r2), "=r"(r3) : "r"(addr));
}

struct AttnParams {
    CUtensorMap mapQ, mapK, mapV;
    CUtensorMap mapO;
    const bf16 *x, *gate_w;
};
constexpr uint32_t FA_Q = 0, FA_KV = 65536, FA_O = 196608, FA_BAR = 229376;
constexpr int FA_SMEM = FA_BAR + 256;
constexpr int FA_ITEMS = 16 * NH;
__device__ __forceinline__ int fa_qt(int t) { return 15 - ((t & 127) >> 3); }
__device__ __forceinline__ int fa_head(int t) { return (t >> 7) * 8 + (t & 7); }
__device__ __forceinline__ uint32_t mbar_test(uint32_t bar, uint32_t parity) {
    uint32_t done;
    asm volatile(
        "{\n.reg .pred p;\n"
        "mbarrier.test_wait.parity.shared::cta.b64 p, [%1], %2;\n"
        "selp.u32 %0, 1, 0, p;\n}\n" : "=r"(done) : "r"(bar), "r"(parity) : "memory");
    return done;
}
__device__ __forceinline__ void mbar_arrive_if(uint32_t bar, bool c) {
    asm volatile("{\n.reg .pred p;\nsetp.ne.u32 p, %1, 0;\n@p mbarrier.arrive.shared::cta.b64 _, [%0];\n}" :: "r"(bar), "r"((uint32_t)c) : "memory");
}
__device__ __forceinline__ void wgmma_rs_n128_tb_lo(float (&d)[64], const uint32_t* a, uint32_t db_lo, int scale_d) {
    asm volatile(
        "{\n.reg .pred p;\n.reg .b64 db;\nsetp.ne.b32 p, %69, 0;\nmov.b64 db, {%68, 0x40000040};\n"
        "wgmma.mma_async.sync.aligned.m64n128k16.f32.bf16.bf16 " ACC64_STR ", {%64, %65, %66, %67}, db, p, 1, 1, 1;\n}\n"
        : ACC64(d) : "r"(a[0]), "r"(a[1]), "r"(a[2]), "r"(a[3]), "r"(db_lo), "r"(scale_d));
}
#define FA_TEST 48
#define FA_PIN 8

__global__ void __launch_bounds__(384, 1) attn_kernel(const __grid_constant__ AttnParams P) {
    extern __shared__ __align__(1024) uint8_t smem_attn[];
    const uint32_t sb = smem_u32(smem_attn);
    const uint32_t bar_q = sb + FA_BAR, bar_qe = bar_q + 16, bar_kf = bar_q + 32, bar_vf = bar_q + 48, bar_ke = bar_q + 64, bar_ve = bar_q + 80,
                   bar_of = bar_q + 96, bar_oe = bar_q + 112, slot = bar_q + 128, oslot = bar_q + 136;
    const int warp = __shfl_sync(0xffffffff, threadIdx.x >> 5, 0);
    const int lane = threadIdx.x & 31;
    TS_BEGIN(1);
    if (threadIdx.x == 0) {
        for (int i = 0; i < 2; i++) {
            mbar_init(bar_q + 8 * i, 1); mbar_init(bar_qe + 8 * i, 8); mbar_init(bar_kf + 8 * i, 1); mbar_init(bar_vf + 8 * i, 1);
            mbar_init(bar_ke + 8 * i, 8); mbar_init(bar_ve + 8 * i, 8); mbar_init(bar_of + 8 * i, 4); mbar_init(bar_oe + 8 * i, 1);
        }
        asm volatile("fence.mbarrier_init.release.cluster;" ::: "memory");
    }
    if (threadIdx.x == 256) wait_ctr(CT_AP + (fa_head(blockIdx.x) >> 1), 96u);
    __syncthreads();
    pdl_launch_dependents();
    if (warp >= 8) {
        asm volatile("setmaxnreg.dec.sync.aligned.u32 40;");
        if (warp == 11) {
            const uint4 gv0 = __ldg(reinterpret_cast<const uint4*>(P.gate_w) + lane), gv1 = __ldg(reinterpret_cast<const uint4*>(P.gate_w) + 32 + lane);
            const uint32_t gw[8] = {gv0.x, gv0.y, gv0.z, gv0.w, gv1.x, gv1.y, gv1.z, gv1.w};
#pragma unroll 1
            for (int r = blockIdx.x; r < SEQ; r += gridDim.x) {
                const uint4 x0 = __ldg(reinterpret_cast<const uint4*>(P.x + (size_t)r * DM) + lane), x1 = __ldg(reinterpret_cast<const uint4*>(P.x + (size_t)r * DM) + 32 + lane);
                const uint32_t xw[8] = {x0.x, x0.y, x0.z, x0.w, x1.x, x1.y, x1.z, x1.w};
                float sum = 0.f;
#pragma unroll
                for (int e = 0; e < 8; e++) {
                    const uint32_t pr = pack_bf16(__uint_as_float(xw[e] << 16) * __uint_as_float(gw[e] << 16), __uint_as_float(xw[e] & 0xffff0000u) * __uint_as_float(gw[e] & 0xffff0000u));
                    sum += __uint_as_float(pr << 16) + __uint_as_float(pr & 0xffff0000u);
                }
#pragma unroll
                for (int o = 16; o; o >>= 1) sum += __shfl_xor_sync(0xffffffff, sum, o);
                if (lane == 0) g_gate[r] = bf16r(1.f / (1.f + __expf(-bf16r(sum))));
            }
            if (lane == 0) signal_ctr_generic(CT_G);
        } else if (warp > 8) {
            if (lane == 0) {
                const int wg = warp - 9;
                const uint32_t stg = sb + FA_O + wg * 16384;
                for (int n = 0;; n++) {
                    mbar_wait(bar_of + 8 * wg, n & 1);
                    int t;
                    asm volatile("ld.shared.s32 %0, [%1];" : "=r"(t) : "r"(oslot + wg * 4) : "memory");
                    asm volatile("fence.proxy.async.shared::cta;" ::: "memory");
                    const bool last = t < 0;
                    t &= 0xffff;
                    const int qt = fa_qt(t), h = fa_head(t);
                    tma_store_2d(&P.mapO, stg, 0, h * SEQ + qt * 128 + wg * 64);
                    tma_store_2d(&P.mapO, stg + 8192, 64, h * SEQ + qt * 128 + wg * 64);
                    asm volatile("cp.async.bulk.commit_group;" ::: "memory");
                    asm volatile("cp.async.bulk.wait_group.read 0;" ::: "memory");
                    mbar_arrive(bar_oe + 8 * wg);
                    asm volatile("cp.async.bulk.wait_group 0;" ::: "memory");
                    signal_ctr(CT_CA + qt * 2 + (h >= O2_HE));
                    if (last) break;
                }
            }
        } else if (lane == 0) {
            int it = 0, t = blockIdx.x, hp_ready = 1 << (fa_head(t) >> 1);
            auto load_q = [&](int item, int t) {
                const uint32_t b = bar_q + 8 * (item & 1);
                asm volatile("st.shared.s32 [%0], %1;" :: "r"(slot + (item & 1) * 4), "r"(t) : "memory");
                if (t < 0) { mbar_arrive(b); return; }
                const int row = fa_head(t) * SEQ + fa_qt(t) * 128;
                mbar_expect_tx(b, 32768);
                tma_load_2d(sb + FA_Q + (item & 1) * 32768, &P.mapQ, b, 0, row);
                tma_load_2d(sb + FA_Q + (item & 1) * 32768 + 16384, &P.mapQ, b, 64, row);
            };
            load_q(0, t);
            for (int item = 0; t >= 0; item++) {
                const int h = fa_head(t);
                for (int j = fa_qt(t); j >= 0; j--, it++) {
                    const int s = it & 1;
                    const uint32_t ph = ((it >> 1) & 1) ^ 1;
                    const uint32_t sk = sb + FA_KV + s * 65536, sv = sk + 32768;
                    if (j == 0) t = (int)(gridDim.x + atomicAdd(&g_ctr[CT_ATTN], 1u));
                    mbar_wait(bar_ke + 8 * s, ph);
                    mbar_expect_tx(bar_kf + 8 * s, 32768);
                    tma_load_2d(sk, &P.mapK, bar_kf + 8 * s, 0, h * SEQ + j * 128);
                    tma_load_2d(sk + 16384, &P.mapK, bar_kf + 8 * s, 64, h * SEQ + j * 128);
                    if (j == 0) {
                        if (t >= FA_ITEMS) t = -1;
                        else {
                            const int hp = fa_head(t) >> 1;
                            if (!((hp_ready >> hp) & 1)) { wait_ctr(CT_AP + hp, 96u); hp_ready |= 1 << hp; }
                        }
                        mbar_wait(bar_qe + 8 * ((item + 1) & 1), (((item + 1) >> 1) & 1) ^ 1);
                        load_q(item + 1, t);
                    }
                    mbar_wait(bar_ve + 8 * s, ph);
                    mbar_expect_tx(bar_vf + 8 * s, 32768);
                    tma_load_2d(sv, &P.mapV, bar_vf + 8 * s, 0, h * SEQ + j * 128);
                    tma_load_2d(sv + 16384, &P.mapV, bar_vf + 8 * s, 64, h * SEQ + j * 128);
                }
            }
        }
    } else {
        asm volatile("setmaxnreg.inc.sync.aligned.u32 232;");
        const int wg = warp >> 2;
        const bool lane0 = lane == 0;
        float o[64], sacc[64];
        uint32_t pa[32];
        float mrow0, mrow1, lrow0, lrow1;
        const float sc = 0.08838834764831845f * 1.4426950408889634f;
        const uint32_t q_lo = desc_lo(sb + FA_Q + wg * 8192, 16), k_lo = desc_lo(sb + FA_KV, 16), v_lo = desc_lo(sb + FA_KV + 32768, 16384);
        auto issue_qk = [&](int item, int it) {
            const uint32_t a = q_lo + (item & 1) * 2048, b = k_lo + (it & 1) * 4096;
#pragma unroll
            for (int kk = 0; kk < 8; kk++) wgmma_ss_n128_lo<0>(sacc, a + (kk >> 2) * 1024 + (kk & 3) * 2, b + (kk >> 2) * 1024 + (kk & 3) * 2, kk != 0);
            wgmma_commit();
        };
        auto issue_pv = [&](int it, bool acc) {
            const uint32_t b = v_lo + (it & 1) * 4096;
#pragma unroll
            for (int kk = 0; kk < 8; kk++) wgmma_rs_n128_tb_lo(o, &pa[kk * 4], b + kk * 128, kk != 0 || acc);
            wgmma_commit();
        };
        auto turn_wait = [&]() { asm volatile("bar.sync %0, 256;" :: "r"(1 + wg) : "memory"); };
        auto turn_pass = [&]() { asm volatile("bar.arrive %0, 256;" :: "r"(2 - wg) : "memory"); };
        auto mask = [&]() {
            const int r0 = wg * 64 + (warp & 3) * 16 + (lane >> 2) - (lane & 3) * 2;
#pragma unroll
            for (int i = 0; i < 64; i++)
                if ((i >> 2) * 8 + (i & 1) - ((i & 2) ? 8 : 0) > r0) sacc[i] = -INFINITY;
        };
        auto row_max = [&](float& mx0, float& mx1) {
            float mx[4];
#pragma unroll
            for (int i = 0; i < 4; i++) mx[i] = fmaxf(sacc[i], sacc[i + 4]);
#pragma unroll
            for (int i = 8; i < 64; i++) mx[i & 3] = fmaxf(mx[i & 3], sacc[i]);
            mx0 = fmaxf(mx0, fmaxf(mx[0], mx[1])); mx1 = fmaxf(mx1, fmaxf(mx[2], mx[3]));
            const float u0 = __shfl_xor_sync(0xffffffff, mx0, 1), u1 = __shfl_xor_sync(0xffffffff, mx1, 1);
            mx0 = fmaxf(mx0, u0); mx1 = fmaxf(mx1, u1);
            const float v0 = __shfl_xor_sync(0xffffffff, mx0, 2), v1 = __shfl_xor_sync(0xffffffff, mx1, 2);
            mx0 = fmaxf(mx0, v0); mx1 = fmaxf(mx1, v1);
        };
        auto pin_after = [&](float v) {
            asm volatile("{\n.reg .pred p;\nsetp.lt.f32 p, %1, 0f00000000;\n@p st.shared.f32 [%0], %1;\n}" :: "r"(slot + 16), "f"(v) : "memory");
        };
        auto pack_p = [&]() {
#pragma unroll
            for (int i = 0; i < 32; i++) pa[i] = pack_bf16(sacc[2 * i], sacc[2 * i + 1]);
        };
        auto first_softmax = [&]() {
            mask();
            mrow0 = -INFINITY; mrow1 = -INFINITY;
            row_max(mrow0, mrow1);
            const float ms0 = mrow0 * sc, ms1 = mrow1 * sc;
            float sum[4] = {0.f, 0.f, 0.f, 0.f};
#pragma unroll
            for (int i = 0; i < 64; i++) { sacc[i] = ex2f(fmaf(sacc[i], sc, (i & 2) ? -ms1 : -ms0)); sum[i & 3] += sacc[i]; }
            lrow0 = sum[0] + sum[1]; lrow1 = sum[2] + sum[3];
        };
        auto epilogue = [&](int item, int tag, float l0, float l1) {
            l0 += __shfl_xor_sync(0xffffffff, l0, 1); l1 += __shfl_xor_sync(0xffffffff, l1, 1);
            l0 += __shfl_xor_sync(0xffffffff, l0, 2); l1 += __shfl_xor_sync(0xffffffff, l1, 2);
            float i0, i1;
            asm("rcp.approx.ftz.f32 %0, %1;" : "=f"(i0) : "f"(l0));
            asm("rcp.approx.ftz.f32 %0, %1;" : "=f"(i1) : "f"(l1));
            const int row = (warp & 3) * 16 + (lane >> 2);
            const uint32_t stg = sb + FA_O + wg * 16384 + row * 128;
#pragma unroll
            for (int i = 0; i < 4; i++) {
                const int ch = i * 4 + (lane & 3);
                const uint32_t a = stg + (ch >> 3) * 8192 + (((ch & 7) ^ (row & 7)) << 4);
                const float* q = &o[i * 16];
                asm volatile("st.shared.v4.b32 [%0], {%1, %2, %3, %4};" :: "r"(a), "r"(pack_bf16(q[0] * i0, q[1] * i0)), "r"(pack_bf16(q[4] * i0, q[5] * i0)),
                             "r"(pack_bf16(q[8] * i0, q[9] * i0)), "r"(pack_bf16(q[12] * i0, q[13] * i0)) : "memory");
                asm volatile("st.shared.v4.b32 [%0], {%1, %2, %3, %4};" :: "r"(a + 1024), "r"(pack_bf16(q[2] * i1, q[3] * i1)), "r"(pack_bf16(q[6] * i1, q[7] * i1)),
                             "r"(pack_bf16(q[10] * i1, q[11] * i1)), "r"(pack_bf16(q[14] * i1, q[15] * i1)) : "memory");
            }
            asm volatile("st.shared.s32 [%0], %1;" :: "r"(oslot + wg * 4), "r"(tag) : "memory");
            __syncwarp();
            mbar_arrive_if(bar_of + 8 * wg, lane0);
        };
        int it = 0, t = blockIdx.x, nkv = fa_qt(t) + 1;
        if (wg == 1) asm volatile("bar.arrive 1, 256;" ::: "memory");
        mbar_wait(bar_q, 0);
        mbar_wait(bar_kf, 0);
        turn_wait();
        wgmma_fence();
        issue_qk(0, 0);
        turn_pass();
        wgmma_wait<0>();
        mbar_arrive_if(bar_ke, lane0);
        mbar_arrive_if(bar_qe, lane0 && nkv == 1);
        first_softmax();
        pack_p();
#pragma unroll 1
        for (int item = 0;; item++) {
            uint32_t ok = 0;
#pragma unroll 1
            for (int j = 1; j < nkv; j++) {
                it++;
                if (__builtin_expect(!ok, 0)) {
                    mbar_wait(bar_kf + 8 * (it & 1), (it >> 1) & 1);
                    mbar_wait(bar_vf + 8 * ((it - 1) & 1), ((it - 1) >> 1) & 1);
                }
                turn_wait();
                wgmma_fence();
                issue_qk(item, it);
                issue_pv(it - 1, j > 1);
                turn_pass();
                wgmma_wait<1>();
                mbar_arrive_if(bar_ke + 8 * (it & 1), lane0);
                mbar_arrive_if(bar_qe + 8 * (item & 1), lane0 && j == nkv - 1);
                float mx0 = mrow0, mx1 = mrow1;
                row_max(mx0, mx1);
                const float ms0 = mx0 * sc, ms1 = mx1 * sc;
                const float a0 = ex2f(fmaf(mrow0, sc, -ms0)), a1 = ex2f(fmaf(mrow1, sc, -ms1));
                mrow0 = mx0; mrow1 = mx1;
                float sum[4] = {lrow0 * a0, 0.f, lrow1 * a1, 0.f};
#pragma unroll
                for (int i = 0; i < FA_PIN; i++) { sacc[i] = ex2f(fmaf(sacc[i], sc, (i & 2) ? -ms1 : -ms0)); sum[i & 3] += sacc[i]; }
                pin_after(sum[0] + sum[2]);
                wgmma_wait<0>();
                mbar_arrive_if(bar_ve + 8 * ((it - 1) & 1), lane0);
#pragma unroll
                for (int i = 0; i < 64; i++) {
                    if (i >= FA_PIN) { sacc[i] = ex2f(fmaf(sacc[i], sc, (i & 2) ? -ms1 : -ms0)); sum[i & 3] += sacc[i]; }
                    o[i] *= (i & 2) ? a1 : a0;
                    if (i & 1) pa[i >> 1] = pack_bf16(sacc[i - 1], sacc[i]);
                    if (i == FA_TEST) pin_after(sum[0]);
                    if (i == FA_TEST) ok = mbar_test(bar_kf + 8 * ((it + 1) & 1), ((it + 1) >> 1) & 1) & mbar_test(bar_vf + 8 * (it & 1), (it >> 1) & 1);
                }
                lrow0 = sum[0] + sum[1]; lrow1 = sum[2] + sum[3];
            }
            it++;
            int tn;
            mbar_wait(bar_q + 8 * ((item + 1) & 1), ((item + 1) >> 1) & 1);
            asm volatile("ld.shared.s32 %0, [%1];" : "=r"(tn) : "r"(slot + ((item + 1) & 1) * 4) : "memory");
            tn = __shfl_sync(0xffffffff, tn, 0);
            mbar_wait(bar_vf + 8 * ((it - 1) & 1), ((it - 1) >> 1) & 1);
            const float l0 = lrow0, l1 = lrow1;
            if (tn < 0) {
                wgmma_fence();
                issue_pv(it - 1, nkv > 1);
                mbar_wait(bar_oe + 8 * wg, (item & 1) ^ 1);
                wgmma_wait<0>();
                epilogue(item, t | 0x80000000, l0, l1);
                break;
            }
            mbar_wait(bar_kf + 8 * (it & 1), (it >> 1) & 1);
            turn_wait();
            wgmma_fence();
            issue_qk(item + 1, it);
            issue_pv(it - 1, nkv > 1);
            turn_pass();
            nkv = fa_qt(tn) + 1;
            mbar_wait(bar_oe + 8 * wg, (item & 1) ^ 1);
            wgmma_wait<1>();
            mbar_arrive_if(bar_ke + 8 * (it & 1), lane0);
            mbar_arrive_if(bar_qe + 8 * ((item + 1) & 1), lane0 && nkv == 1);
            mask();
            mrow0 = -INFINITY; mrow1 = -INFINITY;
            row_max(mrow0, mrow1);
            {
                const float ms0 = mrow0 * sc, ms1 = mrow1 * sc;
                pin_after(fmaf(ex2f(fmaf(sacc[0], sc, -ms0)), l0, ex2f(fmaf(sacc[2], sc, -ms1))));
                wgmma_wait<0>();
                mbar_arrive_if(bar_ve + 8 * ((it - 1) & 1), lane0);
                float sum[4] = {0.f, 0.f, 0.f, 0.f};
#pragma unroll
                for (int i = 0; i < 64; i++) { sacc[i] = ex2f(fmaf(sacc[i], sc, (i & 2) ? -ms1 : -ms0)); sum[i & 3] += sacc[i]; }
                lrow0 = sum[0] + sum[1]; lrow1 = sum[2] + sum[3];
                pack_p();
                epilogue(item, t, l0, l1);
            }
            t = tn;
        }
        TS_END(1);
    }
}

__device__ __forceinline__ uint32_t cluster_ctarank() {
    uint32_t r; asm volatile("mov.u32 %0, %%cluster_ctarank;" : "=r"(r)); return r;
}
__device__ __forceinline__ uint32_t mapa_u32(uint32_t addr, uint32_t rank) {
    uint32_t r; asm volatile("mapa.shared::cluster.u32 %0, %1, %2;" : "=r"(r) : "r"(addr), "r"(rank)); return r;
}
__device__ __forceinline__ void cluster_sync_all() {
    asm volatile("barrier.cluster.arrive.release.aligned;\nbarrier.cluster.wait.acquire.aligned;" ::: "memory");
}
__device__ __forceinline__ void cluster_sync_relaxed() {
    asm volatile("barrier.cluster.arrive.relaxed.aligned;\nbarrier.cluster.wait.aligned;" ::: "memory");
}
__device__ __forceinline__ void st_async_v4(uint32_t addr, uint32_t a, uint32_t b, uint32_t c, uint32_t d, uint32_t mbar) {
    asm volatile("st.async.weak.shared::cluster.mbarrier::complete_tx::bytes.v4.b32 [%0], {%1, %2, %3, %4}, [%5];"
                 :: "r"(addr), "r"(a), "r"(b), "r"(c), "r"(d), "r"(mbar) : "memory");
}
__device__ __forceinline__ void st_async_v2(uint32_t addr, uint32_t a, uint32_t b, uint32_t mbar) {
    asm volatile("st.async.weak.shared::cluster.mbarrier::complete_tx::bytes.v2.b32 [%0], {%1, %2}, [%3];"
                 :: "r"(addr), "r"(a), "r"(b), "r"(mbar) : "memory");
}
__device__ __forceinline__ void st_async_b32(uint32_t addr, uint32_t a, uint32_t mbar) {
    asm volatile("st.async.weak.shared::cluster.mbarrier::complete_tx::bytes.b32 [%0], %1, [%2];" :: "r"(addr), "r"(a), "r"(mbar) : "memory");
}
__device__ __forceinline__ void pace(int cycles) {
    if (cycles > 0) {
        uint32_t t0, t;
        asm volatile("mov.u32 %0, %%clock;" : "=r"(t0));
        do { asm volatile("mov.u32 %0, %%clock;" : "=r"(t)); } while (t - t0 < (uint32_t)cycles);
    }
}
__device__ __forceinline__ void mbar_wait_cl(uint32_t bar, uint32_t parity) {
    uint32_t done = 0;
    for (int it = 0; it < (1 << 22) && !done; it++) {
        asm volatile(
            "{\n.reg .pred p;\n"
            "mbarrier.try_wait.parity.shared::cta.b64 p, [%1], %2;\n"
            "selp.u32 %0, 1, 0, p;\n}\n" : "=r"(done) : "r"(bar), "r"(parity) : "memory");
    }
}
__device__ __forceinline__ void ldmatrix_x4(uint32_t& r0, uint32_t& r1, uint32_t& r2, uint32_t& r3, uint32_t addr) {
    asm volatile("ldmatrix.sync.aligned.m8n8.x4.shared.b16 {%0,%1,%2,%3}, [%4];"
                 : "=r"(r0), "=r"(r1), "=r"(r2), "=r"(r3) : "r"(addr));
}
__device__ __forceinline__ void cp_async16(uint32_t dst, const void* src) {
    asm volatile("cp.async.cg.shared.global [%0], [%1], 16;" :: "r"(dst), "l"(src) : "memory");
}

#define DBG(i)
#define DBGW(i, w)
__device__ __forceinline__ void tma_load_2d_mc(uint32_t dst, const CUtensorMap* map, uint32_t bar, int c0, int c1, uint16_t mask) {
    asm volatile(
        "cp.async.bulk.tensor.2d.shared::cluster.global.mbarrier::complete_tx::bytes.multicast::cluster [%0], [%1, {%3, %4}], [%2], %5;"
        :: "r"(dst), "l"((uint64_t)map), "r"(bar), "r"(c0), "r"(c1), "h"(mask) : "memory");
}
__device__ __forceinline__ void bulk_s2s(uint32_t dst_cl, uint32_t src, uint32_t bytes, uint32_t bar_cl) {
    asm volatile("cp.async.bulk.shared::cluster.shared::cta.mbarrier::complete_tx::bytes [%0], [%1], %2, [%3];"
                 :: "r"(dst_cl), "r"(src), "r"(bytes), "r"(bar_cl) : "memory");
}
__device__ __forceinline__ bool elect_one() {
    uint32_t p;
    asm volatile("{\n.reg .pred p;\nelect.sync _|p, 0xffffffff;\nselp.u32 %0, 1, 0, p;\n}" : "=r"(p));
    return p;
}
__device__ __forceinline__ void fence_async_smem() { asm volatile("fence.proxy.async.shared::cta;" ::: "memory"); }
template <int ID, int N> __device__ __forceinline__ void bar_sync() { asm volatile("bar.sync %0, %1;" :: "n"(ID), "n"(N) : "memory"); }
template <int ID, int N> __device__ __forceinline__ void bar_arrive() { asm volatile("bar.arrive %0, %1;" :: "n"(ID), "n"(N) : "memory"); }
__device__ __forceinline__ void sts32(uint32_t a, uint32_t v) { asm volatile("st.shared.u32 [%0], %1;" :: "r"(a), "r"(v) : "memory"); }
__device__ __forceinline__ void ldsm_x4(uint32_t* r, uint32_t addr) {
    asm volatile("ldmatrix.sync.aligned.m8n8.x4.shared.b16 {%0,%1,%2,%3}, [%4];" : "=r"(r[0]), "=r"(r[1]), "=r"(r[2]), "=r"(r[3]) : "r"(addr) : "memory");
}
__device__ __forceinline__ uint32_t pin(uint32_t v) { asm volatile("" : "+r"(v)); return v; }
constexpr uint32_t DHI128 = 0x40000040u, DHI32 = 0xC0000010u;
#define ACC16(d) "+f"(d[0]), "+f"(d[1]), "+f"(d[2]), "+f"(d[3]), "+f"(d[4]), "+f"(d[5]), "+f"(d[6]), "+f"(d[7]), "+f"(d[8]), "+f"(d[9]), "+f"(d[10]), \
    "+f"(d[11]), "+f"(d[12]), "+f"(d[13]), "+f"(d[14]), "+f"(d[15])
#define ACC20(d) ACC16(d), "+f"(d[16]), "+f"(d[17]), "+f"(d[18]), "+f"(d[19])
__device__ __forceinline__ void wgmma_rs(float (&d)[16], const uint32_t (&a)[4], uint32_t db_lo) {
    asm volatile(
        "{\n.reg .b64 db;\nmov.b64 db, {%20, %21};\n"
        "wgmma.mma_async.sync.aligned.m64n32k16.f32.bf16.bf16 {%0,%1,%2,%3,%4,%5,%6,%7,%8,%9,%10,%11,%12,%13,%14,%15}, {%16,%17,%18,%19}, db, 1, 1, 1, 0;\n}\n"
        : ACC16(d) : "r"(a[0]), "r"(a[1]), "r"(a[2]), "r"(a[3]), "r"(db_lo), "n"(DHI128));
}
__device__ __forceinline__ void wgmma_rs(float (&d)[20], const uint32_t (&a)[4], uint32_t db_lo) {
    asm volatile(
        "{\n.reg .b64 db;\nmov.b64 db, {%24, %25};\n"
        "wgmma.mma_async.sync.aligned.m64n40k16.f32.bf16.bf16 {%0,%1,%2,%3,%4,%5,%6,%7,%8,%9,%10,%11,%12,%13,%14,%15,%16,%17,%18,%19}, {%20,%21,%22,%23}, db, 1, 1, 1, 0;\n}\n"
        : ACC20(d) : "r"(a[0]), "r"(a[1]), "r"(a[2]), "r"(a[3]), "r"(db_lo), "n"(DHI128));
}
template <uint32_t AHI, uint32_t BHI>
__device__ __forceinline__ void wgmma_ss(float (&d)[16], uint32_t da_lo, uint32_t db_lo) {
    asm volatile(
        "{\n.reg .b64 da, db;\nmov.b64 da, {%16, %18};\nmov.b64 db, {%17, %19};\n"
        "wgmma.mma_async.sync.aligned.m64n32k16.f32.bf16.bf16 {%0,%1,%2,%3,%4,%5,%6,%7,%8,%9,%10,%11,%12,%13,%14,%15}, da, db, 1, 1, 1, 0, 0;\n}\n"
        : ACC16(d) : "r"(da_lo), "r"(db_lo), "n"(AHI), "n"(BHI));
}
template <uint32_t AHI, uint32_t BHI>
__device__ __forceinline__ void wgmma_ss(float (&d)[20], uint32_t da_lo, uint32_t db_lo) {
    asm volatile(
        "{\n.reg .b64 da, db;\nmov.b64 da, {%20, %22};\nmov.b64 db, {%21, %23};\n"
        "wgmma.mma_async.sync.aligned.m64n40k16.f32.bf16.bf16 {%0,%1,%2,%3,%4,%5,%6,%7,%8,%9,%10,%11,%12,%13,%14,%15,%16,%17,%18,%19}, da, db, 1, 1, 1, 0, 0;\n}\n"
        : ACC20(d) : "r"(da_lo), "r"(db_lo), "n"(AHI), "n"(BHI));
}
__device__ __forceinline__ void wgmma_ss_n8(float (&d)[4], uint32_t da_lo, uint32_t db_lo) {
    asm volatile(
        "{\n.reg .b64 da, db;\nmov.b64 da, {%4, %6};\nmov.b64 db, {%5, %7};\n"
        "wgmma.mma_async.sync.aligned.m64n8k16.f32.bf16.bf16 {%0,%1,%2,%3}, da, db, 1, 1, 1, 1, 0;\n}\n"
        : "+f"(d[0]), "+f"(d[1]), "+f"(d[2]), "+f"(d[3]) : "r"(da_lo), "r"(db_lo), "n"(DHI128), "n"(DHI32));
}

constexpr uint32_t C2_WO = 0;
constexpr uint32_t C2_XB = 65536;
constexpr uint32_t C2_XS = 40960;
constexpr uint32_t C2_QX = C2_XB + 2 * C2_XS;
constexpr uint32_t C2_KX = C2_QX + 4096;
constexpr uint32_t C2_VT = C2_KX + 5120;
constexpr uint32_t C2_OB = C2_VT + 12288;
constexpr uint32_t C2_QM = C2_OB + 8192;
constexpr uint32_t C2_SC = C2_QM + 1024;
constexpr uint32_t C2_PB = C2_SC + 2560;
constexpr uint32_t C2_BAR = C2_PB + 768;
constexpr uint32_t C2_PX = C2_BAR + 256;
constexpr uint32_t C2_SX = C2_PX + 3072;
#define C2_NS 4
constexpr uint32_t C2_WS = C2_SX + 20480;
constexpr int C2_SMEM = C2_WS + 3 * C2_NS * 2048;
static_assert(C2_PX % 256 == 0 && C2_WS % 256 == 0 && C2_SMEM <= 232448, "smem map");
#define CH_PF 0
#define CH_PFD 3000
#define CH_POLL_DELAY 200

__device__ __forceinline__ uint32_t c2_stage(int wg, int i) { return wg < 2 ? C2_XB + C2_XS + (wg * 4 + i) * 8192 : ((C2_PX + 1023) & ~1023u) + i * 8192; }
static_assert(C2_XB + C2_XS + 8 * 8192 <= C2_BAR && ((C2_PX + 1023) & ~1023u) + 4 * 8192 <= C2_SMEM && (C2_XB + C2_XS) % 1024 == 0, "staging");
__device__ __forceinline__ void c2_stage_load(const CUtensorMap* map, uint32_t sb, int wg, int rank, int col0, int round) {
    const uint32_t bar = sb + C2_BAR + 176 + (wg * 2 + round) * 8;
    mbar_expect_tx(bar, 32768);
    for (int i = 0; i < 4; i++) tma_load_2d(sb + c2_stage(wg, i), map, bar, col0, ((rank - round * 4 - i) & 7) * 64);
}
__device__ __forceinline__ void c2_load_w(uint32_t (&w)[32][4], const CUtensorMap* map, int wg, int rank, int col0, uint32_t t128, uint32_t ws, uint32_t sb) {
#pragma unroll
    for (int r = 0; r < 2; r++) {
        mbar_wait(sb + C2_BAR + 176 + (wg * 2 + r) * 8, 0);
#pragma unroll
        for (int e = 0; e < 16; e++) {
            const uint32_t a = sb + c2_stage(wg, 0) + e * 2048;
            uint32_t w0, w1, w2, w3;
            asm volatile("ld.shared.b32 %0, [%1];" : "=r"(w0) : "r"(a + t128) : "memory");
            asm volatile("ld.shared.b32 %0, [%1];" : "=r"(w1) : "r"(a + (t128 ^ 16) + 128) : "memory");
            asm volatile("ld.shared.b32 %0, [%1];" : "=r"(w2) : "r"(a + t128 + 1024) : "memory");
            asm volatile("ld.shared.b32 %0, [%1];" : "=r"(w3) : "r"(a + (t128 ^ 16) + 1152) : "memory");
            uint32_t* d = w[r * 16 + e];
            d[0] = __byte_perm(w0, w1, 0x5410); d[1] = __byte_perm(w0, w1, 0x7632);
            d[2] = __byte_perm(w2, w3, 0x5410); d[3] = __byte_perm(w2, w3, 0x7632);
        }
        if (r == 0) {
            asm volatile("bar.sync %0, 128;" :: "r"(8 + wg) : "memory");
            if ((threadIdx.x & 127) == 32) c2_stage_load(map, sb, wg, rank, col0, 1);
            mbar_wait(sb + C2_BAR + 168, 0);
#pragma unroll 2
            for (int i = threadIdx.x; i < 2048; i += 384) {
                const int k = i >> 2, b = i & 3;
                const uint32_t a0 = sb + C2_WO + k * 128 + (((2 * b) ^ (k & 7)) << 4), a1 = a0 ^ 16;
                uint4 u, v;
                asm volatile("ld.shared.v4.b32 {%0, %1, %2, %3}, [%4];" : "=r"(u.x), "=r"(u.y), "=r"(u.z), "=r"(u.w) : "r"(a0) : "memory");
                asm volatile("ld.shared.v4.b32 {%0, %1, %2, %3}, [%4];" : "=r"(v.x), "=r"(v.y), "=r"(v.z), "=r"(v.w) : "r"(a1) : "memory");
                asm volatile("st.shared.v4.b32 [%0], {%1, %2, %3, %4};" :: "r"(a0), "r"(__byte_perm(u.x, u.y, 0x5410)),
                             "r"(__byte_perm(u.z, u.w, 0x5410)), "r"(__byte_perm(v.x, v.y, 0x5410)), "r"(__byte_perm(v.z, v.w, 0x5410)) : "memory");
                asm volatile("st.shared.v4.b32 [%0], {%1, %2, %3, %4};" :: "r"(a1), "r"(__byte_perm(u.x, u.y, 0x7632)),
                             "r"(__byte_perm(u.z, u.w, 0x7632)), "r"(__byte_perm(v.x, v.y, 0x7632)), "r"(__byte_perm(v.z, v.w, 0x7632)) : "memory");
            }
        }
    }
    cluster_sync_relaxed();
#pragma unroll
    for (int e = 0; e < C2_NS; e++) stmatrix_x4(ws + e * 2048, w[e][0], w[e][1], w[e][2], w[e][3]);
    for (int i = threadIdx.x; i < 2 * 512 + 256; i += 384)
        sts32(sb + (i < 1024 ? C2_VT + (i >> 9) * 6144 + 4096 + (i & 511) * 4 : C2_PX + 2048 + (i - 1024) * 4), 0u);
    fence_async_smem();
    asm volatile("bar.sync %0, 128;" :: "r"(8 + wg) : "memory");
}
template <int NA>
__device__ __forceinline__ void c2_xstream(float (&acc)[NA], const uint32_t (&w)[32][4], uint32_t xlo, uint32_t rank, uint32_t wslo) {
#pragma unroll
    for (int i = 0; i < NA; i++) acc[i] = 0.f;
    wgmma_fence();
#pragma unroll
    for (int e = 0; e < 32; e++) {
        if (e < C2_NS) wgmma_ss<DHI32, DHI128>(acc, wslo + e * 128, xlo + ((rank - (e >> 2)) & 7) * 320 + (e & 3) * 2);
        else wgmma_rs(acc, w[e], xlo + ((rank - (e >> 2)) & 7) * 320 + (e & 3) * 2);
    }
    wgmma_commit();
    wgmma_wait<0>();
}
__device__ __forceinline__ void c2_mma_slot(float (&a)[4][4], const uint32_t (&w)[32][4], int slot, const uint32_t* b, uint32_t ws) {
#pragma unroll
    for (int kk = 0; kk < 4; kk++) {
        const int e = slot * 4 + kk;
        if (e < C2_NS) {
            uint32_t t[4];
            ldsm_x4(t, ws + e * 2048);
            mma_16816(a[kk], t[0], t[1], t[2], t[3], b[2 * kk], b[2 * kk + 1]);
        } else mma_16816(a[kk], w[e][0], w[e][1], w[e][2], w[e][3], b[2 * kk], b[2 * kk + 1]);
    }
}
__device__ __forceinline__ constexpr int c2_grp(int i) { return i < 2 ? i : 1 + (i >> 1); }

struct ChainParams {
    CUtensorMap mapX;
    CUtensorMap mapM;
    CUtensorMap mapW[3];
    CUtensorMap mapWo;
};
__global__ void __cluster_dims__(8, 1, 1) __launch_bounds__(384, 1)
chain_kernel(const __grid_constant__ ChainParams P) {
    const CUtensorMap& mapX = P.mapX;
    extern __shared__ __align__(1024) uint8_t smem_chain[];
    const uint32_t sb = smem_u32(smem_chain);
    const uint32_t dlo = ((sb & 0x3FFFF) >> 4) | (1u << 16);
    const int tid = threadIdx.x, lane = tid & 31;
    const int warp = __shfl_sync(0xffffffff, tid >> 5, 0), wg = warp >> 2, w4 = warp & 3;
    const uint32_t rank = cluster_ctarank();
    const int C = blockIdx.x >> 3;
    const int h = C * 4 + (rank >> 1);
    const int g = lane >> 2, qc = lane & 3;
    pdl_launch_dependents();
    TS_BEGIN(2);
    const uint32_t bar_m = sb + C2_BAR, bar_o = bar_m + 64, bar_sc = bar_m + 128, bar_x = bar_m + 136, bar_sx = bar_m + 152;
    const uint32_t bar_w = bar_m + 168;
    const int col0 = h * HD + (rank & 1) * 64;
    if (tid == 0) {
        for (int j = 0; j < 5; j++) { mbar_init(bar_m + 8 * j, j ? 1 : 4); mbar_init(bar_o + 8 * j, j ? 1 : 4); }
        for (int j = 0; j < 12; j++) mbar_init(bar_sc + 8 * j, 1);
        asm volatile("fence.mbarrier_init.release.cluster;" ::: "memory");
    }
    __syncwarp();
    cluster_sync_relaxed();
    if (tid == 0) {
        mbar_expect_tx(bar_x, 32768 + 8192);
        tma_load_2d_mc(sb + C2_XB + rank * 5120, &mapX, bar_x, rank * 64, 0, (uint16_t)0xff);
        for (int j = 0; j < 8; j++) tma_load_2d(sb + C2_XB + j * 5120 + 4096, &P.mapM, bar_x, j * 64, 0);
        pace(CH_PFD);
        mbar_expect_tx(bar_w, 65536);
        for (int j = 0; j < 8; j++) tma_load_2d(sb + C2_WO + j * 8192, &P.mapWo, bar_w, rank * 64, C * 512 + ((rank - j) & 7) * 64);
    }
    if ((tid & 127) == 32) {
        pace(CH_PFD);
        c2_stage_load(&P.mapW[wg], sb, wg, rank, col0, 0);
        if (CH_PF)
            for (int i = 4; i < 8; i++)
                asm volatile("cp.async.bulk.prefetch.tensor.2d.L2.global [%0, {%1, %2}];" :: "l"((uint64_t)&P.mapW[wg]), "r"(col0), "r"((int)((rank - i) & 7) * 64) : "memory");
    }
    __syncwarp();

    const uint32_t t32 = w4 * 256 + qc * 64 + (((g >> 2) ^ (qc >> 1)) << 4) + (g & 3) * 4;
    const uint32_t t128 = qc * 256 + (((2 * w4 + (g >> 2)) ^ (2 * qc)) << 4) + (g & 3) * 4;
    const uint32_t a32 = (w4 * 16 + (lane & 15)) * 32 + (((lane >> 4) ^ ((lane >> 2) & 1)) << 4);
    const uint32_t ws = sb + C2_WS + wg * (C2_NS * 2048) + a32;
    uint32_t w[32][4];
    auto proj_mem = [&](float (&a)[4][4], int s) {
        uint32_t b[16];
#pragma unroll
        for (int i = 0; i < 16; i++) a[i >> 2][i & 3] = 0.f;
        const uint32_t par = (s & 1) ^ 1;
        const uint32_t l128 = (lane & 7) * 128 + (((lane >> 3) ^ (lane & 7)) << 4);
        const uint32_t mb = sb + C2_XB + (s & 1) * C2_XS + 4096;
        auto ldb = [&](uint32_t* bb, int i) {
            ldsm_x4(bb, mb + ((rank - i) & 7) * 5120 + l128);
            ldsm_x4(bb + 4, mb + ((rank - i) & 7) * 5120 + (l128 ^ 64));
        };
        mbar_wait(bar_m, par);
        ldb(b, 0);
        c2_mma_slot(a, w, 0, b, ws);
        mbar_wait(bar_m + 8, par);
        DBGW(1 + 16 * wg, 0);
        ldb(b, 1);
        uint32_t nxt = mbar_test(bar_m + 16, par);
        c2_mma_slot(a, w, 1, b, ws);
#pragma unroll
        for (int i = 2; i < 8; i += 2) {
            if (__builtin_expect(!nxt, 0)) mbar_wait(bar_m + 8 * c2_grp(i), par);
            if (i == 6) DBGW(2 + 16 * wg, 0);
            ldb(b, i);
            ldb(b + 8, i + 1);
            if (i < 6) nxt = mbar_test(bar_m + 8 * c2_grp(i + 2), par);
            c2_mma_slot(a, w, i, b, ws);
            c2_mma_slot(a, w, i + 1, b + 8, ws);
        }
#pragma unroll
        for (int i = 0; i < 4; i++) a[0][i] = (a[0][i] + a[1][i]) + (a[2][i] + a[3][i]);
    };
    auto store_x = [&](const float (&acc)[16], uint32_t base) {
#pragma unroll
        for (int j = 0; j < 4; j++) {
            sts32(base + t128 + j * 1024, pack_bf16(acc[4 * j], acc[4 * j + 2]));
            sts32(base + (t128 ^ 16) + 128 + j * 1024, pack_bf16(acc[4 * j + 1], acc[4 * j + 3]));
        }
    };
    const float scale = 0.08838834764831845f, l2e = 1.4426950408889634f;

    if (wg == 0) {
        c2_load_w(w, &P.mapW[0], 0, rank, col0, t128, ws, sb);
        TS_END(6);
        TS_BEGIN(5);
#pragma unroll 1
        for (int s = -1;;) {
            uint32_t xok = 0;
            if (s >= 0) {
                float acc[4] = {0.f, 0.f, 0.f, 0.f};
                const uint32_t tag = ((s >> 1) & 1) ^ 1;
                uint32_t* dst = reinterpret_cast<uint32_t*>(g_xbuf + (((s & 1) * 8 + rank) * 8 + C) * 128) + qc * 64 + w4 * 8 + g;
                asm volatile("" : "+l"(dst));
#pragma unroll
                for (int i = 0; i < 8; i++) {
                    if (i < 2 || !(i & 1)) {
                        mbar_wait(bar_o + 8 * c2_grp(i), s & 1);
                        if (i == 0) DBGW(7, 0);
                        if (i == 1) DBGW(8, 0);
                        if (i == 6) DBGW(9, 0);
                        wgmma_fence();
                    }
#pragma unroll
                    for (int kk = 0; kk < 4; kk++)
                        wgmma_ss_n8(acc, dlo + ((C2_WO + i * 8192 + kk * 2048) >> 4), dlo + ((C2_OB + i * 1024 + kk * 256) >> 4));
                }
                wgmma_commit();
                xok = mbar_test(bar_x + 8 * ((s + 1) & 1), ((s + 1) >> 1) & 1);
                wgmma_wait<0>();
                asm volatile("st.relaxed.gpu.global.u32 [%0], %1;" :: "l"(dst), "r"((pack_bf16(acc[0], acc[2]) & ~1u) | tag) : "memory");
                asm volatile("st.relaxed.gpu.global.u32 [%0 + 128], %1;" :: "l"(dst), "r"((pack_bf16(acc[1], acc[3]) & ~1u) | tag) : "memory");
                bar_arrive<4, 384>();
                DBGW(10, 0);
            }
            s++;
            if (__builtin_expect(!xok, 0)) mbar_wait(bar_x + 8 * (s & 1), (s >> 1) & 1);
            {
                float acc[16];
                c2_xstream(acc, w, dlo + ((C2_XB + (s & 1) * C2_XS) >> 4), rank, dlo + (C2_WS >> 4));
                if (s > 0) bar_sync<5, 256>();
                store_x(acc, sb + C2_QX);
            }
            DBGW(0, 0);
            if (s == NSEG - 1) break;
            const uint32_t sca = w4 < 2 ? sb + C2_SC + w4 * 512 + lane * 16 : sb + C2_SC + 1024 + lane * 8;
            const uint32_t sc_peer = pin(mapa_u32(sca + 1280, rank ^ 1)), sc_own = pin(mapa_u32(sca, rank));
            const uint32_t krow = w4 * 16 + (lane & 15);
            const uint32_t ka0 = pin(sb + C2_KX + krow * 128 + (((lane >> 4) ^ (krow & 7)) << 4));
            const uint32_t l32 = pin(sb + C2_QM + (lane >> 4) * 256 + (lane & 7) * 32 + ((((lane >> 3) & 1) ^ ((lane >> 2) & 1)) << 4));
            const uint32_t qst = pin(sb + C2_QM + t32);
            {
                float a[4][4];
                proj_mem(a, s);
                sts32(qst, pack_bf16(a[0][0], a[0][2]));
                sts32(qst + 32, pack_bf16(a[0][1], a[0][3]));
            }
            DBGW(3, 0);
            if (w4 < 3) {
                uint32_t ka[4][4], qb[8];
                float c[4] = {0.f, 0.f, 0.f, 0.f}, c2[4] = {0.f, 0.f, 0.f, 0.f};
                bar_sync<1, 384>();
                ldsm_x4(qb, l32);
                ldsm_x4(ka[0], ka0);
                ldsm_x4(ka[1], ka0 ^ 32);
                ldsm_x4(qb + 4, l32 + 512);
                ldsm_x4(ka[2], ka0 ^ 64);
                ldsm_x4(ka[3], ka0 ^ 96);
                mma_16816(c, ka[0][0], ka[0][1], ka[0][2], ka[0][3], qb[0], qb[1]);
                mma_16816(c2, ka[1][0], ka[1][1], ka[1][2], ka[1][3], qb[2], qb[3]);
                mma_16816(c, ka[2][0], ka[2][1], ka[2][2], ka[2][3], qb[4], qb[5]);
                mma_16816(c2, ka[3][0], ka[3][1], ka[3][2], ka[3][3], qb[6], qb[7]);
                const uint32_t u0 = __float_as_uint(c[0] + c2[0]), u1 = __float_as_uint(c[1] + c2[1]);
                const uint32_t u2 = __float_as_uint(c[2] + c2[2]), u3 = __float_as_uint(c[3] + c2[3]);
                asm volatile(
                    "{\n.reg .pred p;\nsetp.lt.u32 p, %8, 2;\n"
                    "@p st.async.weak.shared::cluster.mbarrier::complete_tx::bytes.v4.b32 [%0], {%4, %5, %6, %7}, [%1];\n"
                    "@!p st.async.weak.shared::cluster.mbarrier::complete_tx::bytes.v2.b32 [%0], {%4, %5}, [%1];\n"
                    "@p st.async.weak.shared::cluster.mbarrier::complete_tx::bytes.v4.b32 [%2], {%4, %5, %6, %7}, [%3];\n"
                    "@!p st.async.weak.shared::cluster.mbarrier::complete_tx::bytes.v2.b32 [%2], {%4, %5}, [%3];\n}"
                    :: "r"(sc_peer), "r"(mapa_u32(bar_sc, rank ^ 1)), "r"(sc_own), "r"(mapa_u32(bar_sc, rank)), "r"(u0), "r"(u1), "r"(u2), "r"(u3), "r"(w4) : "memory");
                bar_arrive<2, 224>();
                if (s == NSEG - 3 && tid == 0) signal_ctr(CT_CB + 1);
                __syncwarp();
                DBGW(4, 2);
            } else {
                bar_arrive<1, 384>();
                const uint32_t a = pin(sb + C2_SC + lane * 16), a2 = pin(sb + C2_SC + 1024 + lane * 8), pa = pin(sb + C2_PB + lane * 4);
                mbar_wait(bar_sc, s & 1);
                DBG(5);
                float v[10];
                {
                    float4 x0, x1, y0, y1; float2 x2, y2;
                    asm volatile("ld.shared.v4.f32 {%0, %1, %2, %3}, [%4];" : "=f"(x0.x), "=f"(x0.y), "=f"(x0.z), "=f"(x0.w) : "r"(a) : "memory");
                    asm volatile("ld.shared.v4.f32 {%0, %1, %2, %3}, [%4];" : "=f"(y0.x), "=f"(y0.y), "=f"(y0.z), "=f"(y0.w) : "r"(a + 1280) : "memory");
                    asm volatile("ld.shared.v4.f32 {%0, %1, %2, %3}, [%4];" : "=f"(x1.x), "=f"(x1.y), "=f"(x1.z), "=f"(x1.w) : "r"(a + 512) : "memory");
                    asm volatile("ld.shared.v4.f32 {%0, %1, %2, %3}, [%4];" : "=f"(y1.x), "=f"(y1.y), "=f"(y1.z), "=f"(y1.w) : "r"(a + 1792) : "memory");
                    asm volatile("ld.shared.v2.f32 {%0, %1}, [%2];" : "=f"(x2.x), "=f"(x2.y) : "r"(a2) : "memory");
                    asm volatile("ld.shared.v2.f32 {%0, %1}, [%2];" : "=f"(y2.x), "=f"(y2.y) : "r"(a2 + 1280) : "memory");
                    v[0] = x0.x + y0.x; v[1] = x0.y + y0.y; v[2] = x0.z + y0.z; v[3] = x0.w + y0.w;
                    v[4] = x1.x + y1.x; v[5] = x1.y + y1.y; v[6] = x1.z + y1.z; v[7] = x1.w + y1.w;
                    v[8] = x2.x + y2.x; v[9] = x2.y + y2.y;
                }
                float m0 = fmaxf(fmaxf(fmaxf(v[0], v[2]), fmaxf(v[4], v[6])), v[8]);
                float m1 = fmaxf(fmaxf(fmaxf(v[1], v[3]), fmaxf(v[5], v[7])), v[9]);
#pragma unroll
                for (int o = 4; o < 32; o <<= 1) {
                    m0 = fmaxf(m0, __shfl_xor_sync(0xffffffff, m0, o));
                    m1 = fmaxf(m1, __shfl_xor_sync(0xffffffff, m1, o));
                }
                const float sl = scale * l2e;
                m0 *= sl; m1 *= sl;
#pragma unroll
                for (int j = 0; j < 5; j++)
                    sts32(pa + j * 128, pack_bf16(ex2f(fmaf(v[2 * j], sl, -m0)), ex2f(fmaf(v[2 * j + 1], sl, -m1))));
                bar_arrive<3, 160>();
                DBG(6);
            }
            fence_async_smem();
            bar_arrive<6, 256>();
        }
        bar_sync<1, 384>();
        fence_async_smem();
        bar_arrive<6, 256>();
        bar_arrive<4, 384>();
    } else if (wg == 1) {
        c2_load_w(w, &P.mapW[1], 1, rank, col0, t128, ws, sb);
#pragma unroll 1
        for (int s = -1;;) {
            if (s > 0) {
                mbar_wait(bar_sx + 8 * ((s - 1) & 1), ((s - 1) >> 1) & 1);
                const uint32_t a = sb + C2_SX + ((s - 1) & 1) * 10240 + w4 * 1280 + lane * 8;
                float v[10];
                const int lim = 8 * w4 + g - 2 * qc;
#pragma unroll
                for (int j = 0; j < 5; j++) {
                    float2 x, y;
                    asm volatile("ld.shared.v2.f32 {%0, %1}, [%2];" : "=f"(x.x), "=f"(x.y) : "r"(a + j * 256) : "memory");
                    asm volatile("ld.shared.v2.f32 {%0, %1}, [%2];" : "=f"(y.x), "=f"(y.y) : "r"(a + 5120 + j * 256) : "memory");
                    v[2 * j] = (j < 4 && 8 * j > lim) ? -INFINITY : x.x + y.x;
                    v[2 * j + 1] = (j < 4 && 8 * j + 1 > lim) ? -INFINITY : x.y + y.y;
                }
                float mx = fmaxf(fmaxf(fmaxf(v[0], v[1]), fmaxf(v[2], v[3])), fmaxf(fmaxf(v[4], v[5]), fmaxf(v[6], v[7])));
                mx = fmaxf(mx, fmaxf(v[8], v[9]));
                mx = fmaxf(mx, __shfl_xor_sync(0xffffffff, mx, 1));
                mx = fmaxf(mx, __shfl_xor_sync(0xffffffff, mx, 2));
                const float sl = scale * l2e;
                mx *= sl;
#pragma unroll
                for (int j = 0; j < 10; j++) v[j] = ex2f(fmaf(v[j], sl, -mx));
                float sm = ((v[0] + v[1]) + (v[2] + v[3])) + ((v[4] + v[5]) + (v[6] + v[7])) + (v[8] + v[9]);
                sm += __shfl_xor_sync(0xffffffff, sm, 1);
                sm += __shfl_xor_sync(0xffffffff, sm, 2);
                float inv;
                asm("rcp.approx.ftz.f32 %0, %1;" : "=f"(inv) : "f"(sm));
                const uint32_t pa = sb + C2_PX + w4 * 256 + g * 32 + ((g >> 2) << 4) + qc * 4;
#pragma unroll
                for (int j = 0; j < 5; j++) sts32((pa ^ ((j & 1) << 4)) + (j >> 1) * 1024, pack_bf16(v[2 * j] * inv, v[2 * j + 1] * inv));
            }
            if (s >= 0) {
                fence_async_smem();
                if (s < NSEG) bar_sync<6, 256>(); else bar_sync<7, 128>();
                DBGW(20, 0);
                if (s < NSEG - 1) mbar_wait(bar_o, s & 1);
                if (s < NSEG) {
                    float sx[20];
#pragma unroll
                    for (int i = 0; i < 20; i++) sx[i] = 0.f;
                    wgmma_fence();
#pragma unroll
                    for (int kk = 0; kk < 4; kk++) wgmma_ss<DHI128, DHI128>(sx, dlo + (C2_QX >> 4) + kk * 2, dlo + (C2_KX >> 4) + kk * 2);
                    wgmma_commit();
                    wgmma_wait<0>();
                    if (s < NSEG - 1) bar_arrive<5, 256>();
                    if (w4 < 2) {
                        const uint32_t a = sb + C2_SX + (s & 1) * 10240 + w4 * 2560 + lane * 8;
#pragma unroll
                        for (int j = 0; j < 5; j++) {
                            asm volatile("st.shared.v2.f32 [%0], {%1, %2};" :: "r"(a + j * 256), "f"(sx[4 * j]), "f"(sx[4 * j + 1]) : "memory");
                            asm volatile("st.shared.v2.f32 [%0], {%1, %2};" :: "r"(a + 1280 + j * 256), "f"(sx[4 * j + 2]), "f"(sx[4 * j + 3]) : "memory");
                        }
                    }
                }
                DBGW(21, 0);
                if (s > 0) {
                    float cx[16];
#pragma unroll
                    for (int i = 0; i < 16; i++) cx[i] = 0.f;
                    wgmma_fence();
#pragma unroll
                    for (int kk = 0; kk < 3; kk++)
                        wgmma_ss<DHI32, DHI32>(cx, dlo + ((C2_VT + ((s - 1) & 1) * 6144 + kk * 2048) >> 4), dlo + ((C2_PX + kk * 1024) >> 4));
                    wgmma_commit();
                    wgmma_wait<0>();
                    uint32_t* dst = reinterpret_cast<uint32_t*>(g_ctxB + ((size_t)h * SEQ + (s - 1) * SEGL + 2 * qc) * HD + (rank & 1) * 64 + w4 * 16 + 2 * g);
#pragma unroll
                    for (int j = 0; j < 4; j++) {
                        dst[j * 8 * (HD / 2)] = pack_bf16(cx[4 * j], cx[4 * j + 2]);
                        dst[(j * 8 + 1) * (HD / 2)] = pack_bf16(cx[4 * j + 1], cx[4 * j + 3]);
                    }
                }
                DBGW(22, 0);
                if (s == NSEG) break;
                fence_async_smem();
            }
            if (s < NSEG - 1) mbar_wait(bar_x + 8 * ((s + 1) & 1), ((s + 1) >> 1) & 1);
            if (s >= 0) bar_sync<4, 384>();
            s++;
            if (s < NSEG) {
                {
                    float acc[16];
                    c2_xstream(acc, w, dlo + ((C2_XB + (s & 1) * C2_XS) >> 4), rank, dlo + ((C2_WS + C2_NS * 2048) >> 4));
                    store_x(acc, sb + C2_KX);
                }
                DBGW(16, 0);
                const uint32_t kst = pin(sb + C2_KX + 4096 + t128);
                float a[4][4];
                proj_mem(a, s);
                sts32(kst, pack_bf16(a[0][0], a[0][2]));
                sts32((kst ^ 16) + 128, pack_bf16(a[0][1], a[0][3]));
                bar_arrive<1, 384>();
                DBGW(19, 0);
                if (w4 == 0) {
                    if (s < NSEG - 1) {
                        if (lane == 0) mbar_expect_tx(bar_sc, 2560);
                        if (lane < 16 && (lane & 7) >= 1 && (lane & 7) < 5) mbar_expect_tx(bar_m + 8 * lane, (lane & 7) == 1 ? 1024 : 2048);
                        if (lane == 8) {
                            mbar_expect_tx(bar_x + 8 * ((s + 1) & 1), 32768);
                            tma_load_2d_mc(sb + C2_XB + ((s + 1) & 1) * C2_XS + rank * 5120, &mapX, bar_x + 8 * ((s + 1) & 1), rank * 64, (s + 1) * SEGL, (uint16_t)0xff);
                            if (s + 2 < NSEG)
                                asm volatile("cp.async.bulk.prefetch.tensor.2d.L2.global [%0, {%1, %2}];" :: "l"((uint64_t)&mapX), "r"(rank * 64), "r"((s + 2) * SEGL) : "memory");
                        }
                    }
                    if (lane == 16) mbar_expect_tx(bar_sx + 8 * (s & 1), 5120);
                    __syncwarp();
                }
            }
        }
        bar_sync<7, 128>();
        if (tid == 128) signal_ctr(CT_CB);
    } else {
        c2_load_w(w, &P.mapW[2], 2, rank, col0, t128, ws, sb);
#pragma unroll 1
        for (int s = -1;;) {
            if (s >= 0) {
                const int t = tid - 256;
                const uint2* src = g_xbuf + ((s & 1) * 8 + rank) * 1024 + t;
                asm volatile("" : "+l"(src));
                const uint32_t ma = sb + C2_XB + ((s + 1) & 1) * C2_XS + rank * 5120 + 4096 + (t >> 4) * 128 + ((((t >> 1) & 7) ^ (t >> 4)) << 4) + (t & 1) * 8;
                uint32_t ra[8], rb[8];
#pragma unroll
                for (int i = 1; i < 8; i++) {
                    const uint32_t d = (rank + i) & 7;
                    ra[i] = pin(mapa_u32(ma, d)); rb[i] = pin(mapa_u32(bar_m + 8 * c2_grp(i), d));
                }
                bar_sync<4, 384>();
                DBGW(29, 0);
                if (tid == 256) {
                    const uint32_t a = sb + C2_SX + (s & 1) * 10240;
                    bulk_s2s(mapa_u32(a + 5120, rank ^ 1), a, 5120, mapa_u32(bar_sx + 8 * (s & 1), rank ^ 1));
                }
                if (s == NSEG - 1) break;
                pace(CH_POLL_DELAY);
                const uint32_t tag = ((s >> 1) & 1) ^ 1;
                uint32_t p[8][2];
                for (int it = 0; it < (1 << 20); it++) {
#pragma unroll
                    for (int k = 0; k < 8; k++)
                        asm volatile("ld.relaxed.gpu.global.v2.u32 {%0, %1}, [%2];" : "=r"(p[k][0]), "=r"(p[k][1]) : "l"(src + k * 128) : "memory");
                    uint32_t bad[8];
#pragma unroll
                    for (int k = 0; k < 8; k++) asm("lop3.b32 %0, %1, %2, %3, 0x7e;" : "=r"(bad[k]) : "r"(p[k][0]), "r"(p[k][1]), "r"(tag));
                    asm("lop3.b32 %0, %0, %1, %2, 0xfe;" : "+r"(bad[0]) : "r"(bad[1]), "r"(bad[2]));
                    asm("lop3.b32 %0, %0, %1, %2, 0xfe;" : "+r"(bad[3]) : "r"(bad[4]), "r"(bad[5]));
                    asm("lop3.b32 %0, %0, %1, %2, 0xfe;" : "+r"(bad[0]) : "r"(bad[3]), "r"(bad[6]));
                    asm("lop3.b32 %0, %0, %1, 1, 0xa8;" : "+r"(bad[0]) : "r"(bad[7]));
                    if (__all_sync(0xffffffff, bad[0] == 0u)) break;
                }
                DBGW(30, 0);
                float r[4];
#pragma unroll
                for (int e = 0; e < 2; e++) {
                    float lo[8], hi[8];
#pragma unroll
                    for (int k = 0; k < 8; k++) { lo[k] = __uint_as_float(p[k][e] << 16); hi[k] = __uint_as_float(p[k][e] & 0xffff0000u); }
                    r[2 * e] = ((lo[0] + lo[1]) + (lo[2] + lo[3])) + ((lo[4] + lo[5]) + (lo[6] + lo[7]));
                    r[2 * e + 1] = ((hi[0] + hi[1]) + (hi[2] + hi[3])) + ((hi[4] + hi[5]) + (hi[6] + hi[7]));
                }
                const uint32_t m0 = pack_bf16(r[0], r[1]), m1 = pack_bf16(r[2], r[3]);
                st_async_v2(ra[1], m0, m1, rb[1]);
                asm volatile("st.shared.v2.b32 [%0], {%1, %2};" :: "r"(ma), "r"(m0), "r"(m1) : "memory");
                __syncwarp();
                if (lane == 0) mbar_arrive(bar_m);
#pragma unroll
                for (int i = 2; i < 8; i++) st_async_v2(ra[i], m0, m1, rb[i]);
                DBGW(31, 0);
            }
            s++;
            const uint32_t ost = pin(sb + C2_OB + t32), pla = pin(sb + C2_PB + lane * 16), plb = pin(sb + C2_PB + 512 + (lane & 7) * 16);
            bar_sync<1, 384>();
            fence_async_smem();
            DBGW(24, 0);
            if (s < NSEG - 1) bar_sync<2, 224>();
            uint32_t va[5][2];
            {
                float acc[20];
                c2_xstream(acc, w, dlo + ((C2_XB + (s & 1) * C2_XS) >> 4), rank, dlo + ((C2_WS + 2 * C2_NS * 2048) >> 4));
#pragma unroll
                for (int j = 0; j < 5; j++) { va[j][0] = pack_bf16(acc[4 * j], acc[4 * j + 1]); va[j][1] = pack_bf16(acc[4 * j + 2], acc[4 * j + 3]); }
            }
            DBGW(26, 0);
            if (s < NSEG - 1) {
                uint32_t p[5];
                bar_sync<3, 160>();
                DBGW(27, 0);
                ldmatrix_x4_trans(p[0], p[1], p[2], p[3], pla);
                asm volatile("ldmatrix.sync.aligned.m8n8.x1.trans.shared.b16 {%0}, [%1];" : "=r"(p[4]) : "r"(plb) : "memory");
                float oa[4] = {0.f, 0.f, 0.f, 0.f}, ob[4] = {0.f, 0.f, 0.f, 0.f}, sa[4] = {0.f, 0.f, 0.f, 0.f}, sc[4] = {0.f, 0.f, 0.f, 0.f};
                const uint32_t one = 0x3f803f80u;
                mma_16816(sa, one, one, one, one, p[0], p[1]);
                mma_16816(oa, va[0][0], va[0][1], va[1][0], va[1][1], p[0], p[1]);
                mma_16816(sc, one, one, one, one, p[2], p[3]);
                mma_16816(ob, va[2][0], va[2][1], va[3][0], va[3][1], p[2], p[3]);
                mma_16816(sa, one, one, one, one, p[4], 0u);
                mma_16816(oa, va[4][0], va[4][1], 0u, 0u, p[4], 0u);
                float i0, i1;
                asm("rcp.approx.ftz.f32 %0, %1;" : "=f"(i0) : "f"(sa[0] + sc[0]));
                asm("rcp.approx.ftz.f32 %0, %1;" : "=f"(i1) : "f"(sa[1] + sc[1]));
                sts32(ost, pack_bf16((oa[0] + ob[0]) * i0, (oa[2] + ob[2]) * i0));
                sts32(ost + 32, pack_bf16((oa[1] + ob[1]) * i1, (oa[3] + ob[3]) * i1));
                fence_async_smem();
                __syncwarp();
                if (elect_one()) {
#pragma unroll
                    for (int i = 1; i < 8; i++) {
                        const uint32_t d = (rank + i) & 7;
                        bulk_s2s(mapa_u32(sb + C2_OB + i * 1024 + w4 * 256, d), sb + C2_OB + w4 * 256, 256, mapa_u32(bar_o + 8 * c2_grp(i), d));
                        if (i == 1) mbar_arrive(bar_o);
                    }
                }
                __syncwarp();
                DBGW(28, 0);
            }
            {
                const uint32_t a = sb + C2_VT + (s & 1) * 6144 + a32;
                stmatrix_x4(a, va[0][0], va[0][1], va[1][0], va[1][1]);
                stmatrix_x4(a + 2048, va[2][0], va[2][1], va[3][0], va[3][1]);
                asm volatile("stmatrix.sync.aligned.m8n8.x2.shared.b16 [%0], {%1, %2};" :: "r"(a + 4096), "r"(va[4][0]), "r"(va[4][1]) : "memory");
            }
            fence_async_smem();
        }
        g_xbuf[((8 + rank) * 8 + C) * 128 + (tid - 256)] = make_uint2(0u, 0u);
    }
    cluster_sync_relaxed();
    TS_END(2);
}

struct Proj2Params {
    CUtensorMap mapA[2];
    CUtensorMap mapW[3];
    bf16* out[3];
};
#define P2T(i)
#define P2_NOMMA 0
#define P2_NOLOAD 0
constexpr int P2_STAGES = 6;
constexpr int P2_SMEM = 131072 + P2_STAGES * 16384 + 1024 + 1024;
constexpr int P2_ITEMS = 168 + 48;
__device__ __forceinline__ int p2_reps(int t) { return t >= 168 ? 1 : 2; }
__device__ __forceinline__ void p2_tile(int t, int w, int& z, int& mp, int& head) {
    if (t >= 168) { w += ((t - 168) & 1) * 2; t = 168 + ((t - 168) >> 1); }
    const int hq = t / 24, v = t % 24;
    mp = v & 7;
    if (v < 16) { head = hq * 4 + (v >> 3) * 2 + (w >> 1); z = 1 + (w & 1); }
    else { head = hq * 4 + w; z = 0; }
}
__device__ __forceinline__ void mbar_arrive_remote(uint32_t bar_cluster_addr) {
    asm volatile("mbarrier.arrive.release.cluster.shared::cluster.b64 _, [%0];" :: "r"(bar_cluster_addr) : "memory");
}
__device__ __forceinline__ void mbar_arrive_cl(uint32_t bar_cluster_addr) {
    asm volatile("mbarrier.arrive.shared::cluster.b64 _, [%0];" :: "r"(bar_cluster_addr) : "memory");
}
__device__ __forceinline__ void mbar_wait_acq_cluster(uint32_t bar, uint32_t parity) {
    asm volatile(
        "{\n"
        ".reg .pred p, q;\n"
        ".reg .u32 c;\n"
        "mov.u32 c, 0;\n"
        "WAIT_LOOP_C:\n"
        "mbarrier.try_wait.parity.acquire.cluster.shared::cta.b64 p, [%0], %1;\n"
        "@p bra WAIT_DONE_C;\n"
        "add.u32 c, c, 1;\n"
        "setp.lt.u32 q, c, 4000000;\n"
        "@q bra WAIT_LOOP_C;\n"
        "WAIT_DONE_C:\n"
        "}\n" :: "r"(bar), "r"(parity) : "memory");
}
__device__ __forceinline__ uint4 quad_transpose(uint32_t p0, uint32_t p1, uint32_t p2, uint32_t p3, int lane) {
    const bool o1 = lane & 1, o2 = lane & 2;
    uint32_t s0 = o1 ? p0 : p1, s1 = o1 ? p2 : p3;
    s0 = __shfl_xor_sync(0xffffffff, s0, 1); s1 = __shfl_xor_sync(0xffffffff, s1, 1);
    const uint32_t a_lo = o1 ? s0 : p0, a_hi = o1 ? p1 : s0, b_lo = o1 ? s1 : p2, b_hi = o1 ? p3 : s1;
    uint32_t t0 = o2 ? a_lo : b_lo, t1 = o2 ? a_hi : b_hi;
    t0 = __shfl_xor_sync(0xffffffff, t0, 2); t1 = __shfl_xor_sync(0xffffffff, t1, 2);
    return o2 ? make_uint4(t0, t1, b_lo, b_hi) : make_uint4(a_lo, a_hi, t0, t1);
}
#define P2_PACE 35
#define P2_PACE2 0
template <bool PERM, int PACE = 0>
__device__ __forceinline__ void store_frag_128(const float (&acc)[64], bf16* obase, int lane) {
#pragma unroll
    for (int rr = 0; rr < 2; rr++)
#pragma unroll
        for (int g = 0; g < 4; g++) {
            const float* a = &acc[g * 16 + rr * 2];
            const uint32_t p0 = pack_bf16(a[0], a[1]), p1 = pack_bf16(a[4], a[5]), p2 = pack_bf16(a[8], a[9]), p3 = pack_bf16(a[12], a[13]);
            *reinterpret_cast<uint4*>(obase + (size_t)(rr * 8) * HD + g * 32) = PERM ? make_uint4(p0, p1, p2, p3) : quad_transpose(p0, p1, p2, p3, lane);
            pace(PACE);
        }
}
__global__ void __cluster_dims__(2, 1, 1) __launch_bounds__(384, 1) proj2_kernel(const __grid_constant__ Proj2Params P) {
    extern __shared__ uint8_t smem_raw[];
    const uint32_t sbase = (smem_u32(smem_raw) + 1023) & ~1023u;
    const uint32_t sA = sbase, sB = sbase + 131072, sC = sB + P2_STAGES * 16384;
    const uint32_t bars = sC;
    const uint32_t a_full = bars, a_empty = bars + 64, b_full = bars + 128, b_empty = b_full + 8 * P2_STAGES;
    const uint32_t item_bar = b_empty + 8 * P2_STAGES, item_in = item_bar + 16, slot = item_in + 16;
    const uint32_t note_bar = slot + 16, note_free = note_bar + 64, note = note_free + 64;
    const int warp = threadIdx.x >> 5, lane = threadIdx.x & 31;
    const uint32_t rank = cluster_ctarank();
    TS_BEGIN(0);
    if (threadIdx.x == 0) {
        for (int i = 0; i < 8; i++) { mbar_init(a_full + 8 * i, 1); mbar_init(a_empty + 8 * i, 2); }
        for (int i = 0; i < P2_STAGES; i++) { mbar_init(b_full + 8 * i, 1); mbar_init(b_empty + 8 * i, 2); }
        mbar_init(item_bar, 1); mbar_init(item_bar + 8, 1); mbar_init(item_in, 2); mbar_init(item_in + 8, 2);
        for (int i = 0; i < 8; i++) { mbar_init(note_bar + 8 * i, 1); mbar_init(note_free + 8 * i, 1); }
        asm volatile("fence.mbarrier_init.release.cluster;" ::: "memory");
    }
    __syncwarp();
    cluster_sync_relaxed();
    pdl_launch_dependents();
    if (warp == 9) {
        if (lane == 0) {
            for (int n = 0;; n++) {
                const int e = (n & 1) * 4 + ((n >> 1) & 3);
                mbar_wait(note_bar + 8 * e, (n >> 3) & 1);
                int m;
                asm volatile("ld.shared.s32 %0, [%1];" : "=r"(m) : "r"(note + e * 4) : "memory");
                mbar_arrive(note_free + 8 * e);
                if (m < 0) break;
                signal_ctr(m);
            }
        }
    } else if (warp == 10) {
        if (lane == 0) {
            auto publish = [&](int ic, int tq) {
                const int t = tq < P2_ITEMS ? tq : -1;
                asm volatile("st.shared.s32 [%0], %1;" :: "r"(slot + (ic & 3) * 4), "r"(t) : "memory");
                mbar_arrive(item_bar + 8 * (ic & 1));
                st_async_b32(mapa_u32(slot + (ic & 3) * 4, 1), (uint32_t)t, mapa_u32(item_bar + 8 * (ic & 1), 1));
            };
            const int npair = (int)(gridDim.x >> 1), pair = (int)(blockIdx.x >> 1);
            if (rank == 0) publish(0, pair);
            for (int ic = 0;; ic++) {
                if (rank == 1) mbar_expect_tx(item_bar + 8 * (ic & 1), 4);
                mbar_wait(item_bar + 8 * (ic & 1), (ic >> 1) & 1);
                int t;
                asm volatile("ld.shared.s32 %0, [%1];" : "=r"(t) : "r"(slot + (ic & 3) * 4) : "memory");
                if (t < 0) break;
                int z0, mp, h0;
                p2_tile(t, 0, z0, mp, h0);
                const int aidx = z0 >= 1 ? 1 : 0;
                const int m0 = (2 * mp + (int)rank) * 128;
                for (int k = 0; k < 8; k++) {
                    mbar_wait(a_empty + 8 * k, (ic & 1) ^ 1);
                    if (P2_NOLOAD) mbar_arrive(a_full + 8 * k); else {
                    mbar_expect_tx(a_full + 8 * k, 16384);
                    tma_load_2d(sA + k * 16384, &P.mapA[aidx], a_full + 8 * k, k * 64, m0); }
                }
                if (rank == 0) {
                    mbar_wait(item_in + 8 * (ic & 1), (ic >> 1) & 1);
                    publish(ic + 1, ic == 0 ? npair + pair : 2 * npair + (int)atomicAdd(&g_ctr[CT_PROJ], 1u));
                }
            }
        }
    } else if (warp == 8 || warp == 11) {
        if (lane == 0) {
            const int par2 = warp == 8 ? 0 : 1;
            int it = 0; uint32_t bph = 0;
            for (int ic = 0;; ic++) {
                mbar_wait(item_bar + 8 * (ic & 1), (ic >> 1) & 1);
                int t;
                asm volatile("ld.shared.s32 %0, [%1];" : "=r"(t) : "r"(slot + (ic & 3) * 4) : "memory");
                if (t < 0) break;
                const int nt = 2 * p2_reps(t);
                for (int w = 0; w < nt; w++) {
                    int z, mp, hd;
                    p2_tile(t, w, z, mp, hd);
                    for (int k = 0; k < 8; k++) {
                        const int s = it; const uint32_t phb = bph;
                        if (++it == P2_STAGES) { it = 0; bph ^= 1; }
                        if ((k & 1) != par2) continue;
                        mbar_wait(b_empty + 8 * s, phb ^ 1);
                        if (P2_NOLOAD) { mbar_arrive(b_full + 8 * s); continue; }
                        mbar_expect_tx(b_full + 8 * s, 16384);
                        tma_load_2d_mc(sB + s * 16384 + rank * 8192, &P.mapW[z], b_full + 8 * s, hd * 128 + (int)rank * 64, k * 64, (uint16_t)3);
                    }
                }
            }
        }
    } else {
        const int wg = warp >> 2;
        float acc[2][64];
        const uint32_t a_lo = desc_lo(sA, 16), b_lo0 = desc_lo(sB, 8192);
        const bool elected = (threadIdx.x & 127) == 0;
        int s = (wg * 8) % P2_STAGES;
        uint32_t ph = ((wg * 8) / P2_STAGES) & 1;
        int nnote = 0;
        if (wg == 1) asm volatile("bar.arrive 3, 256;" ::: "memory");
        for (int ic = 0;; ic++) {
            mbar_wait(item_bar + 8 * (ic & 1), (ic >> 1) & 1);
            int t;
            asm volatile("ld.shared.s32 %0, [%1];" : "=r"(t) : "r"(slot + (ic & 3) * 4) : "memory");
            P2T(7);
            if (wg == 0 && t < 0) {
                if (elected) {
                    const int e = nnote & 3;
                    mbar_wait(note_free + 8 * e, ((nnote >> 2) & 1) ^ 1);
                    asm volatile("st.shared.s32 [%0], %1;" :: "r"(note + e * 4), "r"(-1) : "memory");
                    mbar_arrive(note_bar + 8 * e);
                }
            }
            if (t < 0) break;
            const int reps = p2_reps(t);
#pragma unroll 1
            for (int rp = 0; rp < reps; rp++) {
            const bool first = rp == 0, last = rp == reps - 1;
            int z, mp, head;
            p2_tile(t, rp * 2 + wg, z, mp, head);
            asm volatile("bar.sync %0, 256;" :: "r"(3 + wg) : "memory");
            P2T(0);
            if (wg == 1 && last && elected) mbar_arrive_cl(mapa_u32(item_in + 8 * (ic & 1), 0));
            int sprev = 0;
#pragma unroll
            for (int k = 0; k < 8; k++) {
                if (k == 0) P2T(5);
                if (wg == 0 && first) mbar_wait(a_full + 8 * k, ic & 1);
                if (k == 0) P2T(6);
                mbar_wait(b_full + 8 * s, ph);
                if (k == 7) asm volatile("bar.arrive %0, 256;" :: "r"(4 - wg) : "memory");
                if (k == 0) P2T(1);
                if (k == 7) P2T(2);
                const uint32_t b_lo = b_lo0 + s * 1024;
                wgmma_fence();
#pragma unroll
                for (int kk = 0; kk < (P2_NOMMA ? 1 : 4); kk++) {
                    wgmma_ss_n128_lo<1>(acc[0], a_lo + k * 1024 + kk * 2, b_lo + kk * 128, (k | kk) != 0);
                    wgmma_ss_n128_lo<1>(acc[1], a_lo + k * 1024 + 512 + kk * 2, b_lo + kk * 128, (k | kk) != 0);
                }
                wgmma_commit();
                if (k > 0) {
                    wgmma_wait<1>();
                    if (elected) {
                        const uint32_t e = b_empty + 8 * sprev;
                        mbar_arrive_cl(mapa_u32(e, 0)); mbar_arrive_cl(mapa_u32(e, 1));
                        if (last) mbar_arrive(a_empty + 8 * (k - 1));
                    }
                }
                sprev = s;
                if (++s == P2_STAGES) { s = 0; ph ^= 1; }
            }
            wgmma_wait<0>();
            P2T(3);
            if (elected) {
                const uint32_t e = b_empty + 8 * sprev;
                mbar_arrive_cl(mapa_u32(e, 0)); mbar_arrive_cl(mapa_u32(e, 1));
                if (last) mbar_arrive(a_empty + 8 * 7);
            }
            s += 8 % P2_STAGES; ph ^= (8 / P2_STAGES) & 1;
            if (s >= P2_STAGES) { s -= P2_STAGES; ph ^= 1; }
            const int m0 = (2 * mp + (int)rank) * 128;
            bf16* obase = P.out[z] + ((size_t)head * SEQ + m0 + (warp & 3) * 16 + (lane >> 2)) * HD + (lane & 3) * 8;
            store_frag_128<true, P2_PACE>(acc[0], obase, lane); store_frag_128<true, P2_PACE>(acc[1], obase + (size_t)64 * HD, lane);
            P2T(4);
            {
                asm volatile("bar.sync %0, 128;" :: "r"(1 + wg) : "memory");
                if (elected) {
                    const int e = wg * 4 + (nnote & 3);
                    mbar_wait(note_free + 8 * e, ((nnote >> 2) & 1) ^ 1);
                    asm volatile("st.shared.s32 [%0], %1;" :: "r"(note + e * 4), "r"(CT_AP + (head >> 1)) : "memory");
                    mbar_arrive(note_bar + 8 * e);
                }
                nnote++;
            }
            }
        }
        TS_END(0);
    }
    __syncwarp();
    cluster_sync_relaxed();
}

struct OutParams {
    CUtensorMap mapCtx[2];
    CUtensorMap mapWo[2];
    CUtensorMap mapOut;
};
__device__ uint4 g_part[4 * 32 * 8 * 16 * 32];

#define OT(i)
#define OTP(i)
#define O3_LK 42
#define O3_D 5
constexpr int O3_E = 68, O3_GRID = O3_E + 64;
constexpr int O2_SMEM = 196608 + 1024 + 256;

__global__ void __cluster_dims__(2, 1, 1) __launch_bounds__(352, 1) out3_kernel(const __grid_constant__ OutParams P) {
    extern __shared__ uint8_t smem_raw[];
    const uint32_t sbase = (smem_u32(smem_raw) + 1023) & ~1023u;
    const uint32_t bar_full = sbase + 196608, bar_empty = bar_full + 64;
    const int warp = threadIdx.x >> 5, lane = threadIdx.x & 31;
    const uint32_t rank = cluster_ctarank();
    const int pair = blockIdx.x >> 1;
    const bool early = pair < O3_E / 2;
    constexpr int EB = 64 - O3_LK;
    int mt, part, a0, na, b0, nb;
    if (pair < 30) {
        part = pair >= 15; mt = part ? 29 - pair : pair;
        const int d = (14 - mt) * O3_D / 14;
        a0 = part ? 32 + d : 0; na = part ? 32 - d : 32 + d;
        b0 = part ? EB / 2 : 0; nb = part ? EB - EB / 2 : EB / 2;
    } else if (early) {
        part = pair - 30; mt = 15;
        a0 = part * 16; na = 16;
        b0 = part * EB / 4; nb = (part + 1) * EB / 4 - b0;
    } else {
        part = (pair - O3_E / 2) & 1; mt = (pair - O3_E / 2) >> 1;
        a0 = 0; na = 0; b0 = EB; nb = O3_LK;
    }
    const int m0 = mt * 128, nk = na + nb;
    const int n0 = early ? (int)rank * 256 : part * 256 + (int)rank * 128;
    const int nst = early ? 4 : 6;
    const uint32_t ssz = early ? 49152 : 32768;
    TS_BEGIN(4);
    OT(0);
    if (threadIdx.x == 0) {
        for (int i = 0; i < 6; i++) { mbar_init(bar_full + 8 * i, 1); mbar_init(bar_empty + 8 * i, 4); }
        asm volatile("fence.mbarrier_init.release.cluster;" ::: "memory");
    }
    if (threadIdx.x == 256) asm volatile("prefetch.tensormap [%0];" :: "l"((uint64_t)&P.mapCtx[early ? 0 : 1]) : "memory");
    if (threadIdx.x == 288) asm volatile("prefetch.tensormap [%0];" :: "l"((uint64_t)&P.mapWo[early ? 0 : 1]) : "memory");
    if (warp == 0 || warp > 8) asm volatile("bar.sync 1, 96;" ::: "memory");
    __syncwarp();
    asm volatile("barrier.cluster.arrive.relaxed.aligned;" ::: "memory");
    if (warp > 8) {
        if (lane == 0) {
            int s = 0; uint32_t ph = 0;
            for (int i = 0; i < nk; i++) {
                if (i >= nst) mbar_wait(bar_empty + 8 * s, ph ^ 1);
                const uint32_t sa = sbase + s * ssz + 16384;
                const int b = i >= na, k = b ? b0 + i - na : a0 + i;
                if (early) {
                    tma_load_2d(sa + (warp - 9) * 16384, &P.mapWo[b], bar_full + 8 * s, n0 + (warp - 9) * 128, k * 64);
                    tma_load_2d(sa + (warp - 9) * 16384 + 8192, &P.mapWo[b], bar_full + 8 * s, n0 + (warp - 9) * 128 + 64, k * 64);
                } else tma_load_2d(sa + (warp - 9) * 8192, &P.mapWo[1], bar_full + 8 * s, n0 + (warp - 9) * 64, k * 64);
                if (++s == nst) { s = 0; ph ^= 1; }
            }
        }
        __syncwarp();
        asm volatile("barrier.cluster.wait.acquire.aligned;" ::: "memory");
    } else if (warp == 8) {
        if (lane == 0) {
            if (early) wait_ctr(CT_CA + mt * 2, 2u * O2_HE); else wait_ctr(mt == 15 ? CT_CB : CT_CB + 1, 64u);
            OTP(3);
        }
        __syncwarp();
        asm volatile("barrier.cluster.wait.acquire.aligned;" ::: "memory");
        if (lane == 0) {
            OTP(7);
            int s = 0; uint32_t ph = 0;
            bool late_a = false;
            for (int i = 0; i < nk; i++) {
                const int b = i >= na, k = b ? b0 + i - na : a0 + i;
                if (!b && k >= 2 * O2_HE && !late_a) { wait_ctr(CT_CA + mt * 2 + 1, 2u * (NH - O2_HE)); late_a = true; }
                if (i == na && early) wait_ctr(mt == 15 ? CT_CB : CT_CB + 1, 64u);
                if (i >= nst) mbar_wait(bar_empty + 8 * s, ph ^ 1);
                mbar_expect_tx(bar_full + 8 * s, ssz);
                tma_load_2d_mc(sbase + s * ssz + rank * 8192, &P.mapCtx[b], bar_full + 8 * s, (k & 1) * 64, (k >> 1) * SEQ + m0 + (int)rank * 64, (uint16_t)3);
                if (++s == nst) { s = 0; ph ^= 1; }
            }
        }
    } else {
        asm volatile("barrier.cluster.wait.acquire.aligned;" ::: "memory");
        const int wg = warp >> 2;
        const bool elected = (threadIdx.x & 127) == 0;
        const int row = (warp & 3) * 16 + (lane >> 2);
        const int mrow = (warp & 3) * 16 + (lane & 15);
        const uint32_t moff = mrow * 128, mx = (lane >> 4) ^ (mrow & 7);
        float g0, g1;
        int s = 0, sprev = 0; uint32_t ph = 0;
        {
            unsigned int v; int it = 0;
            do { asm volatile("ld.acquire.gpu.global.u32 %0, [%1];" : "=r"(v) : "l"(&g_ctr[CT_G]) : "memory"); } while (v < FA_GRID && ++it < (1 << 22));
        }
        asm volatile("ld.relaxed.gpu.global.f32 %0, [%1];" : "=f"(g0) : "l"(g_gate + m0 + wg * 64 + row) : "memory");
        asm volatile("ld.relaxed.gpu.global.f32 %0, [%1];" : "=f"(g1) : "l"(g_gate + m0 + wg * 64 + row + 8) : "memory");
        auto release = [&](int st) {
            if (elected) { const uint32_t e = bar_empty + 8 * st; mbar_arrive_cl(mapa_u32(e, 0)); mbar_arrive_cl(mapa_u32(e, 1)); }
        };
        if (early) {
            float acc[128];
#pragma unroll 1
            for (int i = 0; i < nk; i++) {
                mbar_wait(bar_full + 8 * s, ph);
                if (i == 8) OT(2);
                if (i == na) {
                    wgmma_wait<0>();
                    const float r0 = g0 / fmaxf(1.f - g0, 0x1p-40f), r1 = g1 / fmaxf(1.f - g1, 0x1p-40f);
#pragma unroll
                    for (int j = 0; j < 32; j++) { acc[4 * j] *= r0; acc[4 * j + 1] *= r0; acc[4 * j + 2] *= r1; acc[4 * j + 3] *= r1; }
                }
                const uint32_t sa = sbase + s * 49152 + wg * 8192, sb = sbase + s * 49152 + 16384;
                wgmma_fence();
#pragma unroll
                for (int kk = 0; kk < 4; kk++)
                    wgmma_ss_n256_tb(acc, make_desc(sa + kk * 32, 16, 1024), make_desc(sb + kk * 2048, 8192, 1024), (i | kk) != 0);
                wgmma_commit();
                if (i > 0) { wgmma_wait<1>(); release(sprev); }
                sprev = s;
                if (++s == 4) { s = 0; ph ^= 1; }
            }
            wgmma_wait<0>();
            OT(4);
            const float w0 = fmaxf(1.f - g0, 0x1p-40f), w1 = fmaxf(1.f - g1, 0x1p-40f);
            uint4* dst = g_part + (((part * 32 + mt * 2 + (int)rank) * 8 + warp) * 16) * 32 + lane;
#pragma unroll
            for (int j = 0; j < 16; j++) {
                const float* a = &acc[8 * j];
                dst[j * 32] = make_uint4(pack_bf16(a[0] * w0, a[1] * w0), pack_bf16(a[2] * w1, a[3] * w1), pack_bf16(a[4] * w0, a[5] * w0), pack_bf16(a[6] * w1, a[7] * w1));
            }
            __syncwarp();
            OT(5);
            if (lane == 0) signal_ctr_generic(CT_OP + (mt * 2 + (int)rank) * 8 + warp);
            OT(6);
        } else {
            float acc[64];
            const uint32_t a_lo = desc_lo(sbase + wg * 8192, 16), b_lo = desc_lo(sbase + 16384, 8192);
#pragma unroll 1
            for (int i = 0; i < nk; i++) {
                mbar_wait(bar_full + 8 * s, ph);
                if (i == 8) OT(2);
                wgmma_fence();
#pragma unroll
                for (int kk = 0; kk < 4; kk++) wgmma_ss_n128_lo<1>(acc, a_lo + s * 2048 + kk * 2, b_lo + s * 2048 + kk * 128, (i | kk) != 0);
                wgmma_commit();
                if (i > 0) { wgmma_wait<1>(); release(sprev); }
                sprev = s;
                if (++s == 6) { s = 0; ph ^= 1; }
            }
            const int np = mt == 15 ? 4 : 2;
            wait_ctr(CT_OP + (mt * 2 + part) * 8 + warp, np);
            const uint4* src = g_part + (((mt * 2 + part) * 8 + warp) * 16 + (int)rank * 8) * 32 + lane;
            uint4 u[2][8];
            auto load_parts = [&](int p) {
#pragma unroll
                for (int i = 0; i < 16; i++)
                    asm volatile("ld.relaxed.gpu.global.v4.u32 {%0, %1, %2, %3}, [%4];" : "=r"(u[i >> 3][i & 7].x), "=r"(u[i >> 3][i & 7].y), "=r"(u[i >> 3][i & 7].z),
                                 "=r"(u[i >> 3][i & 7].w) : "l"(src + (p + (i >> 3)) * (32 * 8 * 16 * 32) + (i & 7) * 32) : "memory");
            };
            auto add_parts = [&]() {
#pragma unroll
                for (int i = 0; i < 16; i++) {
                    const uint32_t v[4] = {u[i >> 3][i & 7].x, u[i >> 3][i & 7].y, u[i >> 3][i & 7].z, u[i >> 3][i & 7].w};
#pragma unroll
                    for (int e = 0; e < 4; e++) {
                        acc[8 * (i & 7) + 2 * e] += __uint_as_float(v[e] << 16);
                        acc[8 * (i & 7) + 2 * e + 1] += __uint_as_float(v[e] & 0xffff0000u);
                    }
                }
            };
            load_parts(0);
            wgmma_wait<0>();
            OT(4);
            const float w0 = 1.f - g0, w1 = 1.f - g1;
#pragma unroll
            for (int j = 0; j < 16; j++) { acc[4 * j] *= w0; acc[4 * j + 1] *= w0; acc[4 * j + 2] *= w1; acc[4 * j + 3] *= w1; }
            add_parts();
            if (np == 4) { load_parts(2); add_parts(); }
            OT(5);
            mbar_wait(bar_empty + 8 * s, ph ^ 1);
            const uint32_t stg = sbase + s * 32768 + wg * 16384;
#pragma unroll
            for (int j = 0; j < 8; j++) {
                const float* a = &acc[8 * j];
                stmatrix_x4(stg + (j >> 2) * 8192 + moff + ((mx ^ ((j & 3) * 2)) << 4), pack_bf16(a[0], a[1]), pack_bf16(a[2], a[3]), pack_bf16(a[4], a[5]), pack_bf16(a[6], a[7]));
            }
            fence_async_smem();
            asm volatile("bar.sync %0, 128;" :: "r"(2 + wg) : "memory");
            if (elected) {
                tma_store_2d(&P.mapOut, stg, n0, m0 + wg * 64);
                tma_store_2d(&P.mapOut, stg + 8192, n0 + 64, m0 + wg * 64);
                asm volatile("cp.async.bulk.commit_group;" ::: "memory");
                asm volatile("cp.async.bulk.wait_group 0;" ::: "memory");
            }
            OT(6);
        }
    }
    __syncthreads();
    asm volatile("barrier.cluster.arrive.relaxed.aligned;" ::: "memory");
    if (warp == 0) {
        unsigned int tk = 0;
        if (lane == 0) tk = atomicAdd(&g_ctr[CT_FIN], 1u);
        tk = __shfl_sync(0xffffffff, tk, 0);
        if (tk == gridDim.x - 1)
            for (int i = lane; i < CT_N; i += 32) g_ctr[i] = 0u;
    }
    asm volatile("barrier.cluster.wait.acquire.aligned;" ::: "memory");
    TS_END(4);
}

typedef CUresult (*PFN_encodeTiled)(CUtensorMap*, CUtensorMapDataType, cuuint32_t, void*, const cuuint64_t*,
                                    const cuuint64_t*, const cuuint32_t*, const cuuint32_t*, CUtensorMapInterleave,
                                    CUtensorMapSwizzle, CUtensorMapL2promotion, CUtensorMapFloatOOBfill);
static PFN_encodeTiled g_encode = nullptr;

static void make_map(CUtensorMap* m, const void* ptr, uint64_t rows, uint64_t cols, uint32_t box_rows, bool sw64 = false) {
    cuuint64_t dims[2] = {cols, rows};
    cuuint64_t strides[1] = {cols * 2};
    cuuint32_t box[2] = {sw64 ? 32u : 64u, box_rows};
    cuuint32_t es[2] = {1, 1};
    g_encode(m, CU_TENSOR_MAP_DATA_TYPE_BFLOAT16, 2, const_cast<void*>(ptr), dims, strides, box, es,
             CU_TENSOR_MAP_INTERLEAVE_NONE, sw64 ? CU_TENSOR_MAP_SWIZZLE_64B : CU_TENSOR_MAP_SWIZZLE_128B, CU_TENSOR_MAP_L2_PROMOTION_L2_256B,
             CU_TENSOR_MAP_FLOAT_OOB_FILL_NONE);
}

template <typename... KArgs, typename... Args>
static void launch_pdl(void (*kernel)(KArgs...), int grid, int block, size_t smem, cudaStream_t st, bool pdl, Args... args) {
    cudaLaunchConfig_t cfg = {};
    cfg.gridDim = dim3(grid); cfg.blockDim = dim3(block); cfg.dynamicSmemBytes = smem; cfg.stream = st;
    cudaLaunchAttribute at[1];
    at[0].id = cudaLaunchAttributeProgrammaticStreamSerialization;
    at[0].val.programmaticStreamSerializationAllowed = 1;
    cfg.attrs = at; cfg.numAttrs = pdl ? 1 : 0;
    cudaLaunchKernelEx(&cfg, kernel, KArgs(args)...);
}

extern "C" void kernel_launch(void* const* d_in, const int* in_sizes, int n_in, void* d_out, int out_size) {
    const bf16* x = (const bf16*)d_in[0];
    const bf16* ckv = (const bf16*)d_in[1];
    const bf16* wq = (const bf16*)d_in[2];
    const bf16* wuk = (const bf16*)d_in[3];
    const bf16* wuv = (const bf16*)d_in[4];
    const bf16* wo = (const bf16*)d_in[5];
    const bf16* mem0 = (const bf16*)d_in[7];
    const bf16* Wq = (const bf16*)d_in[8];
    const bf16* Wk = (const bf16*)d_in[9];
    const bf16* Wv = (const bf16*)d_in[10];
    const bf16* Wo = (const bf16*)d_in[11];
    const bf16* gate_w = (const bf16*)d_in[13];
    bf16* out = (bf16*)d_out;

    static Proj2Params P2;
    static ChainParams CP;
    static AttnParams AP;
    static OutParams OP;
    static bool init = false;
    static const void* last_in[15];
    bool same = init;
    for (int i = 0; i < 14 && same; i++) same = last_in[i] == d_in[i];
    same = same && last_in[14] == d_out;
    if (!init) {
        cudaDriverEntryPointQueryResult qr;
        cudaGetDriverEntryPoint("cuTensorMapEncodeTiled", (void**)&g_encode, cudaEnableDefault, &qr);
        cudaFuncSetAttribute(proj2_kernel, cudaFuncAttributeMaxDynamicSharedMemorySize, P2_SMEM);
        cudaFuncSetAttribute(attn_kernel, cudaFuncAttributeMaxDynamicSharedMemorySize, FA_SMEM);
        cudaFuncSetAttribute(chain_kernel, cudaFuncAttributeMaxDynamicSharedMemorySize, C2_SMEM);
        cudaFuncSetAttribute(out3_kernel, cudaFuncAttributeMaxDynamicSharedMemorySize, O2_SMEM);
        init = true;
    }
    if (!same) {
        for (int i = 0; i < 14; i++) last_in[i] = d_in[i];
        last_in[14] = d_out;
        void *pQA, *pKA, *pVA, *pCA, *pCB;
        cudaGetSymbolAddress(&pQA, g_QA); cudaGetSymbolAddress(&pKA, g_KA); cudaGetSymbolAddress(&pVA, g_VA);
        cudaGetSymbolAddress(&pCA, g_ctxA); cudaGetSymbolAddress(&pCB, g_ctxB);
        make_map(&P2.mapA[0], x, SEQ, DM, 128);
        make_map(&P2.mapA[1], ckv, SEQ, DM, 128);
        const void* ws[3] = {wq, wuk, wuv};
        void* cs[3] = {pQA, pKA, pVA};
        for (int i = 0; i < 3; i++) { make_map(&P2.mapW[i], ws[i], DM, NQ, 64); P2.out[i] = (bf16*)cs[i]; }
        make_map(&CP.mapX, x, SEQ, DM, SEGL);
        make_map(&CP.mapM, mem0, NMEM, DM, NMEM);
        make_map(&CP.mapW[0], Wq, DM, NQ, 64);
        make_map(&CP.mapW[1], Wk, DM, NQ, 64);
        make_map(&CP.mapW[2], Wv, DM, NQ, 64);
        make_map(&CP.mapWo, Wo, NQ, DM, 64);
        make_map(&AP.mapQ, pQA, NH * SEQ, HD, 128);
        make_map(&AP.mapK, pKA, NH * SEQ, HD, 128);
        make_map(&AP.mapV, pVA, NH * SEQ, HD, 128);
        make_map(&AP.mapO, pCA, NH * SEQ, HD, 64);
        make_map(&OP.mapCtx[0], pCA, NH * SEQ, HD, 64);
        make_map(&OP.mapCtx[1], pCB, NH * SEQ, HD, 64);
        make_map(&OP.mapWo[0], wo, NQ, DM, 64);
        make_map(&OP.mapWo[1], Wo, NQ, DM, 64);
        make_map(&OP.mapOut, out, SEQ, DM, 64);
        AP.x = x; AP.gate_w = gate_w;
    }
    cudaStream_t s1 = cudaStreamPerThread;
    const bool pdl = true;
    launch_pdl(chain_kernel, 64, 384, C2_SMEM, s1, false, CP);
    launch_pdl(proj2_kernel, 68, 384, P2_SMEM, s1, pdl, P2);
    launch_pdl(attn_kernel, FA_GRID, 384, FA_SMEM, s1, pdl, AP);
    launch_pdl(out3_kernel, O3_GRID, 352, O2_SMEM, s1, pdl, OP);
}
```

```cpp
#include <cuda_runtime.h>
#include <cuda_bf16.h>
#include <cuda.h>
#include <stdint.h>
#include <type_traits>

constexpr int SEQ = 2048;
constexpr int DM = 512;
constexpr int NH = 32;
constexpr int HD = 128;
constexpr int NQ = NH * HD;
constexpr int SEGL = 32;
constexpr int NMEM = 8;
constexpr int NSEG = SEQ / SEGL;

typedef __nv_bfloat16 bf16;

__device__ bf16 g_QA[SEQ * NQ];
__device__ bf16 g_KA[SEQ * NQ];
__device__ bf16 g_VA[SEQ * NQ];
__device__ bf16 g_ctxA[SEQ * NQ];
__device__ bf16 g_ctxB[SEQ * NQ];
constexpr int CT_PROJ = 0, CT_ATTN = 1, CT_FIN = 5;
constexpr int CT_G = 32;
constexpr int CT_AP = 64;
#define O2_HE 24
constexpr int CT_CA = 128;
constexpr int CT_CB = 160;
#define CB_FIRST 13
constexpr int CT_OP = 192;
constexpr int CT_N = 448;
__device__ unsigned int g_ctr[CT_N];
__device__ float g_gate[SEQ];
__device__ uint2 g_xbuf[2 * 8 * 8 * 128];

#define FA_GRID 68

#define TS_BEGIN(id)
#define TS_END(id)
__device__ __forceinline__ void pdl_launch_dependents() { asm volatile("griddepcontrol.launch_dependents;" ::: "memory"); }
__device__ __forceinline__ void wait_ctr(int idx, unsigned int n) {
    unsigned int v; int it = 0;
    do { asm volatile("ld.acquire.gpu.global.u32 %0, [%1];" : "=r"(v) : "l"(&g_ctr[idx]) : "memory"); } while (v < n && ++it < (1 << 22));
}
__device__ __forceinline__ void signal_ctr(int idx) {
    asm volatile("fence.proxy.async.global;" ::: "memory");
    asm volatile("red.release.gpu.global.add.u32 [%0], 1;" :: "l"(&g_ctr[idx]) : "memory");
}
__device__ __forceinline__ void signal_ctr_generic(int idx) {
    asm volatile("red.release.gpu.global.add.u32 [%0], 1;" :: "l"(&g_ctr[idx]) : "memory");
}
__device__ __forceinline__ uint32_t smem_u32(const void* p) {
    return (uint32_t)__cvta_generic_to_shared(p);
}
__device__ __forceinline__ void mbar_init(uint32_t bar, uint32_t count) {
    asm volatile("mbarrier.init.shared::cta.b64 [%0], %1;" :: "r"(bar), "r"(count));
}
__device__ __forceinline__ void mbar_expect_tx(uint32_t bar, uint32_t bytes) {
    asm volatile("mbarrier.arrive.expect_tx.shared::cta.b64 _, [%0], %1;" :: "r"(bar), "r"(bytes) : "memory");
}
__device__ __forceinline__ void mbar_arrive(uint32_t bar) {
    asm volatile("mbarrier.arrive.shared::cta.b64 _, [%0];" :: "r"(bar) : "memory");
}
__device__ __forceinline__ void mbar_wait(uint32_t bar, uint32_t parity) {
    asm volatile(
        "{\n"
        ".reg .pred p, q;\n"
        ".reg .u32 c;\n"
        "mov.u32 c, 0;\n"
        "WAIT_LOOP:\n"
        "mbarrier.try_wait.parity.shared::cta.b64 p, [%0], %1;\n"
        "@p bra WAIT_DONE;\n"
        "add.u32 c, c, 1;\n"
        "setp.lt.u32 q, c, 4000000;\n"
        "@q bra WAIT_LOOP;\n"
        "WAIT_DONE:\n"
        "}\n" :: "r"(bar), "r"(parity) : "memory");
}
__device__ __forceinline__ void tma_load_2d(uint32_t dst, const CUtensorMap* map, uint32_t bar, int c0, int c1) {
    asm volatile(
        "cp.async.bulk.tensor.2d.shared::cluster.global.mbarrier::complete_tx::bytes [%0], [%1, {%3, %4}], [%2];"
        :: "r"(dst), "l"((uint64_t)map), "r"(bar), "r"(c0), "r"(c1) : "memory");
}
__device__ __forceinline__ void wgmma_fence() { asm volatile("wgmma.fence.sync.aligned;" ::: "memory"); }
__device__ __forceinline__ void wgmma_commit() { asm volatile("wgmma.commit_group.sync.aligned;" ::: "memory"); }
template <int N> __device__ __forceinline__ void wgmma_wait() {
    asm volatile("wgmma.wait_group.sync.aligned %0;" :: "n"(N) : "memory");
}
__device__ __forceinline__ uint64_t make_desc(uint32_t addr, uint32_t lbo, uint32_t sbo) {
    uint64_t d = 0;
    d |= (uint64_t)((addr & 0x3FFFF) >> 4);
    d |= (uint64_t)((lbo >> 4) & 0x3FFF) << 16;
    d |= (uint64_t)((sbo >> 4) & 0x3FFF) << 32;
    d |= (uint64_t)1 << 62;
    return d;
}

#define ACC64(d) \
    "+f"(d[0]), "+f"(d[1]), "+f"(d[2]), "+f"(d[3]), "+f"(d[4]), "+f"(d[5]), "+f"(d[6]), "+f"(d[7]), \
    "+f"(d[8]), "+f"(d[9]), "+f"(d[10]), "+f"(d[11]), "+f"(d[12]), "+f"(d[13]), "+f"(d[14]), "+f"(d[15]), \
    "+f"(d[16]), "+f"(d[17]), "+f"(d[18]), "+f"(d[19]), "+f"(d[20]), "+f"(d[21]), "+f"(d[22]), "+f"(d[23]), \
    "+f"(d[24]), "+f"(d[25]), "+f"(d[26]), "+f"(d[27]), "+f"(d[28]), "+f"(d[29]), "+f"(d[30]), "+f"(d[31]), \
    "+f"(d[32]), "+f"(d[33]), "+f"(d[34]), "+f"(d[35]), "+f"(d[36]), "+f"(d[37]), "+f"(d[38]), "+f"(d[39]), \
    "+f"(d[40]), "+f"(d[41]), "+f"(d[42]), "+f"(d[43]), "+f"(d[44]), "+f"(d[45]), "+f"(d[46]), "+f"(d[47]), \
    "+f"(d[48]), "+f"(d[49]), "+f"(d[50]), "+f"(d[51]), "+f"(d[52]), "+f"(d[53]), "+f"(d[54]), "+f"(d[55]), \
    "+f"(d[56]), "+f"(d[57]), "+f"(d[58]), "+f"(d[59]), "+f"(d[60]), "+f"(d[61]), "+f"(d[62]), "+f"(d[63])
#define ACC64_STR \
    "{%0, %1, %2, %3, %4, %5, %6, %7, %8, %9, %10, %11, %12, %13, %14, %15, " \
    "%16, %17, %18, %19, %20, %21, %22, %23, %24, %25, %26, %27, %28, %29, %30, %31, " \
    "%32, %33, %34, %35, %36, %37, %38, %39, %40, %41, %42, %43, %44, %45, %46, %47, " \
    "%48, %49, %50, %51, %52, %53, %54, %55, %56, %57, %58, %59, %60, %61, %62, %63}"

template <int TB>
__device__ __forceinline__ void wgmma_ss_n128(float (&d)[64], uint64_t da, uint64_t db, int scale_d) {
    asm volatile(
        "{\n.reg .pred p;\nsetp.ne.b32 p, %66, 0;\n"
        "wgmma.mma_async.sync.aligned.m64n128k16.f32.bf16.bf16 " ACC64_STR ", %64, %65, p, 1, 1, 0, %67;\n}\n"
        : ACC64(d) : "l"(da), "l"(db), "r"(scale_d), "n"(TB));
}
__device__ __forceinline__ uint32_t desc_lo(uint32_t addr, uint32_t lbo) { return ((addr & 0x3FFFF) >> 4) | ((lbo >> 4) << 16); }
template <int TB>
__device__ __forceinline__ void wgmma_ss_n128_lo(float (&d)[64], uint32_t da_lo, uint32_t db_lo, int scale_d) {
    asm volatile(
        "{\n.reg .pred p;\n.reg .b64 da, db;\nsetp.ne.b32 p, %66, 0;\n"
        "mov.b64 da, {%64, 0x40000040};\nmov.b64 db, {%65, 0x40000040};\n"
        "wgmma.mma_async.sync.aligned.m64n128k16.f32.bf16.bf16 " ACC64_STR ", da, db, p, 1, 1, 0, %67;\n}\n"
        : ACC64(d) : "r"(da_lo), "r"(db_lo), "r"(scale_d), "n"(TB));
}
__device__ __forceinline__ void wgmma_rs_n128_tb(float (&d)[64], uint32_t a0, uint32_t a1, uint32_t a2, uint32_t a3,
                                                 uint64_t db, int scale_d) {
    asm volatile(
        "{\n.reg .pred p;\nsetp.ne.b32 p, %69, 0;\n"
        "wgmma.mma_async.sync.aligned.m64n128k16.f32.bf16.bf16 " ACC64_STR ", {%64, %65, %66, %67}, %68, p, 1, 1, 1;\n}\n"
        : ACC64(d) : "r"(a0), "r"(a1), "r"(a2), "r"(a3), "l"(db), "r"(scale_d));
}
__device__ __forceinline__ void wgmma_rs_n80(float (&d)[40], const uint32_t (&a)[4], uint32_t db_lo, int scale_d) {
    asm volatile(
        "{\n.reg .pred p;\n.reg .b64 db;\nsetp.ne.b32 p, %45, 0;\nmov.b64 db, {%44, 0x40000040};\n"
        "wgmma.mma_async.sync.aligned.m64n80k16.f32.bf16.bf16 "
        "{%0, %1, %2, %3, %4, %5, %6, %7, %8, %9, %10, %11, %12, %13, %14, %15, %16, %17, %18, %19, %20, %21, %22, %23, %24, %25, %26, %27, %28, %29, %30, %31, %32, %33, %34, %35, %36, %37, %38, %39}, "
        "{%40, %41, %42, %43}, db, p, 1, 1, 0;\n}\n"
        : "+f"(d[0]), "+f"(d[1]), "+f"(d[2]), "+f"(d[3]), "+f"(d[4]), "+f"(d[5]), "+f"(d[6]), "+f"(d[7]), "+f"(d[8]), "+f"(d[9]), "+f"(d[10]), "+f"(d[11]), "+f"(d[12]), "+f"(d[13]), "+f"(d[14]), "+f"(d[15]), "+f"(d[16]), "+f"(d[17]), "+f"(d[18]), "+f"(d[19]), "+f"(d[20]), "+f"(d[21]), "+f"(d[22]), "+f"(d[23]), "+f"(d[24]), "+f"(d[25]), "+f"(d[26]), "+f"(d[27]), "+f"(d[28]), "+f"(d[29]), "+f"(d[30]), "+f"(d[31]), "+f"(d[32]), "+f"(d[33]), "+f"(d[34]), "+f"(d[35]), "+f"(d[36]), "+f"(d[37]), "+f"(d[38]), "+f"(d[39])
        : "r"(a[0]), "r"(a[1]), "r"(a[2]), "r"(a[3]), "r"(db_lo), "r"(scale_d));
}
__device__ __forceinline__ void wgmma_ss_n256_tb(float (&d)[128], uint64_t da, uint64_t db, int scale_d) {
    asm volatile(
        "{\n.reg .pred p;\nsetp.ne.b32 p, %130, 0;\n"
        "wgmma.mma_async.sync.aligned.m64n256k16.f32.bf16.bf16 {%0, %1, %2, %3, %4, %5, %6, %7, %8, %9, %10, %11, %12, %13, %14, %15, %16, %17, %18, %19, %20, %21, %22, %23, %24, %25, %26, %27, %28, %29, %30, %31, %32, %33, %34, %35, %36, %37, %38, %39, %40, %41, %42, %43, %44, %45, %46, %47, %48, %49, %50, %51, %52, %53, %54, %55, %56, %57, %58, %59, %60, %61, %62, %63, %64, %65, %66, %67, %68, %69, %70, %71, %72, %73, %74, %75, %76, %77, %78, %79, %80, %81, %82, %83, %84, %85, %86, %87, %88, %89, %90, %91, %92, %93, %94, %95, %96, %97, %98, %99, %100, %101, %102, %103, %104, %105, %106, %107, %108, %109, %110, %111, %112, %113, %114, %115, %116, %117, %118, %119, %120, %121, %122, %123, %124, %125, %126, %127}, %128, %129, p, 1, 1, 0, 1;\n}\n"
        : "+f"(d[0]), "+f"(d[1]), "+f"(d[2]), "+f"(d[3]), "+f"(d[4]), "+f"(d[5]), "+f"(d[6]), "+f"(d[7]), "+f"(d[8]), "+f"(d[9]), "+f"(d[10]), "+f"(d[11]), "+f"(d[12]), "+f"(d[13]), "+f"(d[14]), "+f"(d[15]), "+f"(d[16]), "+f"(d[17]), "+f"(d[18]), "+f"(d[19]), "+f"(d[20]), "+f"(d[21]), "+f"(d[22]), "+f"(d[23]), "+f"(d[24]), "+f"(d[25]), "+f"(d[26]), "+f"(d[27]), "+f"(d[28]), "+f"(d[29]), "+f"(d[30]), "+f"(d[31]), "+f"(d[32]), "+f"(d[33]), "+f"(d[34]), "+f"(d[35]), "+f"(d[36]), "+f"(d[37]), "+f"(d[38]), "+f"(d[39]), "+f"(d[40]), "+f"(d[41]), "+f"(d[42]), "+f"(d[43]), "+f"(d[44]), "+f"(d[45]), "+f"(d[46]), "+f"(d[47]), "+f"(d[48]), "+f"(d[49]), "+f"(d[50]), "+f"(d[51]), "+f"(d[52]), "+f"(d[53]), "+f"(d[54]), "+f"(d[55]), "+f"(d[56]), "+f"(d[57]), "+f"(d[58]), "+f"(d[59]), "+f"(d[60]), "+f"(d[61]), "+f"(d[62]), "+f"(d[63]), "+f"(d[64]), "+f"(d[65]), "+f"(d[66]), "+f"(d[67]), "+f"(d[68]), "+f"(d[69]), "+f"(d[70]), "+f"(d[71]), "+f"(d[72]), "+f"(d[73]), "+f"(d[74]), "+f"(d[75]), "+f"(d[76]), "+f"(d[77]), "+f"(d[78]), "+f"(d[79]), "+f"(d[80]), "+f"(d[81]), "+f"(d[82]), "+f"(d[83]), "+f"(d[84]), "+f"(d[85]), "+f"(d[86]), "+f"(d[87]), "+f"(d[88]), "+f"(d[89]), "+f"(d[90]), "+f"(d[91]), "+f"(d[92]), "+f"(d[93]), "+f"(d[94]), "+f"(d[95]), "+f"(d[96]), "+f"(d[97]), "+f"(d[98]), "+f"(d[99]), "+f"(d[100]), "+f"(d[101]), "+f"(d[102]), "+f"(d[103]), "+f"(d[104]), "+f"(d[105]), "+f"(d[106]), "+f"(d[107]), "+f"(d[108]), "+f"(d[109]), "+f"(d[110]), "+f"(d[111]), "+f"(d[112]), "+f"(d[113]), "+f"(d[114]), "+f"(d[115]), "+f"(d[116]), "+f"(d[117]), "+f"(d[118]), "+f"(d[119]), "+f"(d[120]), "+f"(d[121]), "+f"(d[122]), "+f"(d[123]), "+f"(d[124]), "+f"(d[125]), "+f"(d[126]), "+f"(d[127])
        : "l"(da), "l"(db), "r"(scale_d));
}
__device__ __forceinline__ void stmatrix_x4(uint32_t addr, uint32_t r0, uint32_t r1, uint32_t r2, uint32_t r3) {
    asm volatile("stmatrix.sync.aligned.m8n8.x4.shared.b16 [%0], {%1, %2, %3, %4};" :: "r"(addr), "r"(r0), "r"(r1), "r"(r2), "r"(r3) : "memory");
}
__device__ __forceinline__ void tma_store_2d(const CUtensorMap* map, uint32_t src, int c0, int c1) {
    asm volatile("cp.async.bulk.tensor.2d.global.shared::cta.bulk_group [%0, {%2, %3}], [%1];"
                 :: "l"((uint64_t)map), "r"(src), "r"(c0), "r"(c1) : "memory");
}
__device__ __forceinline__ float ex2f(float x) { float y; asm("ex2.approx.ftz.f32 %0, %1;" : "=f"(y) : "f"(x)); return y; }
__device__ __forceinline__ uint32_t pack_bf16(float lo, float hi) {
    __nv_bfloat162 v = __floats2bfloat162_rn(lo, hi);
    return *reinterpret_cast<uint32_t*>(&v);
}
__device__ __forceinline__ float bf16r(float x) { return __uint_as_float(pack_bf16(0.f, x) & 0xffff0000u); }
__device__ __forceinline__ void mma_16816(float (&c)[4], uint32_t a0, uint32_t a1, uint32_t a2, uint32_t a3,
                                          uint32_t b0, uint32_t b1) {
    asm volatile(
        "mma.sync.aligned.m16n8k16.row.col.f32.bf16.bf16.f32 {%0,%1,%2,%3}, {%4,%5,%6,%7}, {%8,%9}, {%0,%1,%2,%3};"
        : "+f"(c[0]), "+f"(c[1]), "+f"(c[2]), "+f"(c[3])
        : "r"(a0), "r"(a1), "r"(a2), "r"(a3), "r"(b0), "r"(b1));
}
__device__ __forceinline__ void ldmatrix_x4_trans(uint32_t& r0, uint32_t& r1, uint32_t& r2, uint32_t& r3, uint32_t addr) {
    asm volatile("ldmatrix.sync.aligned.m8n8.x4.trans.shared.b16 {%0,%1,%2,%3}, [%4];"
                 : "=r"(r0), "=r"(r1), "=r"(r2), "=r"(r3) : "r"(addr));
}

struct AttnParams {
    CUtensorMap mapQ, mapK, mapV;
    CUtensorMap mapO;
    const bf16 *x, *gate_w;
};
constexpr uint32_t FA_Q = 0, FA_KV = 65536, FA_O = 196608, FA_BAR = 229376;
constexpr int FA_SMEM = FA_BAR + 256;
constexpr int FA_ITEMS = 16 * NH;
__device__ __forceinline__ int fa_qt(int t) { return 15 - ((t & 127) >> 3); }
__device__ __forceinline__ int fa_head(int t) { return (t >> 7) * 8 + (t & 7); }
__device__ __forceinline__ uint32_t mbar_test(uint32_t bar, uint32_t parity) {
    uint32_t done;
    asm volatile(
        "{\n.reg .pred p;\n"
        "mbarrier.test_wait.parity.shared::cta.b64 p, [%1], %2;\n"
        "selp.u32 %0, 1, 0, p;\n}\n" : "=r"(done) : "r"(bar), "r"(parity) : "memory");
    return done;
}
__device__ __forceinline__ void mbar_arrive_if(uint32_t bar, bool c) {
    asm volatile("{\n.reg .pred p;\nsetp.ne.u32 p, %1, 0;\n@p mbarrier.arrive.shared::cta.b64 _, [%0];\n}" :: "r"(bar), "r"((uint32_t)c) : "memory");
}
__device__ __forceinline__ void wgmma_rs_n128_tb_lo(float (&d)[64], const uint32_t* a, uint32_t db_lo, int scale_d) {
    asm volatile(
        "{\n.reg .pred p;\n.reg .b64 db;\nsetp.ne.b32 p, %69, 0;\nmov.b64 db, {%68, 0x40000040};\n"
        "wgmma.mma_async.sync.aligned.m64n128k16.f32.bf16.bf16 " ACC64_STR ", {%64, %65, %66, %67}, db, p, 1, 1, 1;\n}\n"
        : ACC64(d) : "r"(a[0]), "r"(a[1]), "r"(a[2]), "r"(a[3]), "r"(db_lo), "r"(scale_d));
}
#define FA_TEST 48
#define FA_PIN 8

__global__ void __launch_bounds__(384, 1) attn_kernel(const __grid_constant__ AttnParams P) {
    extern __shared__ __align__(1024) uint8_t smem_attn[];
    const uint32_t sb = smem_u32(smem_attn);
    const uint32_t bar_q = sb + FA_BAR, bar_qe = bar_q + 16, bar_kf = bar_q + 32, bar_vf = bar_q + 48, bar_ke = bar_q + 64, bar_ve = bar_q + 80,
                   bar_of = bar_q + 96, bar_oe = bar_q + 112, slot = bar_q + 128, oslot = bar_q + 136;
    const int warp = __shfl_sync(0xffffffff, threadIdx.x >> 5, 0);
    const int lane = threadIdx.x & 31;
    TS_BEGIN(1);
    if (threadIdx.x == 0) {
        for (int i = 0; i < 2; i++) {
            mbar_init(bar_q + 8 * i, 1); mbar_init(bar_qe + 8 * i, 8); mbar_init(bar_kf + 8 * i, 1); mbar_init(bar_vf + 8 * i, 1);
            mbar_init(bar_ke + 8 * i, 8); mbar_init(bar_ve + 8 * i, 8); mbar_init(bar_of + 8 * i, 4); mbar_init(bar_oe + 8 * i, 1);
        }
        asm volatile("fence.mbarrier_init.release.cluster;" ::: "memory");
    }
    if (threadIdx.x == 256) wait_ctr(CT_AP + (fa_head(blockIdx.x) >> 1), 96u);
    __syncthreads();
    pdl_launch_dependents();
    if (warp >= 8) {
        asm volatile("setmaxnreg.dec.sync.aligned.u32 40;");
        if (warp == 11) {
            const uint4 gv0 = __ldg(reinterpret_cast<const uint4*>(P.gate_w) + lane), gv1 = __ldg(reinterpret_cast<const uint4*>(P.gate_w) + 32 + lane);
            const uint32_t gw[8] = {gv0.x, gv0.y, gv0.z, gv0.w, gv1.x, gv1.y, gv1.z, gv1.w};
#pragma unroll 1
            for (int r = blockIdx.x; r < SEQ; r += gridDim.x) {
                const uint4 x0 = __ldg(reinterpret_cast<const uint4*>(P.x + (size_t)r * DM) + lane), x1 = __ldg(reinterpret_cast<const uint4*>(P.x + (size_t)r * DM) + 32 + lane);
                const uint32_t xw[8] = {x0.x, x0.y, x0.z, x0.w, x1.x, x1.y, x1.z, x1.w};
                float sum = 0.f;
#pragma unroll
                for (int e = 0; e < 8; e++) {
                    const uint32_t pr = pack_bf16(__uint_as_float(xw[e] << 16) * __uint_as_float(gw[e] << 16), __uint_as_float(xw[e] & 0xffff0000u) * __uint_as_float(gw[e] & 0xffff0000u));
                    sum += __uint_as_float(pr << 16) + __uint_as_float(pr & 0xffff0000u);
                }
#pragma unroll
                for (int o = 16; o; o >>= 1) sum += __shfl_xor_sync(0xffffffff, sum, o);
                if (lane == 0) g_gate[r] = bf16r(1.f / (1.f + __expf(-bf16r(sum))));
            }
            if (lane == 0) signal_ctr_generic(CT_G);
        } else if (warp > 8) {
            if (lane == 0) {
                const int wg = warp - 9;
                const uint32_t stg = sb + FA_O + wg * 16384;
                for (int n = 0;; n++) {
                    mbar_wait(bar_of + 8 * wg, n & 1);
                    int t;
                    asm volatile("ld.shared.s32 %0, [%1];" : "=r"(t) : "r"(oslot + wg * 4) : "memory");
                    asm volatile("fence.proxy.async.shared::cta;" ::: "memory");
                    const bool last = t < 0;
                    t &= 0xffff;
                    const int qt = fa_qt(t), h = fa_head(t);
                    tma_store_2d(&P.mapO, stg, 0, h * SEQ + qt * 128 + wg * 64);
                    tma_store_2d(&P.mapO, stg + 8192, 64, h * SEQ + qt * 128 + wg * 64);
                    asm volatile("cp.async.bulk.commit_group;" ::: "memory");
                    asm volatile("cp.async.bulk.wait_group.read 0;" ::: "memory");
                    mbar_arrive(bar_oe + 8 * wg);
                    asm volatile("cp.async.bulk.wait_group 0;" ::: "memory");
                    signal_ctr(CT_CA + qt * 2 + (h >= O2_HE));
                    if (last) break;
                }
            }
        } else if (lane == 0) {
            int it = 0, t = blockIdx.x, hp_ready = 1 << (fa_head(t) >> 1);
            auto load_q = [&](int item, int t) {
                const uint32_t b = bar_q + 8 * (item & 1);
                asm volatile("st.shared.s32 [%0], %1;" :: "r"(slot + (item & 1) * 4), "r"(t) : "memory");
                if (t < 0) { mbar_arrive(b); return; }
                const int row = fa_head(t) * SEQ + fa_qt(t) * 128;
                mbar_expect_tx(b, 32768);
                tma_load_2d(sb + FA_Q + (item & 1) * 32768, &P.mapQ, b, 0, row);
                tma_load_2d(sb + FA_Q + (item & 1) * 32768 + 16384, &P.mapQ, b, 64, row);
            };
            load_q(0, t);
            for (int item = 0; t >= 0; item++) {
                const int h = fa_head(t);
                for (int j = fa_qt(t); j >= 0; j--, it++) {
                    const int s = it & 1;
                    const uint32_t ph = ((it >> 1) & 1) ^ 1;
                    const uint32_t sk = sb + FA_KV + s * 65536, sv = sk + 32768;
                    if (j == 0) t = (int)(gridDim.x + atomicAdd(&g_ctr[CT_ATTN], 1u));
                    mbar_wait(bar_ke + 8 * s, ph);
                    mbar_expect_tx(bar_kf + 8 * s, 32768);
                    tma_load_2d(sk, &P.mapK, bar_kf + 8 * s, 0, h * SEQ + j * 128);
                    tma_load_2d(sk + 16384, &P.mapK, bar_kf + 8 * s, 64, h * SEQ + j * 128);
                    if (j == 0) {
                        if (t >= FA_ITEMS) t = -1;
                        else {
                            const int hp = fa_head(t) >> 1;
                            if (!((hp_ready >> hp) & 1)) { wait_ctr(CT_AP + hp, 96u); hp_ready |= 1 << hp; }
                        }
                        mbar_wait(bar_qe + 8 * ((item + 1) & 1), (((item + 1) >> 1) & 1) ^ 1);
                        load_q(item + 1, t);
                    }
                    mbar_wait(bar_ve + 8 * s, ph);
                    mbar_expect_tx(bar_vf + 8 * s, 32768);
                    tma_load_2d(sv, &P.mapV, bar_vf + 8 * s, 0, h * SEQ + j * 128);
                    tma_load_2d(sv + 16384, &P.mapV, bar_vf + 8 * s, 64, h * SEQ + j * 128);
                }
            }
        }
    } else {
        asm volatile("setmaxnreg.inc.sync.aligned.u32 232;");
        const int wg = warp >> 2;
        const bool lane0 = lane == 0;
        float o[64], sacc[64];
        uint32_t pa[32];
        float mrow0, mrow1, lrow0, lrow1;
        const float sc = 0.08838834764831845f * 1.4426950408889634f;
        const uint32_t q_lo = desc_lo(sb + FA_Q + wg * 8192, 16), k_lo = desc_lo(sb + FA_KV, 16), v_lo = desc_lo(sb + FA_KV + 32768, 16384);
        auto issue_qk = [&](int item, int it) {
            const uint32_t a = q_lo + (item & 1) * 2048, b = k_lo + (it & 1) * 4096;
#pragma unroll
            for (int kk = 0; kk < 8; kk++) wgmma_ss_n128_lo<0>(sacc, a + (kk >> 2) * 1024 + (kk & 3) * 2, b + (kk >> 2) * 1024 + (kk & 3) * 2, kk != 0);
            wgmma_commit();
        };
        auto issue_pv = [&](int it, bool acc) {
            const uint32_t b = v_lo + (it & 1) * 4096;
#pragma unroll
            for (int kk = 0; kk < 8; kk++) wgmma_rs_n128_tb_lo(o, &pa[kk * 4], b + kk * 128, kk != 0 || acc);
            wgmma_commit();
        };
        auto turn_wait = [&]() { asm volatile("bar.sync %0, 256;" :: "r"(1 + wg) : "memory"); };
        auto turn_pass = [&]() { asm volatile("bar.arrive %0, 256;" :: "r"(2 - wg) : "memory"); };
        auto mask = [&]() {
            const int r0 = wg * 64 + (warp & 3) * 16 + (lane >> 2) - (lane & 3) * 2;
#pragma unroll
            for (int i = 0; i < 64; i++)
                if ((i >> 2) * 8 + (i & 1) - ((i & 2) ? 8 : 0) > r0) sacc[i] = -INFINITY;
        };
        auto row_max = [&](float& mx0, float& mx1) {
            float mx[4];
#pragma unroll
            for (int i = 0; i < 4; i++) mx[i] = fmaxf(sacc[i], sacc[i + 4]);
#pragma unroll
            for (int i = 8; i < 64; i++) mx[i & 3] = fmaxf(mx[i & 3], sacc[i]);
            mx0 = fmaxf(mx0, fmaxf(mx[0], mx[1])); mx1 = fmaxf(mx1, fmaxf(mx[2], mx[3]));
            const float u0 = __shfl_xor_sync(0xffffffff, mx0, 1), u1 = __shfl_xor_sync(0xffffffff, mx1, 1);
            mx0 = fmaxf(mx0, u0); mx1 = fmaxf(mx1, u1);
            const float v0 = __shfl_xor_sync(0xffffffff, mx0, 2), v1 = __shfl_xor_sync(0xffffffff, mx1, 2);
            mx0 = fmaxf(mx0, v0); mx1 = fmaxf(mx1, v1);
        };
        auto pin_after = [&](float v) {
            asm volatile("{\n.reg .pred p;\nsetp.lt.f32 p, %1, 0f00000000;\n@p st.shared.f32 [%0], %1;\n}" :: "r"(slot + 16), "f"(v) : "memory");
        };
        auto pack_p = [&]() {
#pragma unroll
            for (int i = 0; i < 32; i++) pa[i] = pack_bf16(sacc[2 * i], sacc[2 * i + 1]);
        };
        auto first_softmax = [&]() {
            mask();
            mrow0 = -INFINITY; mrow1 = -INFINITY;
            row_max(mrow0, mrow1);
            const float ms0 = mrow0 * sc, ms1 = mrow1 * sc;
            float sum[4] = {0.f, 0.f, 0.f, 0.f};
#pragma unroll
            for (int i = 0; i < 64; i++) { sacc[i] = ex2f(fmaf(sacc[i], sc, (i & 2) ? -ms1 : -ms0)); sum[i & 3] += sacc[i]; }
            lrow0 = sum[0] + sum[1]; lrow1 = sum[2] + sum[3];
        };
        auto epilogue = [&](int item, int tag, float l0, float l1) {
            l0 += __shfl_xor_sync(0xffffffff, l0, 1); l1 += __shfl_xor_sync(0xffffffff, l1, 1);
            l0 += __shfl_xor_sync(0xffffffff, l0, 2); l1 += __shfl_xor_sync(0xffffffff, l1, 2);
            float i0, i1;
            asm("rcp.approx.ftz.f32 %0, %1;" : "=f"(i0) : "f"(l0));
            asm("rcp.approx.ftz.f32 %0, %1;" : "=f"(i1) : "f"(l1));
            const int row = (warp & 3) * 16 + (lane >> 2);
            const uint32_t stg = sb + FA_O + wg * 16384 + row * 128;
#pragma unroll
            for (int i = 0; i < 4; i++) {
                const int ch = i * 4 + (lane & 3);
                const uint32_t a = stg + (ch >> 3) * 8192 + (((ch & 7) ^ (row & 7)) << 4);
                const float* q = &o[i * 16];
                asm volatile("st.shared.v4.b32 [%0], {%1, %2, %3, %4};" :: "r"(a), "r"(pack_bf16(q[0] * i0, q[1] * i0)), "r"(pack_bf16(q[4] * i0, q[5] * i0)),
                             "r"(pack_bf16(q[8] * i0, q[9] * i0)), "r"(pack_bf16(q[12] * i0, q[13] * i0)) : "memory");
                asm volatile("st.shared.v4.b32 [%0], {%1, %2, %3, %4};" :: "r"(a + 1024), "r"(pack_bf16(q[2] * i1, q[3] * i1)), "r"(pack_bf16(q[6] * i1, q[7] * i1)),
                             "r"(pack_bf16(q[10] * i1, q[11] * i1)), "r"(pack_bf16(q[14] * i1, q[15] * i1)) : "memory");
            }
            asm volatile("st.shared.s32 [%0], %1;" :: "r"(oslot + wg * 4), "r"(tag) : "memory");
            __syncwarp();
            mbar_arrive_if(bar_of + 8 * wg, lane0);
        };
        int it = 0, t = blockIdx.x, nkv = fa_qt(t) + 1;
        if (wg == 1) asm volatile("bar.arrive 1, 256;" ::: "memory");
        mbar_wait(bar_q, 0);
        mbar_wait(bar_kf, 0);
        turn_wait();
        wgmma_fence();
        issue_qk(0, 0);
        turn_pass();
        wgmma_wait<0>();
        mbar_arrive_if(bar_ke, lane0);
        mbar_arrive_if(bar_qe, lane0 && nkv == 1);
        first_softmax();
        pack_p();
#pragma unroll 1
        for (int item = 0;; item++) {
            uint32_t ok = 0;
#pragma unroll 1
            for (int j = 1; j < nkv; j++) {
                it++;
                if (__builtin_expect(!ok, 0)) {
                    mbar_wait(bar_kf + 8 * (it & 1), (it >> 1) & 1);
                    mbar_wait(bar_vf + 8 * ((it - 1) & 1), ((it - 1) >> 1) & 1);
                }
                turn_wait();
                wgmma_fence();
                issue_qk(item, it);
                issue_pv(it - 1, j > 1);
                turn_pass();
                wgmma_wait<1>();
                mbar_arrive_if(bar_ke + 8 * (it & 1), lane0);
                mbar_arrive_if(bar_qe + 8 * (item & 1), lane0 && j == nkv - 1);
                float mx0 = mrow0, mx1 = mrow1;
                row_max(mx0, mx1);
                const float ms0 = mx0 * sc, ms1 = mx1 * sc;
                const float a0 = ex2f(fmaf(mrow0, sc, -ms0)), a1 = ex2f(fmaf(mrow1, sc, -ms1));
                mrow0 = mx0; mrow1 = mx1;
                float sum[4] = {lrow0 * a0, 0.f, lrow1 * a1, 0.f};
#pragma unroll
                for (int i = 0; i < FA_PIN; i++) { sacc[i] = ex2f(fmaf(sacc[i], sc, (i & 2) ? -ms1 : -ms0)); sum[i & 3] += sacc[i]; }
                pin_after(sum[0] + sum[2]);
                wgmma_wait<0>();
                mbar_arrive_if(bar_ve + 8 * ((it - 1) & 1), lane0);
#pragma unroll
                for (int i = 0; i < 64; i++) {
                    if (i >= FA_PIN) { sacc[i] = ex2f(fmaf(sacc[i], sc, (i & 2) ? -ms1 : -ms0)); sum[i & 3] += sacc[i]; }
                    o[i] *= (i & 2) ? a1 : a0;
                    if (i & 1) pa[i >> 1] = pack_bf16(sacc[i - 1], sacc[i]);
                    if (i == FA_TEST) pin_after(sum[0]);
                    if (i == FA_TEST) ok = mbar_test(bar_kf + 8 * ((it + 1) & 1), ((it + 1) >> 1) & 1) & mbar_test(bar_vf + 8 * (it & 1), (it >> 1) & 1);
                }
                lrow0 = sum[0] + sum[1]; lrow1 = sum[2] + sum[3];
            }
            it++;
            int tn;
            mbar_wait(bar_q + 8 * ((item + 1) & 1), ((item + 1) >> 1) & 1);
            asm volatile("ld.shared.s32 %0, [%1];" : "=r"(tn) : "r"(slot + ((item + 1) & 1) * 4) : "memory");
            tn = __shfl_sync(0xffffffff, tn, 0);
            mbar_wait(bar_vf + 8 * ((it - 1) & 1), ((it - 1) >> 1) & 1);
            const float l0 = lrow0, l1 = lrow1;
            if (tn < 0) {
                wgmma_fence();
                issue_pv(it - 1, nkv > 1);
                mbar_wait(bar_oe + 8 * wg, (item & 1) ^ 1);
                wgmma_wait<0>();
                epilogue(item, t | 0x80000000, l0, l1);
                break;
            }
            mbar_wait(bar_kf + 8 * (it & 1), (it >> 1) & 1);
            turn_wait();
            wgmma_fence();
            issue_qk(item + 1, it);
            issue_pv(it - 1, nkv > 1);
            turn_pass();
            nkv = fa_qt(tn) + 1;
            mbar_wait(bar_oe + 8 * wg, (item & 1) ^ 1);
            wgmma_wait<1>();
            mbar_arrive_if(bar_ke + 8 * (it & 1), lane0);
            mbar_arrive_if(bar_qe + 8 * ((item + 1) & 1), lane0 && nkv == 1);
            mask();
            mrow0 = -INFINITY; mrow1 = -INFINITY;
            row_max(mrow0, mrow1);
            {
                const float ms0 = mrow0 * sc, ms1 = mrow1 * sc;
                pin_after(fmaf(ex2f(fmaf(sacc[0], sc, -ms0)), l0, ex2f(fmaf(sacc[2], sc, -ms1))));
                wgmma_wait<0>();
                mbar_arrive_if(bar_ve + 8 * ((it - 1) & 1), lane0);
                float sum[4] = {0.f, 0.f, 0.f, 0.f};
#pragma unroll
                for (int i = 0; i < 64; i++) { sacc[i] = ex2f(fmaf(sacc[i], sc, (i & 2) ? -ms1 : -ms0)); sum[i & 3] += sacc[i]; }
                lrow0 = sum[0] + sum[1]; lrow1 = sum[2] + sum[3];
                pack_p();
                epilogue(item, t, l0, l1);
            }
            t = tn;
        }
        TS_END(1);
    }
}

__device__ __forceinline__ uint32_t cluster_ctarank() {
    uint32_t r; asm volatile("mov.u32 %0, %%cluster_ctarank;" : "=r"(r)); return r;
}
__device__ __forceinline__ uint32_t mapa_u32(uint32_t addr, uint32_t rank) {
    uint32_t r; asm volatile("mapa.shared::cluster.u32 %0, %1, %2;" : "=r"(r) : "r"(addr), "r"(rank)); return r;
}
__device__ __forceinline__ void cluster_sync_all() {
    asm volatile("barrier.cluster.arrive.release.aligned;\nbarrier.cluster.wait.acquire.aligned;" ::: "memory");
}
__device__ __forceinline__ void cluster_sync_relaxed() {
    asm volatile("barrier.cluster.arrive.relaxed.aligned;\nbarrier.cluster.wait.aligned;" ::: "memory");
}
__device__ __forceinline__ void st_async_v4(uint32_t addr, uint32_t a, uint32_t b, uint32_t c, uint32_t d, uint32_t mbar) {
    asm volatile("st.async.weak.shared::cluster.mbarrier::complete_tx::bytes.v4.b32 [%0], {%1, %2, %3, %4}, [%5];"
                 :: "r"(addr), "r"(a), "r"(b), "r"(c), "r"(d), "r"(mbar) : "memory");
}
__device__ __forceinline__ void st_async_v2(uint32_t addr, uint32_t a, uint32_t b, uint32_t mbar) {
    asm volatile("st.async.weak.shared::cluster.mbarrier::complete_tx::bytes.v2.b32 [%0], {%1, %2}, [%3];"
                 :: "r"(addr), "r"(a), "r"(b), "r"(mbar) : "memory");
}
__device__ __forceinline__ void st_async_b32(uint32_t addr, uint32_t a, uint32_t mbar) {
    asm volatile("st.async.weak.shared::cluster.mbarrier::complete_tx::bytes.b32 [%0], %1, [%2];" :: "r"(addr), "r"(a), "r"(mbar) : "memory");
}
__device__ __forceinline__ void pace(int cycles) {
    if (cycles > 0) {
        uint32_t t0, t;
        asm volatile("mov.u32 %0, %%clock;" : "=r"(t0));
        do { asm volatile("mov.u32 %0, %%clock;" : "=r"(t)); } while (t - t0 < (uint32_t)cycles);
    }
}
__device__ __forceinline__ void mbar_wait_cl(uint32_t bar, uint32_t parity) {
    uint32_t done = 0;
    for (int it = 0; it < (1 << 22) && !done; it++) {
        asm volatile(
            "{\n.reg .pred p;\n"
            "mbarrier.try_wait.parity.shared::cta.b64 p, [%1], %2;\n"
            "selp.u32 %0, 1, 0, p;\n}\n" : "=r"(done) : "r"(bar), "r"(parity) : "memory");
    }
}
__device__ __forceinline__ void ldmatrix_x4(uint32_t& r0, uint32_t& r1, uint32_t& r2, uint32_t& r3, uint32_t addr) {
    asm volatile("ldmatrix.sync.aligned.m8n8.x4.shared.b16 {%0,%1,%2,%3}, [%4];"
                 : "=r"(r0), "=r"(r1), "=r"(r2), "=r"(r3) : "r"(addr));
}
__device__ __forceinline__ void cp_async16(uint32_t dst, const void* src) {
    asm volatile("cp.async.cg.shared.global [%0], [%1], 16;" :: "r"(dst), "l"(src) : "memory");
}

#define DBG(i)
#define DBGW(i, w)
__device__ __forceinline__ void tma_load_2d_mc(uint32_t dst, const CUtensorMap* map, uint32_t bar, int c0, int c1, uint16_t mask) {
    asm volatile(
        "cp.async.bulk.tensor.2d.shared::cluster.global.mbarrier::complete_tx::bytes.multicast::cluster [%0], [%1, {%3, %4}], [%2], %5;"
        :: "r"(dst), "l"((uint64_t)map), "r"(bar), "r"(c0), "r"(c1), "h"(mask) : "memory");
}
__device__ __forceinline__ void bulk_s2s(uint32_t dst_cl, uint32_t src, uint32_t bytes, uint32_t bar_cl) {
    asm volatile("cp.async.bulk.shared::cluster.shared::cta.mbarrier::complete_tx::bytes [%0], [%1], %2, [%3];"
                 :: "r"(dst_cl), "r"(src), "r"(bytes), "r"(bar_cl) : "memory");
}
__device__ __forceinline__ bool elect_one() {
    uint32_t p;
    asm volatile("{\n.reg .pred p;\nelect.sync _|p, 0xffffffff;\nselp.u32 %0, 1, 0, p;\n}" : "=r"(p));
    return p;
}
__device__ __forceinline__ void fence_async_smem() { asm volatile("fence.proxy.async.shared::cta;" ::: "memory"); }
template <int ID, int N> __device__ __forceinline__ void bar_sync() { asm volatile("bar.sync %0, %1;" :: "n"(ID), "n"(N) : "memory"); }
template <int ID, int N> __device__ __forceinline__ void bar_arrive() { asm volatile("bar.arrive %0, %1;" :: "n"(ID), "n"(N) : "memory"); }
__device__ __forceinline__ void sts32(uint32_t a, uint32_t v) { asm volatile("st.shared.u32 [%0], %1;" :: "r"(a), "r"(v) : "memory"); }
__device__ __forceinline__ void ldsm_x4(uint32_t* r, uint32_t addr) {
    asm volatile("ldmatrix.sync.aligned.m8n8.x4.shared.b16 {%0,%1,%2,%3}, [%4];" : "=r"(r[0]), "=r"(r[1]), "=r"(r[2]), "=r"(r[3]) : "r"(addr) : "memory");
}
__device__ __forceinline__ uint32_t pin(uint32_t v) { asm volatile("" : "+r"(v)); return v; }
constexpr uint32_t DHI128 = 0x40000040u, DHI32 = 0xC0000010u;
#define ACC16(d) "+f"(d[0]), "+f"(d[1]), "+f"(d[2]), "+f"(d[3]), "+f"(d[4]), "+f"(d[5]), "+f"(d[6]), "+f"(d[7]), "+f"(d[8]), "+f"(d[9]), "+f"(d[10]), \
    "+f"(d[11]), "+f"(d[12]), "+f"(d[13]), "+f"(d[14]), "+f"(d[15])
#define ACC20(d) ACC16(d), "+f"(d[16]), "+f"(d[17]), "+f"(d[18]), "+f"(d[19])
__device__ __forceinline__ void wgmma_rs(float (&d)[16], const uint32_t (&a)[4], uint32_t db_lo) {
    asm volatile(
        "{\n.reg .b64 db;\nmov.b64 db, {%20, %21};\n"
        "wgmma.mma_async.sync.aligned.m64n32k16.f32.bf16.bf16 {%0,%1,%2,%3,%4,%5,%6,%7,%8,%9,%10,%11,%12,%13,%14,%15}, {%16,%17,%18,%19}, db, 1, 1, 1, 0;\n}\n"
        : ACC16(d) : "r"(a[0]), "r"(a[1]), "r"(a[2]), "r"(a[3]), "r"(db_lo), "n"(DHI128));
}
__device__ __forceinline__ void wgmma_rs(float (&d)[20], const uint32_t (&a)[4], uint32_t db_lo) {
    asm volatile(
        "{\n.reg .b64 db;\nmov.b64 db, {%24, %25};\n"
        "wgmma.mma_async.sync.aligned.m64n40k16.f32.bf16.bf16 {%0,%1,%2,%3,%4,%5,%6,%7,%8,%9,%10,%11,%12,%13,%14,%15,%16,%17,%18,%19}, {%20,%21,%22,%23}, db, 1, 1, 1, 0;\n}\n"
        : ACC20(d) : "r"(a[0]), "r"(a[1]), "r"(a[2]), "r"(a[3]), "r"(db_lo), "n"(DHI128));
}
template <uint32_t AHI, uint32_t BHI>
__device__ __forceinline__ void wgmma_ss(float (&d)[16], uint32_t da_lo, uint32_t db_lo) {
    asm volatile(
        "{\n.reg .b64 da, db;\nmov.b64 da, {%16, %18};\nmov.b64 db, {%17, %19};\n"
        "wgmma.mma_async.sync.aligned.m64n32k16.f32.bf16.bf16 {%0,%1,%2,%3,%4,%5,%6,%7,%8,%9,%10,%11,%12,%13,%14,%15}, da, db, 1, 1, 1, 0, 0;\n}\n"
        : ACC16(d) : "r"(da_lo), "r"(db_lo), "n"(AHI), "n"(BHI));
}
template <uint32_t AHI, uint32_t BHI>
__device__ __forceinline__ void wgmma_ss(float (&d)[20], uint32_t da_lo, uint32_t db_lo) {
    asm volatile(
        "{\n.reg .b64 da, db;\nmov.b64 da, {%20, %22};\nmov.b64 db, {%21, %23};\n"
        "wgmma.mma_async.sync.aligned.m64n40k16.f32.bf16.bf16 {%0,%1,%2,%3,%4,%5,%6,%7,%8,%9,%10,%11,%12,%13,%14,%15,%16,%17,%18,%19}, da, db, 1, 1, 1, 0, 0;\n}\n"
        : ACC20(d) : "r"(da_lo), "r"(db_lo), "n"(AHI), "n"(BHI));
}
__device__ __forceinline__ void wgmma_ss_n8(float (&d)[4], uint32_t da_lo, uint32_t db_lo) {
    asm volatile(
        "{\n.reg .b64 da, db;\nmov.b64 da, {%4, %6};\nmov.b64 db, {%5, %7};\n"
        "wgmma.mma_async.sync.aligned.m64n8k16.f32.bf16.bf16 {%0,%1,%2,%3}, da, db, 1, 1, 1, 1, 0;\n}\n"
        : "+f"(d[0]), "+f"(d[1]), "+f"(d[2]), "+f"(d[3]) : "r"(da_lo), "r"(db_lo), "n"(DHI128), "n"(DHI32));
}

constexpr uint32_t C2_WO = 0;
constexpr uint32_t C2_XB = 65536;
constexpr uint32_t C2_XS = 40960;
constexpr uint32_t C2_QX = C2_XB + 2 * C2_XS;
constexpr uint32_t C2_KX = C2_QX + 4096;
constexpr uint32_t C2_VT = C2_KX + 5120;
constexpr uint32_t C2_OB = C2_VT + 12288;
constexpr uint32_t C2_QM = C2_OB + 8192;
constexpr uint32_t C2_SC = C2_QM + 1024;
constexpr uint32_t C2_PB = C2_SC + 2560;
constexpr uint32_t C2_BAR = C2_PB + 768;
constexpr uint32_t C2_PX = C2_BAR + 256;
constexpr uint32_t C2_SX = C2_PX + 3072;
#define C2_NS 4
constexpr uint32_t C2_WS = C2_SX + 20480;
constexpr int C2_SMEM = C2_WS + 3 * C2_NS * 2048;
static_assert(C2_PX % 256 == 0 && C2_WS % 256 == 0 && C2_SMEM <= 232448, "smem map");
#define CH_PF 0
#define CH_PFD 3000
#define CH_POLL_DELAY 200

__device__ __forceinline__ uint32_t c2_stage(int wg, int i) { return wg < 2 ? C2_XB + C2_XS + (wg * 4 + i) * 8192 : ((C2_PX + 1023) & ~1023u) + i * 8192; }
static_assert(C2_XB + C2_XS + 8 * 8192 <= C2_BAR && ((C2_PX + 1023) & ~1023u) + 4 * 8192 <= C2_SMEM && (C2_XB + C2_XS) % 1024 == 0, "staging");
__device__ __forceinline__ void c2_stage_load(const CUtensorMap* map, uint32_t sb, int wg, int rank, int col0, int round) {
    const uint32_t bar = sb + C2_BAR + 176 + (wg * 2 + round) * 8;
    mbar_expect_tx(bar, 32768);
    for (int i = 0; i < 4; i++) tma_load_2d(sb + c2_stage(wg, i), map, bar, col0, ((rank - round * 4 - i) & 7) * 64);
}
__device__ __forceinline__ void c2_load_w(uint32_t (&w)[32][4], const CUtensorMap* map, int wg, int rank, int col0, uint32_t t128, uint32_t ws, uint32_t sb) {
#pragma unroll
    for (int r = 0; r < 2; r++) {
        mbar_wait(sb + C2_BAR + 176 + (wg * 2 + r) * 8, 0);
#pragma unroll
        for (int e = 0; e < 16; e++) {
            const uint32_t a = sb + c2_stage(wg, 0) + e * 2048;
            uint32_t w0, w1, w2, w3;
            asm volatile("ld.shared.b32 %0, [%1];" : "=r"(w0) : "r"(a + t128) : "memory");
            asm volatile("ld.shared.b32 %0, [%1];" : "=r"(w1) : "r"(a + (t128 ^ 16) + 128) : "memory");
            asm volatile("ld.shared.b32 %0, [%1];" : "=r"(w2) : "r"(a + t128 + 1024) : "memory");
            asm volatile("ld.shared.b32 %0, [%1];" : "=r"(w3) : "r"(a + (t128 ^ 16) + 1152) : "memory");
            uint32_t* d = w[r * 16 + e];
            d[0] = __byte_perm(w0, w1, 0x5410); d[1] = __byte_perm(w0, w1, 0x7632);
            d[2] = __byte_perm(w2, w3, 0x5410); d[3] = __byte_perm(w2, w3, 0x7632);
        }
        if (r == 0) {
            asm volatile("bar.sync %0, 128;" :: "r"(8 + wg) : "memory");
            if ((threadIdx.x & 127) == 32) c2_stage_load(map, sb, wg, rank, col0, 1);
            mbar_wait(sb + C2_BAR + 168, 0);
#pragma unroll 2
            for (int i = threadIdx.x; i < 2048; i += 384) {
                const int k = i >> 2, b = i & 3;
                const uint32_t a0 = sb + C2_WO + k * 128 + (((2 * b) ^ (k & 7)) << 4), a1 = a0 ^ 16;
                uint4 u, v;
                asm volatile("ld.shared.v4.b32 {%0, %1, %2, %3}, [%4];" : "=r"(u.x), "=r"(u.y), "=r"(u.z), "=r"(u.w) : "r"(a0) : "memory");
                asm volatile("ld.shared.v4.b32 {%0, %1, %2, %3}, [%4];" : "=r"(v.x), "=r"(v.y), "=r"(v.z), "=r"(v.w) : "r"(a1) : "memory");
                asm volatile("st.shared.v4.b32 [%0], {%1, %2, %3, %4};" :: "r"(a0), "r"(__byte_perm(u.x, u.y, 0x5410)),
                             "r"(__byte_perm(u.z, u.w, 0x5410)), "r"(__byte_perm(v.x, v.y, 0x5410)), "r"(__byte_perm(v.z, v.w, 0x5410)) : "memory");
                asm volatile("st.shared.v4.b32 [%0], {%1, %2, %3, %4};" :: "r"(a1), "r"(__byte_perm(u.x, u.y, 0x7632)),
                             "r"(__byte_perm(u.z, u.w, 0x7632)), "r"(__byte_perm(v.x, v.y, 0x7632)), "r"(__byte_perm(v.z, v.w, 0x7632)) : "memory");
            }
        }
    }
    cluster_sync_relaxed();
#pragma unroll
    for (int e = 0; e < C2_NS; e++) stmatrix_x4(ws + e * 2048, w[e][0], w[e][1], w[e][2], w[e][3]);
    for (int i = threadIdx.x; i < 2 * 512 + 256; i += 384)
        sts32(sb + (i < 1024 ? C2_VT + (i >> 9) * 6144 + 4096 + (i & 511) * 4 : C2_PX + 2048 + (i - 1024) * 4), 0u);
    fence_async_smem();
    asm volatile("bar.sync %0, 128;" :: "r"(8 + wg) : "memory");
}
template <int NA>
__device__ __forceinline__ void c2_xstream(float (&acc)[NA], const uint32_t (&w)[32][4], uint32_t xlo, uint32_t rank, uint32_t wslo) {
#pragma unroll
    for (int i = 0; i < NA; i++) acc[i] = 0.f;
    wgmma_fence();
#pragma unroll
    for (int e = 0; e < 32; e++) {
        if (e < C2_NS) wgmma_ss<DHI32, DHI128>(acc, wslo + e * 128, xlo + ((rank - (e >> 2)) & 7) * 320 + (e & 3) * 2);
        else wgmma_rs(acc, w[e], xlo + ((rank - (e >> 2)) & 7) * 320 + (e & 3) * 2);
    }
    wgmma_commit();
    wgmma_wait<0>();
}
__device__ __forceinline__ void c2_mma_slot(float (&a)[4][4], const uint32_t (&w)[32][4], int slot, const uint32_t* b, uint32_t ws) {
#pragma unroll
    for (int kk = 0; kk < 4; kk++) {
        const int e = slot * 4 + kk;
        if (e < C2_NS) {
            uint32_t t[4];
            ldsm_x4(t, ws + e * 2048);
            mma_16816(a[kk], t[0], t[1], t[2], t[3], b[2 * kk], b[2 * kk + 1]);
        } else mma_16816(a[kk], w[e][0], w[e][1], w[e][2], w[e][3], b[2 * kk], b[2 * kk + 1]);
    }
}
__device__ __forceinline__ constexpr int c2_grp(int i) { return i < 2 ? i : 1 + (i >> 1); }

struct ChainParams {
    CUtensorMap mapX;
    CUtensorMap mapM;
    CUtensorMap mapW[3];
    CUtensorMap mapWo;
};
__global__ void __cluster_dims__(8, 1, 1) __launch_bounds__(384, 1)
chain_kernel(const __grid_constant__ ChainParams P) {
    const CUtensorMap& mapX = P.mapX;
    extern __shared__ __align__(1024) uint8_t smem_chain[];
    const uint32_t sb = smem_u32(smem_chain);
    const uint32_t dlo = ((sb & 0x3FFFF) >> 4) | (1u << 16);
    const int tid = threadIdx.x, lane = tid & 31;
    const int warp = __shfl_sync(0xffffffff, tid >> 5, 0), wg = warp >> 2, w4 = warp & 3;
    const uint32_t rank = cluster_ctarank();
    const int C = blockIdx.x >> 3;
    const int h = C * 4 + (rank >> 1);
    const int g = lane >> 2, qc = lane & 3;
    pdl_launch_dependents();
    TS_BEGIN(2);
    const uint32_t bar_m = sb + C2_BAR, bar_o = bar_m + 64, bar_sc = bar_m + 128, bar_x = bar_m + 136, bar_sx = bar_m + 152;
    const uint32_t bar_w = bar_m + 168;
    const int col0 = h * HD + (rank & 1) * 64;
    if (tid == 0) {
        for (int j = 0; j < 5; j++) { mbar_init(bar_m + 8 * j, j ? 1 : 4); mbar_init(bar_o + 8 * j, j ? 1 : 4); }
        for (int j = 0; j < 12; j++) mbar_init(bar_sc + 8 * j, 1);
        asm volatile("fence.mbarrier_init.release.cluster;" ::: "memory");
    }
    __syncwarp();
    cluster_sync_relaxed();
    if (tid == 0) {
        mbar_expect_tx(bar_x, 32768 + 8192);
        tma_load_2d_mc(sb + C2_XB + rank * 5120, &mapX, bar_x, rank * 64, 0, (uint16_t)0xff);
        for (int j = 0; j < 8; j++) tma_load_2d(sb + C2_XB + j * 5120 + 4096, &P.mapM, bar_x, j * 64, 0);
        pace(CH_PFD);
        mbar_expect_tx(bar_w, 65536);
        for (int j = 0; j < 8; j++) tma_load_2d(sb + C2_WO + j * 8192, &P.mapWo, bar_w, rank * 64, C * 512 + ((rank - j) & 7) * 64);
    }
    if ((tid & 127) == 32) {
        pace(CH_PFD);
        c2_stage_load(&P.mapW[wg], sb, wg, rank, col0, 0);
        if (CH_PF)
            for (int i = 4; i < 8; i++)
                asm volatile("cp.async.bulk.prefetch.tensor.2d.L2.global [%0, {%1, %2}];" :: "l"((uint64_t)&P.mapW[wg]), "r"(col0), "r"((int)((rank - i) & 7) * 64) : "memory");
    }
    __syncwarp();

    const uint32_t t32 = w4 * 256 + qc * 64 + (((g >> 2) ^ (qc >> 1)) << 4) + (g & 3) * 4;
    const uint32_t t128 = qc * 256 + (((2 * w4 + (g >> 2)) ^ (2 * qc)) << 4) + (g & 3) * 4;
    const uint32_t a32 = (w4 * 16 + (lane & 15)) * 32 + (((lane >> 4) ^ ((lane >> 2) & 1)) << 4);
    const uint32_t ws = sb + C2_WS + wg * (C2_NS * 2048) + a32;
    uint32_t w[32][4];
    auto proj_mem = [&](float (&a)[4][4], int s) {
        uint32_t b[16];
#pragma unroll
        for (int i = 0; i < 16; i++) a[i >> 2][i & 3] = 0.f;
        const uint32_t par = (s & 1) ^ 1;
        const uint32_t l128 = (lane & 7) * 128 + (((lane >> 3) ^ (lane & 7)) << 4);
        const uint32_t mb = sb + C2_XB + (s & 1) * C2_XS + 4096;
        auto ldb = [&](uint32_t* bb, int i) {
            ldsm_x4(bb, mb + ((rank - i) & 7) * 5120 + l128);
            ldsm_x4(bb + 4, mb + ((rank - i) & 7) * 5120 + (l128 ^ 64));
        };
        mbar_wait(bar_m, par);
        ldb(b, 0);
        c2_mma_slot(a, w, 0, b, ws);
        mbar_wait(bar_m + 8, par);
        DBGW(1 + 16 * wg, 0);
        ldb(b, 1);
        uint32_t nxt = mbar_test(bar_m + 16, par);
        c2_mma_slot(a, w, 1, b, ws);
#pragma unroll
        for (int i = 2; i < 8; i += 2) {
            if (__builtin_expect(!nxt, 0)) mbar_wait(bar_m + 8 * c2_grp(i), par);
            if (i == 6) DBGW(2 + 16 * wg, 0);
            ldb(b, i);
            ldb(b + 8, i + 1);
            if (i < 6) nxt = mbar_test(bar_m + 8 * c2_grp(i + 2), par);
            c2_mma_slot(a, w, i, b, ws);
            c2_mma_slot(a, w, i + 1, b + 8, ws);
        }
#pragma unroll
        for (int i = 0; i < 4; i++) a[0][i] = (a[0][i] + a[1][i]) + (a[2][i] + a[3][i]);
    };
    auto store_x = [&](const float (&acc)[16], uint32_t base) {
#pragma unroll
        for (int j = 0; j < 4; j++) {
            sts32(base + t128 + j * 1024, pack_bf16(acc[4 * j], acc[4 * j + 2]));
            sts32(base + (t128 ^ 16) + 128 + j * 1024, pack_bf16(acc[4 * j + 1], acc[4 * j + 3]));
        }
    };
    const float scale = 0.08838834764831845f, l2e = 1.4426950408889634f;

    if (wg == 0) {
        c2_load_w(w, &P.mapW[0], 0, rank, col0, t128, ws, sb);
        TS_END(6);
        TS_BEGIN(5);
#pragma unroll 1
        for (int s = -1;;) {
            uint32_t xok = 0;
            if (s >= 0) {
                float acc[4] = {0.f, 0.f, 0.f, 0.f};
                const uint32_t tag = ((s >> 1) & 1) ^ 1;
                uint32_t* dst = reinterpret_cast<uint32_t*>(g_xbuf + (((s & 1) * 8 + rank) * 8 + C) * 128) + qc * 64 + w4 * 8 + g;
                asm volatile("" : "+l"(dst));
#pragma unroll
                for (int i = 0; i < 8; i++) {
                    if (i < 2 || !(i & 1)) {
                        mbar_wait(bar_o + 8 * c2_grp(i), s & 1);
                        if (i == 0) DBGW(7, 0);
                        if (i == 1) DBGW(8, 0);
                        if (i == 6) DBGW(9, 0);
                        wgmma_fence();
                    }
#pragma unroll
                    for (int kk = 0; kk < 4; kk++)
                        wgmma_ss_n8(acc, dlo + ((C2_WO + i * 8192 + kk * 2048) >> 4), dlo + ((C2_OB + i * 1024 + kk * 256) >> 4));
                }
                wgmma_commit();
                xok = mbar_test(bar_x + 8 * ((s + 1) & 1), ((s + 1) >> 1) & 1);
                wgmma_wait<0>();
                asm volatile("st.relaxed.gpu.global.u32 [%0], %1;" :: "l"(dst), "r"((pack_bf16(acc[0], acc[2]) & ~1u) | tag) : "memory");
                asm volatile("st.relaxed.gpu.global.u32 [%0 + 128], %1;" :: "l"(dst), "r"((pack_bf16(acc[1], acc[3]) & ~1u) | tag) : "memory");
                bar_arrive<4, 384>();
                DBGW(10, 0);
            }
            s++;
            if (__builtin_expect(!xok, 0)) mbar_wait(bar_x + 8 * (s & 1), (s >> 1) & 1);
            {
                float acc[16];
                c2_xstream(acc, w, dlo + ((C2_XB + (s & 1) * C2_XS) >> 4), rank, dlo + (C2_WS >> 4));
                if (s > 0) bar_sync<5, 256>();
                store_x(acc, sb + C2_QX);
            }
            DBGW(0, 0);
            if (s == NSEG - 1) break;
            const uint32_t sca = w4 < 2 ? sb + C2_SC + w4 * 512 + lane * 16 : sb + C2_SC + 1024 + lane * 8;
            const uint32_t sc_peer = pin(mapa_u32(sca + 1280, rank ^ 1)), sc_own = pin(mapa_u32(sca, rank));
            const uint32_t krow = w4 * 16 + (lane & 15);
            const uint32_t ka0 = pin(sb + C2_KX + krow * 128 + (((lane >> 4) ^ (krow & 7)) << 4));
            const uint32_t l32 = pin(sb + C2_QM + (lane >> 4) * 256 + (lane & 7) * 32 + ((((lane >> 3) & 1) ^ ((lane >> 2) & 1)) << 4));
            const uint32_t qst = pin(sb + C2_QM + t32);
            {
                float a[4][4];
                proj_mem(a, s);
                sts32(qst, pack_bf16(a[0][0], a[0][2]));
                sts32(qst + 32, pack_bf16(a[0][1], a[0][3]));
            }
            DBGW(3, 0);
            if (w4 < 3) {
                uint32_t ka[4][4], qb[8];
                float c[4] = {0.f, 0.f, 0.f, 0.f}, c2[4] = {0.f, 0.f, 0.f, 0.f};
                bar_sync<1, 384>();
                ldsm_x4(qb, l32);
                ldsm_x4(ka[0], ka0);
                ldsm_x4(ka[1], ka0 ^ 32);
                ldsm_x4(qb + 4, l32 + 512);
                ldsm_x4(ka[2], ka0 ^ 64);
                ldsm_x4(ka[3], ka0 ^ 96);
                mma_16816(c, ka[0][0], ka[0][1], ka[0][2], ka[0][3], qb[0], qb[1]);
                mma_16816(c2, ka[1][0], ka[1][1], ka[1][2], ka[1][3], qb[2], qb[3]);
                mma_16816(c, ka[2][0], ka[2][1], ka[2][2], ka[2][3], qb[4], qb[5]);
                mma_16816(c2, ka[3][0], ka[3][1], ka[3][2], ka[3][3], qb[6], qb[7]);
                const uint32_t u0 = __float_as_uint(c[0] + c2[0]), u1 = __float_as_uint(c[1] + c2[1]);
                const uint32_t u2 = __float_as_uint(c[2] + c2[2]), u3 = __float_as_uint(c[3] + c2[3]);
                asm volatile(
                    "{\n.reg .pred p;\nsetp.lt.u32 p, %8, 2;\n"
                    "@p st.async.weak.shared::cluster.mbarrier::complete_tx::bytes.v4.b32 [%0], {%4, %5, %6, %7}, [%1];\n"
                    "@!p st.async.weak.shared::cluster.mbarrier::complete_tx::bytes.v2.b32 [%0], {%4, %5}, [%1];\n"
                    "@p st.async.weak.shared::cluster.mbarrier::complete_tx::bytes.v4.b32 [%2], {%4, %5, %6, %7}, [%3];\n"
                    "@!p st.async.weak.shared::cluster.mbarrier::complete_tx::bytes.v2.b32 [%2], {%4, %5}, [%3];\n}"
                    :: "r"(sc_peer), "r"(mapa_u32(bar_sc, rank ^ 1)), "r"(sc_own), "r"(mapa_u32(bar_sc, rank)), "r"(u0), "r"(u1), "r"(u2), "r"(u3), "r"(w4) : "memory");
                bar_arrive<2, 224>();
                if (s >= 4 * CB_FIRST + 5 && (s & 3) == 1 && tid == 0) signal_ctr(CT_CB + ((s - 5) >> 2));
                __syncwarp();
                DBGW(4, 2);
            } else {
                bar_arrive<1, 384>();
                const uint32_t a = pin(sb + C2_SC + lane * 16), a2 = pin(sb + C2_SC + 1024 + lane * 8), pa = pin(sb + C2_PB + lane * 4);
                mbar_wait(bar_sc, s & 1);
                DBG(5);
                float v[10];
                {
                    float4 x0, x1, y0, y1; float2 x2, y2;
                    asm volatile("ld.shared.v4.f32 {%0, %1, %2, %3}, [%4];" : "=f"(x0.x), "=f"(x0.y), "=f"(x0.z), "=f"(x0.w) : "r"(a) : "memory");
                    asm volatile("ld.shared.v4.f32 {%0, %1, %2, %3}, [%4];" : "=f"(y0.x), "=f"(y0.y), "=f"(y0.z), "=f"(y0.w) : "r"(a + 1280) : "memory");
                    asm volatile("ld.shared.v4.f32 {%0, %1, %2, %3}, [%4];" : "=f"(x1.x), "=f"(x1.y), "=f"(x1.z), "=f"(x1.w) : "r"(a + 512) : "memory");
                    asm volatile("ld.shared.v4.f32 {%0, %1, %2, %3}, [%4];" : "=f"(y1.x), "=f"(y1.y), "=f"(y1.z), "=f"(y1.w) : "r"(a + 1792) : "memory");
                    asm volatile("ld.shared.v2.f32 {%0, %1}, [%2];" : "=f"(x2.x), "=f"(x2.y) : "r"(a2) : "memory");
                    asm volatile("ld.shared.v2.f32 {%0, %1}, [%2];" : "=f"(y2.x), "=f"(y2.y) : "r"(a2 + 1280) : "memory");
                    v[0] = x0.x + y0.x; v[1] = x0.y + y0.y; v[2] = x0.z + y0.z; v[3] = x0.w + y0.w;
                    v[4] = x1.x + y1.x; v[5] = x1.y + y1.y; v[6] = x1.z + y1.z; v[7] = x1.w + y1.w;
                    v[8] = x2.x + y2.x; v[9] = x2.y + y2.y;
                }
                float m0 = fmaxf(fmaxf(fmaxf(v[0], v[2]), fmaxf(v[4], v[6])), v[8]);
                float m1 = fmaxf(fmaxf(fmaxf(v[1], v[3]), fmaxf(v[5], v[7])), v[9]);
#pragma unroll
                for (int o = 4; o < 32; o <<= 1) {
                    m0 = fmaxf(m0, __shfl_xor_sync(0xffffffff, m0, o));
                    m1 = fmaxf(m1, __shfl_xor_sync(0xffffffff, m1, o));
                }
                const float sl = scale * l2e;
                m0 *= sl; m1 *= sl;
#pragma unroll
                for (int j = 0; j < 5; j++)
                    sts32(pa + j * 128, pack_bf16(ex2f(fmaf(v[2 * j], sl, -m0)), ex2f(fmaf(v[2 * j + 1], sl, -m1))));
                bar_arrive<3, 160>();
                DBG(6);
            }
            fence_async_smem();
            bar_arrive<6, 256>();
        }
        bar_sync<1, 384>();
        fence_async_smem();
        bar_arrive<6, 256>();
        bar_arrive<4, 384>();
    } else if (wg == 1) {
        c2_load_w(w, &P.mapW[1], 1, rank, col0, t128, ws, sb);
#pragma unroll 1
        for (int s = -1;;) {
            if (s > 0) {
                mbar_wait(bar_sx + 8 * ((s - 1) & 1), ((s - 1) >> 1) & 1);
                const uint32_t a = sb + C2_SX + ((s - 1) & 1) * 10240 + w4 * 1280 + lane * 8;
                float v[10];
                const int lim = 8 * w4 + g - 2 * qc;
#pragma unroll
                for (int j = 0; j < 5; j++) {
                    float2 x, y;
                    asm volatile("ld.shared.v2.f32 {%0, %1}, [%2];" : "=f"(x.x), "=f"(x.y) : "r"(a + j * 256) : "memory");
                    asm volatile("ld.shared.v2.f32 {%0, %1}, [%2];" : "=f"(y.x), "=f"(y.y) : "r"(a + 5120 + j * 256) : "memory");
                    v[2 * j] = (j < 4 && 8 * j > lim) ? -INFINITY : x.x + y.x;
                    v[2 * j + 1] = (j < 4 && 8 * j + 1 > lim) ? -INFINITY : x.y + y.y;
                }
                float mx = fmaxf(fmaxf(fmaxf(v[0], v[1]), fmaxf(v[2], v[3])), fmaxf(fmaxf(v[4], v[5]), fmaxf(v[6], v[7])));
                mx = fmaxf(mx, fmaxf(v[8], v[9]));
                mx = fmaxf(mx, __shfl_xor_sync(0xffffffff, mx, 1));
                mx = fmaxf(mx, __shfl_xor_sync(0xffffffff, mx, 2));
                const float sl = scale * l2e;
                mx *= sl;
#pragma unroll
                for (int j = 0; j < 10; j++) v[j] = ex2f(fmaf(v[j], sl, -mx));
                float sm = ((v[0] + v[1]) + (v[2] + v[3])) + ((v[4] + v[5]) + (v[6] + v[7])) + (v[8] + v[9]);
                sm += __shfl_xor_sync(0xffffffff, sm, 1);
                sm += __shfl_xor_sync(0xffffffff, sm, 2);
                float inv;
                asm("rcp.approx.ftz.f32 %0, %1;" : "=f"(inv) : "f"(sm));
                const uint32_t pa = sb + C2_PX + w4 * 256 + g * 32 + ((g >> 2) << 4) + qc * 4;
#pragma unroll
                for (int j = 0; j < 5; j++) sts32((pa ^ ((j & 1) << 4)) + (j >> 1) * 1024, pack_bf16(v[2 * j] * inv, v[2 * j + 1] * inv));
            }
            if (s >= 0) {
                fence_async_smem();
                if (s < NSEG) bar_sync<6, 256>(); else bar_sync<7, 128>();
                DBGW(20, 0);
                if (s < NSEG - 1) mbar_wait(bar_o, s & 1);
                if (s < NSEG) {
                    float sx[20];
#pragma unroll
                    for (int i = 0; i < 20; i++) sx[i] = 0.f;
                    wgmma_fence();
#pragma unroll
                    for (int kk = 0; kk < 4; kk++) wgmma_ss<DHI128, DHI128>(sx, dlo + (C2_QX >> 4) + kk * 2, dlo + (C2_KX >> 4) + kk * 2);
                    wgmma_commit();
                    wgmma_wait<0>();
                    if (s < NSEG - 1) bar_arrive<5, 256>();
                    if (w4 < 2) {
                        const uint32_t a = sb + C2_SX + (s & 1) * 10240 + w4 * 2560 + lane * 8;
#pragma unroll
                        for (int j = 0; j < 5; j++) {
                            asm volatile("st.shared.v2.f32 [%0], {%1, %2};" :: "r"(a + j * 256), "f"(sx[4 * j]), "f"(sx[4 * j + 1]) : "memory");
                            asm volatile("st.shared.v2.f32 [%0], {%1, %2};" :: "r"(a + 1280 + j * 256), "f"(sx[4 * j + 2]), "f"(sx[4 * j + 3]) : "memory");
                        }
                    }
                }
                DBGW(21, 0);
                if (s > 0) {
                    float cx[16];
#pragma unroll
                    for (int i = 0; i < 16; i++) cx[i] = 0.f;
                    wgmma_fence();
#pragma unroll
                    for (int kk = 0; kk < 3; kk++)
                        wgmma_ss<DHI32, DHI32>(cx, dlo + ((C2_VT + ((s - 1) & 1) * 6144 + kk * 2048) >> 4), dlo + ((C2_PX + kk * 1024) >> 4));
                    wgmma_commit();
                    wgmma_wait<0>();
                    uint32_t* dst = reinterpret_cast<uint32_t*>(g_ctxB + ((size_t)h * SEQ + (s - 1) * SEGL + 2 * qc) * HD + (rank & 1) * 64 + w4 * 16 + 2 * g);
#pragma unroll
                    for (int j = 0; j < 4; j++) {
                        dst[j * 8 * (HD / 2)] = pack_bf16(cx[4 * j], cx[4 * j + 2]);
                        dst[(j * 8 + 1) * (HD / 2)] = pack_bf16(cx[4 * j + 1], cx[4 * j + 3]);
                    }
                }
                DBGW(22, 0);
                if (s == NSEG) break;
                fence_async_smem();
            }
            if (s < NSEG - 1) mbar_wait(bar_x + 8 * ((s + 1) & 1), ((s + 1) >> 1) & 1);
            if (s >= 0) bar_sync<4, 384>();
            s++;
            if (s < NSEG) {
                {
                    float acc[16];
                    c2_xstream(acc, w, dlo + ((C2_XB + (s & 1) * C2_XS) >> 4), rank, dlo + ((C2_WS + C2_NS * 2048) >> 4));
                    store_x(acc, sb + C2_KX);
                }
                DBGW(16, 0);
                const uint32_t kst = pin(sb + C2_KX + 4096 + t128);
                float a[4][4];
                proj_mem(a, s);
                sts32(kst, pack_bf16(a[0][0], a[0][2]));
                sts32((kst ^ 16) + 128, pack_bf16(a[0][1], a[0][3]));
                bar_arrive<1, 384>();
                DBGW(19, 0);
                if (w4 == 0) {
                    if (s < NSEG - 1) {
                        if (lane == 0) mbar_expect_tx(bar_sc, 2560);
                        if (lane < 16 && (lane & 7) >= 1 && (lane & 7) < 5) mbar_expect_tx(bar_m + 8 * lane, (lane & 7) == 1 ? 1024 : 2048);
                        if (lane == 8) {
                            mbar_expect_tx(bar_x + 8 * ((s + 1) & 1), 32768);
                            tma_load_2d_mc(sb + C2_XB + ((s + 1) & 1) * C2_XS + rank * 5120, &mapX, bar_x + 8 * ((s + 1) & 1), rank * 64, (s + 1) * SEGL, (uint16_t)0xff);
                            if (s + 2 < NSEG)
                                asm volatile("cp.async.bulk.prefetch.tensor.2d.L2.global [%0, {%1, %2}];" :: "l"((uint64_t)&mapX), "r"(rank * 64), "r"((s + 2) * SEGL) : "memory");
                        }
                    }
                    if (lane == 16) mbar_expect_tx(bar_sx + 8 * (s & 1), 5120);
                    __syncwarp();
                }
            }
        }
        bar_sync<7, 128>();
        if (tid == 128) signal_ctr(CT_CB + 15);
    } else {
        c2_load_w(w, &P.mapW[2], 2, rank, col0, t128, ws, sb);
#pragma unroll 1
        for (int s = -1;;) {
            if (s >= 0) {
                const int t = tid - 256;
                const uint2* src = g_xbuf + ((s & 1) * 8 + rank) * 1024 + t;
                asm volatile("" : "+l"(src));
                const uint32_t ma = sb + C2_XB + ((s + 1) & 1) * C2_XS + rank * 5120 + 4096 + (t >> 4) * 128 + ((((t >> 1) & 7) ^ (t >> 4)) << 4) + (t & 1) * 8;
                uint32_t ra[8], rb[8];
#pragma unroll
                for (int i = 1; i < 8; i++) {
                    const uint32_t d = (rank + i) & 7;
                    ra[i] = pin(mapa_u32(ma, d)); rb[i] = pin(mapa_u32(bar_m + 8 * c2_grp(i), d));
                }
                bar_sync<4, 384>();
                DBGW(29, 0);
                if (tid == 256) {
                    const uint32_t a = sb + C2_SX + (s & 1) * 10240;
                    bulk_s2s(mapa_u32(a + 5120, rank ^ 1), a, 5120, mapa_u32(bar_sx + 8 * (s & 1), rank ^ 1));
                }
                if (s == NSEG - 1) break;
                pace(CH_POLL_DELAY);
                const uint32_t tag = ((s >> 1) & 1) ^ 1;
                uint32_t p[8][2];
                for (int it = 0; it < (1 << 20); it++) {
#pragma unroll
                    for (int k = 0; k < 8; k++)
                        asm volatile("ld.relaxed.gpu.global.v2.u32 {%0, %1}, [%2];" : "=r"(p[k][0]), "=r"(p[k][1]) : "l"(src + k * 128) : "memory");
                    uint32_t bad[8];
#pragma unroll
                    for (int k = 0; k < 8; k++) asm("lop3.b32 %0, %1, %2, %3, 0x7e;" : "=r"(bad[k]) : "r"(p[k][0]), "r"(p[k][1]), "r"(tag));
                    asm("lop3.b32 %0, %0, %1, %2, 0xfe;" : "+r"(bad[0]) : "r"(bad[1]), "r"(bad[2]));
                    asm("lop3.b32 %0, %0, %1, %2, 0xfe;" : "+r"(bad[3]) : "r"(bad[4]), "r"(bad[5]));
                    asm("lop3.b32 %0, %0, %1, %2, 0xfe;" : "+r"(bad[0]) : "r"(bad[3]), "r"(bad[6]));
                    asm("lop3.b32 %0, %0, %1, 1, 0xa8;" : "+r"(bad[0]) : "r"(bad[7]));
                    if (__all_sync(0xffffffff, bad[0] == 0u)) break;
                }
                DBGW(30, 0);
                float r[4];
#pragma unroll
                for (int e = 0; e < 2; e++) {
                    float lo[8], hi[8];
#pragma unroll
                    for (int k = 0; k < 8; k++) { lo[k] = __uint_as_float(p[k][e] << 16); hi[k] = __uint_as_float(p[k][e] & 0xffff0000u); }
                    r[2 * e] = ((lo[0] + lo[1]) + (lo[2] + lo[3])) + ((lo[4] + lo[5]) + (lo[6] + lo[7]));
                    r[2 * e + 1] = ((hi[0] + hi[1]) + (hi[2] + hi[3])) + ((hi[4] + hi[5]) + (hi[6] + hi[7]));
                }
                const uint32_t m0 = pack_bf16(r[0], r[1]), m1 = pack_bf16(r[2], r[3]);
                st_async_v2(ra[1], m0, m1, rb[1]);
                asm volatile("st.shared.v2.b32 [%0], {%1, %2};" :: "r"(ma), "r"(m0), "r"(m1) : "memory");
                __syncwarp();
                if (lane == 0) mbar_arrive(bar_m);
#pragma unroll
                for (int i = 2; i < 8; i++) st_async_v2(ra[i], m0, m1, rb[i]);
                DBGW(31, 0);
            }
            s++;
            const uint32_t ost = pin(sb + C2_OB + t32), pla = pin(sb + C2_PB + lane * 16), plb = pin(sb + C2_PB + 512 + (lane & 7) * 16);
            bar_sync<1, 384>();
            fence_async_smem();
            DBGW(24, 0);
            if (s < NSEG - 1) bar_sync<2, 224>();
            uint32_t va[5][2];
            {
                float acc[20];
                c2_xstream(acc, w, dlo + ((C2_XB + (s & 1) * C2_XS) >> 4), rank, dlo + ((C2_WS + 2 * C2_NS * 2048) >> 4));
#pragma unroll
                for (int j = 0; j < 5; j++) { va[j][0] = pack_bf16(acc[4 * j], acc[4 * j + 1]); va[j][1] = pack_bf16(acc[4 * j + 2], acc[4 * j + 3]); }
            }
            DBGW(26, 0);
            if (s < NSEG - 1) {
                uint32_t p[5];
                bar_sync<3, 160>();
                DBGW(27, 0);
                ldmatrix_x4_trans(p[0], p[1], p[2], p[3], pla);
                asm volatile("ldmatrix.sync.aligned.m8n8.x1.trans.shared.b16 {%0}, [%1];" : "=r"(p[4]) : "r"(plb) : "memory");
                float oa[4] = {0.f, 0.f, 0.f, 0.f}, ob[4] = {0.f, 0.f, 0.f, 0.f}, sa[4] = {0.f, 0.f, 0.f, 0.f}, sc[4] = {0.f, 0.f, 0.f, 0.f};
                const uint32_t one = 0x3f803f80u;
                mma_16816(sa, one, one, one, one, p[0], p[1]);
                mma_16816(oa, va[0][0], va[0][1], va[1][0], va[1][1], p[0], p[1]);
                mma_16816(sc, one, one, one, one, p[2], p[3]);
                mma_16816(ob, va[2][0], va[2][1], va[3][0], va[3][1], p[2], p[3]);
                mma_16816(sa, one, one, one, one, p[4], 0u);
                mma_16816(oa, va[4][0], va[4][1], 0u, 0u, p[4], 0u);
                float i0, i1;
                asm("rcp.approx.ftz.f32 %0, %1;" : "=f"(i0) : "f"(sa[0] + sc[0]));
                asm("rcp.approx.ftz.f32 %0, %1;" : "=f"(i1) : "f"(sa[1] + sc[1]));
                sts32(ost, pack_bf16((oa[0] + ob[0]) * i0, (oa[2] + ob[2]) * i0));
                sts32(ost + 32, pack_bf16((oa[1] + ob[1]) * i1, (oa[3] + ob[3]) * i1));
                fence_async_smem();
                __syncwarp();
                if (elect_one()) {
#pragma unroll
                    for (int i = 1; i < 8; i++) {
                        const uint32_t d = (rank + i) & 7;
                        bulk_s2s(mapa_u32(sb + C2_OB + i * 1024 + w4 * 256, d), sb + C2_OB + w4 * 256, 256, mapa_u32(bar_o + 8 * c2_grp(i), d));
                        if (i == 1) mbar_arrive(bar_o);
                    }
                }
                __syncwarp();
                DBGW(28, 0);
            }
            {
                const uint32_t a = sb + C2_VT + (s & 1) * 6144 + a32;
                stmatrix_x4(a, va[0][0], va[0][1], va[1][0], va[1][1]);
                stmatrix_x4(a + 2048, va[2][0], va[2][1], va[3][0], va[3][1]);
                asm volatile("stmatrix.sync.aligned.m8n8.x2.shared.b16 [%0], {%1, %2};" :: "r"(a + 4096), "r"(va[4][0]), "r"(va[4][1]) : "memory");
            }
            fence_async_smem();
        }
        g_xbuf[((8 + rank) * 8 + C) * 128 + (tid - 256)] = make_uint2(0u, 0u);
    }
    cluster_sync_relaxed();
    TS_END(2);
}

struct Proj2Params {
    CUtensorMap mapA[2];
    CUtensorMap mapW[3];
    bf16* out[3];
};
#define P2T(i)
#define P2_NOMMA 0
#define P2_NOLOAD 0
constexpr int P2_STAGES = 6;
constexpr int P2_SMEM = 131072 + P2_STAGES * 16384 + 1024 + 1024;
constexpr int P2_ITEMS = 168 + 48;
__device__ __forceinline__ int p2_reps(int t) { return t >= 168 ? 1 : 2; }
__device__ __forceinline__ void p2_tile(int t, int w, int& z, int& mp, int& head) {
    if (t >= 168) { w += ((t - 168) & 1) * 2; t = 168 + ((t - 168) >> 1); }
    const int hq = t / 24, v = t % 24;
    mp = v & 7;
    if (v < 16) { head = hq * 4 + (v >> 3) * 2 + (w >> 1); z = 1 + (w & 1); }
    else { head = hq * 4 + w; z = 0; }
}
__device__ __forceinline__ void mbar_arrive_remote(uint32_t bar_cluster_addr) {
    asm volatile("mbarrier.arrive.release.cluster.shared::cluster.b64 _, [%0];" :: "r"(bar_cluster_addr) : "memory");
}
__device__ __forceinline__ void mbar_arrive_cl(uint32_t bar_cluster_addr) {
    asm volatile("mbarrier.arrive.shared::cluster.b64 _, [%0];" :: "r"(bar_cluster_addr) : "memory");
}
__device__ __forceinline__ void mbar_wait_acq_cluster(uint32_t bar, uint32_t parity) {
    asm volatile(
        "{\n"
        ".reg .pred p, q;\n"
        ".reg .u32 c;\n"
        "mov.u32 c, 0;\n"
        "WAIT_LOOP_C:\n"
        "mbarrier.try_wait.parity.acquire.cluster.shared::cta.b64 p, [%0], %1;\n"
        "@p bra WAIT_DONE_C;\n"
        "add.u32 c, c, 1;\n"
        "setp.lt.u32 q, c, 4000000;\n"
        "@q bra WAIT_LOOP_C;\n"
        "WAIT_DONE_C:\n"
        "}\n" :: "r"(bar), "r"(parity) : "memory");
}
__device__ __forceinline__ uint4 quad_transpose(uint32_t p0, uint32_t p1, uint32_t p2, uint32_t p3, int lane) {
    const bool o1 = lane & 1, o2 = lane & 2;
    uint32_t s0 = o1 ? p0 : p1, s1 = o1 ? p2 : p3;
    s0 = __shfl_xor_sync(0xffffffff, s0, 1); s1 = __shfl_xor_sync(0xffffffff, s1, 1);
    const uint32_t a_lo = o1 ? s0 : p0, a_hi = o1 ? p1 : s0, b_lo = o1 ? s1 : p2, b_hi = o1 ? p3 : s1;
    uint32_t t0 = o2 ? a_lo : b_lo, t1 = o2 ? a_hi : b_hi;
    t0 = __shfl_xor_sync(0xffffffff, t0, 2); t1 = __shfl_xor_sync(0xffffffff, t1, 2);
    return o2 ? make_uint4(t0, t1, b_lo, b_hi) : make_uint4(a_lo, a_hi, t0, t1);
}
#define P2_PACE 35
#define P2_PACE2 0
template <bool PERM, int PACE = 0>
__device__ __forceinline__ void store_frag_128(const float (&acc)[64], bf16* obase, int lane) {
#pragma unroll
    for (int rr = 0; rr < 2; rr++)
#pragma unroll
        for (int g = 0; g < 4; g++) {
            const float* a = &acc[g * 16 + rr * 2];
            const uint32_t p0 = pack_bf16(a[0], a[1]), p1 = pack_bf16(a[4], a[5]), p2 = pack_bf16(a[8], a[9]), p3 = pack_bf16(a[12], a[13]);
            *reinterpret_cast<uint4*>(obase + (size_t)(rr * 8) * HD + g * 32) = PERM ? make_uint4(p0, p1, p2, p3) : quad_transpose(p0, p1, p2, p3, lane);
            pace(PACE);
        }
}
__global__ void __cluster_dims__(2, 1, 1) __launch_bounds__(384, 1) proj2_kernel(const __grid_constant__ Proj2Params P) {
    extern __shared__ uint8_t smem_raw[];
    const uint32_t sbase = (smem_u32(smem_raw) + 1023) & ~1023u;
    const uint32_t sA = sbase, sB = sbase + 131072, sC = sB + P2_STAGES * 16384;
    const uint32_t bars = sC;
    const uint32_t a_full = bars, a_empty = bars + 64, b_full = bars + 128, b_empty = b_full + 8 * P2_STAGES;
    const uint32_t item_bar = b_empty + 8 * P2_STAGES, item_in = item_bar + 16, slot = item_in + 16;
    const uint32_t note_bar = slot + 16, note_free = note_bar + 64, note = note_free + 64;
    const int warp = threadIdx.x >> 5, lane = threadIdx.x & 31;
    const uint32_t rank = cluster_ctarank();
    TS_BEGIN(0);
    if (threadIdx.x == 0) {
        for (int i = 0; i < 8; i++) { mbar_init(a_full + 8 * i, 1); mbar_init(a_empty + 8 * i, 2); }
        for (int i = 0; i < P2_STAGES; i++) { mbar_init(b_full + 8 * i, 1); mbar_init(b_empty + 8 * i, 2); }
        mbar_init(item_bar, 1); mbar_init(item_bar + 8, 1); mbar_init(item_in, 2); mbar_init(item_in + 8, 2);
        for (int i = 0; i < 8; i++) { mbar_init(note_bar + 8 * i, 1); mbar_init(note_free + 8 * i, 1); }
        asm volatile("fence.mbarrier_init.release.cluster;" ::: "memory");
    }
    __syncwarp();
    cluster_sync_relaxed();
    pdl_launch_dependents();
    if (warp == 9) {
        if (lane == 0) {
            for (int n = 0;; n++) {
                const int e = (n & 1) * 4 + ((n >> 1) & 3);
                mbar_wait(note_bar + 8 * e, (n >> 3) & 1);
                int m;
                asm volatile("ld.shared.s32 %0, [%1];" : "=r"(m) : "r"(note + e * 4) : "memory");
                mbar_arrive(note_free + 8 * e);
                if (m < 0) break;
                signal_ctr(m);
            }
        }
    } else if (warp == 10) {
        if (lane == 0) {
            auto publish = [&](int ic, int tq) {
                const int t = tq < P2_ITEMS ? tq : -1;
                asm volatile("st.shared.s32 [%0], %1;" :: "r"(slot + (ic & 3) * 4), "r"(t) : "memory");
                mbar_arrive(item_bar + 8 * (ic & 1));
                st_async_b32(mapa_u32(slot + (ic & 3) * 4, 1), (uint32_t)t, mapa_u32(item_bar + 8 * (ic & 1), 1));
            };
            const int npair = (int)(gridDim.x >> 1), pair = (int)(blockIdx.x >> 1);
            if (rank == 0) publish(0, pair);
            for (int ic = 0;; ic++) {
                if (rank == 1) mbar_expect_tx(item_bar + 8 * (ic & 1), 4);
                mbar_wait(item_bar + 8 * (ic & 1), (ic >> 1) & 1);
                int t;
                asm volatile("ld.shared.s32 %0, [%1];" : "=r"(t) : "r"(slot + (ic & 3) * 4) : "memory");
                if (t < 0) break;
                int z0, mp, h0;
                p2_tile(t, 0, z0, mp, h0);
                const int aidx = z0 >= 1 ? 1 : 0;
                const int m0 = (2 * mp + (int)rank) * 128;
                for (int k = 0; k < 8; k++) {
                    mbar_wait(a_empty + 8 * k, (ic & 1) ^ 1);
                    if (P2_NOLOAD) mbar_arrive(a_full + 8 * k); else {
                    mbar_expect_tx(a_full + 8 * k, 16384);
                    tma_load_2d(sA + k * 16384, &P.mapA[aidx], a_full + 8 * k, k * 64, m0); }
                }
                if (rank == 0) {
                    mbar_wait(item_in + 8 * (ic & 1), (ic >> 1) & 1);
                    publish(ic + 1, ic == 0 ? npair + pair : 2 * npair + (int)atomicAdd(&g_ctr[CT_PROJ], 1u));
                }
            }
        }
    } else if (warp == 8 || warp == 11) {
        if (lane == 0) {
            const int par2 = warp == 8 ? 0 : 1;
            int it = 0; uint32_t bph = 0;
            for (int ic = 0;; ic++) {
                mbar_wait(item_bar + 8 * (ic & 1), (ic >> 1) & 1);
                int t;
                asm volatile("ld.shared.s32 %0, [%1];" : "=r"(t) : "r"(slot + (ic & 3) * 4) : "memory");
                if (t < 0) break;
                const int nt = 2 * p2_reps(t);
                for (int w = 0; w < nt; w++) {
                    int z, mp, hd;
                    p2_tile(t, w, z, mp, hd);
                    for (int k = 0; k < 8; k++) {
                        const int s = it; const uint32_t phb = bph;
                        if (++it == P2_STAGES) { it = 0; bph ^= 1; }
                        if ((k & 1) != par2) continue;
                        mbar_wait(b_empty + 8 * s, phb ^ 1);
                        if (P2_NOLOAD) { mbar_arrive(b_full + 8 * s); continue; }
                        mbar_expect_tx(b_full + 8 * s, 16384);
                        tma_load_2d_mc(sB + s * 16384 + rank * 8192, &P.mapW[z], b_full + 8 * s, hd * 128 + (int)rank * 64, k * 64, (uint16_t)3);
                    }
                }
            }
        }
    } else {
        const int wg = warp >> 2;
        float acc[2][64];
        const uint32_t a_lo = desc_lo(sA, 16), b_lo0 = desc_lo(sB, 8192);
        const bool elected = (threadIdx.x & 127) == 0;
        int s = (wg * 8) % P2_STAGES;
        uint32_t ph = ((wg * 8) / P2_STAGES) & 1;
        int nnote = 0;
        if (wg == 1) asm volatile("bar.arrive 3, 256;" ::: "memory");
        for (int ic = 0;; ic++) {
            mbar_wait(item_bar + 8 * (ic & 1), (ic >> 1) & 1);
            int t;
            asm volatile("ld.shared.s32 %0, [%1];" : "=r"(t) : "r"(slot + (ic & 3) * 4) : "memory");
            P2T(7);
            if (wg == 0 && t < 0) {
                if (elected) {
                    const int e = nnote & 3;
                    mbar_wait(note_free + 8 * e, ((nnote >> 2) & 1) ^ 1);
                    asm volatile("st.shared.s32 [%0], %1;" :: "r"(note + e * 4), "r"(-1) : "memory");
                    mbar_arrive(note_bar + 8 * e);
                }
            }
            if (t < 0) break;
            const int reps = p2_reps(t);
#pragma unroll 1
            for (int rp = 0; rp < reps; rp++) {
            const bool first = rp == 0, last = rp == reps - 1;
            int z, mp, head;
            p2_tile(t, rp * 2 + wg, z, mp, head);
            asm volatile("bar.sync %0, 256;" :: "r"(3 + wg) : "memory");
            P2T(0);
            if (wg == 1 && last && elected) mbar_arrive_cl(mapa_u32(item_in + 8 * (ic & 1), 0));
            int sprev = 0;
#pragma unroll
            for (int k = 0; k < 8; k++) {
                if (k == 0) P2T(5);
                if (wg == 0 && first) mbar_wait(a_full + 8 * k, ic & 1);
                if (k == 0) P2T(6);
                mbar_wait(b_full + 8 * s, ph);
                if (k == 7) asm volatile("bar.arrive %0, 256;" :: "r"(4 - wg) : "memory");
                if (k == 0) P2T(1);
                if (k == 7) P2T(2);
                const uint32_t b_lo = b_lo0 + s * 1024;
                wgmma_fence();
#pragma unroll
                for (int kk = 0; kk < (P2_NOMMA ? 1 : 4); kk++) {
                    wgmma_ss_n128_lo<1>(acc[0], a_lo + k * 1024 + kk * 2, b_lo + kk * 128, (k | kk) != 0);
                    wgmma_ss_n128_lo<1>(acc[1], a_lo + k * 1024 + 512 + kk * 2, b_lo + kk * 128, (k | kk) != 0);
                }
                wgmma_commit();
                if (k > 0) {
                    wgmma_wait<1>();
                    if (elected) {
                        const uint32_t e = b_empty + 8 * sprev;
                        mbar_arrive_cl(mapa_u32(e, 0)); mbar_arrive_cl(mapa_u32(e, 1));
                        if (last) mbar_arrive(a_empty + 8 * (k - 1));
                    }
                }
                sprev = s;
                if (++s == P2_STAGES) { s = 0; ph ^= 1; }
            }
            wgmma_wait<0>();
            P2T(3);
            if (elected) {
                const uint32_t e = b_empty + 8 * sprev;
                mbar_arrive_cl(mapa_u32(e, 0)); mbar_arrive_cl(mapa_u32(e, 1));
                if (last) mbar_arrive(a_empty + 8 * 7);
            }
            s += 8 % P2_STAGES; ph ^= (8 / P2_STAGES) & 1;
            if (s >= P2_STAGES) { s -= P2_STAGES; ph ^= 1; }
            const int m0 = (2 * mp + (int)rank) * 128;
            bf16* obase = P.out[z] + ((size_t)head * SEQ + m0 + (warp & 3) * 16 + (lane >> 2)) * HD + (lane & 3) * 8;
            store_frag_128<true, P2_PACE>(acc[0], obase, lane); store_frag_128<true, P2_PACE>(acc[1], obase + (size_t)64 * HD, lane);
            P2T(4);
            {
                asm volatile("bar.sync %0, 128;" :: "r"(1 + wg) : "memory");
                if (elected) {
                    const int e = wg * 4 + (nnote & 3);
                    mbar_wait(note_free + 8 * e, ((nnote >> 2) & 1) ^ 1);
                    asm volatile("st.shared.s32 [%0], %1;" :: "r"(note + e * 4), "r"(CT_AP + (head >> 1)) : "memory");
                    mbar_arrive(note_bar + 8 * e);
                }
                nnote++;
            }
            }
        }
        TS_END(0);
    }
    __syncwarp();
    cluster_sync_relaxed();
}

struct OutParams {
    CUtensorMap mapCtx[2];
    CUtensorMap mapWo[2];
    CUtensorMap mapOut;
};
__device__ uint4 g_part[4 * 32 * 8 * 16 * 32];

#define OT(i)
#define OTP(i)
#define O3_LK 16
#define O3_LK15 20
#define O3_D 5
constexpr int O3_E = 68, O3_GRID = O3_E + 64;
constexpr int O2_SMEM = 196608 + 1024 + 256;

__global__ void __cluster_dims__(2, 1, 1) __launch_bounds__(352, 1) out3_kernel(const __grid_constant__ OutParams P) {
    extern __shared__ uint8_t smem_raw[];
    const uint32_t sbase = (smem_u32(smem_raw) + 1023) & ~1023u;
    const uint32_t bar_full = sbase + 196608, bar_empty = bar_full + 64;
    const int warp = threadIdx.x >> 5, lane = threadIdx.x & 31;
    const uint32_t rank = cluster_ctarank();
    const int pair = blockIdx.x >> 1;
    const bool early = pair < O3_E / 2;
    constexpr int EB = 64 - O3_LK, EB15 = 64 - O3_LK15;
    int mt, part, a0, na, b0, nb;
    if (pair < 30) {
        part = pair >= 15; mt = part ? 29 - pair : pair;
        const int d = (14 - mt) * O3_D / 14;
        a0 = part ? 32 + d : 0; na = part ? 32 - d : 32 + d;
        b0 = part ? EB / 2 : 0; nb = part ? EB - EB / 2 : EB / 2;
    } else if (early) {
        part = pair - 30; mt = 15;
        a0 = part * 16; na = 16;
        b0 = part * EB15 / 4; nb = (part + 1) * EB15 / 4 - b0;
    } else {
        part = (pair - O3_E / 2) & 1; mt = (pair - O3_E / 2) >> 1;
        a0 = 0; na = 0; b0 = mt == 15 ? EB15 : EB; nb = 64 - b0;
    }
    const int m0 = mt * 128, nk = na + nb;
    const int n0 = early ? (int)rank * 256 : part * 256 + (int)rank * 128;
    const int nst = early ? 4 : 6;
    const uint32_t ssz = early ? 49152 : 32768;
    TS_BEGIN(4);
    OT(0);
    if (threadIdx.x == 0) {
        for (int i = 0; i < 6; i++) { mbar_init(bar_full + 8 * i, 1); mbar_init(bar_empty + 8 * i, 4); }
        asm volatile("fence.mbarrier_init.release.cluster;" ::: "memory");
    }
    if (threadIdx.x == 256) asm volatile("prefetch.tensormap [%0];" :: "l"((uint64_t)&P.mapCtx[early ? 0 : 1]) : "memory");
    if (threadIdx.x == 288) asm volatile("prefetch.tensormap [%0];" :: "l"((uint64_t)&P.mapWo[early ? 0 : 1]) : "memory");
    if (warp == 0 || warp > 8) asm volatile("bar.sync 1, 96;" ::: "memory");
    __syncwarp();
    asm volatile("barrier.cluster.arrive.relaxed.aligned;" ::: "memory");
    if (warp > 8) {
        if (lane == 0) {
            int s = 0; uint32_t ph = 0;
            for (int i = 0; i < nk; i++) {
                if (i >= nst) mbar_wait(bar_empty + 8 * s, ph ^ 1);
                const uint32_t sa = sbase + s * ssz + 16384;
                const int b = i >= na, k = b ? b0 + i - na : a0 + i;
                if (early) {
                    tma_load_2d(sa + (warp - 9) * 16384, &P.mapWo[b], bar_full + 8 * s, n0 + (warp - 9) * 128, k * 64);
                    tma_load_2d(sa + (warp - 9) * 16384 + 8192, &P.mapWo[b], bar_full + 8 * s, n0 + (warp - 9) * 128 + 64, k * 64);
                } else tma_load_2d(sa + (warp - 9) * 8192, &P.mapWo[1], bar_full + 8 * s, n0 + (warp - 9) * 64, k * 64);
                if (++s == nst) { s = 0; ph ^= 1; }
            }
        }
        __syncwarp();
        asm volatile("barrier.cluster.wait.acquire.aligned;" ::: "memory");
    } else if (warp == 8) {
        if (lane == 0) {
            if (early) wait_ctr(CT_CA + mt * 2, 2u * O2_HE); else wait_ctr(CT_CB + max(mt, CB_FIRST), 64u);
            OTP(3);
        }
        __syncwarp();
        asm volatile("barrier.cluster.wait.acquire.aligned;" ::: "memory");
        if (lane == 0) {
            OTP(7);
            int s = 0; uint32_t ph = 0;
            bool late_a = false;
            for (int i = 0; i < nk; i++) {
                const int b = i >= na, k = b ? b0 + i - na : a0 + i;
                if (!b && k >= 2 * O2_HE && !late_a) { wait_ctr(CT_CA + mt * 2 + 1, 2u * (NH - O2_HE)); late_a = true; }
                if (i == na && early) wait_ctr(CT_CB + max(mt, CB_FIRST), 64u);
                if (i >= nst) mbar_wait(bar_empty + 8 * s, ph ^ 1);
                mbar_expect_tx(bar_full + 8 * s, ssz);
                tma_load_2d_mc(sbase + s * ssz + rank * 8192, &P.mapCtx[b], bar_full + 8 * s, (k & 1) * 64, (k >> 1) * SEQ + m0 + (int)rank * 64, (uint16_t)3);
                if (++s == nst) { s = 0; ph ^= 1; }
            }
        }
    } else {
        asm volatile("barrier.cluster.wait.acquire.aligned;" ::: "memory");
        const int wg = warp >> 2;
        const bool elected = (threadIdx.x & 127) == 0;
        const int row = (warp & 3) * 16 + (lane >> 2);
        const int mrow = (warp & 3) * 16 + (lane & 15);
        const uint32_t moff = mrow * 128, mx = (lane >> 4) ^ (mrow & 7);
        float g0, g1;
        int s = 0, sprev = 0; uint32_t ph = 0;
        {
            unsigned int v; int it = 0;
            do { asm volatile("ld.acquire.gpu.global.u32 %0, [%1];" : "=r"(v) : "l"(&g_ctr[CT_G]) : "memory"); } while (v < FA_GRID && ++it < (1 << 22));
        }
        asm volatile("ld.relaxed.gpu.global.f32 %0, [%1];" : "=f"(g0) : "l"(g_gate + m0 + wg * 64 + row) : "memory");
        asm volatile("ld.relaxed.gpu.global.f32 %0, [%1];" : "=f"(g1) : "l"(g_gate + m0 + wg * 64 + row + 8) : "memory");
        auto release = [&](int st) {
            if (elected) { const uint32_t e = bar_empty + 8 * st; mbar_arrive_cl(mapa_u32(e, 0)); mbar_arrive_cl(mapa_u32(e, 1)); }
        };
        if (early) {
            float acc[128];
#pragma unroll 1
            for (int i = 0; i < nk; i++) {
                mbar_wait(bar_full + 8 * s, ph);
                if (i == 8) OT(2);
                if (i == na) {
                    wgmma_wait<0>();
                    const float r0 = g0 / fmaxf(1.f - g0, 0x1p-40f), r1 = g1 / fmaxf(1.f - g1, 0x1p-40f);
#pragma unroll
                    for (int j = 0; j < 32; j++) { acc[4 * j] *= r0; acc[4 * j + 1] *= r0; acc[4 * j + 2] *= r1; acc[4 * j + 3] *= r1; }
                }
                const uint32_t sa = sbase + s * 49152 + wg * 8192, sb = sbase + s * 49152 + 16384;
                wgmma_fence();
#pragma unroll
                for (int kk = 0; kk < 4; kk++)
                    wgmma_ss_n256_tb(acc, make_desc(sa + kk * 32, 16, 1024), make_desc(sb + kk * 2048, 8192, 1024), (i | kk) != 0);
                wgmma_commit();
                if (i > 0) { wgmma_wait<1>(); release(sprev); }
                sprev = s;
                if (++s == 4) { s = 0; ph ^= 1; }
            }
            wgmma_wait<0>();
            OT(4);
            const float w0 = fmaxf(1.f - g0, 0x1p-40f), w1 = fmaxf(1.f - g1, 0x1p-40f);
            uint4* dst = g_part + (((part * 32 + mt * 2 + (int)rank) * 8 + warp) * 16) * 32 + lane;
#pragma unroll
            for (int j = 0; j < 16; j++) {
                const float* a = &acc[8 * j];
                dst[j * 32] = make_uint4(pack_bf16(a[0] * w0, a[1] * w0), pack_bf16(a[2] * w1, a[3] * w1), pack_bf16(a[4] * w0, a[5] * w0), pack_bf16(a[6] * w1, a[7] * w1));
            }
            __syncwarp();
            OT(5);
            if (lane == 0) signal_ctr_generic(CT_OP + (mt * 2 + (int)rank) * 8 + warp);
            OT(6);
        } else {
            float acc[64];
            const uint32_t a_lo = desc_lo(sbase + wg * 8192, 16), b_lo = desc_lo(sbase + 16384, 8192);
#pragma unroll 1
            for (int i = 0; i < nk; i++) {
                mbar_wait(bar_full + 8 * s, ph);
                if (i == 8) OT(2);
                wgmma_fence();
#pragma unroll
                for (int kk = 0; kk < 4; kk++) wgmma_ss_n128_lo<1>(acc, a_lo + s * 2048 + kk * 2, b_lo + s * 2048 + kk * 128, (i | kk) != 0);
                wgmma_commit();
                if (i > 0) { wgmma_wait<1>(); release(sprev); }
                sprev = s;
                if (++s == 6) { s = 0; ph ^= 1; }
            }
            const int np = mt == 15 ? 4 : 2;
            wait_ctr(CT_OP + (mt * 2 + part) * 8 + warp, np);
            const uint4* src = g_part + (((mt * 2 + part) * 8 + warp) * 16 + (int)rank * 8) * 32 + lane;
            uint4 u[2][8];
            auto load_parts = [&](int p) {
#pragma unroll
                for (int i = 0; i < 16; i++)
                    asm volatile("ld.relaxed.gpu.global.v4.u32 {%0, %1, %2, %3}, [%4];" : "=r"(u[i >> 3][i & 7].x), "=r"(u[i >> 3][i & 7].y), "=r"(u[i >> 3][i & 7].z),
                                 "=r"(u[i >> 3][i & 7].w) : "l"(src + (p + (i >> 3)) * (32 * 8 * 16 * 32) + (i & 7) * 32) : "memory");
            };
            auto add_parts = [&]() {
#pragma unroll
                for (int i = 0; i < 16; i++) {
                    const uint32_t v[4] = {u[i >> 3][i & 7].x, u[i >> 3][i & 7].y, u[i >> 3][i & 7].z, u[i >> 3][i & 7].w};
#pragma unroll
                    for (int e = 0; e < 4; e++) {
                        acc[8 * (i & 7) + 2 * e] += __uint_as_float(v[e] << 16);
                        acc[8 * (i & 7) + 2 * e + 1] += __uint_as_float(v[e] & 0xffff0000u);
                    }
                }
            };
            load_parts(0);
            wgmma_wait<0>();
            OT(4);
            const float w0 = 1.f - g0, w1 = 1.f - g1;
#pragma unroll
            for (int j = 0; j < 16; j++) { acc[4 * j] *= w0; acc[4 * j + 1] *= w0; acc[4 * j + 2] *= w1; acc[4 * j + 3] *= w1; }
            add_parts();
            if (np == 4) { load_parts(2); add_parts(); }
            OT(5);
            mbar_wait(bar_empty + 8 * s, ph ^ 1);
            const uint32_t stg = sbase + s * 32768 + wg * 16384;
#pragma unroll
            for (int j = 0; j < 8; j++) {
                const float* a = &acc[8 * j];
                stmatrix_x4(stg + (j >> 2) * 8192 + moff + ((mx ^ ((j & 3) * 2)) << 4), pack_bf16(a[0], a[1]), pack_bf16(a[2], a[3]), pack_bf16(a[4], a[5]), pack_bf16(a[6], a[7]));
            }
            fence_async_smem();
            asm volatile("bar.sync %0, 128;" :: "r"(2 + wg) : "memory");
            if (elected) {
                tma_store_2d(&P.mapOut, stg, n0, m0 + wg * 64);
                tma_store_2d(&P.mapOut, stg + 8192, n0 + 64, m0 + wg * 64);
                asm volatile("cp.async.bulk.commit_group;" ::: "memory");
                asm volatile("cp.async.bulk.wait_group 0;" ::: "memory");
            }
            OT(6);
        }
    }
    __syncthreads();
    asm volatile("barrier.cluster.arrive.relaxed.aligned;" ::: "memory");
    if (warp == 0) {
        unsigned int tk = 0;
        if (lane == 0) tk = atomicAdd(&g_ctr[CT_FIN], 1u);
        tk = __shfl_sync(0xffffffff, tk, 0);
        if (tk == gridDim.x - 1)
            for (int i = lane; i < CT_N; i += 32) g_ctr[i] = 0u;
    }
    asm volatile("barrier.cluster.wait.acquire.aligned;" ::: "memory");
    TS_END(4);
}

typedef CUresult (*PFN_encodeTiled)(CUtensorMap*, CUtensorMapDataType, cuuint32_t, void*, const cuuint64_t*,
                                    const cuuint64_t*, const cuuint32_t*, const cuuint32_t*, CUtensorMapInterleave,
                                    CUtensorMapSwizzle, CUtensorMapL2promotion, CUtensorMapFloatOOBfill);
static PFN_encodeTiled g_encode = nullptr;

static void make_map(CUtensorMap* m, const void* ptr, uint64_t rows, uint64_t cols, uint32_t box_rows, bool sw64 = false) {
    cuuint64_t dims[2] = {cols, rows};
    cuuint64_t strides[1] = {cols * 2};
    cuuint32_t box[2] = {sw64 ? 32u : 64u, box_rows};
    cuuint32_t es[2] = {1, 1};
    g_encode(m, CU_TENSOR_MAP_DATA_TYPE_BFLOAT16, 2, const_cast<void*>(ptr), dims, strides, box, es,
             CU_TENSOR_MAP_INTERLEAVE_NONE, sw64 ? CU_TENSOR_MAP_SWIZZLE_64B : CU_TENSOR_MAP_SWIZZLE_128B, CU_TENSOR_MAP_L2_PROMOTION_L2_256B,
             CU_TENSOR_MAP_FLOAT_OOB_FILL_NONE);
}

template <typename... KArgs, typename... Args>
static void launch_pdl(void (*kernel)(KArgs...), int grid, int block, size_t smem, cudaStream_t st, bool pdl, Args... args) {
    cudaLaunchConfig_t cfg = {};
    cfg.gridDim = dim3(grid); cfg.blockDim = dim3(block); cfg.dynamicSmemBytes = smem; cfg.stream = st;
    cudaLaunchAttribute at[1];
    at[0].id = cudaLaunchAttributeProgrammaticStreamSerialization;
    at[0].val.programmaticStreamSerializationAllowed = 1;
    cfg.attrs = at; cfg.numAttrs = pdl ? 1 : 0;
    cudaLaunchKernelEx(&cfg, kernel, KArgs(args)...);
}

extern "C" void kernel_launch(void* const* d_in, const int* in_sizes, int n_in, void* d_out, int out_size) {
    const bf16* x = (const bf16*)d_in[0];
    const bf16* ckv = (const bf16*)d_in[1];
    const bf16* wq = (const bf16*)d_in[2];
    const bf16* wuk = (const bf16*)d_in[3];
    const bf16* wuv = (const bf16*)d_in[4];
    const bf16* wo = (const bf16*)d_in[5];
    const bf16* mem0 = (const bf16*)d_in[7];
    const bf16* Wq = (const bf16*)d_in[8];
    const bf16* Wk = (const bf16*)d_in[9];
    const bf16* Wv = (const bf16*)d_in[10];
    const bf16* Wo = (const bf16*)d_in[11];
    const bf16* gate_w = (const bf16*)d_in[13];
    bf16* out = (bf16*)d_out;

    static Proj2Params P2;
    static ChainParams CP;
    static AttnParams AP;
    static OutParams OP;
    static bool init = false;
    static const void* last_in[15];
    bool same = init;
    for (int i = 0; i < 14 && same; i++) same = last_in[i] == d_in[i];
    same = same && last_in[14] == d_out;
    if (!init) {
        cudaDriverEntryPointQueryResult qr;
        cudaGetDriverEntryPoint("cuTensorMapEncodeTiled", (void**)&g_encode, cudaEnableDefault, &qr);
        cudaFuncSetAttribute(proj2_kernel, cudaFuncAttributeMaxDynamicSharedMemorySize, P2_SMEM);
        cudaFuncSetAttribute(attn_kernel, cudaFuncAttributeMaxDynamicSharedMemorySize, FA_SMEM);
        cudaFuncSetAttribute(chain_kernel, cudaFuncAttributeMaxDynamicSharedMemorySize, C2_SMEM);
        cudaFuncSetAttribute(out3_kernel, cudaFuncAttributeMaxDynamicSharedMemorySize, O2_SMEM);
        init = true;
    }
    if (!same) {
        for (int i = 0; i < 14; i++) last_in[i] = d_in[i];
        last_in[14] = d_out;
        void *pQA, *pKA, *pVA, *pCA, *pCB;
        cudaGetSymbolAddress(&pQA, g_QA); cudaGetSymbolAddress(&pKA, g_KA); cudaGetSymbolAddress(&pVA, g_VA);
        cudaGetSymbolAddress(&pCA, g_ctxA); cudaGetSymbolAddress(&pCB, g_ctxB);
        make_map(&P2.mapA[0], x, SEQ, DM, 128);
        make_map(&P2.mapA[1], ckv, SEQ, DM, 128);
        const void* ws[3] = {wq, wuk, wuv};
        void* cs[3] = {pQA, pKA, pVA};
        for (int i = 0; i < 3; i++) { make_map(&P2.mapW[i], ws[i], DM, NQ, 64); P2.out[i] = (bf16*)cs[i]; }
        make_map(&CP.mapX, x, SEQ, DM, SEGL);
        make_map(&CP.mapM, mem0, NMEM, DM, NMEM);
        make_map(&CP.mapW[0], Wq, DM, NQ, 64);
        make_map(&CP.mapW[1], Wk, DM, NQ, 64);
        make_map(&CP.mapW[2], Wv, DM, NQ, 64);
        make_map(&CP.mapWo, Wo, NQ, DM, 64);
        make_map(&AP.mapQ, pQA, NH * SEQ, HD, 128);
        make_map(&AP.mapK, pKA, NH * SEQ, HD, 128);
        make_map(&AP.mapV, pVA, NH * SEQ, HD, 128);
        make_map(&AP.mapO, pCA, NH * SEQ, HD, 64);
        make_map(&OP.mapCtx[0], pCA, NH * SEQ, HD, 64);
        make_map(&OP.mapCtx[1], pCB, NH * SEQ, HD, 64);
        make_map(&OP.mapWo[0], wo, NQ, DM, 64);
        make_map(&OP.mapWo[1], Wo, NQ, DM, 64);
        make_map(&OP.mapOut, out, SEQ, DM, 64);
        AP.x = x; AP.gate_w = gate_w;
    }
    cudaStream_t s1 = cudaStreamPerThread;
    const bool pdl = true;
    launch_pdl(chain_kernel, 64, 384, C2_SMEM, s1, false, CP);
    launch_pdl(proj2_kernel, 68, 384, P2_SMEM, s1, pdl, P2);
    launch_pdl(attn_kernel, FA_GRID, 384, FA_SMEM, s1, pdl, AP);
    launch_pdl(out3_kernel, O3_GRID, 352, O2_SMEM, s1, pdl, OP);
}
```

```cpp
#include <cuda_runtime.h>
#include <cuda_bf16.h>
#include <cuda.h>
#include <stdint.h>
#include <type_traits>

constexpr int SEQ = 2048;
constexpr int DM = 512;
constexpr int NH = 32;
constexpr int HD = 128;
constexpr int NQ = NH * HD;
constexpr int SEGL = 32;
constexpr int NMEM = 8;
constexpr int NSEG = SEQ / SEGL;

typedef __nv_bfloat16 bf16;

__device__ bf16 g_QA[SEQ * NQ];
__device__ bf16 g_KA[SEQ * NQ];
__device__ bf16 g_VA[SEQ * NQ];
__device__ bf16 g_ctxA[SEQ * NQ];
__device__ bf16 g_ctxB[SEQ * NQ];
constexpr int CT_PROJ = 0, CT_ATTN = 1, CT_FIN = 5;
constexpr int CT_G = 32;
constexpr int CT_AP = 64;
#define O2_HE 24
constexpr int CT_CA = 128;
constexpr int CT_CB = 160;
#define CB_FIRST 13
constexpr int CT_OP = 192;
constexpr int CT_N = 448;
__device__ unsigned int g_ctr[CT_N];
__device__ float g_gate[SEQ];
__device__ uint2 g_xbuf[2 * 8 * 8 * 128];

#define FA_GRID 68

#define TS_BEGIN(id)
#define TS_END(id)
__device__ __forceinline__ void pdl_launch_dependents() { asm volatile("griddepcontrol.launch_dependents;" ::: "memory"); }
__device__ __forceinline__ void wait_ctr(int idx, unsigned int n) {
    unsigned int v; int it = 0;
    do { asm volatile("ld.acquire.gpu.global.u32 %0, [%1];" : "=r"(v) : "l"(&g_ctr[idx]) : "memory"); } while (v < n && ++it < (1 << 22));
}
__device__ __forceinline__ void signal_ctr(int idx) {
    asm volatile("fence.proxy.async.global;" ::: "memory");
    asm volatile("red.release.gpu.global.add.u32 [%0], 1;" :: "l"(&g_ctr[idx]) : "memory");
}
__device__ __forceinline__ void signal_ctr_generic(int idx) {
    asm volatile("red.release.gpu.global.add.u32 [%0], 1;" :: "l"(&g_ctr[idx]) : "memory");
}
__device__ __forceinline__ uint32_t smem_u32(const void* p) {
    return (uint32_t)__cvta_generic_to_shared(p);
}
__device__ __forceinline__ void mbar_init(uint32_t bar, uint32_t count) {
    asm volatile("mbarrier.init.shared::cta.b64 [%0], %1;" :: "r"(bar), "r"(count));
}
__device__ __forceinline__ void mbar_expect_tx(uint32_t bar, uint32_t bytes) {
    asm volatile("mbarrier.arrive.expect_tx.shared::cta.b64 _, [%0], %1;" :: "r"(bar), "r"(bytes) : "memory");
}
__device__ __forceinline__ void mbar_arrive(uint32_t bar) {
    asm volatile("mbarrier.arrive.shared::cta.b64 _, [%0];" :: "r"(bar) : "memory");
}
__device__ __forceinline__ void mbar_wait(uint32_t bar, uint32_t parity) {
    asm volatile(
        "{\n"
        ".reg .pred p, q;\n"
        ".reg .u32 c;\n"
        "mov.u32 c, 0;\n"
        "WAIT_LOOP:\n"
        "mbarrier.try_wait.parity.shared::cta.b64 p, [%0], %1;\n"
        "@p bra WAIT_DONE;\n"
        "add.u32 c, c, 1;\n"
        "setp.lt.u32 q, c, 4000000;\n"
        "@q bra WAIT_LOOP;\n"
        "WAIT_DONE:\n"
        "}\n" :: "r"(bar), "r"(parity) : "memory");
}
__device__ __forceinline__ void tma_load_2d(uint32_t dst, const CUtensorMap* map, uint32_t bar, int c0, int c1) {
    asm volatile(
        "cp.async.bulk.tensor.2d.shared::cluster.global.mbarrier::complete_tx::bytes [%0], [%1, {%3, %4}], [%2];"
        :: "r"(dst), "l"((uint64_t)map), "r"(bar), "r"(c0), "r"(c1) : "memory");
}
__device__ __forceinline__ void wgmma_fence() { asm volatile("wgmma.fence.sync.aligned;" ::: "memory"); }
__device__ __forceinline__ void wgmma_commit() { asm volatile("wgmma.commit_group.sync.aligned;" ::: "memory"); }
template <int N> __device__ __forceinline__ void wgmma_wait() {
    asm volatile("wgmma.wait_group.sync.aligned %0;" :: "n"(N) : "memory");
}
__device__ __forceinline__ uint64_t make_desc(uint32_t addr, uint32_t lbo, uint32_t sbo) {
    uint64_t d = 0;
    d |= (uint64_t)((addr & 0x3FFFF) >> 4);
    d |= (uint64_t)((lbo >> 4) & 0x3FFF) << 16;
    d |= (uint64_t)((sbo >> 4) & 0x3FFF) << 32;
    d |= (uint64_t)1 << 62;
    return d;
}

#define ACC64(d) \
    "+f"(d[0]), "+f"(d[1]), "+f"(d[2]), "+f"(d[3]), "+f"(d[4]), "+f"(d[5]), "+f"(d[6]), "+f"(d[7]), \
    "+f"(d[8]), "+f"(d[9]), "+f"(d[10]), "+f"(d[11]), "+f"(d[12]), "+f"(d[13]), "+f"(d[14]), "+f"(d[15]), \
    "+f"(d[16]), "+f"(d[17]), "+f"(d[18]), "+f"(d[19]), "+f"(d[20]), "+f"(d[21]), "+f"(d[22]), "+f"(d[23]), \
    "+f"(d[24]), "+f"(d[25]), "+f"(d[26]), "+f"(d[27]), "+f"(d[28]), "+f"(d[29]), "+f"(d[30]), "+f"(d[31]), \
    "+f"(d[32]), "+f"(d[33]), "+f"(d[34]), "+f"(d[35]), "+f"(d[36]), "+f"(d[37]), "+f"(d[38]), "+f"(d[39]), \
    "+f"(d[40]), "+f"(d[41]), "+f"(d[42]), "+f"(d[43]), "+f"(d[44]), "+f"(d[45]), "+f"(d[46]), "+f"(d[47]), \
    "+f"(d[48]), "+f"(d[49]), "+f"(d[50]), "+f"(d[51]), "+f"(d[52]), "+f"(d[53]), "+f"(d[54]), "+f"(d[55]), \
    "+f"(d[56]), "+f"(d[57]), "+f"(d[58]), "+f"(d[59]), "+f"(d[60]), "+f"(d[61]), "+f"(d[62]), "+f"(d[63])
#define ACC64_STR \
    "{%0, %1, %2, %3, %4, %5, %6, %7, %8, %9, %10, %11, %12, %13, %14, %15, " \
    "%16, %17, %18, %19, %20, %21, %22, %23, %24, %25, %26, %27, %28, %29, %30, %31, " \
    "%32, %33, %34, %35, %36, %37, %38, %39, %40, %41, %42, %43, %44, %45, %46, %47, " \
    "%48, %49, %50, %51, %52, %53, %54, %55, %56, %57, %58, %59, %60, %61, %62, %63}"

template <int TB>
__device__ __forceinline__ void wgmma_ss_n128(float (&d)[64], uint64_t da, uint64_t db, int scale_d) {
    asm volatile(
        "{\n.reg .pred p;\nsetp.ne.b32 p, %66, 0;\n"
        "wgmma.mma_async.sync.aligned.m64n128k16.f32.bf16.bf16 " ACC64_STR ", %64, %65, p, 1, 1, 0, %67;\n}\n"
        : ACC64(d) : "l"(da), "l"(db), "r"(scale_d), "n"(TB));
}
__device__ __forceinline__ uint32_t desc_lo(uint32_t addr, uint32_t lbo) { return ((addr & 0x3FFFF) >> 4) | ((lbo >> 4) << 16); }
template <int TB>
__device__ __forceinline__ void wgmma_ss_n128_lo(float (&d)[64], uint32_t da_lo, uint32_t db_lo, int scale_d) {
    asm volatile(
        "{\n.reg .pred p;\n.reg .b64 da, db;\nsetp.ne.b32 p, %66, 0;\n"
        "mov.b64 da, {%64, 0x40000040};\nmov.b64 db, {%65, 0x40000040};\n"
        "wgmma.mma_async.sync.aligned.m64n128k16.f32.bf16.bf16 " ACC64_STR ", da, db, p, 1, 1, 0, %67;\n}\n"
        : ACC64(d) : "r"(da_lo), "r"(db_lo), "r"(scale_d), "n"(TB));
}
__device__ __forceinline__ void wgmma_rs_n128_tb(float (&d)[64], uint32_t a0, uint32_t a1, uint32_t a2, uint32_t a3,
                                                 uint64_t db, int scale_d) {
    asm volatile(
        "{\n.reg .pred p;\nsetp.ne.b32 p, %69, 0;\n"
        "wgmma.mma_async.sync.aligned.m64n128k16.f32.bf16.bf16 " ACC64_STR ", {%64, %65, %66, %67}, %68, p, 1, 1, 1;\n}\n"
        : ACC64(d) : "r"(a0), "r"(a1), "r"(a2), "r"(a3), "l"(db), "r"(scale_d));
}
__device__ __forceinline__ void wgmma_rs_n80(float (&d)[40], const uint32_t (&a)[4], uint32_t db_lo, int scale_d) {
    asm volatile(
        "{\n.reg .pred p;\n.reg .b64 db;\nsetp.ne.b32 p, %45, 0;\nmov.b64 db, {%44, 0x40000040};\n"
        "wgmma.mma_async.sync.aligned.m64n80k16.f32.bf16.bf16 "
        "{%0, %1, %2, %3, %4, %5, %6, %7, %8, %9, %10, %11, %12, %13, %14, %15, %16, %17, %18, %19, %20, %21, %22, %23, %24, %25, %26, %27, %28, %29, %30, %31, %32, %33, %34, %35, %36, %37, %38, %39}, "
        "{%40, %41, %42, %43}, db, p, 1, 1, 0;\n}\n"
        : "+f"(d[0]), "+f"(d[1]), "+f"(d[2]), "+f"(d[3]), "+f"(d[4]), "+f"(d[5]), "+f"(d[6]), "+f"(d[7]), "+f"(d[8]), "+f"(d[9]), "+f"(d[10]), "+f"(d[11]), "+f"(d[12]), "+f"(d[13]), "+f"(d[14]), "+f"(d[15]), "+f"(d[16]), "+f"(d[17]), "+f"(d[18]), "+f"(d[19]), "+f"(d[20]), "+f"(d[21]), "+f"(d[22]), "+f"(d[23]), "+f"(d[24]), "+f"(d[25]), "+f"(d[26]), "+f"(d[27]), "+f"(d[28]), "+f"(d[29]), "+f"(d[30]), "+f"(d[31]), "+f"(d[32]), "+f"(d[33]), "+f"(d[34]), "+f"(d[35]), "+f"(d[36]), "+f"(d[37]), "+f"(d[38]), "+f"(d[39])
        : "r"(a[0]), "r"(a[1]), "r"(a[2]), "r"(a[3]), "r"(db_lo), "r"(scale_d));
}
__device__ __forceinline__ void wgmma_ss_n256_tb(float (&d)[128], uint64_t da, uint64_t db, int scale_d) {
    asm volatile(
        "{\n.reg .pred p;\nsetp.ne.b32 p, %130, 0;\n"
        "wgmma.mma_async.sync.aligned.m64n256k16.f32.bf16.bf16 {%0, %1, %2, %3, %4, %5, %6, %7, %8, %9, %10, %11, %12, %13, %14, %15, %16, %17, %18, %19, %20, %21, %22, %23, %24, %25, %26, %27, %28, %29, %30, %31, %32, %33, %34, %35, %36, %37, %38, %39, %40, %41, %42, %43, %44, %45, %46, %47, %48, %49, %50, %51, %52, %53, %54, %55, %56, %57, %58, %59, %60, %61, %62, %63, %64, %65, %66, %67, %68, %69, %70, %71, %72, %73, %74, %75, %76, %77, %78, %79, %80, %81, %82, %83, %84, %85, %86, %87, %88, %89, %90, %91, %92, %93, %94, %95, %96, %97, %98, %99, %100, %101, %102, %103, %104, %105, %106, %107, %108, %109, %110, %111, %112, %113, %114, %115, %116, %117, %118, %119, %120, %121, %122, %123, %124, %125, %126, %127}, %128, %129, p, 1, 1, 0, 1;\n}\n"
        : "+f"(d[0]), "+f"(d[1]), "+f"(d[2]), "+f"(d[3]), "+f"(d[4]), "+f"(d[5]), "+f"(d[6]), "+f"(d[7]), "+f"(d[8]), "+f"(d[9]), "+f"(d[10]), "+f"(d[11]), "+f"(d[12]), "+f"(d[13]), "+f"(d[14]), "+f"(d[15]), "+f"(d[16]), "+f"(d[17]), "+f"(d[18]), "+f"(d[19]), "+f"(d[20]), "+f"(d[21]), "+f"(d[22]), "+f"(d[23]), "+f"(d[24]), "+f"(d[25]), "+f"(d[26]), "+f"(d[27]), "+f"(d[28]), "+f"(d[29]), "+f"(d[30]), "+f"(d[31]), "+f"(d[32]), "+f"(d[33]), "+f"(d[34]), "+f"(d[35]), "+f"(d[36]), "+f"(d[37]), "+f"(d[38]), "+f"(d[39]), "+f"(d[40]), "+f"(d[41]), "+f"(d[42]), "+f"(d[43]), "+f"(d[44]), "+f"(d[45]), "+f"(d[46]), "+f"(d[47]), "+f"(d[48]), "+f"(d[49]), "+f"(d[50]), "+f"(d[51]), "+f"(d[52]), "+f"(d[53]), "+f"(d[54]), "+f"(d[55]), "+f"(d[56]), "+f"(d[57]), "+f"(d[58]), "+f"(d[59]), "+f"(d[60]), "+f"(d[61]), "+f"(d[62]), "+f"(d[63]), "+f"(d[64]), "+f"(d[65]), "+f"(d[66]), "+f"(d[67]), "+f"(d[68]), "+f"(d[69]), "+f"(d[70]), "+f"(d[71]), "+f"(d[72]), "+f"(d[73]), "+f"(d[74]), "+f"(d[75]), "+f"(d[76]), "+f"(d[77]), "+f"(d[78]), "+f"(d[79]), "+f"(d[80]), "+f"(d[81]), "+f"(d[82]), "+f"(d[83]), "+f"(d[84]), "+f"(d[85]), "+f"(d[86]), "+f"(d[87]), "+f"(d[88]), "+f"(d[89]), "+f"(d[90]), "+f"(d[91]), "+f"(d[92]), "+f"(d[93]), "+f"(d[94]), "+f"(d[95]), "+f"(d[96]), "+f"(d[97]), "+f"(d[98]), "+f"(d[99]), "+f"(d[100]), "+f"(d[101]), "+f"(d[102]), "+f"(d[103]), "+f"(d[104]), "+f"(d[105]), "+f"(d[106]), "+f"(d[107]), "+f"(d[108]), "+f"(d[109]), "+f"(d[110]), "+f"(d[111]), "+f"(d[112]), "+f"(d[113]), "+f"(d[114]), "+f"(d[115]), "+f"(d[116]), "+f"(d[117]), "+f"(d[118]), "+f"(d[119]), "+f"(d[120]), "+f"(d[121]), "+f"(d[122]), "+f"(d[123]), "+f"(d[124]), "+f"(d[125]), "+f"(d[126]), "+f"(d[127])
        : "l"(da), "l"(db), "r"(scale_d));
}
__device__ __forceinline__ void stmatrix_x4(uint32_t addr, uint32_t r0, uint32_t r1, uint32_t r2, uint32_t r3) {
    asm volatile("stmatrix.sync.aligned.m8n8.x4.shared.b16 [%0], {%1, %2, %3, %4};" :: "r"(addr), "r"(r0), "r"(r1), "r"(r2), "r"(r3) : "memory");
}
__device__ __forceinline__ void tma_store_2d(const CUtensorMap* map, uint32_t src, int c0, int c1) {
    asm volatile("cp.async.bulk.tensor.2d.global.shared::cta.bulk_group [%0, {%2, %3}], [%1];"
                 :: "l"((uint64_t)map), "r"(src), "r"(c0), "r"(c1) : "memory");
}
__device__ __forceinline__ float ex2f(float x) { float y; asm("ex2.approx.ftz.f32 %0, %1;" : "=f"(y) : "f"(x)); return y; }
__device__ __forceinline__ uint32_t pack_bf16(float lo, float hi) {
    __nv_bfloat162 v = __floats2bfloat162_rn(lo, hi);
    return *reinterpret_cast<uint32_t*>(&v);
}
__device__ __forceinline__ float bf16r(float x) { return __uint_as_float(pack_bf16(0.f, x) & 0xffff0000u); }
__device__ __forceinline__ void mma_16816(float (&c)[4], uint32_t a0, uint32_t a1, uint32_t a2, uint32_t a3,
                                          uint32_t b0, uint32_t b1) {
    asm volatile(
        "mma.sync.aligned.m16n8k16.row.col.f32.bf16.bf16.f32 {%0,%1,%2,%3}, {%4,%5,%6,%7}, {%8,%9}, {%0,%1,%2,%3};"
        : "+f"(c[0]), "+f"(c[1]), "+f"(c[2]), "+f"(c[3])
        : "r"(a0), "r"(a1), "r"(a2), "r"(a3), "r"(b0), "r"(b1));
}
__device__ __forceinline__ void ldmatrix_x4_trans(uint32_t& r0, uint32_t& r1, uint32_t& r2, uint32_t& r3, uint32_t addr) {
    asm volatile("ldmatrix.sync.aligned.m8n8.x4.trans.shared.b16 {%0,%1,%2,%3}, [%4];"
                 : "=r"(r0), "=r"(r1), "=r"(r2), "=r"(r3) : "r"(addr));
}

struct AttnParams {
    CUtensorMap mapQ, mapK, mapV;
    CUtensorMap mapO;
    const bf16 *x, *gate_w;
};
constexpr uint32_t FA_Q = 0, FA_KV = 65536, FA_O = 196608, FA_BAR = 229376;
constexpr int FA_SMEM = FA_BAR + 256;
constexpr int FA_ITEMS = 16 * NH;
__device__ __forceinline__ int fa_qt(int t) { return 15 - ((t & 127) >> 3); }
__device__ __forceinline__ int fa_head(int t) { return (t >> 7) * 8 + (t & 7); }
__device__ __forceinline__ uint32_t mbar_test(uint32_t bar, uint32_t parity) {
    uint32_t done;
    asm volatile(
        "{\n.reg .pred p;\n"
        "mbarrier.test_wait.parity.shared::cta.b64 p, [%1], %2;\n"
        "selp.u32 %0, 1, 0, p;\n}\n" : "=r"(done) : "r"(bar), "r"(parity) : "memory");
    return done;
}
__device__ __forceinline__ void mbar_arrive_if(uint32_t bar, bool c) {
    asm volatile("{\n.reg .pred p;\nsetp.ne.u32 p, %1, 0;\n@p mbarrier.arrive.shared::cta.b64 _, [%0];\n}" :: "r"(bar), "r"((uint32_t)c) : "memory");
}
__device__ __forceinline__ void wgmma_rs_n128_tb_lo(float (&d)[64], const uint32_t* a, uint32_t db_lo, int scale_d) {
    asm volatile(
        "{\n.reg .pred p;\n.reg .b64 db;\nsetp.ne.b32 p, %69, 0;\nmov.b64 db, {%68, 0x40000040};\n"
        "wgmma.mma_async.sync.aligned.m64n128k16.f32.bf16.bf16 " ACC64_STR ", {%64, %65, %66, %67}, db, p, 1, 1, 1;\n}\n"
        : ACC64(d) : "r"(a[0]), "r"(a[1]), "r"(a[2]), "r"(a[3]), "r"(db_lo), "r"(scale_d));
}
#define FA_TEST 48
#define FA_PIN 8

__global__ void __launch_bounds__(384, 1) attn_kernel(const __grid_constant__ AttnParams P) {
    extern __shared__ __align__(1024) uint8_t smem_attn[];
    const uint32_t sb = smem_u32(smem_attn);
    const uint32_t bar_q = sb + FA_BAR, bar_qe = bar_q + 16, bar_kf = bar_q + 32, bar_vf = bar_q + 48, bar_ke = bar_q + 64, bar_ve = bar_q + 80,
                   bar_of = bar_q + 96, bar_oe = bar_q + 112, slot = bar_q + 128, oslot = bar_q + 136;
    const int warp = __shfl_sync(0xffffffff, threadIdx.x >> 5, 0);
    const int lane = threadIdx.x & 31;
    TS_BEGIN(1);
    if (threadIdx.x == 0) {
        for (int i = 0; i < 2; i++) {
            mbar_init(bar_q + 8 * i, 1); mbar_init(bar_qe + 8 * i, 8); mbar_init(bar_kf + 8 * i, 1); mbar_init(bar_vf + 8 * i, 1);
            mbar_init(bar_ke + 8 * i, 8); mbar_init(bar_ve + 8 * i, 8); mbar_init(bar_of + 8 * i, 4); mbar_init(bar_oe + 8 * i, 1);
        }
        asm volatile("fence.mbarrier_init.release.cluster;" ::: "memory");
    }
    if (threadIdx.x == 256) wait_ctr(CT_AP + (fa_head(blockIdx.x) >> 1), 96u);
    __syncthreads();
    pdl_launch_dependents();
    if (warp >= 8) {
        asm volatile("setmaxnreg.dec.sync.aligned.u32 40;");
        if (warp == 11) {
            const uint4 gv0 = __ldg(reinterpret_cast<const uint4*>(P.gate_w) + lane), gv1 = __ldg(reinterpret_cast<const uint4*>(P.gate_w) + 32 + lane);
            const uint32_t gw[8] = {gv0.x, gv0.y, gv0.z, gv0.w, gv1.x, gv1.y, gv1.z, gv1.w};
#pragma unroll 1
            for (int r = blockIdx.x; r < SEQ; r += gridDim.x) {
                const uint4 x0 = __ldg(reinterpret_cast<const uint4*>(P.x + (size_t)r * DM) + lane), x1 = __ldg(reinterpret_cast<const uint4*>(P.x + (size_t)r * DM) + 32 + lane);
                const uint32_t xw[8] = {x0.x, x0.y, x0.z, x0.w, x1.x, x1.y, x1.z, x1.w};
                float sum = 0.f;
#pragma unroll
                for (int e = 0; e < 8; e++) {
                    const uint32_t pr = pack_bf16(__uint_as_float(xw[e] << 16) * __uint_as_float(gw[e] << 16), __uint_as_float(xw[e] & 0xffff0000u) * __uint_as_float(gw[e] & 0xffff0000u));
                    sum += __uint_as_float(pr << 16) + __uint_as_float(pr & 0xffff0000u);
                }
#pragma unroll
                for (int o = 16; o; o >>= 1) sum += __shfl_xor_sync(0xffffffff, sum, o);
                if (lane == 0) g_gate[r] = bf16r(1.f / (1.f + __expf(-bf16r(sum))));
            }
            if (lane == 0) signal_ctr_generic(CT_G);
        } else if (warp > 8) {
            if (lane == 0) {
                const int wg = warp - 9;
                const uint32_t stg = sb + FA_O + wg * 16384;
                for (int n = 0;; n++) {
                    mbar_wait(bar_of + 8 * wg, n & 1);
                    int t;
                    asm volatile("ld.shared.s32 %0, [%1];" : "=r"(t) : "r"(oslot + wg * 4) : "memory");
                    asm volatile("fence.proxy.async.shared::cta;" ::: "memory");
                    const bool last = t < 0;
                    t &= 0xffff;
                    const int qt = fa_qt(t), h = fa_head(t);
                    tma_store_2d(&P.mapO, stg, 0, h * SEQ + qt * 128 + wg * 64);
                    tma_store_2d(&P.mapO, stg + 8192, 64, h * SEQ + qt * 128 + wg * 64);
                    asm volatile("cp.async.bulk.commit_group;" ::: "memory");
                    asm volatile("cp.async.bulk.wait_group.read 0;" ::: "memory");
                    mbar_arrive(bar_oe + 8 * wg);
                    asm volatile("cp.async.bulk.wait_group 0;" ::: "memory");
                    signal_ctr(CT_CA + qt * 2 + (h >= O2_HE));
                    if (last) break;
                }
            }
        } else if (lane == 0) {
            int it = 0, t = blockIdx.x, hp_ready = 1 << (fa_head(t) >> 1);
            auto load_q = [&](int item, int t) {
                const uint32_t b = bar_q + 8 * (item & 1);
                asm volatile("st.shared.s32 [%0], %1;" :: "r"(slot + (item & 1) * 4), "r"(t) : "memory");
                if (t < 0) { mbar_arrive(b); return; }
                const int row = fa_head(t) * SEQ + fa_qt(t) * 128;
                mbar_expect_tx(b, 32768);
                tma_load_2d(sb + FA_Q + (item & 1) * 32768, &P.mapQ, b, 0, row);
                tma_load_2d(sb + FA_Q + (item & 1) * 32768 + 16384, &P.mapQ, b, 64, row);
            };
            load_q(0, t);
            for (int item = 0; t >= 0; item++) {
                const int h = fa_head(t);
                for (int j = fa_qt(t); j >= 0; j--, it++) {
                    const int s = it & 1;
                    const uint32_t ph = ((it >> 1) & 1) ^ 1;
                    const uint32_t sk = sb + FA_KV + s * 65536, sv = sk + 32768;
                    if (j == 0) t = (int)(gridDim.x + atomicAdd(&g_ctr[CT_ATTN], 1u));
                    mbar_wait(bar_ke + 8 * s, ph);
                    mbar_expect_tx(bar_kf + 8 * s, 32768);
                    tma_load_2d(sk, &P.mapK, bar_kf + 8 * s, 0, h * SEQ + j * 128);
                    tma_load_2d(sk + 16384, &P.mapK, bar_kf + 8 * s, 64, h * SEQ + j * 128);
                    if (j == 0) {
                        if (t >= FA_ITEMS) t = -1;
                        else {
                            const int hp = fa_head(t) >> 1;
                            if (!((hp_ready >> hp) & 1)) { wait_ctr(CT_AP + hp, 96u); hp_ready |= 1 << hp; }
                        }
                        mbar_wait(bar_qe + 8 * ((item + 1) & 1), (((item + 1) >> 1) & 1) ^ 1);
                        load_q(item + 1, t);
                    }
                    mbar_wait(bar_ve + 8 * s, ph);
                    mbar_expect_tx(bar_vf + 8 * s, 32768);
                    tma_load_2d(sv, &P.mapV, bar_vf + 8 * s, 0, h * SEQ + j * 128);
                    tma_load_2d(sv + 16384, &P.mapV, bar_vf + 8 * s, 64, h * SEQ + j * 128);
                }
            }
        }
    } else {
        asm volatile("setmaxnreg.inc.sync.aligned.u32 232;");
        const int wg = warp >> 2;
        const bool lane0 = lane == 0;
        float o[64], sacc[64];
        uint32_t pa[32];
        float mrow0, mrow1, lrow0, lrow1;
        const float sc = 0.08838834764831845f * 1.4426950408889634f;
        const uint32_t q_lo = desc_lo(sb + FA_Q + wg * 8192, 16), k_lo = desc_lo(sb + FA_KV, 16), v_lo = desc_lo(sb + FA_KV + 32768, 16384);
        auto issue_qk = [&](int item, int it) {
            const uint32_t a = q_lo + (item & 1) * 2048, b = k_lo + (it & 1) * 4096;
#pragma unroll
            for (int kk = 0; kk < 8; kk++) wgmma_ss_n128_lo<0>(sacc, a + (kk >> 2) * 1024 + (kk & 3) * 2, b + (kk >> 2) * 1024 + (kk & 3) * 2, kk != 0);
            wgmma_commit();
        };
        auto issue_pv = [&](int it, bool acc) {
            const uint32_t b = v_lo + (it & 1) * 4096;
#pragma unroll
            for (int kk = 0; kk < 8; kk++) wgmma_rs_n128_tb_lo(o, &pa[kk * 4], b + kk * 128, kk != 0 || acc);
            wgmma_commit();
        };
        auto turn_wait = [&]() { asm volatile("bar.sync %0, 256;" :: "r"(1 + wg) : "memory"); };
        auto turn_pass = [&]() { asm volatile("bar.arrive %0, 256;" :: "r"(2 - wg) : "memory"); };
        auto mask = [&]() {
            const int r0 = wg * 64 + (warp & 3) * 16 + (lane >> 2) - (lane & 3) * 2;
#pragma unroll
            for (int i = 0; i < 64; i++)
                if ((i >> 2) * 8 + (i & 1) - ((i & 2) ? 8 : 0) > r0) sacc[i] = -INFINITY;
        };
        auto row_max = [&](float& mx0, float& mx1) {
            float mx[4];
#pragma unroll
            for (int i = 0; i < 4; i++) mx[i] = fmaxf(sacc[i], sacc[i + 4]);
#pragma unroll
            for (int i = 8; i < 64; i++) mx[i & 3] = fmaxf(mx[i & 3], sacc[i]);
            mx0 = fmaxf(mx0, fmaxf(mx[0], mx[1])); mx1 = fmaxf(mx1, fmaxf(mx[2], mx[3]));
            const float u0 = __shfl_xor_sync(0xffffffff, mx0, 1), u1 = __shfl_xor_sync(0xffffffff, mx1, 1);
            mx0 = fmaxf(mx0, u0); mx1 = fmaxf(mx1, u1);
            const float v0 = __shfl_xor_sync(0xffffffff, mx0, 2), v1 = __shfl_xor_sync(0xffffffff, mx1, 2);
            mx0 = fmaxf(mx0, v0); mx1 = fmaxf(mx1, v1);
        };
        auto pin_after = [&](float v) {
            asm volatile("{\n.reg .pred p;\nsetp.lt.f32 p, %1, 0f00000000;\n@p st.shared.f32 [%0], %1;\n}" :: "r"(slot + 16), "f"(v) : "memory");
        };
        auto pack_p = [&]() {
#pragma unroll
            for (int i = 0; i < 32; i++) pa[i] = pack_bf16(sacc[2 * i], sacc[2 * i + 1]);
        };
        auto first_softmax = [&]() {
            mask();
            mrow0 = -INFINITY; mrow1 = -INFINITY;
            row_max(mrow0, mrow1);
            const float ms0 = mrow0 * sc, ms1 = mrow1 * sc;
            float sum[4] = {0.f, 0.f, 0.f, 0.f};
#pragma unroll
            for (int i = 0; i < 64; i++) { sacc[i] = ex2f(fmaf(sacc[i], sc, (i & 2) ? -ms1 : -ms0)); sum[i & 3] += sacc[i]; }
            lrow0 = sum[0] + sum[1]; lrow1 = sum[2] + sum[3];
        };
        auto epilogue = [&](int item, int tag, float l0, float l1) {
            l0 += __shfl_xor_sync(0xffffffff, l0, 1); l1 += __shfl_xor_sync(0xffffffff, l1, 1);
            l0 += __shfl_xor_sync(0xffffffff, l0, 2); l1 += __shfl_xor_sync(0xffffffff, l1, 2);
            float i0, i1;
            asm("rcp.approx.ftz.f32 %0, %1;" : "=f"(i0) : "f"(l0));
            asm("rcp.approx.ftz.f32 %0, %1;" : "=f"(i1) : "f"(l1));
            const int row = (warp & 3) * 16 + (lane >> 2);
            const uint32_t stg = sb + FA_O + wg * 16384 + row * 128;
#pragma unroll
            for (int i = 0; i < 4; i++) {
                const int ch = i * 4 + (lane & 3);
                const uint32_t a = stg + (ch >> 3) * 8192 + (((ch & 7) ^ (row & 7)) << 4);
                const float* q = &o[i * 16];
                asm volatile("st.shared.v4.b32 [%0], {%1, %2, %3, %4};" :: "r"(a), "r"(pack_bf16(q[0] * i0, q[1] * i0)), "r"(pack_bf16(q[4] * i0, q[5] * i0)),
                             "r"(pack_bf16(q[8] * i0, q[9] * i0)), "r"(pack_bf16(q[12] * i0, q[13] * i0)) : "memory");
                asm volatile("st.shared.v4.b32 [%0], {%1, %2, %3, %4};" :: "r"(a + 1024), "r"(pack_bf16(q[2] * i1, q[3] * i1)), "r"(pack_bf16(q[6] * i1, q[7] * i1)),
                             "r"(pack_bf16(q[10] * i1, q[11] * i1)), "r"(pack_bf16(q[14] * i1, q[15] * i1)) : "memory");
            }
            asm volatile("st.shared.s32 [%0], %1;" :: "r"(oslot + wg * 4), "r"(tag) : "memory");
            __syncwarp();
            mbar_arrive_if(bar_of + 8 * wg, lane0);
        };
        int it = 0, t = blockIdx.x, nkv = fa_qt(t) + 1;
        if (wg == 1) asm volatile("bar.arrive 1, 256;" ::: "memory");
        mbar_wait(bar_q, 0);
        mbar_wait(bar_kf, 0);
        turn_wait();
        wgmma_fence();
        issue_qk(0, 0);
        turn_pass();
        wgmma_wait<0>();
        mbar_arrive_if(bar_ke, lane0);
        mbar_arrive_if(bar_qe, lane0 && nkv == 1);
        first_softmax();
        pack_p();
#pragma unroll 1
        for (int item = 0;; item++) {
            uint32_t ok = 0;
#pragma unroll 1
            for (int j = 1; j < nkv; j++) {
                it++;
                if (__builtin_expect(!ok, 0)) {
                    mbar_wait(bar_kf + 8 * (it & 1), (it >> 1) & 1);
                    mbar_wait(bar_vf + 8 * ((it - 1) & 1), ((it - 1) >> 1) & 1);
                }
                turn_wait();
                wgmma_fence();
                issue_qk(item, it);
                issue_pv(it - 1, j > 1);
                turn_pass();
                wgmma_wait<1>();
                mbar_arrive_if(bar_ke + 8 * (it & 1), lane0);
                mbar_arrive_if(bar_qe + 8 * (item & 1), lane0 && j == nkv - 1);
                float mx0 = mrow0, mx1 = mrow1;
                row_max(mx0, mx1);
                const float ms0 = mx0 * sc, ms1 = mx1 * sc;
                const float a0 = ex2f(fmaf(mrow0, sc, -ms0)), a1 = ex2f(fmaf(mrow1, sc, -ms1));
                mrow0 = mx0; mrow1 = mx1;
                float sum[4] = {lrow0 * a0, 0.f, lrow1 * a1, 0.f};
#pragma unroll
                for (int i = 0; i < FA_PIN; i++) { sacc[i] = ex2f(fmaf(sacc[i], sc, (i & 2) ? -ms1 : -ms0)); sum[i & 3] += sacc[i]; }
                pin_after(sum[0] + sum[2]);
                wgmma_wait<0>();
                mbar_arrive_if(bar_ve + 8 * ((it - 1) & 1), lane0);
#pragma unroll
                for (int i = 0; i < 64; i++) {
                    if (i >= FA_PIN) { sacc[i] = ex2f(fmaf(sacc[i], sc, (i & 2) ? -ms1 : -ms0)); sum[i & 3] += sacc[i]; }
                    o[i] *= (i & 2) ? a1 : a0;
                    if (i & 1) pa[i >> 1] = pack_bf16(sacc[i - 1], sacc[i]);
                    if (i == FA_TEST) pin_after(sum[0]);
                    if (i == FA_TEST) ok = mbar_test(bar_kf + 8 * ((it + 1) & 1), ((it + 1) >> 1) & 1) & mbar_test(bar_vf + 8 * (it & 1), (it >> 1) & 1);
                }
                lrow0 = sum[0] + sum[1]; lrow1 = sum[2] + sum[3];
            }
            it++;
            int tn;
            mbar_wait(bar_q + 8 * ((item + 1) & 1), ((item + 1) >> 1) & 1);
            asm volatile("ld.shared.s32 %0, [%1];" : "=r"(tn) : "r"(slot + ((item + 1) & 1) * 4) : "memory");
            tn = __shfl_sync(0xffffffff, tn, 0);
            mbar_wait(bar_vf + 8 * ((it - 1) & 1), ((it - 1) >> 1) & 1);
            const float l0 = lrow0, l1 = lrow1;
            if (tn < 0) {
                wgmma_fence();
                issue_pv(it - 1, nkv > 1);
                mbar_wait(bar_oe + 8 * wg, (item & 1) ^ 1);
                wgmma_wait<0>();
                epilogue(item, t | 0x80000000, l0, l1);
                break;
            }
            mbar_wait(bar_kf + 8 * (it & 1), (it >> 1) & 1);
            turn_wait();
            wgmma_fence();
            issue_qk(item + 1, it);
            issue_pv(it - 1, nkv > 1);
            turn_pass();
            nkv = fa_qt(tn) + 1;
            mbar_wait(bar_oe + 8 * wg, (item & 1) ^ 1);
            wgmma_wait<1>();
            mbar_arrive_if(bar_ke + 8 * (it & 1), lane0);
            mbar_arrive_if(bar_qe + 8 * ((item + 1) & 1), lane0 && nkv == 1);
            mask();
            mrow0 = -INFINITY; mrow1 = -INFINITY;
            row_max(mrow0, mrow1);
            {
                const float ms0 = mrow0 * sc, ms1 = mrow1 * sc;
                pin_after(fmaf(ex2f(fmaf(sacc[0], sc, -ms0)), l0, ex2f(fmaf(sacc[2], sc, -ms1))));
                wgmma_wait<0>();
                mbar_arrive_if(bar_ve + 8 * ((it - 1) & 1), lane0);
                float sum[4] = {0.f, 0.f, 0.f, 0.f};
#pragma unroll
                for (int i = 0; i < 64; i++) { sacc[i] = ex2f(fmaf(sacc[i], sc, (i & 2) ? -ms1 : -ms0)); sum[i & 3] += sacc[i]; }
                lrow0 = sum[0] + sum[1]; lrow1 = sum[2] + sum[3];
                pack_p();
                epilogue(item, t, l0, l1);
            }
            t = tn;
        }
        TS_END(1);
    }
}

__device__ __forceinline__ uint32_t cluster_ctarank() {
    uint32_t r; asm volatile("mov.u32 %0, %%cluster_ctarank;" : "=r"(r)); return r;
}
__device__ __forceinline__ uint32_t mapa_u32(uint32_t addr, uint32_t rank) {
    uint32_t r; asm volatile("mapa.shared::cluster.u32 %0, %1, %2;" : "=r"(r) : "r"(addr), "r"(rank)); return r;
}
__device__ __forceinline__ void cluster_sync_all() {
    asm volatile("barrier.cluster.arrive.release.aligned;\nbarrier.cluster.wait.acquire.aligned;" ::: "memory");
}
__device__ __forceinline__ void cluster_sync_relaxed() {
    asm volatile("barrier.cluster.arrive.relaxed.aligned;\nbarrier.cluster.wait.aligned;" ::: "memory");
}
__device__ __forceinline__ void st_async_v4(uint32_t addr, uint32_t a, uint32_t b, uint32_t c, uint32_t d, uint32_t mbar) {
    asm volatile("st.async.weak.shared::cluster.mbarrier::complete_tx::bytes.v4.b32 [%0], {%1, %2, %3, %4}, [%5];"
                 :: "r"(addr), "r"(a), "r"(b), "r"(c), "r"(d), "r"(mbar) : "memory");
}
__device__ __forceinline__ void st_async_v2(uint32_t addr, uint32_t a, uint32_t b, uint32_t mbar) {
    asm volatile("st.async.weak.shared::cluster.mbarrier::complete_tx::bytes.v2.b32 [%0], {%1, %2}, [%3];"
                 :: "r"(addr), "r"(a), "r"(b), "r"(mbar) : "memory");
}
__device__ __forceinline__ void st_async_b32(uint32_t addr, uint32_t a, uint32_t mbar) {
    asm volatile("st.async.weak.shared::cluster.mbarrier::complete_tx::bytes.b32 [%0], %1, [%2];" :: "r"(addr), "r"(a), "r"(mbar) : "memory");
}
__device__ __forceinline__ void pace(int cycles) {
    if (cycles > 0) {
        uint32_t t0, t;
        asm volatile("mov.u32 %0, %%clock;" : "=r"(t0));
        do { asm volatile("mov.u32 %0, %%clock;" : "=r"(t)); } while (t - t0 < (uint32_t)cycles);
    }
}
__device__ __forceinline__ void mbar_wait_cl(uint32_t bar, uint32_t parity) {
    uint32_t done = 0;
    for (int it = 0; it < (1 << 22) && !done; it++) {
        asm volatile(
            "{\n.reg .pred p;\n"
            "mbarrier.try_wait.parity.shared::cta.b64 p, [%1], %2;\n"
            "selp.u32 %0, 1, 0, p;\n}\n" : "=r"(done) : "r"(bar), "r"(parity) : "memory");
    }
}
__device__ __forceinline__ void ldmatrix_x4(uint32_t& r0, uint32_t& r1, uint32_t& r2, uint32_t& r3, uint32_t addr) {
    asm volatile("ldmatrix.sync.aligned.m8n8.x4.shared.b16 {%0,%1,%2,%3}, [%4];"
                 : "=r"(r0), "=r"(r1), "=r"(r2), "=r"(r3) : "r"(addr));
}
__device__ __forceinline__ void cp_async16(uint32_t dst, const void* src) {
    asm volatile("cp.async.cg.shared.global [%0], [%1], 16;" :: "r"(dst), "l"(src) : "memory");
}

#define DBG(i)
#define DBGW(i, w)
__device__ __forceinline__ void tma_load_2d_mc(uint32_t dst, const CUtensorMap* map, uint32_t bar, int c0, int c1, uint16_t mask) {
    asm volatile(
        "cp.async.bulk.tensor.2d.shared::cluster.global.mbarrier::complete_tx::bytes.multicast::cluster [%0], [%1, {%3, %4}], [%2], %5;"
        :: "r"(dst), "l"((uint64_t)map), "r"(bar), "r"(c0), "r"(c1), "h"(mask) : "memory");
}
__device__ __forceinline__ void bulk_s2s(uint32_t dst_cl, uint32_t src, uint32_t bytes, uint32_t bar_cl) {
    asm volatile("cp.async.bulk.shared::cluster.shared::cta.mbarrier::complete_tx::bytes [%0], [%1], %2, [%3];"
                 :: "r"(dst_cl), "r"(src), "r"(bytes), "r"(bar_cl) : "memory");
}
__device__ __forceinline__ bool elect_one() {
    uint32_t p;
    asm volatile("{\n.reg .pred p;\nelect.sync _|p, 0xffffffff;\nselp.u32 %0, 1, 0, p;\n}" : "=r"(p));
    return p;
}
__device__ __forceinline__ void fence_async_smem() { asm volatile("fence.proxy.async.shared::cta;" ::: "memory"); }
template <int ID, int N> __device__ __forceinline__ void bar_sync() { asm volatile("bar.sync %0, %1;" :: "n"(ID), "n"(N) : "memory"); }
template <int ID, int N> __device__ __forceinline__ void bar_arrive() { asm volatile("bar.arrive %0, %1;" :: "n"(ID), "n"(N) : "memory"); }
__device__ __forceinline__ void sts32(uint32_t a, uint32_t v) { asm volatile("st.shared.u32 [%0], %1;" :: "r"(a), "r"(v) : "memory"); }
__device__ __forceinline__ void ldsm_x4(uint32_t* r, uint32_t addr) {
    asm volatile("ldmatrix.sync.aligned.m8n8.x4.shared.b16 {%0,%1,%2,%3}, [%4];" : "=r"(r[0]), "=r"(r[1]), "=r"(r[2]), "=r"(r[3]) : "r"(addr) : "memory");
}
__device__ __forceinline__ uint32_t pin(uint32_t v) { asm volatile("" : "+r"(v)); return v; }
constexpr uint32_t DHI128 = 0x40000040u, DHI32 = 0xC0000010u;
#define ACC16(d) "+f"(d[0]), "+f"(d[1]), "+f"(d[2]), "+f"(d[3]), "+f"(d[4]), "+f"(d[5]), "+f"(d[6]), "+f"(d[7]), "+f"(d[8]), "+f"(d[9]), "+f"(d[10]), \
    "+f"(d[11]), "+f"(d[12]), "+f"(d[13]), "+f"(d[14]), "+f"(d[15])
#define ACC20(d) ACC16(d), "+f"(d[16]), "+f"(d[17]), "+f"(d[18]), "+f"(d[19])
__device__ __forceinline__ void wgmma_rs(float (&d)[16], const uint32_t (&a)[4], uint32_t db_lo) {
    asm volatile(
        "{\n.reg .b64 db;\nmov.b64 db, {%20, %21};\n"
        "wgmma.mma_async.sync.aligned.m64n32k16.f32.bf16.bf16 {%0,%1,%2,%3,%4,%5,%6,%7,%8,%9,%10,%11,%12,%13,%14,%15}, {%16,%17,%18,%19}, db, 1, 1, 1, 0;\n}\n"
        : ACC16(d) : "r"(a[0]), "r"(a[1]), "r"(a[2]), "r"(a[3]), "r"(db_lo), "n"(DHI128));
}
__device__ __forceinline__ void wgmma_rs(float (&d)[20], const uint32_t (&a)[4], uint32_t db_lo) {
    asm volatile(
        "{\n.reg .b64 db;\nmov.b64 db, {%24, %25};\n"
        "wgmma.mma_async.sync.aligned.m64n40k16.f32.bf16.bf16 {%0,%1,%2,%3,%4,%5,%6,%7,%8,%9,%10,%11,%12,%13,%14,%15,%16,%17,%18,%19}, {%20,%21,%22,%23}, db, 1, 1, 1, 0;\n}\n"
        : ACC20(d) : "r"(a[0]), "r"(a[1]), "r"(a[2]), "r"(a[3]), "r"(db_lo), "n"(DHI128));
}
template <uint32_t AHI, uint32_t BHI>
__device__ __forceinline__ void wgmma_ss(float (&d)[16], uint32_t da_lo, uint32_t db_lo) {
    asm volatile(
        "{\n.reg .b64 da, db;\nmov.b64 da, {%16, %18};\nmov.b64 db, {%17, %19};\n"
        "wgmma.mma_async.sync.aligned.m64n32k16.f32.bf16.bf16 {%0,%1,%2,%3,%4,%5,%6,%7,%8,%9,%10,%11,%12,%13,%14,%15}, da, db, 1, 1, 1, 0, 0;\n}\n"
        : ACC16(d) : "r"(da_lo), "r"(db_lo), "n"(AHI), "n"(BHI));
}
template <uint32_t AHI, uint32_t BHI>
__device__ __forceinline__ void wgmma_ss(float (&d)[20], uint32_t da_lo, uint32_t db_lo) {
    asm volatile(
        "{\n.reg .b64 da, db;\nmov.b64 da, {%20, %22};\nmov.b64 db, {%21, %23};\n"
        "wgmma.mma_async.sync.aligned.m64n40k16.f32.bf16.bf16 {%0,%1,%2,%3,%4,%5,%6,%7,%8,%9,%10,%11,%12,%13,%14,%15,%16,%17,%18,%19}, da, db, 1, 1, 1, 0, 0;\n}\n"
        : ACC20(d) : "r"(da_lo), "r"(db_lo), "n"(AHI), "n"(BHI));
}
template <uint32_t AHI, uint32_t BHI>
__device__ __forceinline__ void wgmma_ss0(float (&d)[20], uint32_t da_lo, uint32_t db_lo) {
    asm volatile(
        "{\n.reg .b64 da, db;\nmov.b64 da, {%20, %22};\nmov.b64 db, {%21, %23};\n"
        "wgmma.mma_async.sync.aligned.m64n40k16.f32.bf16.bf16 {%0,%1,%2,%3,%4,%5,%6,%7,%8,%9,%10,%11,%12,%13,%14,%15,%16,%17,%18,%19}, da, db, 0, 1, 1, 0, 0;\n}\n"
        : "=f"(d[0]), "=f"(d[1]), "=f"(d[2]), "=f"(d[3]), "=f"(d[4]), "=f"(d[5]), "=f"(d[6]), "=f"(d[7]), "=f"(d[8]), "=f"(d[9]), "=f"(d[10]),
          "=f"(d[11]), "=f"(d[12]), "=f"(d[13]), "=f"(d[14]), "=f"(d[15]), "=f"(d[16]), "=f"(d[17]), "=f"(d[18]), "=f"(d[19])
        : "r"(da_lo), "r"(db_lo), "n"(AHI), "n"(BHI));
}
__device__ __forceinline__ void wgmma_ss_n8(float (&d)[4], uint32_t da_lo, uint32_t db_lo) {
    asm volatile(
        "{\n.reg .b64 da, db;\nmov.b64 da, {%4, %6};\nmov.b64 db, {%5, %7};\n"
        "wgmma.mma_async.sync.aligned.m64n8k16.f32.bf16.bf16 {%0,%1,%2,%3}, da, db, 1, 1, 1, 1, 0;\n}\n"
        : "+f"(d[0]), "+f"(d[1]), "+f"(d[2]), "+f"(d[3]) : "r"(da_lo), "r"(db_lo), "n"(DHI128), "n"(DHI32));
}

constexpr uint32_t C2_WO = 0;
constexpr uint32_t C2_XB = 65536;
constexpr uint32_t C2_XS = 40960;
constexpr uint32_t C2_QX = C2_XB + 2 * C2_XS;
constexpr uint32_t C2_KX = C2_QX + 4096;
constexpr uint32_t C2_VT = C2_KX + 5120;
constexpr uint32_t C2_OB = C2_VT + 12288;
constexpr uint32_t C2_QM = C2_OB + 8192;
constexpr uint32_t C2_SC = C2_QM + 1024;
constexpr uint32_t C2_PB = C2_SC + 2560;
constexpr uint32_t C2_BAR = C2_PB + 768;
constexpr uint32_t C2_PX = C2_BAR + 256;
constexpr uint32_t C2_SX = C2_PX + 3072;
#define C2_NS 4
constexpr uint32_t C2_WS = C2_SX + 20480;
constexpr int C2_SMEM = C2_WS + 3 * C2_NS * 2048;
static_assert(C2_PX % 256 == 0 && C2_WS % 256 == 0 && C2_SMEM <= 232448, "smem map");
#define CH_PF 0
#define CH_PFD 3000
#define CH_WOT 1
#define CH_B4E 0
#define CH_NCH 4
#define CH_POLL_DELAY 600

__device__ __forceinline__ uint32_t c2_stage(int wg, int i) { return wg < 2 ? C2_XB + C2_XS + (wg * 4 + i) * 8192 : ((C2_PX + 1023) & ~1023u) + i * 8192; }
static_assert(C2_XB + C2_XS + 8 * 8192 <= C2_BAR && ((C2_PX + 1023) & ~1023u) + 4 * 8192 <= C2_SMEM && (C2_XB + C2_XS) % 1024 == 0, "staging");
__device__ __forceinline__ void c2_stage_load(const CUtensorMap* map, uint32_t sb, int wg, int rank, int col0, int round) {
    const uint32_t bar = sb + C2_BAR + 176 + (wg * 2 + round) * 8;
    mbar_expect_tx(bar, 32768);
    for (int i = 0; i < 4; i++) tma_load_2d(sb + c2_stage(wg, i), map, bar, col0, ((rank - round * 4 - i) & 7) * 64);
}
__device__ __forceinline__ void c2_load_w(uint32_t (&w)[32][4], const CUtensorMap* map, int wg, int rank, int col0, uint32_t t128, uint32_t ws, uint32_t sb) {
#pragma unroll
    for (int r = 0; r < 2; r++) {
        mbar_wait(sb + C2_BAR + 176 + (wg * 2 + r) * 8, 0);
#pragma unroll
        for (int e = 0; e < 16; e++) {
            const uint32_t a = sb + c2_stage(wg, 0) + e * 2048;
            uint32_t w0, w1, w2, w3;
            asm volatile("ld.shared.b32 %0, [%1];" : "=r"(w0) : "r"(a + t128) : "memory");
            asm volatile("ld.shared.b32 %0, [%1];" : "=r"(w1) : "r"(a + (t128 ^ 16) + 128) : "memory");
            asm volatile("ld.shared.b32 %0, [%1];" : "=r"(w2) : "r"(a + t128 + 1024) : "memory");
            asm volatile("ld.shared.b32 %0, [%1];" : "=r"(w3) : "r"(a + (t128 ^ 16) + 1152) : "memory");
            uint32_t* d = w[r * 16 + e];
            d[0] = __byte_perm(w0, w1, 0x5410); d[1] = __byte_perm(w0, w1, 0x7632);
            d[2] = __byte_perm(w2, w3, 0x5410); d[3] = __byte_perm(w2, w3, 0x7632);
        }
        if (r == 0) {
            asm volatile("bar.sync %0, 128;" :: "r"(8 + wg) : "memory");
            if ((threadIdx.x & 127) == 32) c2_stage_load(map, sb, wg, rank, col0, 1);
            mbar_wait(sb + C2_BAR + 168, 0);
#pragma unroll 2
            for (int i = threadIdx.x; i < 2048; i += 384) {
                const int k = i >> 2, b = i & 3;
                const uint32_t a0 = sb + C2_WO + k * 128 + (((2 * b) ^ (k & 7)) << 4), a1 = a0 ^ 16;
                uint4 u, v;
                asm volatile("ld.shared.v4.b32 {%0, %1, %2, %3}, [%4];" : "=r"(u.x), "=r"(u.y), "=r"(u.z), "=r"(u.w) : "r"(a0) : "memory");
                asm volatile("ld.shared.v4.b32 {%0, %1, %2, %3}, [%4];" : "=r"(v.x), "=r"(v.y), "=r"(v.z), "=r"(v.w) : "r"(a1) : "memory");
                asm volatile("st.shared.v4.b32 [%0], {%1, %2, %3, %4};" :: "r"(a0), "r"(__byte_perm(u.x, u.y, 0x5410)),
                             "r"(__byte_perm(u.z, u.w, 0x5410)), "r"(__byte_perm(v.x, v.y, 0x5410)), "r"(__byte_perm(v.z, v.w, 0x5410)) : "memory");
                asm volatile("st.shared.v4.b32 [%0], {%1, %2, %3, %4};" :: "r"(a1), "r"(__byte_perm(u.x, u.y, 0x7632)),
                             "r"(__byte_perm(u.z, u.w, 0x7632)), "r"(__byte_perm(v.x, v.y, 0x7632)), "r"(__byte_perm(v.z, v.w, 0x7632)) : "memory");
            }
        }
    }
    cluster_sync_relaxed();
#pragma unroll
    for (int e = 0; e < C2_NS; e++) stmatrix_x4(ws + e * 2048, w[e][0], w[e][1], w[e][2], w[e][3]);
    for (int i = threadIdx.x; i < 2 * 512 + 256; i += 384)
        sts32(sb + (i < 1024 ? C2_VT + (i >> 9) * 6144 + 4096 + (i & 511) * 4 : C2_PX + 2048 + (i - 1024) * 4), 0u);
    fence_async_smem();
    asm volatile("bar.sync %0, 128;" :: "r"(8 + wg) : "memory");
}
template <int NA>
__device__ __forceinline__ void c2_xstream(float (&acc)[NA], const uint32_t (&w)[32][4], uint32_t xlo, uint32_t rank, uint32_t wslo) {
#pragma unroll
    for (int i = 0; i < NA; i++) acc[i] = 0.f;
    wgmma_fence();
#pragma unroll
    for (int e = 0; e < 32; e++) {
        if (e < C2_NS) wgmma_ss<DHI32, DHI128>(acc, wslo + e * 128, xlo + ((rank - (e >> 2)) & 7) * 320 + (e & 3) * 2);
        else wgmma_rs(acc, w[e], xlo + ((rank - (e >> 2)) & 7) * 320 + (e & 3) * 2);
    }
    wgmma_commit();
}
__device__ __forceinline__ constexpr int c2_grp(int i) { return i < 2 ? i : 1 + (i >> 1); }

struct ChainParams {
    CUtensorMap mapX;
    CUtensorMap mapM;
    CUtensorMap mapW[3];
    CUtensorMap mapWo;
};
__global__ void __cluster_dims__(8, 1, 1) __launch_bounds__(384, 1)
chain_kernel(const __grid_constant__ ChainParams P) {
    const CUtensorMap& mapX = P.mapX;
    extern __shared__ __align__(1024) uint8_t smem_chain[];
    const uint32_t sb = smem_u32(smem_chain);
    const uint32_t dlo = ((sb & 0x3FFFF) >> 4) | (1u << 16);
    const int tid = threadIdx.x, lane = tid & 31;
    const int warp = __shfl_sync(0xffffffff, tid >> 5, 0), wg = warp >> 2, w4 = warp & 3;
    const uint32_t rank = cluster_ctarank();
    const int C = blockIdx.x >> 3;
    const int h = C * 4 + (rank >> 1);
    const int g = lane >> 2, qc = lane & 3;
    pdl_launch_dependents();
    TS_BEGIN(2);
    const uint32_t bar_m = sb + C2_BAR, bar_o = bar_m + 64, bar_sc = bar_m + 128, bar_x = bar_m + 136, bar_sx = bar_m + 152;
    const uint32_t bar_w = bar_m + 168;
    const int col0 = h * HD + (rank & 1) * 64;
    if (tid == 0) {
        for (int j = 0; j < 5; j++) { mbar_init(bar_m + 8 * j, j ? 1 : 4); mbar_init(bar_o + 8 * j, j ? 1 : 4); }
        for (int j = 0; j < 12; j++) mbar_init(bar_sc + 8 * j, 1);
        asm volatile("fence.mbarrier_init.release.cluster;" ::: "memory");
    }
    __syncwarp();
    cluster_sync_relaxed();
    if (tid == 0) {
        mbar_expect_tx(bar_x, 32768 + 8192);
        tma_load_2d_mc(sb + C2_XB + rank * 5120, &mapX, bar_x, rank * 64, 0, (uint16_t)0xff);
        for (int j = 0; j < 8; j++) tma_load_2d(sb + C2_XB + j * 5120 + 4096, &P.mapM, bar_x, j * 64, 0);
        pace(CH_PFD);
        mbar_expect_tx(bar_w, 65536);
        for (int j = 0; j < 8; j++) tma_load_2d(sb + C2_WO + j * 8192, &P.mapWo, bar_w, rank * 64, C * 512 + ((rank - j) & 7) * 64);
    }
    if ((tid & 127) == 32) {
        pace(CH_PFD);
        c2_stage_load(&P.mapW[wg], sb, wg, rank, col0, 0);
        if (CH_PF)
            for (int i = 4; i < 8; i++)
                asm volatile("cp.async.bulk.prefetch.tensor.2d.L2.global [%0, {%1, %2}];" :: "l"((uint64_t)&P.mapW[wg]), "r"(col0), "r"((int)((rank - i) & 7) * 64) : "memory");
    }
    __syncwarp();

    const uint32_t t32 = w4 * 256 + qc * 64 + (((g >> 2) ^ (qc >> 1)) << 4) + (g & 3) * 4;
    const uint32_t t128 = qc * 256 + (((2 * w4 + (g >> 2)) ^ (2 * qc)) << 4) + (g & 3) * 4;
    const uint32_t a32 = (w4 * 16 + (lane & 15)) * 32 + (((lane >> 4) ^ ((lane >> 2) & 1)) << 4);
    const uint32_t ws = sb + C2_WS + wg * (C2_NS * 2048) + a32;
    uint32_t w[32][4];
    static_assert(C2_NS == 4, "slot 0");
    auto proj_mem = [&](float (&a)[CH_NCH][4], int s, uint32_t l128) {
        uint32_t b[4][8];
#pragma unroll
        for (int i = 0; i < 4 * CH_NCH; i++) a[i >> 2][i & 3] = 0.f;
        const uint32_t par = (s & 1) ^ 1;
        const uint32_t mb = sb + C2_XB + (s & 1) * C2_XS + 4096;
        auto L = [&](int i) {
            ldsm_x4(b[i & 3], mb + ((rank - i) & 7) * 5120 + l128);
            ldsm_x4(b[i & 3] + 4, mb + ((rank - i) & 7) * 5120 + (l128 ^ 64));
        };
        auto H = [&](int i) {
#pragma unroll
            for (int kk = 0; kk < 4; kk++) {
                const uint32_t* f = i ? w[i * 4 + kk] : &b[2 + (kk >> 1)][(kk & 1) * 4];
                mma_16816(a[(i * 4 + kk) % CH_NCH], f[0], f[1], f[2], f[3], b[i & 3][2 * kk], b[i & 3][2 * kk + 1]);
            }
        };
#pragma unroll
        for (int e = 0; e < 4; e++) ldsm_x4(&b[2 + (e >> 1)][(e & 1) * 4], ws + e * 2048);
        mbar_wait(bar_m, par);
        L(0);
        H(0);
        mbar_wait(bar_m + 8, par);
        DBGW(1 + 16 * wg, 0);
        L(1);
        mbar_wait(bar_m + 16, par);
        uint32_t nxt = mbar_test(bar_m + 24, par);
        L(2); L(3);
        H(1);
        if (__builtin_expect(!nxt, 0)) mbar_wait(bar_m + 24, par);
        nxt = mbar_test(bar_m + 32, par);
        L(4); L(5);
        H(2); H(3);
        if (__builtin_expect(!nxt, 0)) mbar_wait(bar_m + 32, par);
        DBGW(2 + 16 * wg, 0);
        L(6); L(7);
        H(4); H(5); H(6); H(7);
#pragma unroll
        for (int i = 0; i < 4; i++) a[0][i] = CH_NCH == 4 ? (a[0][i] + a[1][i]) + (a[2][i] + a[3 % CH_NCH][i]) : CH_NCH == 3 ? a[0][i] + a[1][i] + a[2 % CH_NCH][i] : a[0][i] + a[1][i];
    };
    auto store_x = [&](const float (&acc)[16], uint32_t base) {
#pragma unroll
        for (int j = 0; j < 4; j++) {
            sts32(base + t128 + j * 1024, pack_bf16(acc[4 * j], acc[4 * j + 2]));
            sts32(base + (t128 ^ 16) + 128 + j * 1024, pack_bf16(acc[4 * j + 1], acc[4 * j + 3]));
        }
    };
    const float scale = 0.08838834764831845f, l2e = 1.4426950408889634f;

    if (wg == 0) {
        c2_load_w(w, &P.mapW[0], 0, rank, col0, t128, ws, sb);
        TS_END(6);
        TS_BEGIN(5);
#pragma unroll 1
        for (int s = -1;;) {
            uint32_t xok = 0;
            if (s >= 0) {
                float acc[4] = {0.f, 0.f, 0.f, 0.f};
                const uint32_t tag = ((s >> 1) & 1) ^ 1;
                uint32_t* dst = reinterpret_cast<uint32_t*>(g_xbuf + (((s & 1) * 8 + rank) * 8 + C) * 128) + qc * 64 + w4 * 8 + g;
                asm volatile("" : "+l"(dst));
                uint32_t nxt = 0;
#pragma unroll
                for (int i = 0; i < 8; i++) {
                    if (i < 2 || !(i & 1)) {
                        if (i < 2 || __builtin_expect(!nxt, 0)) mbar_wait(bar_o + 8 * c2_grp(i), s & 1);
                        if (i == 0) DBGW(7, 0);
                        if (i == 1) DBGW(8, 0);
                        if (i == 6) DBGW(9, 0);
                        wgmma_fence();
                    }
#pragma unroll
                    for (int kk = 0; kk < 4; kk++) {
                        if ((i & 1) && i < 7 && kk == CH_WOT) nxt = mbar_test(bar_o + 8 * c2_grp(i + 1), s & 1);
                        wgmma_ss_n8(acc, dlo + ((C2_WO + i * 8192 + kk * 2048) >> 4), dlo + ((C2_OB + i * 1024 + kk * 256) >> 4));
                    }
                }
                wgmma_commit();
                if (CH_B4E) bar_arrive<4, 384>();
                bar_arrive<11, 256>();
                xok = mbar_test(bar_x + 8 * ((s + 1) & 1), ((s + 1) >> 1) & 1);
                wgmma_wait<0>();
                asm volatile("st.relaxed.gpu.global.u32 [%0], %1;" :: "l"(dst), "r"((pack_bf16(acc[0], acc[2]) & ~1u) | tag) : "memory");
                asm volatile("st.relaxed.gpu.global.u32 [%0 + 128], %1;" :: "l"(dst), "r"((pack_bf16(acc[1], acc[3]) & ~1u) | tag) : "memory");
                if (!CH_B4E) bar_arrive<4, 384>();
                DBGW(10, 0);
            }
            s++;
            if (__builtin_expect(!xok, 0)) mbar_wait(bar_x + 8 * (s & 1), (s >> 1) & 1);
            float acc[16];
            c2_xstream(acc, w, dlo + ((C2_XB + (s & 1) * C2_XS) >> 4), rank, dlo + (C2_WS >> 4));
            const uint32_t sca = pin(w4 < 2 ? sb + C2_SC + w4 * 512 + lane * 16 : sb + C2_SC + 1024 + lane * 8);
            const uint32_t krow = w4 * 16 + (lane & 15);
            const uint32_t ka0 = pin(sb + C2_KX + krow * 128 + (((lane >> 4) ^ (krow & 7)) << 4));
            const uint32_t l32 = pin(sb + C2_QM + (lane >> 4) * 256 + (lane & 7) * 32 + ((((lane >> 3) & 1) ^ ((lane >> 2) & 1)) << 4));
            const uint32_t qst = pin(sb + C2_QM + t32);
            const uint32_t l128 = pin((lane & 7) * 128 + (((lane >> 3) ^ (lane & 7)) << 4));
            if (s > 0) bar_sync<5, 256>();
            wgmma_wait<0>();
            store_x(acc, sb + C2_QX);
            DBGW(0, 0);
            if (s == NSEG - 1) break;
            {
                float a[CH_NCH][4];
                proj_mem(a, s, l128);
                sts32(qst, pack_bf16(a[0][0], a[0][2]));
                sts32(qst + 32, pack_bf16(a[0][1], a[0][3]));
            }
            DBGW(3, 0);
            if (w4 < 3) {
                uint32_t ka[4][4], qb[8];
                float c[4] = {0.f, 0.f, 0.f, 0.f}, c2[4] = {0.f, 0.f, 0.f, 0.f};
                const uint32_t sc_peer = pin(mapa_u32(sca + 1280, rank ^ 1)), sc_own = pin(mapa_u32(sca, rank));
                bar_sync<1, 384>();
                ldsm_x4(qb, l32);
                ldsm_x4(ka[0], ka0);
                ldsm_x4(ka[1], ka0 ^ 32);
                ldsm_x4(qb + 4, l32 + 512);
                ldsm_x4(ka[2], ka0 ^ 64);
                ldsm_x4(ka[3], ka0 ^ 96);
                mma_16816(c, ka[0][0], ka[0][1], ka[0][2], ka[0][3], qb[0], qb[1]);
                mma_16816(c2, ka[1][0], ka[1][1], ka[1][2], ka[1][3], qb[2], qb[3]);
                mma_16816(c, ka[2][0], ka[2][1], ka[2][2], ka[2][3], qb[4], qb[5]);
                mma_16816(c2, ka[3][0], ka[3][1], ka[3][2], ka[3][3], qb[6], qb[7]);
                const uint32_t u0 = __float_as_uint(c[0] + c2[0]), u1 = __float_as_uint(c[1] + c2[1]);
                const uint32_t u2 = __float_as_uint(c[2] + c2[2]), u3 = __float_as_uint(c[3] + c2[3]);
                asm volatile(
                    "{\n.reg .pred p;\nsetp.lt.u32 p, %8, 2;\n"
                    "@p st.async.weak.shared::cluster.mbarrier::complete_tx::bytes.v4.b32 [%0], {%4, %5, %6, %7}, [%1];\n"
                    "@!p st.async.weak.shared::cluster.mbarrier::complete_tx::bytes.v2.b32 [%0], {%4, %5}, [%1];\n"
                    "@p st.async.weak.shared::cluster.mbarrier::complete_tx::bytes.v4.b32 [%2], {%4, %5, %6, %7}, [%3];\n"
                    "@!p st.async.weak.shared::cluster.mbarrier::complete_tx::bytes.v2.b32 [%2], {%4, %5}, [%3];\n}"
                    :: "r"(sc_peer), "r"(mapa_u32(bar_sc, rank ^ 1)), "r"(sc_own), "r"(mapa_u32(bar_sc, rank)), "r"(u0), "r"(u1), "r"(u2), "r"(u3), "r"(w4) : "memory");
                bar_arrive<2, 224>();
                if (s >= 4 * CB_FIRST + 5 && (s & 3) == 1 && tid == 0) signal_ctr(CT_CB + ((s - 5) >> 2));
                __syncwarp();
                DBGW(4, 2);
            } else {
                bar_arrive<1, 384>();
                const uint32_t a = pin(sb + C2_SC + lane * 16), a2 = pin(sb + C2_SC + 1024 + lane * 8), pa = pin(sb + C2_PB + lane * 4);
                mbar_wait(bar_sc, s & 1);
                DBG(5);
                float v[10];
                {
                    float4 x0, x1, y0, y1; float2 x2, y2;
                    asm volatile("ld.shared.v4.f32 {%0, %1, %2, %3}, [%4];" : "=f"(x0.x), "=f"(x0.y), "=f"(x0.z), "=f"(x0.w) : "r"(a) : "memory");
                    asm volatile("ld.shared.v4.f32 {%0, %1, %2, %3}, [%4];" : "=f"(y0.x), "=f"(y0.y), "=f"(y0.z), "=f"(y0.w) : "r"(a + 1280) : "memory");
                    asm volatile("ld.shared.v4.f32 {%0, %1, %2, %3}, [%4];" : "=f"(x1.x), "=f"(x1.y), "=f"(x1.z), "=f"(x1.w) : "r"(a + 512) : "memory");
                    asm volatile("ld.shared.v4.f32 {%0, %1, %2, %3}, [%4];" : "=f"(y1.x), "=f"(y1.y), "=f"(y1.z), "=f"(y1.w) : "r"(a + 1792) : "memory");
                    asm volatile("ld.shared.v2.f32 {%0, %1}, [%2];" : "=f"(x2.x), "=f"(x2.y) : "r"(a2) : "memory");
                    asm volatile("ld.shared.v2.f32 {%0, %1}, [%2];" : "=f"(y2.x), "=f"(y2.y) : "r"(a2 + 1280) : "memory");
                    v[0] = x0.x + y0.x; v[1] = x0.y + y0.y; v[2] = x0.z + y0.z; v[3] = x0.w + y0.w;
                    v[4] = x1.x + y1.x; v[5] = x1.y + y1.y; v[6] = x1.z + y1.z; v[7] = x1.w + y1.w;
                    v[8] = x2.x + y2.x; v[9] = x2.y + y2.y;
                }
                float m0 = fmaxf(fmaxf(fmaxf(v[0], v[2]), fmaxf(v[4], v[6])), v[8]);
                float m1 = fmaxf(fmaxf(fmaxf(v[1], v[3]), fmaxf(v[5], v[7])), v[9]);
#pragma unroll
                for (int o = 4; o < 32; o <<= 1) {
                    m0 = fmaxf(m0, __shfl_xor_sync(0xffffffff, m0, o));
                    m1 = fmaxf(m1, __shfl_xor_sync(0xffffffff, m1, o));
                }
                const float sl = scale * l2e;
                m0 *= sl; m1 *= sl;
#pragma unroll
                for (int j = 0; j < 5; j++)
                    sts32(pa + j * 128, pack_bf16(ex2f(fmaf(v[2 * j], sl, -m0)), ex2f(fmaf(v[2 * j + 1], sl, -m1))));
                bar_arrive<3, 160>();
                DBG(6);
            }
            fence_async_smem();
            bar_arrive<6, 384>();
        }
        bar_sync<1, 384>();
        fence_async_smem();
        bar_arrive<6, 384>();
        bar_arrive<4, 384>();
    } else if (wg == 1) {
        c2_load_w(w, &P.mapW[1], 1, rank, col0, t128, ws, sb);
#pragma unroll 1
        for (int s = -1;;) {
            if (s > 0) {
                mbar_wait(bar_sx + 8 * ((s - 1) & 1), ((s - 1) >> 1) & 1);
                const uint32_t a = sb + C2_SX + ((s - 1) & 1) * 10240 + w4 * 1280 + lane * 8;
                float v[10];
                const int lim = 8 * w4 + g - 2 * qc;
#pragma unroll
                for (int j = 0; j < 5; j++) {
                    float2 x, y;
                    asm volatile("ld.shared.v2.f32 {%0, %1}, [%2];" : "=f"(x.x), "=f"(x.y) : "r"(a + j * 256) : "memory");
                    asm volatile("ld.shared.v2.f32 {%0, %1}, [%2];" : "=f"(y.x), "=f"(y.y) : "r"(a + 5120 + j * 256) : "memory");
                    v[2 * j] = (j < 4 && 8 * j > lim) ? -INFINITY : x.x + y.x;
                    v[2 * j + 1] = (j < 4 && 8 * j + 1 > lim) ? -INFINITY : x.y + y.y;
                }
                float mx = fmaxf(fmaxf(fmaxf(v[0], v[1]), fmaxf(v[2], v[3])), fmaxf(fmaxf(v[4], v[5]), fmaxf(v[6], v[7])));
                mx = fmaxf(mx, fmaxf(v[8], v[9]));
                mx = fmaxf(mx, __shfl_xor_sync(0xffffffff, mx, 1));
                mx = fmaxf(mx, __shfl_xor_sync(0xffffffff, mx, 2));
                const float sl = scale * l2e;
                mx *= sl;
#pragma unroll
                for (int j = 0; j < 10; j++) v[j] = ex2f(fmaf(v[j], sl, -mx));
                float sm = ((v[0] + v[1]) + (v[2] + v[3])) + ((v[4] + v[5]) + (v[6] + v[7])) + (v[8] + v[9]);
                sm += __shfl_xor_sync(0xffffffff, sm, 1);
                sm += __shfl_xor_sync(0xffffffff, sm, 2);
                float inv;
                asm("rcp.approx.ftz.f32 %0, %1;" : "=f"(inv) : "f"(sm));
                const uint32_t pa = sb + C2_PX + w4 * 256 + g * 32 + ((g >> 2) << 4) + qc * 4;
#pragma unroll
                for (int j = 0; j < 5; j++) sts32((pa ^ ((j & 1) << 4)) + (j >> 1) * 1024, pack_bf16(v[2 * j] * inv, v[2 * j + 1] * inv));
            }
            if (s >= 0) {
                fence_async_smem();
                if (s < NSEG) bar_sync<6, 384>(); else bar_sync<7, 128>();
                DBGW(20, 0);
                uint32_t cp[8];
                {
                    float cx[16];
#pragma unroll
                    for (int i = 0; i < 16; i++) cx[i] = 0.f;
                    wgmma_fence();
#pragma unroll
                    for (int kk = 0; kk < 3; kk++)
                        wgmma_ss<DHI32, DHI32>(cx, dlo + ((C2_VT + ((s - 1) & 1) * 6144 + kk * 2048) >> 4), dlo + ((C2_PX + kk * 1024) >> 4));
                    wgmma_commit();
                    wgmma_wait<0>();
#pragma unroll
                    for (int j = 0; j < 4; j++) { cp[2 * j] = pack_bf16(cx[4 * j], cx[4 * j + 2]); cp[2 * j + 1] = pack_bf16(cx[4 * j + 1], cx[4 * j + 3]); }
                    asm volatile("{\n.reg .pred p;\nsetp.gt.u32 p, %0, 99;\n@p st.shared.v4.b32 [%0], {%1, %2, %3, %4};\n@p st.shared.v4.b32 [%0], {%5, %6, %7, %8};\n}"
                                 :: "r"(rank), "r"(cp[0]), "r"(cp[1]), "r"(cp[2]), "r"(cp[3]), "r"(cp[4]), "r"(cp[5]), "r"(cp[6]), "r"(cp[7]) : "memory");
                }
                float sx[20];
                wgmma_fence();
                wgmma_ss0<DHI128, DHI128>(sx, dlo + (C2_QX >> 4), dlo + (C2_KX >> 4));
#pragma unroll
                for (int kk = 1; kk < 4; kk++) wgmma_ss<DHI128, DHI128>(sx, dlo + (C2_QX >> 4) + kk * 2, dlo + (C2_KX >> 4) + kk * 2);
                wgmma_commit();
                wgmma_wait<0>();
                if (s < NSEG - 1) bar_arrive<5, 256>();
                if (s < NSEG && w4 < 2) {
                    const uint32_t a = sb + C2_SX + (s & 1) * 10240 + w4 * 2560;
#pragma unroll
                    for (int j = 0; j < 5; j++) {
                        asm volatile("st.shared.v2.f32 [%0], {%1, %2};" :: "r"(a + lane * 8 + j * 256), "f"(sx[4 * j]), "f"(sx[4 * j + 1]) : "memory");
                        asm volatile("st.shared.v2.f32 [%0], {%1, %2};" :: "r"(a + lane * 8 + 1280 + j * 256), "f"(sx[4 * j + 2]), "f"(sx[4 * j + 3]) : "memory");
                    }
                    fence_async_smem();
                    __syncwarp();
                    if (elect_one()) bulk_s2s(mapa_u32(a + 5120, rank ^ 1), a, 2560, mapa_u32(bar_sx + 8 * (s & 1), rank ^ 1));
                    __syncwarp();
                }
                if (s > 0) {
                    uint32_t* dst = reinterpret_cast<uint32_t*>(g_ctxB + ((size_t)h * SEQ + (s - 1) * SEGL + 2 * qc) * HD + (rank & 1) * 64 + w4 * 16 + 2 * g);
#pragma unroll
                    for (int j = 0; j < 4; j++) {
                        asm volatile("st.global.u32 [%0], %1;" :: "l"(dst + j * 8 * (HD / 2)), "r"(cp[2 * j]) : "memory");
                        asm volatile("st.global.u32 [%0], %1;" :: "l"(dst + (j * 8 + 1) * (HD / 2)), "r"(cp[2 * j + 1]) : "memory");
                    }
                }
                DBGW(22, 0);
                if (s == NSEG) break;
            }
            if (s < NSEG - 1) mbar_wait(bar_x + 8 * ((s + 1) & 1), ((s + 1) >> 1) & 1);
            if (s >= 0) bar_sync<4, 384>();
            s++;
            if (s < NSEG) {
                float acc[16];
                c2_xstream(acc, w, dlo + ((C2_XB + (s & 1) * C2_XS) >> 4), rank, dlo + ((C2_WS + C2_NS * 2048) >> 4));
                const uint32_t kst = pin(sb + C2_KX + 4096 + t128);
                const uint32_t l128 = pin((lane & 7) * 128 + (((lane >> 3) ^ (lane & 7)) << 4));
                wgmma_wait<0>();
                store_x(acc, sb + C2_KX);
                DBGW(16, 0);
                float a[CH_NCH][4];
                proj_mem(a, s, l128);
                sts32(kst, pack_bf16(a[0][0], a[0][2]));
                sts32((kst ^ 16) + 128, pack_bf16(a[0][1], a[0][3]));
                bar_arrive<1, 384>();
                DBGW(19, 0);
                if (w4 == 0) {
                    if (s < NSEG - 1) {
                        if (lane == 0) mbar_expect_tx(bar_sc, 2560);
                        if (lane < 16 && (lane & 7) >= 1 && (lane & 7) < 5) mbar_expect_tx(bar_m + 8 * lane, (lane & 7) == 1 ? 1024 : 2048);
                        if (lane == 8) {
                            mbar_expect_tx(bar_x + 8 * ((s + 1) & 1), 32768);
                            tma_load_2d_mc(sb + C2_XB + ((s + 1) & 1) * C2_XS + rank * 5120, &mapX, bar_x + 8 * ((s + 1) & 1), rank * 64, (s + 1) * SEGL, (uint16_t)0xff);
                            if (s + 2 < NSEG)
                                asm volatile("cp.async.bulk.prefetch.tensor.2d.L2.global [%0, {%1, %2}];" :: "l"((uint64_t)&mapX), "r"(rank * 64), "r"((s + 2) * SEGL) : "memory");
                        }
                    }
                    if (lane == 16) mbar_expect_tx(bar_sx + 8 * (s & 1), 5120);
                    __syncwarp();
                }
            }
        }
        bar_sync<7, 128>();
        if (tid == 128) signal_ctr(CT_CB + 15);
    } else {
        c2_load_w(w, &P.mapW[2], 2, rank, col0, t128, ws, sb);
#pragma unroll 1
        for (int s = -1;;) {
            if (s >= 0) {
                const int t = tid - 256;
                const uint2* src = g_xbuf + ((s & 1) * 8 + rank) * 1024 + t;
                asm volatile("" : "+l"(src));
                const uint32_t ma = sb + C2_XB + ((s + 1) & 1) * C2_XS + rank * 5120 + 4096 + (t >> 4) * 128 + ((((t >> 1) & 7) ^ (t >> 4)) << 4) + (t & 1) * 8;
                uint32_t ra[8], rb[8];
#pragma unroll
                for (int i = 1; i < 8; i++) {
                    const uint32_t d = (rank + i) & 7;
                    ra[i] = pin(mapa_u32(ma, d)); rb[i] = pin(mapa_u32(bar_m + 8 * c2_grp(i), d));
                }
                bar_arrive<4, 384>();
                if (s == NSEG - 1) break;
                bar_sync<11, 256>();
                DBGW(29, 0);
                pace(CH_POLL_DELAY);
                const uint32_t tag = ((s >> 1) & 1) ^ 1;
                uint32_t p[8][2], m0, m1;
                auto issue = [&](uint32_t (&x)[8][2]) {
#pragma unroll
                    for (int k = 0; k < 8; k++)
                        asm volatile("ld.relaxed.gpu.global.v2.u32 {%0, %1}, [%2];" : "=r"(x[k][0]), "=r"(x[k][1]) : "l"(src + k * 128) : "memory");
                };
                auto check = [&](const uint32_t (&x)[8][2]) {
                    uint32_t bad = 0, bad2 = 0;
                    float r[4];
#pragma unroll
                    for (int k = 0; k < 8; k++) {
                        asm("lop3.b32 %0, %0, %1, %2, 0xf6;" : "+r"(bad) : "r"(x[k][0]), "r"(tag));
                        asm("lop3.b32 %0, %0, %1, %2, 0xf6;" : "+r"(bad2) : "r"(x[k][1]), "r"(tag));
#pragma unroll
                        for (int e = 0; e < 2; e++) {
                            const float lo = __uint_as_float(x[k][e] << 16), hi = __uint_as_float(x[k][e] & 0xffff0000u);
                            r[2 * e] = k ? r[2 * e] + lo : lo;
                            r[2 * e + 1] = k ? r[2 * e + 1] + hi : hi;
                        }
                    }
                    m0 = pack_bf16(r[0], r[1]); m1 = pack_bf16(r[2], r[3]);
                    asm volatile("" : "+r"(m0), "+r"(m1));
                    return __all_sync(0xffffffff, ((bad | bad2) & 1u) == 0u);
                };
                for (int it = 0; it < (1 << 20); it++) {
                    issue(p);
                    if (check(p)) break;
                }
                DBGW(30, 0);
                st_async_v2(ra[1], m0, m1, rb[1]);
                asm volatile("st.shared.v2.b32 [%0], {%1, %2};" :: "r"(ma), "r"(m0), "r"(m1) : "memory");
                __syncwarp();
                if (lane == 0) mbar_arrive(bar_m);
#pragma unroll
                for (int i = 2; i < 8; i++) st_async_v2(ra[i], m0, m1, rb[i]);
                DBGW(31, 0);
            }
            s++;
            const uint32_t ost = pin(sb + C2_OB + t32), pla = pin(sb + C2_PB + lane * 16), plb = pin(sb + C2_PB + 512 + (lane & 7) * 16);
            bar_sync<1, 384>();
            fence_async_smem();
            DBGW(24, 0);
            if (s < NSEG - 1) bar_sync<2, 224>();
            uint32_t va[5][2];
            {
                float acc[20];
                c2_xstream(acc, w, dlo + ((C2_XB + (s & 1) * C2_XS) >> 4), rank, dlo + ((C2_WS + 2 * C2_NS * 2048) >> 4));
                wgmma_wait<0>();
#pragma unroll
                for (int j = 0; j < 5; j++) { va[j][0] = pack_bf16(acc[4 * j], acc[4 * j + 1]); va[j][1] = pack_bf16(acc[4 * j + 2], acc[4 * j + 3]); }
            }
            DBGW(26, 0);
            if (s < NSEG - 1) {
                uint32_t p[5];
                bar_sync<3, 160>();
                DBGW(27, 0);
                ldmatrix_x4_trans(p[0], p[1], p[2], p[3], pla);
                asm volatile("ldmatrix.sync.aligned.m8n8.x1.trans.shared.b16 {%0}, [%1];" : "=r"(p[4]) : "r"(plb) : "memory");
                float oa[4] = {0.f, 0.f, 0.f, 0.f}, ob[4] = {0.f, 0.f, 0.f, 0.f}, sa[4] = {0.f, 0.f, 0.f, 0.f}, sc[4] = {0.f, 0.f, 0.f, 0.f};
                const uint32_t one = 0x3f803f80u;
                mma_16816(sa, one, one, one, one, p[0], p[1]);
                mma_16816(oa, va[0][0], va[0][1], va[1][0], va[1][1], p[0], p[1]);
                mma_16816(sc, one, one, one, one, p[2], p[3]);
                mma_16816(ob, va[2][0], va[2][1], va[3][0], va[3][1], p[2], p[3]);
                mma_16816(sa, one, one, one, one, p[4], 0u);
                mma_16816(oa, va[4][0], va[4][1], 0u, 0u, p[4], 0u);
                bar_arrive<6, 384>();
                float i0, i1;
                asm("rcp.approx.ftz.f32 %0, %1;" : "=f"(i0) : "f"(sa[0] + sc[0]));
                asm("rcp.approx.ftz.f32 %0, %1;" : "=f"(i1) : "f"(sa[1] + sc[1]));
                sts32(ost, pack_bf16((oa[0] + ob[0]) * i0, (oa[2] + ob[2]) * i0));
                sts32(ost + 32, pack_bf16((oa[1] + ob[1]) * i1, (oa[3] + ob[3]) * i1));
                fence_async_smem();
                __syncwarp();
                if (elect_one()) {
#pragma unroll
                    for (int i = 1; i < 8; i++) {
                        const uint32_t d = (rank + i) & 7;
                        bulk_s2s(mapa_u32(sb + C2_OB + i * 1024 + w4 * 256, d), sb + C2_OB + w4 * 256, 256, mapa_u32(bar_o + 8 * c2_grp(i), d));
                        if (i == 1) mbar_arrive(bar_o);
                    }
                }
                __syncwarp();
                DBGW(28, 0);
            } else bar_arrive<6, 384>();
            {
                const uint32_t a = sb + C2_VT + (s & 1) * 6144 + a32;
                stmatrix_x4(a, va[0][0], va[0][1], va[1][0], va[1][1]);
                stmatrix_x4(a + 2048, va[2][0], va[2][1], va[3][0], va[3][1]);
                asm volatile("stmatrix.sync.aligned.m8n8.x2.shared.b16 [%0], {%1, %2};" :: "r"(a + 4096), "r"(va[4][0]), "r"(va[4][1]) : "memory");
            }
            fence_async_smem();
        }
        g_xbuf[((8 + rank) * 8 + C) * 128 + (tid - 256)] = make_uint2(0u, 0u);
    }
    cluster_sync_relaxed();
    TS_END(2);
}

struct Proj2Params {
    CUtensorMap mapA[2];
    CUtensorMap mapW[3];
    bf16* out[3];
};
#define P2T(i)
#define P2_NOMMA 0
#define P2_NOLOAD 0
constexpr int P2_STAGES = 6;
constexpr int P2_SMEM = 131072 + P2_STAGES * 16384 + 1024 + 1024;
constexpr int P2_ITEMS = 168 + 48;
__device__ __forceinline__ int p2_reps(int t) { return t >= 168 ? 1 : 2; }
__device__ __forceinline__ void p2_tile(int t, int w, int& z, int& mp, int& head) {
    if (t >= 168) { w += ((t - 168) & 1) * 2; t = 168 + ((t - 168) >> 1); }
    const int hq = t / 24, v = t % 24;
    mp = v & 7;
    if (v < 16) { head = hq * 4 + (v >> 3) * 2 + (w >> 1); z = 1 + (w & 1); }
    else { head = hq * 4 + w; z = 0; }
}
__device__ __forceinline__ void mbar_arrive_remote(uint32_t bar_cluster_addr) {
    asm volatile("mbarrier.arrive.release.cluster.shared::cluster.b64 _, [%0];" :: "r"(bar_cluster_addr) : "memory");
}
__device__ __forceinline__ void mbar_arrive_cl(uint32_t bar_cluster_addr) {
    asm volatile("mbarrier.arrive.shared::cluster.b64 _, [%0];" :: "r"(bar_cluster_addr) : "memory");
}
__device__ __forceinline__ void mbar_wait_acq_cluster(uint32_t bar, uint32_t parity) {
    asm volatile(
        "{\n"
        ".reg .pred p, q;\n"
        ".reg .u32 c;\n"
        "mov.u32 c, 0;\n"
        "WAIT_LOOP_C:\n"
        "mbarrier.try_wait.parity.acquire.cluster.shared::cta.b64 p, [%0], %1;\n"
        "@p bra WAIT_DONE_C;\n"
        "add.u32 c, c, 1;\n"
        "setp.lt.u32 q, c, 4000000;\n"
        "@q bra WAIT_LOOP_C;\n"
        "WAIT_DONE_C:\n"
        "}\n" :: "r"(bar), "r"(parity) : "memory");
}
__device__ __forceinline__ uint4 quad_transpose(uint32_t p0, uint32_t p1, uint32_t p2, uint32_t p3, int lane) {
    const bool o1 = lane & 1, o2 = lane & 2;
    uint32_t s0 = o1 ? p0 : p1, s1 = o1 ? p2 : p3;
    s0 = __shfl_xor_sync(0xffffffff, s0, 1); s1 = __shfl_xor_sync(0xffffffff, s1, 1);
    const uint32_t a_lo = o1 ? s0 : p0, a_hi = o1 ? p1 : s0, b_lo = o1 ? s1 : p2, b_hi = o1 ? p3 : s1;
    uint32_t t0 = o2 ? a_lo : b_lo, t1 = o2 ? a_hi : b_hi;
    t0 = __shfl_xor_sync(0xffffffff, t0, 2); t1 = __shfl_xor_sync(0xffffffff, t1, 2);
    return o2 ? make_uint4(t0, t1, b_lo, b_hi) : make_uint4(a_lo, a_hi, t0, t1);
}
#define P2_PACE 35
#define P2_PACE2 0
template <bool PERM, int PACE = 0>
__device__ __forceinline__ void store_frag_128(const float (&acc)[64], bf16* obase, int lane) {
#pragma unroll
    for (int rr = 0; rr < 2; rr++)
#pragma unroll
        for (int g = 0; g < 4; g++) {
            const float* a = &acc[g * 16 + rr * 2];
            const uint32_t p0 = pack_bf16(a[0], a[1]), p1 = pack_bf16(a[4], a[5]), p2 = pack_bf16(a[8], a[9]), p3 = pack_bf16(a[12], a[13]);
            *reinterpret_cast<uint4*>(obase + (size_t)(rr * 8) * HD + g * 32) = PERM ? make_uint4(p0, p1, p2, p3) : quad_transpose(p0, p1, p2, p3, lane);
            pace(PACE);
        }
}
__global__ void __cluster_dims__(2, 1, 1) __launch_bounds__(384, 1) proj2_kernel(const __grid_constant__ Proj2Params P) {
    extern __shared__ uint8_t smem_raw[];
    const uint32_t sbase = (smem_u32(smem_raw) + 1023) & ~1023u;
    const uint32_t sA = sbase, sB = sbase + 131072, sC = sB + P2_STAGES * 16384;
    const uint32_t bars = sC;
    const uint32_t a_full = bars, a_empty = bars + 64, b_full = bars + 128, b_empty = b_full + 8 * P2_STAGES;
    const uint32_t item_bar = b_empty + 8 * P2_STAGES, item_in = item_bar + 16, slot = item_in + 16;
    const uint32_t note_bar = slot + 16, note_free = note_bar + 64, note = note_free + 64;
    const int warp = threadIdx.x >> 5, lane = threadIdx.x & 31;
    const uint32_t rank = cluster_ctarank();
    TS_BEGIN(0);
    if (threadIdx.x == 0) {
        for (int i = 0; i < 8; i++) { mbar_init(a_full + 8 * i, 1); mbar_init(a_empty + 8 * i, 2); }
        for (int i = 0; i < P2_STAGES; i++) { mbar_init(b_full + 8 * i, 1); mbar_init(b_empty + 8 * i, 2); }
        mbar_init(item_bar, 1); mbar_init(item_bar + 8, 1); mbar_init(item_in, 2); mbar_init(item_in + 8, 2);
        for (int i = 0; i < 8; i++) { mbar_init(note_bar + 8 * i, 1); mbar_init(note_free + 8 * i, 1); }
        asm volatile("fence.mbarrier_init.release.cluster;" ::: "memory");
    }
    __syncwarp();
    cluster_sync_relaxed();
    pdl_launch_dependents();
    if (warp == 9) {
        if (lane == 0) {
            for (int n = 0;; n++) {
                const int e = (n & 1) * 4 + ((n >> 1) & 3);
                mbar_wait(note_bar + 8 * e, (n >> 3) & 1);
                int m;
                asm volatile("ld.shared.s32 %0, [%1];" : "=r"(m) : "r"(note + e * 4) : "memory");
                mbar_arrive(note_free + 8 * e);
                if (m < 0) break;
                signal_ctr(m);
            }
        }
    } else if (warp == 10) {
        if (lane == 0) {
            auto publish = [&](int ic, int tq) {
                const int t = tq < P2_ITEMS ? tq : -1;
                asm volatile("st.shared.s32 [%0], %1;" :: "r"(slot + (ic & 3) * 4), "r"(t) : "memory");
                mbar_arrive(item_bar + 8 * (ic & 1));
                st_async_b32(mapa_u32(slot + (ic & 3) * 4, 1), (uint32_t)t, mapa_u32(item_bar + 8 * (ic & 1), 1));
            };
            const int npair = (int)(gridDim.x >> 1), pair = (int)(blockIdx.x >> 1);
            if (rank == 0) publish(0, pair);
            for (int ic = 0;; ic++) {
                if (rank == 1) mbar_expect_tx(item_bar + 8 * (ic & 1), 4);
                mbar_wait(item_bar + 8 * (ic & 1), (ic >> 1) & 1);
                int t;
                asm volatile("ld.shared.s32 %0, [%1];" : "=r"(t) : "r"(slot + (ic & 3) * 4) : "memory");
                if (t < 0) break;
                int z0, mp, h0;
                p2_tile(t, 0, z0, mp, h0);
                const int aidx = z0 >= 1 ? 1 : 0;
                const int m0 = (2 * mp + (int)rank) * 128;
                for (int k = 0; k < 8; k++) {
                    mbar_wait(a_empty + 8 * k, (ic & 1) ^ 1);
                    if (P2_NOLOAD) mbar_arrive(a_full + 8 * k); else {
                    mbar_expect_tx(a_full + 8 * k, 16384);
                    tma_load_2d(sA + k * 16384, &P.mapA[aidx], a_full + 8 * k, k * 64, m0); }
                }
                if (rank == 0) {
                    mbar_wait(item_in + 8 * (ic & 1), (ic >> 1) & 1);
                    publish(ic + 1, ic == 0 ? npair + pair : 2 * npair + (int)atomicAdd(&g_ctr[CT_PROJ], 1u));
                }
            }
        }
    } else if (warp == 8 || warp == 11) {
        if (lane == 0) {
            const int par2 = warp == 8 ? 0 : 1;
            int it = 0; uint32_t bph = 0;
            for (int ic = 0;; ic++) {
                mbar_wait(item_bar + 8 * (ic & 1), (ic >> 1) & 1);
                int t;
                asm volatile("ld.shared.s32 %0, [%1];" : "=r"(t) : "r"(slot + (ic & 3) * 4) : "memory");
                if (t < 0) break;
                const int nt = 2 * p2_reps(t);
                for (int w = 0; w < nt; w++) {
                    int z, mp, hd;
                    p2_tile(t, w, z, mp, hd);
                    for (int k = 0; k < 8; k++) {
                        const int s = it; const uint32_t phb = bph;
                        if (++it == P2_STAGES) { it = 0; bph ^= 1; }
                        if ((k & 1) != par2) continue;
                        mbar_wait(b_empty + 8 * s, phb ^ 1);
                        if (P2_NOLOAD) { mbar_arrive(b_full + 8 * s); continue; }
                        mbar_expect_tx(b_full + 8 * s, 16384);
                        tma_load_2d_mc(sB + s * 16384 + rank * 8192, &P.mapW[z], b_full + 8 * s, hd * 128 + (int)rank * 64, k * 64, (uint16_t)3);
                    }
                }
            }
        }
    } else {
        const int wg = warp >> 2;
        float acc[2][64];
        const uint32_t a_lo = desc_lo(sA, 16), b_lo0 = desc_lo(sB, 8192);
        const bool elected = (threadIdx.x & 127) == 0;
        int s = (wg * 8) % P2_STAGES;
        uint32_t ph = ((wg * 8) / P2_STAGES) & 1;
        int nnote = 0;
        if (wg == 1) asm volatile("bar.arrive 3, 256;" ::: "memory");
        for (int ic = 0;; ic++) {
            mbar_wait(item_bar + 8 * (ic & 1), (ic >> 1) & 1);
            int t;
            asm volatile("ld.shared.s32 %0, [%1];" : "=r"(t) : "r"(slot + (ic & 3) * 4) : "memory");
            P2T(7);
            if (wg == 0 && t < 0) {
                if (elected) {
                    const int e = nnote & 3;
                    mbar_wait(note_free + 8 * e, ((nnote >> 2) & 1) ^ 1);
                    asm volatile("st.shared.s32 [%0], %1;" :: "r"(note + e * 4), "r"(-1) : "memory");
                    mbar_arrive(note_bar + 8 * e);
                }
            }
            if (t < 0) break;
            const int reps = p2_reps(t);
#pragma unroll 1
            for (int rp = 0; rp < reps; rp++) {
            const bool first = rp == 0, last = rp == reps - 1;
            int z, mp, head;
            p2_tile(t, rp * 2 + wg, z, mp, head);
            asm volatile("bar.sync %0, 256;" :: "r"(3 + wg) : "memory");
            P2T(0);
            if (wg == 1 && last && elected) mbar_arrive_cl(mapa_u32(item_in + 8 * (ic & 1), 0));
            int sprev = 0;
#pragma unroll
            for (int k = 0; k < 8; k++) {
                if (k == 0) P2T(5);
                if (wg == 0 && first) mbar_wait(a_full + 8 * k, ic & 1);
                if (k == 0) P2T(6);
                mbar_wait(b_full + 8 * s, ph);
                if (k == 7) asm volatile("bar.arrive %0, 256;" :: "r"(4 - wg) : "memory");
                if (k == 0) P2T(1);
                if (k == 7) P2T(2);
                const uint32_t b_lo = b_lo0 + s * 1024;
                wgmma_fence();
#pragma unroll
                for (int kk = 0; kk < (P2_NOMMA ? 1 : 4); kk++) {
                    wgmma_ss_n128_lo<1>(acc[0], a_lo + k * 1024 + kk * 2, b_lo + kk * 128, (k | kk) != 0);
                    wgmma_ss_n128_lo<1>(acc[1], a_lo + k * 1024 + 512 + kk * 2, b_lo + kk * 128, (k | kk) != 0);
                }
                wgmma_commit();
                if (k > 0) {
                    wgmma_wait<1>();
                    if (elected) {
                        const uint32_t e = b_empty + 8 * sprev;
                        mbar_arrive_cl(mapa_u32(e, 0)); mbar_arrive_cl(mapa_u32(e, 1));
                        if (last) mbar_arrive(a_empty + 8 * (k - 1));
                    }
                }
                sprev = s;
                if (++s == P2_STAGES) { s = 0; ph ^= 1; }
            }
            wgmma_wait<0>();
            P2T(3);
            if (elected) {
                const uint32_t e = b_empty + 8 * sprev;
                mbar_arrive_cl(mapa_u32(e, 0)); mbar_arrive_cl(mapa_u32(e, 1));
                if (last) mbar_arrive(a_empty + 8 * 7);
            }
            s += 8 % P2_STAGES; ph ^= (8 / P2_STAGES) & 1;
            if (s >= P2_STAGES) { s -= P2_STAGES; ph ^= 1; }
            const int m0 = (2 * mp + (int)rank) * 128;
            bf16* obase = P.out[z] + ((size_t)head * SEQ + m0 + (warp & 3) * 16 + (lane >> 2)) * HD + (lane & 3) * 8;
            store_frag_128<true, P2_PACE>(acc[0], obase, lane); store_frag_128<true, P2_PACE>(acc[1], obase + (size_t)64 * HD, lane);
            P2T(4);
            {
                asm volatile("bar.sync %0, 128;" :: "r"(1 + wg) : "memory");
                if (elected) {
                    const int e = wg * 4 + (nnote & 3);
                    mbar_wait(note_free + 8 * e, ((nnote >> 2) & 1) ^ 1);
                    asm volatile("st.shared.s32 [%0], %1;" :: "r"(note + e * 4), "r"(CT_AP + (head >> 1)) : "memory");
                    mbar_arrive(note_bar + 8 * e);
                }
                nnote++;
            }
            }
        }
        TS_END(0);
    }
    __syncwarp();
    cluster_sync_relaxed();
}

struct OutParams {
    CUtensorMap mapCtx[2];
    CUtensorMap mapWo[2];
    CUtensorMap mapOut;
};
__device__ uint4 g_part[4 * 32 * 8 * 16 * 32];

#define OT(i)
#define OTP(i)
#define O3_LK 16
#define O3_LK15 20
#define O3_D 5
constexpr int O3_E = 68, O3_GRID = O3_E + 64;
constexpr int O2_SMEM = 196608 + 1024 + 256;

__global__ void __cluster_dims__(2, 1, 1) __launch_bounds__(352, 1) out3_kernel(const __grid_constant__ OutParams P) {
    extern __shared__ uint8_t smem_raw[];
    const uint32_t sbase = (smem_u32(smem_raw) + 1023) & ~1023u;
    const uint32_t bar_full = sbase + 196608, bar_empty = bar_full + 64;
    const int warp = threadIdx.x >> 5, lane = threadIdx.x & 31;
    const uint32_t rank = cluster_ctarank();
    const int pair = blockIdx.x >> 1;
    const bool early = pair < O3_E / 2;
    constexpr int EB = 64 - O3_LK, EB15 = 64 - O3_LK15;
    int mt, part, a0, na, b0, nb;
    if (pair < 30) {
        part = pair >= 15; mt = part ? 29 - pair : pair;
        const int d = (14 - mt) * O3_D / 14;
        a0 = part ? 32 + d : 0; na = part ? 32 - d : 32 + d;
        b0 = part ? EB / 2 : 0; nb = part ? EB - EB / 2 : EB / 2;
    } else if (early) {
        part = pair - 30; mt = 15;
        a0 = part * 16; na = 16;
        b0 = part * EB15 / 4; nb = (part + 1) * EB15 / 4 - b0;
    } else {
        part = (pair - O3_E / 2) & 1; mt = (pair - O3_E / 2) >> 1;
        a0 = 0; na = 0; b0 = mt == 15 ? EB15 : EB; nb = 64 - b0;
    }
    const int m0 = mt * 128, nk = na + nb;
    const int n0 = early ? (int)rank * 256 : part * 256 + (int)rank * 128;
    const int nst = early ? 4 : 6;
    const uint32_t ssz = early ? 49152 : 32768;
    TS_BEGIN(4);
    OT(0);
    if (threadIdx.x == 0) {
        for (int i = 0; i < 6; i++) { mbar_init(bar_full + 8 * i, 1); mbar_init(bar_empty + 8 * i, 4); }
        asm volatile("fence.mbarrier_init.release.cluster;" ::: "memory");
    }
    if (threadIdx.x == 256) asm volatile("prefetch.tensormap [%0];" :: "l"((uint64_t)&P.mapCtx[early ? 0 : 1]) : "memory");
    if (threadIdx.x == 288) asm volatile("prefetch.tensormap [%0];" :: "l"((uint64_t)&P.mapWo[early ? 0 : 1]) : "memory");
    if (warp == 0 || warp > 8) asm volatile("bar.sync 1, 96;" ::: "memory");
    __syncwarp();
    asm volatile("barrier.cluster.arrive.relaxed.aligned;" ::: "memory");
    if (warp > 8) {
        if (lane == 0) {
            int s = 0; uint32_t ph = 0;
            for (int i = 0; i < nk; i++) {
                if (i >= nst) mbar_wait(bar_empty + 8 * s, ph ^ 1);
                const uint32_t sa = sbase + s * ssz + 16384;
                const int b = i >= na, k = b ? b0 + i - na : a0 + i;
                if (early) {
                    tma_load_2d(sa + (warp - 9) * 16384, &P.mapWo[b], bar_full + 8 * s, n0 + (warp - 9) * 128, k * 64);
                    tma_load_2d(sa + (warp - 9) * 16384 + 8192, &P.mapWo[b], bar_full + 8 * s, n0 + (warp - 9) * 128 + 64, k * 64);
                } else tma_load_2d(sa + (warp - 9) * 8192, &P.mapWo[1], bar_full + 8 * s, n0 + (warp - 9) * 64, k * 64);
                if (++s == nst) { s = 0; ph ^= 1; }
            }
        }
        __syncwarp();
        asm volatile("barrier.cluster.wait.acquire.aligned;" ::: "memory");
    } else if (warp == 8) {
        if (lane == 0) {
            if (early) wait_ctr(CT_CA + mt * 2, 2u * O2_HE); else wait_ctr(CT_CB + max(mt, CB_FIRST), 64u);
            OTP(3);
        }
        __syncwarp();
        asm volatile("barrier.cluster.wait.acquire.aligned;" ::: "memory");
        if (lane == 0) {
            OTP(7);
            int s = 0; uint32_t ph = 0;
            bool late_a = false;
            for (int i = 0; i < nk; i++) {
                const int b = i >= na, k = b ? b0 + i - na : a0 + i;
                if (!b && k >= 2 * O2_HE && !late_a) { wait_ctr(CT_CA + mt * 2 + 1, 2u * (NH - O2_HE)); late_a = true; }
                if (i == na && early) wait_ctr(CT_CB + max(mt, CB_FIRST), 64u);
                if (i >= nst) mbar_wait(bar_empty + 8 * s, ph ^ 1);
                mbar_expect_tx(bar_full + 8 * s, ssz);
                tma_load_2d_mc(sbase + s * ssz + rank * 8192, &P.mapCtx[b], bar_full + 8 * s, (k & 1) * 64, (k >> 1) * SEQ + m0 + (int)rank * 64, (uint16_t)3);
                if (++s == nst) { s = 0; ph ^= 1; }
            }
        }
    } else {
        asm volatile("barrier.cluster.wait.acquire.aligned;" ::: "memory");
        const int wg = warp >> 2;
        const bool elected = (threadIdx.x & 127) == 0;
        const int row = (warp & 3) * 16 + (lane >> 2);
        const int mrow = (warp & 3) * 16 + (lane & 15);
        const uint32_t moff = mrow * 128, mx = (lane >> 4) ^ (mrow & 7);
        float g0, g1;
        int s = 0, sprev = 0; uint32_t ph = 0;
        {
            unsigned int v; int it = 0;
            do { asm volatile("ld.acquire.gpu.global.u32 %0, [%1];" : "=r"(v) : "l"(&g_ctr[CT_G]) : "memory"); } while (v < FA_GRID && ++it < (1 << 22));
        }
        asm volatile("ld.relaxed.gpu.global.f32 %0, [%1];" : "=f"(g0) : "l"(g_gate + m0 + wg * 64 + row) : "memory");
        asm volatile("ld.relaxed.gpu.global.f32 %0, [%1];" : "=f"(g1) : "l"(g_gate + m0 + wg * 64 + row + 8) : "memory");
        auto release = [&](int st) {
            if (elected) { const uint32_t e = bar_empty + 8 * st; mbar_arrive_cl(mapa_u32(e, 0)); mbar_arrive_cl(mapa_u32(e, 1)); }
        };
        if (early) {
            float acc[128];
#pragma unroll 1
            for (int i = 0; i < nk; i++) {
                mbar_wait(bar_full + 8 * s, ph);
                if (i == 8) OT(2);
                if (i == na) {
                    wgmma_wait<0>();
                    const float r0 = g0 / fmaxf(1.f - g0, 0x1p-40f), r1 = g1 / fmaxf(1.f - g1, 0x1p-40f);
#pragma unroll
                    for (int j = 0; j < 32; j++) { acc[4 * j] *= r0; acc[4 * j + 1] *= r0; acc[4 * j + 2] *= r1; acc[4 * j + 3] *= r1; }
                }
                const uint32_t sa = sbase + s * 49152 + wg * 8192, sb = sbase + s * 49152 + 16384;
                wgmma_fence();
#pragma unroll
                for (int kk = 0; kk < 4; kk++)
                    wgmma_ss_n256_tb(acc, make_desc(sa + kk * 32, 16, 1024), make_desc(sb + kk * 2048, 8192, 1024), (i | kk) != 0);
                wgmma_commit();
                if (i > 0) { wgmma_wait<1>(); release(sprev); }
                sprev = s;
                if (++s == 4) { s = 0; ph ^= 1; }
            }
            wgmma_wait<0>();
            OT(4);
            const float w0 = fmaxf(1.f - g0, 0x1p-40f), w1 = fmaxf(1.f - g1, 0x1p-40f);
            uint4* dst = g_part + (((part * 32 + mt * 2 + (int)rank) * 8 + warp) * 16) * 32 + lane;
#pragma unroll
            for (int j = 0; j < 16; j++) {
                const float* a = &acc[8 * j];
                dst[j * 32] = make_uint4(pack_bf16(a[0] * w0, a[1] * w0), pack_bf16(a[2] * w1, a[3] * w1), pack_bf16(a[4] * w0, a[5] * w0), pack_bf16(a[6] * w1, a[7] * w1));
            }
            __syncwarp();
            OT(5);
            if (lane == 0) signal_ctr_generic(CT_OP + (mt * 2 + (int)rank) * 8 + warp);
            OT(6);
        } else {
            float acc[64];
            const uint32_t a_lo = desc_lo(sbase + wg * 8192, 16), b_lo = desc_lo(sbase + 16384, 8192);
#pragma unroll 1
            for (int i = 0; i < nk; i++) {
                mbar_wait(bar_full + 8 * s, ph);
                if (i == 8) OT(2);
                wgmma_fence();
#pragma unroll
                for (int kk = 0; kk < 4; kk++) wgmma_ss_n128_lo<1>(acc, a_lo + s * 2048 + kk * 2, b_lo + s * 2048 + kk * 128, (i | kk) != 0);
                wgmma_commit();
                if (i > 0) { wgmma_wait<1>(); release(sprev); }
                sprev = s;
                if (++s == 6) { s = 0; ph ^= 1; }
            }
            const int np = mt == 15 ? 4 : 2;
            wait_ctr(CT_OP + (mt * 2 + part) * 8 + warp, np);
            const uint4* src = g_part + (((mt * 2 + part) * 8 + warp) * 16 + (int)rank * 8) * 32 + lane;
            uint4 u[2][8];
            auto load_parts = [&](int p) {
#pragma unroll
                for (int i = 0; i < 16; i++)
                    asm volatile("ld.relaxed.gpu.global.v4.u32 {%0, %1, %2, %3}, [%4];" : "=r"(u[i >> 3][i & 7].x), "=r"(u[i >> 3][i & 7].y), "=r"(u[i >> 3][i & 7].z),
                                 "=r"(u[i >> 3][i & 7].w) : "l"(src + (p + (i >> 3)) * (32 * 8 * 16 * 32) + (i & 7) * 32) : "memory");
            };
            auto add_parts = [&]() {
#pragma unroll
                for (int i = 0; i < 16; i++) {
                    const uint32_t v[4] = {u[i >> 3][i & 7].x, u[i >> 3][i & 7].y, u[i >> 3][i & 7].z, u[i >> 3][i & 7].w};
#pragma unroll
                    for (int e = 0; e < 4; e++) {
                        acc[8 * (i & 7) + 2 * e] += __uint_as_float(v[e] << 16);
                        acc[8 * (i & 7) + 2 * e + 1] += __uint_as_float(v[e] & 0xffff0000u);
                    }
                }
            };
            load_parts(0);
            wgmma_wait<0>();
            OT(4);
            const float w0 = 1.f - g0, w1 = 1.f - g1;
#pragma unroll
            for (int j = 0; j < 16; j++) { acc[4 * j] *= w0; acc[4 * j + 1] *= w0; acc[4 * j + 2] *= w1; acc[4 * j + 3] *= w1; }
            add_parts();
            if (np == 4) { load_parts(2); add_parts(); }
            OT(5);
            mbar_wait(bar_empty + 8 * s, ph ^ 1);
            const uint32_t stg = sbase + s * 32768 + wg * 16384;
#pragma unroll
            for (int j = 0; j < 8; j++) {
                const float* a = &acc[8 * j];
                stmatrix_x4(stg + (j >> 2) * 8192 + moff + ((mx ^ ((j & 3) * 2)) << 4), pack_bf16(a[0], a[1]), pack_bf16(a[2], a[3]), pack_bf16(a[4], a[5]), pack_bf16(a[6], a[7]));
            }
            fence_async_smem();
            asm volatile("bar.sync %0, 128;" :: "r"(2 + wg) : "memory");
            if (elected) {
                tma_store_2d(&P.mapOut, stg, n0, m0 + wg * 64);
                tma_store_2d(&P.mapOut, stg + 8192, n0 + 64, m0 + wg * 64);
                asm volatile("cp.async.bulk.commit_group;" ::: "memory");
                asm volatile("cp.async.bulk.wait_group 0;" ::: "memory");
            }
            OT(6);
        }
    }
    __syncthreads();
    asm volatile("barrier.cluster.arrive.relaxed.aligned;" ::: "memory");
    if (warp == 0) {
        unsigned int tk = 0;
        if (lane == 0) tk = atomicAdd(&g_ctr[CT_FIN], 1u);
        tk = __shfl_sync(0xffffffff, tk, 0);
        if (tk == gridDim.x - 1)
            for (int i = lane; i < CT_N; i += 32) g_ctr[i] = 0u;
    }
    asm volatile("barrier.cluster.wait.acquire.aligned;" ::: "memory");
    TS_END(4);
}

typedef CUresult (*PFN_encodeTiled)(CUtensorMap*, CUtensorMapDataType, cuuint32_t, void*, const cuuint64_t*,
                                    const cuuint64_t*, const cuuint32_t*, const cuuint32_t*, CUtensorMapInterleave,
                                    CUtensorMapSwizzle, CUtensorMapL2promotion, CUtensorMapFloatOOBfill);
static PFN_encodeTiled g_encode = nullptr;

static void make_map(CUtensorMap* m, const void* ptr, uint64_t rows, uint64_t cols, uint32_t box_rows, bool sw64 = false) {
    cuuint64_t dims[2] = {cols, rows};
    cuuint64_t strides[1] = {cols * 2};
    cuuint32_t box[2] = {sw64 ? 32u : 64u, box_rows};
    cuuint32_t es[2] = {1, 1};
    g_encode(m, CU_TENSOR_MAP_DATA_TYPE_BFLOAT16, 2, const_cast<void*>(ptr), dims, strides, box, es,
             CU_TENSOR_MAP_INTERLEAVE_NONE, sw64 ? CU_TENSOR_MAP_SWIZZLE_64B : CU_TENSOR_MAP_SWIZZLE_128B, CU_TENSOR_MAP_L2_PROMOTION_L2_256B,
             CU_TENSOR_MAP_FLOAT_OOB_FILL_NONE);
}

template <typename... KArgs, typename... Args>
static void launch_pdl(void (*kernel)(KArgs...), int grid, int block, size_t smem, cudaStream_t st, bool pdl, Args... args) {
    cudaLaunchConfig_t cfg = {};
    cfg.gridDim = dim3(grid); cfg.blockDim = dim3(block); cfg.dynamicSmemBytes = smem; cfg.stream = st;
    cudaLaunchAttribute at[1];
    at[0].id = cudaLaunchAttributeProgrammaticStreamSerialization;
    at[0].val.programmaticStreamSerializationAllowed = 1;
    cfg.attrs = at; cfg.numAttrs = pdl ? 1 : 0;
    cudaLaunchKernelEx(&cfg, kernel, KArgs(args)...);
}

extern "C" void kernel_launch(void* const* d_in, const int* in_sizes, int n_in, void* d_out, int out_size) {
    const bf16* x = (const bf16*)d_in[0];
    const bf16* ckv = (const bf16*)d_in[1];
    const bf16* wq = (const bf16*)d_in[2];
    const bf16* wuk = (const bf16*)d_in[3];
    const bf16* wuv = (const bf16*)d_in[4];
    const bf16* wo = (const bf16*)d_in[5];
    const bf16* mem0 = (const bf16*)d_in[7];
    const bf16* Wq = (const bf16*)d_in[8];
    const bf16* Wk = (const bf16*)d_in[9];
    const bf16* Wv = (const bf16*)d_in[10];
    const bf16* Wo = (const bf16*)d_in[11];
    const bf16* gate_w = (const bf16*)d_in[13];
    bf16* out = (bf16*)d_out;

    static Proj2Params P2;
    static ChainParams CP;
    static AttnParams AP;
    static OutParams OP;
    static bool init = false;
    static const void* last_in[15];
    bool same = init;
    for (int i = 0; i < 14 && same; i++) same = last_in[i] == d_in[i];
    same = same && last_in[14] == d_out;
    if (!init) {
        cudaDriverEntryPointQueryResult qr;
        cudaGetDriverEntryPoint("cuTensorMapEncodeTiled", (void**)&g_encode, cudaEnableDefault, &qr);
        cudaFuncSetAttribute(proj2_kernel, cudaFuncAttributeMaxDynamicSharedMemorySize, P2_SMEM);
        cudaFuncSetAttribute(attn_kernel, cudaFuncAttributeMaxDynamicSharedMemorySize, FA_SMEM);
        cudaFuncSetAttribute(chain_kernel, cudaFuncAttributeMaxDynamicSharedMemorySize, C2_SMEM);
        cudaFuncSetAttribute(out3_kernel, cudaFuncAttributeMaxDynamicSharedMemorySize, O2_SMEM);
        init = true;
    }
    if (!same) {
        for (int i = 0; i < 14; i++) last_in[i] = d_in[i];
        last_in[14] = d_out;
        void *pQA, *pKA, *pVA, *pCA, *pCB;
        cudaGetSymbolAddress(&pQA, g_QA); cudaGetSymbolAddress(&pKA, g_KA); cudaGetSymbolAddress(&pVA, g_VA);
        cudaGetSymbolAddress(&pCA, g_ctxA); cudaGetSymbolAddress(&pCB, g_ctxB);
        make_map(&P2.mapA[0], x, SEQ, DM, 128);
        make_map(&P2.mapA[1], ckv, SEQ, DM, 128);
        const void* ws[3] = {wq, wuk, wuv};
        void* cs[3] = {pQA, pKA, pVA};
        for (int i = 0; i < 3; i++) { make_map(&P2.mapW[i], ws[i], DM, NQ, 64); P2.out[i] = (bf16*)cs[i]; }
        make_map(&CP.mapX, x, SEQ, DM, SEGL);
        make_map(&CP.mapM, mem0, NMEM, DM, NMEM);
        make_map(&CP.mapW[0], Wq, DM, NQ, 64);
        make_map(&CP.mapW[1], Wk, DM, NQ, 64);
        make_map(&CP.mapW[2], Wv, DM, NQ, 64);
        make_map(&CP.mapWo, Wo, NQ, DM, 64);
        make_map(&AP.mapQ, pQA, NH * SEQ, HD, 128);
        make_map(&AP.mapK, pKA, NH * SEQ, HD, 128);
        make_map(&AP.mapV, pVA, NH * SEQ, HD, 128);
        make_map(&AP.mapO, pCA, NH * SEQ, HD, 64);
        make_map(&OP.mapCtx[0], pCA, NH * SEQ, HD, 64);
        make_map(&OP.mapCtx[1], pCB, NH * SEQ, HD, 64);
        make_map(&OP.mapWo[0], wo, NQ, DM, 64);
        make_map(&OP.mapWo[1], Wo, NQ, DM, 64);
        make_map(&OP.mapOut, out, SEQ, DM, 64);
        AP.x = x; AP.gate_w = gate_w;
    }
    cudaStream_t s1 = cudaStreamPerThread;
    const bool pdl = true;
    launch_pdl(chain_kernel, 64, 384, C2_SMEM, s1, false, CP);
    launch_pdl(proj2_kernel, 68, 384, P2_SMEM, s1, pdl, P2);
    launch_pdl(attn_kernel, FA_GRID, 384, FA_SMEM, s1, pdl, AP);
    launch_pdl(out3_kernel, O3_GRID, 352, O2_SMEM, s1, pdl, OP);
}
```

```cpp
#include <cuda_runtime.h>
#include <cuda_bf16.h>
#include <cuda.h>
#include <stdint.h>
#include <type_traits>

constexpr int SEQ = 2048;
constexpr int DM = 512;
constexpr int NH = 32;
constexpr int HD = 128;
constexpr int NQ = NH * HD;
constexpr int SEGL = 32;
constexpr int NMEM = 8;
constexpr int NSEG = SEQ / SEGL;

typedef __nv_bfloat16 bf16;

__device__ bf16 g_QA[SEQ * NQ];
__device__ bf16 g_KA[SEQ * NQ];
__device__ bf16 g_VA[SEQ * NQ];
__device__ bf16 g_ctxA[SEQ * NQ];
__device__ bf16 g_ctxB[SEQ * NQ];
constexpr int CT_PROJ = 0, CT_ATTN = 1, CT_FIN = 5;
constexpr int CT_G = 32;
constexpr int CT_AP = 64;
#define O2_HE 24
constexpr int CT_CA = 128;
constexpr int CT_CB = 160;
#define CB_FIRST 13
constexpr int CT_OP = 192;
constexpr int CT_N = 448;
__device__ unsigned int g_ctr[CT_N];
__device__ float g_gate[SEQ];
__device__ uint2 g_xbuf[2 * 8 * 8 * 128];

#define FA_GRID 68

#define TS_BEGIN(id)
#define TS_END(id)
__device__ __forceinline__ void pdl_launch_dependents() { asm volatile("griddepcontrol.launch_dependents;" ::: "memory"); }
__device__ __forceinline__ void wait_ctr(int idx, unsigned int n) {
    unsigned int v; int it = 0;
    do { asm volatile("ld.acquire.gpu.global.u32 %0, [%1];" : "=r"(v) : "l"(&g_ctr[idx]) : "memory"); } while (v < n && ++it < (1 << 22));
}
__device__ __forceinline__ void signal_ctr(int idx) {
    asm volatile("fence.proxy.async.global;" ::: "memory");
    asm volatile("red.release.gpu.global.add.u32 [%0], 1;" :: "l"(&g_ctr[idx]) : "memory");
}
__device__ __forceinline__ void signal_ctr_generic(int idx) {
    asm volatile("red.release.gpu.global.add.u32 [%0], 1;" :: "l"(&g_ctr[idx]) : "memory");
}
__device__ __forceinline__ uint32_t smem_u32(const void* p) {
    return (uint32_t)__cvta_generic_to_shared(p);
}
__device__ __forceinline__ void mbar_init(uint32_t bar, uint32_t count) {
    asm volatile("mbarrier.init.shared::cta.b64 [%0], %1;" :: "r"(bar), "r"(count));
}
__device__ __forceinline__ void mbar_expect_tx(uint32_t bar, uint32_t bytes) {
    asm volatile("mbarrier.arrive.expect_tx.shared::cta.b64 _, [%0], %1;" :: "r"(bar), "r"(bytes) : "memory");
}
__device__ __forceinline__ void mbar_arrive(uint32_t bar) {
    asm volatile("mbarrier.arrive.shared::cta.b64 _, [%0];" :: "r"(bar) : "memory");
}
__device__ __forceinline__ void mbar_wait(uint32_t bar, uint32_t parity) {
    asm volatile(
        "{\n"
        ".reg .pred p, q;\n"
        ".reg .u32 c;\n"
        "mov.u32 c, 0;\n"
        "WAIT_LOOP:\n"
        "mbarrier.try_wait.parity.shared::cta.b64 p, [%0], %1;\n"
        "@p bra WAIT_DONE;\n"
        "add.u32 c, c, 1;\n"
        "setp.lt.u32 q, c, 4000000;\n"
        "@q bra WAIT_LOOP;\n"
        "WAIT_DONE:\n"
        "}\n" :: "r"(bar), "r"(parity) : "memory");
}
__device__ __forceinline__ void tma_load_2d(uint32_t dst, const CUtensorMap* map, uint32_t bar, int c0, int c1) {
    asm volatile(
        "cp.async.bulk.tensor.2d.shared::cluster.global.mbarrier::complete_tx::bytes [%0], [%1, {%3, %4}], [%2];"
        :: "r"(dst), "l"((uint64_t)map), "r"(bar), "r"(c0), "r"(c1) : "memory");
}
__device__ __forceinline__ void wgmma_fence() { asm volatile("wgmma.fence.sync.aligned;" ::: "memory"); }
__device__ __forceinline__ void wgmma_commit() { asm volatile("wgmma.commit_group.sync.aligned;" ::: "memory"); }
template <int N> __device__ __forceinline__ void wgmma_wait() {
    asm volatile("wgmma.wait_group.sync.aligned %0;" :: "n"(N) : "memory");
}
__device__ __forceinline__ uint64_t make_desc(uint32_t addr, uint32_t lbo, uint32_t sbo) {
    uint64_t d = 0;
    d |= (uint64_t)((addr & 0x3FFFF) >> 4);
    d |= (uint64_t)((lbo >> 4) & 0x3FFF) << 16;
    d |= (uint64_t)((sbo >> 4) & 0x3FFF) << 32;
    d |= (uint64_t)1 << 62;
    return d;
}

#define ACC64(d) \
    "+f"(d[0]), "+f"(d[1]), "+f"(d[2]), "+f"(d[3]), "+f"(d[4]), "+f"(d[5]), "+f"(d[6]), "+f"(d[7]), \
    "+f"(d[8]), "+f"(d[9]), "+f"(d[10]), "+f"(d[11]), "+f"(d[12]), "+f"(d[13]), "+f"(d[14]), "+f"(d[15]), \
    "+f"(d[16]), "+f"(d[17]), "+f"(d[18]), "+f"(d[19]), "+f"(d[20]), "+f"(d[21]), "+f"(d[22]), "+f"(d[23]), \
    "+f"(d[24]), "+f"(d[25]), "+f"(d[26]), "+f"(d[27]), "+f"(d[28]), "+f"(d[29]), "+f"(d[30]), "+f"(d[31]), \
    "+f"(d[32]), "+f"(d[33]), "+f"(d[34]), "+f"(d[35]), "+f"(d[36]), "+f"(d[37]), "+f"(d[38]), "+f"(d[39]), \
    "+f"(d[40]), "+f"(d[41]), "+f"(d[42]), "+f"(d[43]), "+f"(d[44]), "+f"(d[45]), "+f"(d[46]), "+f"(d[47]), \
    "+f"(d[48]), "+f"(d[49]), "+f"(d[50]), "+f"(d[51]), "+f"(d[52]), "+f"(d[53]), "+f"(d[54]), "+f"(d[55]), \
    "+f"(d[56]), "+f"(d[57]), "+f"(d[58]), "+f"(d[59]), "+f"(d[60]), "+f"(d[61]), "+f"(d[62]), "+f"(d[63])
#define ACC64_STR \
    "{%0, %1, %2, %3, %4, %5, %6, %7, %8, %9, %10, %11, %12, %13, %14, %15, " \
    "%16, %17, %18, %19, %20, %21, %22, %23, %24, %25, %26, %27, %28, %29, %30, %31, " \
    "%32, %33, %34, %35, %36, %37, %38, %39, %40, %41, %42, %43, %44, %45, %46, %47, " \
    "%48, %49, %50, %51, %52, %53, %54, %55, %56, %57, %58, %59, %60, %61, %62, %63}"

template <int TB>
__device__ __forceinline__ void wgmma_ss_n128(float (&d)[64], uint64_t da, uint64_t db, int scale_d) {
    asm volatile(
        "{\n.reg .pred p;\nsetp.ne.b32 p, %66, 0;\n"
        "wgmma.mma_async.sync.aligned.m64n128k16.f32.bf16.bf16 " ACC64_STR ", %64, %65, p, 1, 1, 0, %67;\n}\n"
        : ACC64(d) : "l"(da), "l"(db), "r"(scale_d), "n"(TB));
}
__device__ __forceinline__ uint32_t desc_lo(uint32_t addr, uint32_t lbo) { return ((addr & 0x3FFFF) >> 4) | ((lbo >> 4) << 16); }
template <int TB>
__device__ __forceinline__ void wgmma_ss_n128_lo(float (&d)[64], uint32_t da_lo, uint32_t db_lo, int scale_d) {
    asm volatile(
        "{\n.reg .pred p;\n.reg .b64 da, db;\nsetp.ne.b32 p, %66, 0;\n"
        "mov.b64 da, {%64, 0x40000040};\nmov.b64 db, {%65, 0x40000040};\n"
        "wgmma.mma_async.sync.aligned.m64n128k16.f32.bf16.bf16 " ACC64_STR ", da, db, p, 1, 1, 0, %67;\n}\n"
        : ACC64(d) : "r"(da_lo), "r"(db_lo), "r"(scale_d), "n"(TB));
}
__device__ __forceinline__ void wgmma_rs_n128_tb(float (&d)[64], uint32_t a0, uint32_t a1, uint32_t a2, uint32_t a3,
                                                 uint64_t db, int scale_d) {
    asm volatile(
        "{\n.reg .pred p;\nsetp.ne.b32 p, %69, 0;\n"
        "wgmma.mma_async.sync.aligned.m64n128k16.f32.bf16.bf16 " ACC64_STR ", {%64, %65, %66, %67}, %68, p, 1, 1, 1;\n}\n"
        : ACC64(d) : "r"(a0), "r"(a1), "r"(a2), "r"(a3), "l"(db), "r"(scale_d));
}
__device__ __forceinline__ void wgmma_rs_n80(float (&d)[40], const uint32_t (&a)[4], uint32_t db_lo, int scale_d) {
    asm volatile(
        "{\n.reg .pred p;\n.reg .b64 db;\nsetp.ne.b32 p, %45, 0;\nmov.b64 db, {%44, 0x40000040};\n"
        "wgmma.mma_async.sync.aligned.m64n80k16.f32.bf16.bf16 "
        "{%0, %1, %2, %3, %4, %5, %6, %7, %8, %9, %10, %11, %12, %13, %14, %15, %16, %17, %18, %19, %20, %21, %22, %23, %24, %25, %26, %27, %28, %29, %30, %31, %32, %33, %34, %35, %36, %37, %38, %39}, "
        "{%40, %41, %42, %43}, db, p, 1, 1, 0;\n}\n"
        : "+f"(d[0]), "+f"(d[1]), "+f"(d[2]), "+f"(d[3]), "+f"(d[4]), "+f"(d[5]), "+f"(d[6]), "+f"(d[7]), "+f"(d[8]), "+f"(d[9]), "+f"(d[10]), "+f"(d[11]), "+f"(d[12]), "+f"(d[13]), "+f"(d[14]), "+f"(d[15]), "+f"(d[16]), "+f"(d[17]), "+f"(d[18]), "+f"(d[19]), "+f"(d[20]), "+f"(d[21]), "+f"(d[22]), "+f"(d[23]), "+f"(d[24]), "+f"(d[25]), "+f"(d[26]), "+f"(d[27]), "+f"(d[28]), "+f"(d[29]), "+f"(d[30]), "+f"(d[31]), "+f"(d[32]), "+f"(d[33]), "+f"(d[34]), "+f"(d[35]), "+f"(d[36]), "+f"(d[37]), "+f"(d[38]), "+f"(d[39])
        : "r"(a[0]), "r"(a[1]), "r"(a[2]), "r"(a[3]), "r"(db_lo), "r"(scale_d));
}
__device__ __forceinline__ void wgmma_ss_n256_tb(float (&d)[128], uint64_t da, uint64_t db, int scale_d) {
    asm volatile(
        "{\n.reg .pred p;\nsetp.ne.b32 p, %130, 0;\n"
        "wgmma.mma_async.sync.aligned.m64n256k16.f32.bf16.bf16 {%0, %1, %2, %3, %4, %5, %6, %7, %8, %9, %10, %11, %12, %13, %14, %15, %16, %17, %18, %19, %20, %21, %22, %23, %24, %25, %26, %27, %28, %29, %30, %31, %32, %33, %34, %35, %36, %37, %38, %39, %40, %41, %42, %43, %44, %45, %46, %47, %48, %49, %50, %51, %52, %53, %54, %55, %56, %57, %58, %59, %60, %61, %62, %63, %64, %65, %66, %67, %68, %69, %70, %71, %72, %73, %74, %75, %76, %77, %78, %79, %80, %81, %82, %83, %84, %85, %86, %87, %88, %89, %90, %91, %92, %93, %94, %95, %96, %97, %98, %99, %100, %101, %102, %103, %104, %105, %106, %107, %108, %109, %110, %111, %112, %113, %114, %115, %116, %117, %118, %119, %120, %121, %122, %123, %124, %125, %126, %127}, %128, %129, p, 1, 1, 0, 1;\n}\n"
        : "+f"(d[0]), "+f"(d[1]), "+f"(d[2]), "+f"(d[3]), "+f"(d[4]), "+f"(d[5]), "+f"(d[6]), "+f"(d[7]), "+f"(d[8]), "+f"(d[9]), "+f"(d[10]), "+f"(d[11]), "+f"(d[12]), "+f"(d[13]), "+f"(d[14]), "+f"(d[15]), "+f"(d[16]), "+f"(d[17]), "+f"(d[18]), "+f"(d[19]), "+f"(d[20]), "+f"(d[21]), "+f"(d[22]), "+f"(d[23]), "+f"(d[24]), "+f"(d[25]), "+f"(d[26]), "+f"(d[27]), "+f"(d[28]), "+f"(d[29]), "+f"(d[30]), "+f"(d[31]), "+f"(d[32]), "+f"(d[33]), "+f"(d[34]), "+f"(d[35]), "+f"(d[36]), "+f"(d[37]), "+f"(d[38]), "+f"(d[39]), "+f"(d[40]), "+f"(d[41]), "+f"(d[42]), "+f"(d[43]), "+f"(d[44]), "+f"(d[45]), "+f"(d[46]), "+f"(d[47]), "+f"(d[48]), "+f"(d[49]), "+f"(d[50]), "+f"(d[51]), "+f"(d[52]), "+f"(d[53]), "+f"(d[54]), "+f"(d[55]), "+f"(d[56]), "+f"(d[57]), "+f"(d[58]), "+f"(d[59]), "+f"(d[60]), "+f"(d[61]), "+f"(d[62]), "+f"(d[63]), "+f"(d[64]), "+f"(d[65]), "+f"(d[66]), "+f"(d[67]), "+f"(d[68]), "+f"(d[69]), "+f"(d[70]), "+f"(d[71]), "+f"(d[72]), "+f"(d[73]), "+f"(d[74]), "+f"(d[75]), "+f"(d[76]), "+f"(d[77]), "+f"(d[78]), "+f"(d[79]), "+f"(d[80]), "+f"(d[81]), "+f"(d[82]), "+f"(d[83]), "+f"(d[84]), "+f"(d[85]), "+f"(d[86]), "+f"(d[87]), "+f"(d[88]), "+f"(d[89]), "+f"(d[90]), "+f"(d[91]), "+f"(d[92]), "+f"(d[93]), "+f"(d[94]), "+f"(d[95]), "+f"(d[96]), "+f"(d[97]), "+f"(d[98]), "+f"(d[99]), "+f"(d[100]), "+f"(d[101]), "+f"(d[102]), "+f"(d[103]), "+f"(d[104]), "+f"(d[105]), "+f"(d[106]), "+f"(d[107]), "+f"(d[108]), "+f"(d[109]), "+f"(d[110]), "+f"(d[111]), "+f"(d[112]), "+f"(d[113]), "+f"(d[114]), "+f"(d[115]), "+f"(d[116]), "+f"(d[117]), "+f"(d[118]), "+f"(d[119]), "+f"(d[120]), "+f"(d[121]), "+f"(d[122]), "+f"(d[123]), "+f"(d[124]), "+f"(d[125]), "+f"(d[126]), "+f"(d[127])
        : "l"(da), "l"(db), "r"(scale_d));
}
__device__ __forceinline__ void stmatrix_x4(uint32_t addr, uint32_t r0, uint32_t r1, uint32_t r2, uint32_t r3) {
    asm volatile("stmatrix.sync.aligned.m8n8.x4.shared.b16 [%0], {%1, %2, %3, %4};" :: "r"(addr), "r"(r0), "r"(r1), "r"(r2), "r"(r3) : "memory");
}
__device__ __forceinline__ void tma_store_2d(const CUtensorMap* map, uint32_t src, int c0, int c1) {
    asm volatile("cp.async.bulk.tensor.2d.global.shared::cta.bulk_group [%0, {%2, %3}], [%1];"
                 :: "l"((uint64_t)map), "r"(src), "r"(c0), "r"(c1) : "memory");
}
__device__ __forceinline__ float ex2f(float x) { float y; asm("ex2.approx.ftz.f32 %0, %1;" : "=f"(y) : "f"(x)); return y; }
__device__ __forceinline__ uint32_t pack_bf16(float lo, float hi) {
    __nv_bfloat162 v = __floats2bfloat162_rn(lo, hi);
    return *reinterpret_cast<uint32_t*>(&v);
}
__device__ __forceinline__ float bf16r(float x) { return __uint_as_float(pack_bf16(0.f, x) & 0xffff0000u); }
__device__ __forceinline__ void mma_16816(float (&c)[4], uint32_t a0, uint32_t a1, uint32_t a2, uint32_t a3,
                                          uint32_t b0, uint32_t b1) {
    asm volatile(
        "mma.sync.aligned.m16n8k16.row.col.f32.bf16.bf16.f32 {%0,%1,%2,%3}, {%4,%5,%6,%7}, {%8,%9}, {%0,%1,%2,%3};"
        : "+f"(c[0]), "+f"(c[1]), "+f"(c[2]), "+f"(c[3])
        : "r"(a0), "r"(a1), "r"(a2), "r"(a3), "r"(b0), "r"(b1));
}
__device__ __forceinline__ void ldmatrix_x4_trans(uint32_t& r0, uint32_t& r1, uint32_t& r2, uint32_t& r3, uint32_t addr) {
    asm volatile("ldmatrix.sync.aligned.m8n8.x4.trans.shared.b16 {%0,%1,%2,%3}, [%4];"
                 : "=r"(r0), "=r"(r1), "=r"(r2), "=r"(r3) : "r"(addr));
}

struct AttnParams {
    CUtensorMap mapQ, mapK, mapV;
    CUtensorMap mapO;
    const bf16 *x, *gate_w;
};
constexpr uint32_t FA_Q = 0, FA_KV = 65536, FA_O = 196608, FA_BAR = 229376;
constexpr int FA_SMEM = FA_BAR + 256;
constexpr int FA_ITEMS = 16 * NH;
__device__ __forceinline__ int fa_qt(int t) { return 15 - ((t & 127) >> 3); }
__device__ __forceinline__ int fa_head(int t) { return (t >> 7) * 8 + (t & 7); }
__device__ __forceinline__ uint32_t mbar_test(uint32_t bar, uint32_t parity) {
    uint32_t done;
    asm volatile(
        "{\n.reg .pred p;\n"
        "mbarrier.test_wait.parity.shared::cta.b64 p, [%1], %2;\n"
        "selp.u32 %0, 1, 0, p;\n}\n" : "=r"(done) : "r"(bar), "r"(parity) : "memory");
    return done;
}
__device__ __forceinline__ void mbar_arrive_if(uint32_t bar, bool c) {
    asm volatile("{\n.reg .pred p;\nsetp.ne.u32 p, %1, 0;\n@p mbarrier.arrive.shared::cta.b64 _, [%0];\n}" :: "r"(bar), "r"((uint32_t)c) : "memory");
}
__device__ __forceinline__ void wgmma_rs_n128_tb_lo(float (&d)[64], const uint32_t* a, uint32_t db_lo, int scale_d) {
    asm volatile(
        "{\n.reg .pred p;\n.reg .b64 db;\nsetp.ne.b32 p, %69, 0;\nmov.b64 db, {%68, 0x40000040};\n"
        "wgmma.mma_async.sync.aligned.m64n128k16.f32.bf16.bf16 " ACC64_STR ", {%64, %65, %66, %67}, db, p, 1, 1, 1;\n}\n"
        : ACC64(d) : "r"(a[0]), "r"(a[1]), "r"(a[2]), "r"(a[3]), "r"(db_lo), "r"(scale_d));
}
#define FA_TEST 48
#define FA_PIN 8

__global__ void __launch_bounds__(384, 1) attn_kernel(const __grid_constant__ AttnParams P) {
    extern __shared__ __align__(1024) uint8_t smem_attn[];
    const uint32_t sb = smem_u32(smem_attn);
    const uint32_t bar_q = sb + FA_BAR, bar_qe = bar_q + 16, bar_kf = bar_q + 32, bar_vf = bar_q + 48, bar_ke = bar_q + 64, bar_ve = bar_q + 80,
                   bar_of = bar_q + 96, bar_oe = bar_q + 112, slot = bar_q + 128, oslot = bar_q + 136;
    const int warp = __shfl_sync(0xffffffff, threadIdx.x >> 5, 0);
    const int lane = threadIdx.x & 31;
    TS_BEGIN(1);
    if (threadIdx.x == 0) {
        for (int i = 0; i < 2; i++) {
            mbar_init(bar_q + 8 * i, 1); mbar_init(bar_qe + 8 * i, 8); mbar_init(bar_kf + 8 * i, 1); mbar_init(bar_vf + 8 * i, 1);
            mbar_init(bar_ke + 8 * i, 8); mbar_init(bar_ve + 8 * i, 8); mbar_init(bar_of + 8 * i, 4); mbar_init(bar_oe + 8 * i, 1);
        }
        asm volatile("fence.mbarrier_init.release.cluster;" ::: "memory");
    }
    if (threadIdx.x == 256) wait_ctr(CT_AP + (fa_head(blockIdx.x) >> 1), 96u);
    __syncthreads();
    pdl_launch_dependents();
    if (warp >= 8) {
        asm volatile("setmaxnreg.dec.sync.aligned.u32 40;");
        if (warp == 11) {
            const uint4 gv0 = __ldg(reinterpret_cast<const uint4*>(P.gate_w) + lane), gv1 = __ldg(reinterpret_cast<const uint4*>(P.gate_w) + 32 + lane);
            const uint32_t gw[8] = {gv0.x, gv0.y, gv0.z, gv0.w, gv1.x, gv1.y, gv1.z, gv1.w};
#pragma unroll 1
            for (int r = blockIdx.x; r < SEQ; r += gridDim.x) {
                const uint4 x0 = __ldg(reinterpret_cast<const uint4*>(P.x + (size_t)r * DM) + lane), x1 = __ldg(reinterpret_cast<const uint4*>(P.x + (size_t)r * DM) + 32 + lane);
                const uint32_t xw[8] = {x0.x, x0.y, x0.z, x0.w, x1.x, x1.y, x1.z, x1.w};
                float sum = 0.f;
#pragma unroll
                for (int e = 0; e < 8; e++) {
                    const uint32_t pr = pack_bf16(__uint_as_float(xw[e] << 16) * __uint_as_float(gw[e] << 16), __uint_as_float(xw[e] & 0xffff0000u) * __uint_as_float(gw[e] & 0xffff0000u));
                    sum += __uint_as_float(pr << 16) + __uint_as_float(pr & 0xffff0000u);
                }
#pragma unroll
                for (int o = 16; o; o >>= 1) sum += __shfl_xor_sync(0xffffffff, sum, o);
                if (lane == 0) g_gate[r] = bf16r(1.f / (1.f + __expf(-bf16r(sum))));
            }
            if (lane == 0) signal_ctr_generic(CT_G);
        } else if (warp > 8) {
            if (lane == 0) {
                const int wg = warp - 9;
                const uint32_t stg = sb + FA_O + wg * 16384;
                for (int n = 0;; n++) {
                    mbar_wait(bar_of + 8 * wg, n & 1);
                    int t;
                    asm volatile("ld.shared.s32 %0, [%1];" : "=r"(t) : "r"(oslot + wg * 4) : "memory");
                    asm volatile("fence.proxy.async.shared::cta;" ::: "memory");
                    const bool last = t < 0;
                    t &= 0xffff;
                    const int qt = fa_qt(t), h = fa_head(t);
                    tma_store_2d(&P.mapO, stg, 0, h * SEQ + qt * 128 + wg * 64);
                    tma_store_2d(&P.mapO, stg + 8192, 64, h * SEQ + qt * 128 + wg * 64);
                    asm volatile("cp.async.bulk.commit_group;" ::: "memory");
                    asm volatile("cp.async.bulk.wait_group.read 0;" ::: "memory");
                    mbar_arrive(bar_oe + 8 * wg);
                    asm volatile("cp.async.bulk.wait_group 0;" ::: "memory");
                    signal_ctr(CT_CA + qt * 2 + (h >= O2_HE));
                    if (last) break;
                }
            }
        } else if (lane == 0) {
            int it = 0, t = blockIdx.x, hp_ready = 1 << (fa_head(t) >> 1);
            auto load_q = [&](int item, int t) {
                const uint32_t b = bar_q + 8 * (item & 1);
                asm volatile("st.shared.s32 [%0], %1;" :: "r"(slot + (item & 1) * 4), "r"(t) : "memory");
                if (t < 0) { mbar_arrive(b); return; }
                const int row = fa_head(t) * SEQ + fa_qt(t) * 128;
                mbar_expect_tx(b, 32768);
                tma_load_2d(sb + FA_Q + (item & 1) * 32768, &P.mapQ, b, 0, row);
                tma_load_2d(sb + FA_Q + (item & 1) * 32768 + 16384, &P.mapQ, b, 64, row);
            };
            load_q(0, t);
            for (int item = 0; t >= 0; item++) {
                const int h = fa_head(t);
                for (int j = fa_qt(t); j >= 0; j--, it++) {
                    const int s = it & 1;
                    const uint32_t ph = ((it >> 1) & 1) ^ 1;
                    const uint32_t sk = sb + FA_KV + s * 65536, sv = sk + 32768;
                    if (j == 0) t = (int)(gridDim.x + atomicAdd(&g_ctr[CT_ATTN], 1u));
                    mbar_wait(bar_ke + 8 * s, ph);
                    mbar_expect_tx(bar_kf + 8 * s, 32768);
                    tma_load_2d(sk, &P.mapK, bar_kf + 8 * s, 0, h * SEQ + j * 128);
                    tma_load_2d(sk + 16384, &P.mapK, bar_kf + 8 * s, 64, h * SEQ + j * 128);
                    if (j == 0) {
                        if (t >= FA_ITEMS) t = -1;
                        else {
                            const int hp = fa_head(t) >> 1;
                            if (!((hp_ready >> hp) & 1)) { wait_ctr(CT_AP + hp, 96u); hp_ready |= 1 << hp; }
                        }
                        mbar_wait(bar_qe + 8 * ((item + 1) & 1), (((item + 1) >> 1) & 1) ^ 1);
                        load_q(item + 1, t);
                    }
                    mbar_wait(bar_ve + 8 * s, ph);
                    mbar_expect_tx(bar_vf + 8 * s, 32768);
                    tma_load_2d(sv, &P.mapV, bar_vf + 8 * s, 0, h * SEQ + j * 128);
                    tma_load_2d(sv + 16384, &P.mapV, bar_vf + 8 * s, 64, h * SEQ + j * 128);
                }
            }
        }
    } else {
        asm volatile("setmaxnreg.inc.sync.aligned.u32 232;");
        const int wg = warp >> 2;
        const bool lane0 = lane == 0;
        float o[64], sacc[64];
        uint32_t pa[32];
        float mrow0, mrow1, lrow0, lrow1;
        const float sc = 0.08838834764831845f * 1.4426950408889634f;
        const uint32_t q_lo = desc_lo(sb + FA_Q + wg * 8192, 16), k_lo = desc_lo(sb + FA_KV, 16), v_lo = desc_lo(sb + FA_KV + 32768, 16384);
        auto issue_qk = [&](int item, int it) {
            const uint32_t a = q_lo + (item & 1) * 2048, b = k_lo + (it & 1) * 4096;
#pragma unroll
            for (int kk = 0; kk < 8; kk++) wgmma_ss_n128_lo<0>(sacc, a + (kk >> 2) * 1024 + (kk & 3) * 2, b + (kk >> 2) * 1024 + (kk & 3) * 2, kk != 0);
            wgmma_commit();
        };
        auto issue_pv = [&](int it, bool acc) {
            const uint32_t b = v_lo + (it & 1) * 4096;
#pragma unroll
            for (int kk = 0; kk < 8; kk++) wgmma_rs_n128_tb_lo(o, &pa[kk * 4], b + kk * 128, kk != 0 || acc);
            wgmma_commit();
        };
        auto turn_wait = [&]() { asm volatile("bar.sync %0, 256;" :: "r"(1 + wg) : "memory"); };
        auto turn_pass = [&]() { asm volatile("bar.arrive %0, 256;" :: "r"(2 - wg) : "memory"); };
        auto mask = [&]() {
            const int r0 = wg * 64 + (warp & 3) * 16 + (lane >> 2) - (lane & 3) * 2;
#pragma unroll
            for (int i = 0; i < 64; i++)
                if ((i >> 2) * 8 + (i & 1) - ((i & 2) ? 8 : 0) > r0) sacc[i] = -INFINITY;
        };
        auto row_max = [&](float& mx0, float& mx1) {
            float mx[4];
#pragma unroll
            for (int i = 0; i < 4; i++) mx[i] = fmaxf(sacc[i], sacc[i + 4]);
#pragma unroll
            for (int i = 8; i < 64; i++) mx[i & 3] = fmaxf(mx[i & 3], sacc[i]);
            mx0 = fmaxf(mx0, fmaxf(mx[0], mx[1])); mx1 = fmaxf(mx1, fmaxf(mx[2], mx[3]));
            const float u0 = __shfl_xor_sync(0xffffffff, mx0, 1), u1 = __shfl_xor_sync(0xffffffff, mx1, 1);
            mx0 = fmaxf(mx0, u0); mx1 = fmaxf(mx1, u1);
            const float v0 = __shfl_xor_sync(0xffffffff, mx0, 2), v1 = __shfl_xor_sync(0xffffffff, mx1, 2);
            mx0 = fmaxf(mx0, v0); mx1 = fmaxf(mx1, v1);
        };
        auto pin_after = [&](float v) {
            asm volatile("{\n.reg .pred p;\nsetp.lt.f32 p, %1, 0f00000000;\n@p st.shared.f32 [%0], %1;\n}" :: "r"(slot + 16), "f"(v) : "memory");
        };
        auto pack_p = [&]() {
#pragma unroll
            for (int i = 0; i < 32; i++) pa[i] = pack_bf16(sacc[2 * i], sacc[2 * i + 1]);
        };
        auto first_softmax = [&]() {
            mask();
            mrow0 = -INFINITY; mrow1 = -INFINITY;
            row_max(mrow0, mrow1);
            const float ms0 = mrow0 * sc, ms1 = mrow1 * sc;
            float sum[4] = {0.f, 0.f, 0.f, 0.f};
#pragma unroll
            for (int i = 0; i < 64; i++) { sacc[i] = ex2f(fmaf(sacc[i], sc, (i & 2) ? -ms1 : -ms0)); sum[i & 3] += sacc[i]; }
            lrow0 = sum[0] + sum[1]; lrow1 = sum[2] + sum[3];
        };
        auto epilogue = [&](int item, int tag, float l0, float l1) {
            l0 += __shfl_xor_sync(0xffffffff, l0, 1); l1 += __shfl_xor_sync(0xffffffff, l1, 1);
            l0 += __shfl_xor_sync(0xffffffff, l0, 2); l1 += __shfl_xor_sync(0xffffffff, l1, 2);
            float i0, i1;
            asm("rcp.approx.ftz.f32 %0, %1;" : "=f"(i0) : "f"(l0));
            asm("rcp.approx.ftz.f32 %0, %1;" : "=f"(i1) : "f"(l1));
            const int row = (warp & 3) * 16 + (lane >> 2);
            const uint32_t stg = sb + FA_O + wg * 16384 + row * 128;
#pragma unroll
            for (int i = 0; i < 4; i++) {
                const int ch = i * 4 + (lane & 3);
                const uint32_t a = stg + (ch >> 3) * 8192 + (((ch & 7) ^ (row & 7)) << 4);
                const float* q = &o[i * 16];
                asm volatile("st.shared.v4.b32 [%0], {%1, %2, %3, %4};" :: "r"(a), "r"(pack_bf16(q[0] * i0, q[1] * i0)), "r"(pack_bf16(q[4] * i0, q[5] * i0)),
                             "r"(pack_bf16(q[8] * i0, q[9] * i0)), "r"(pack_bf16(q[12] * i0, q[13] * i0)) : "memory");
                asm volatile("st.shared.v4.b32 [%0], {%1, %2, %3, %4};" :: "r"(a + 1024), "r"(pack_bf16(q[2] * i1, q[3] * i1)), "r"(pack_bf16(q[6] * i1, q[7] * i1)),
                             "r"(pack_bf16(q[10] * i1, q[11] * i1)), "r"(pack_bf16(q[14] * i1, q[15] * i1)) : "memory");
            }
            asm volatile("st.shared.s32 [%0], %1;" :: "r"(oslot + wg * 4), "r"(tag) : "memory");
            __syncwarp();
            mbar_arrive_if(bar_of + 8 * wg, lane0);
        };
        int it = 0, t = blockIdx.x, nkv = fa_qt(t) + 1;
        if (wg == 1) asm volatile("bar.arrive 1, 256;" ::: "memory");
        mbar_wait(bar_q, 0);
        mbar_wait(bar_kf, 0);
        turn_wait();
        wgmma_fence();
        issue_qk(0, 0);
        turn_pass();
        wgmma_wait<0>();
        mbar_arrive_if(bar_ke, lane0);
        mbar_arrive_if(bar_qe, lane0 && nkv == 1);
        first_softmax();
        pack_p();
#pragma unroll 1
        for (int item = 0;; item++) {
            uint32_t ok = 0;
#pragma unroll 1
            for (int j = 1; j < nkv; j++) {
                it++;
                if (__builtin_expect(!ok, 0)) {
                    mbar_wait(bar_kf + 8 * (it & 1), (it >> 1) & 1);
                    mbar_wait(bar_vf + 8 * ((it - 1) & 1), ((it - 1) >> 1) & 1);
                }
                turn_wait();
                wgmma_fence();
                issue_qk(item, it);
                issue_pv(it - 1, j > 1);
                turn_pass();
                wgmma_wait<1>();
                mbar_arrive_if(bar_ke + 8 * (it & 1), lane0);
                mbar_arrive_if(bar_qe + 8 * (item & 1), lane0 && j == nkv - 1);
                float mx0 = mrow0, mx1 = mrow1;
                row_max(mx0, mx1);
                const float ms0 = mx0 * sc, ms1 = mx1 * sc;
                const float a0 = ex2f(fmaf(mrow0, sc, -ms0)), a1 = ex2f(fmaf(mrow1, sc, -ms1));
                mrow0 = mx0; mrow1 = mx1;
                float sum[4] = {lrow0 * a0, 0.f, lrow1 * a1, 0.f};
#pragma unroll
                for (int i = 0; i < FA_PIN; i++) { sacc[i] = ex2f(fmaf(sacc[i], sc, (i & 2) ? -ms1 : -ms0)); sum[i & 3] += sacc[i]; }
                pin_after(sum[0] + sum[2]);
                wgmma_wait<0>();
                mbar_arrive_if(bar_ve + 8 * ((it - 1) & 1), lane0);
#pragma unroll
                for (int i = 0; i < 64; i++) {
                    if (i >= FA_PIN) { sacc[i] = ex2f(fmaf(sacc[i], sc, (i & 2) ? -ms1 : -ms0)); sum[i & 3] += sacc[i]; }
                    o[i] *= (i & 2) ? a1 : a0;
                    if (i & 1) pa[i >> 1] = pack_bf16(sacc[i - 1], sacc[i]);
                    if (i == FA_TEST) pin_after(sum[0]);
                    if (i == FA_TEST) ok = mbar_test(bar_kf + 8 * ((it + 1) & 1), ((it + 1) >> 1) & 1) & mbar_test(bar_vf + 8 * (it & 1), (it >> 1) & 1);
                }
                lrow0 = sum[0] + sum[1]; lrow1 = sum[2] + sum[3];
            }
            it++;
            int tn;
            mbar_wait(bar_q + 8 * ((item + 1) & 1), ((item + 1) >> 1) & 1);
            asm volatile("ld.shared.s32 %0, [%1];" : "=r"(tn) : "r"(slot + ((item + 1) & 1) * 4) : "memory");
            tn = __shfl_sync(0xffffffff, tn, 0);
            mbar_wait(bar_vf + 8 * ((it - 1) & 1), ((it - 1) >> 1) & 1);
            const float l0 = lrow0, l1 = lrow1;
            if (tn < 0) {
                wgmma_fence();
                issue_pv(it - 1, nkv > 1);
                mbar_wait(bar_oe + 8 * wg, (item & 1) ^ 1);
                wgmma_wait<0>();
                epilogue(item, t | 0x80000000, l0, l1);
                break;
            }
            mbar_wait(bar_kf + 8 * (it & 1), (it >> 1) & 1);
            turn_wait();
            wgmma_fence();
            issue_qk(item + 1, it);
            issue_pv(it - 1, nkv > 1);
            turn_pass();
            nkv = fa_qt(tn) + 1;
            mbar_wait(bar_oe + 8 * wg, (item & 1) ^ 1);
            wgmma_wait<1>();
            mbar_arrive_if(bar_ke + 8 * (it & 1), lane0);
            mbar_arrive_if(bar_qe + 8 * ((item + 1) & 1), lane0 && nkv == 1);
            mask();
            mrow0 = -INFINITY; mrow1 = -INFINITY;
            row_max(mrow0, mrow1);
            {
                const float ms0 = mrow0 * sc, ms1 = mrow1 * sc;
                pin_after(fmaf(ex2f(fmaf(sacc[0], sc, -ms0)), l0, ex2f(fmaf(sacc[2], sc, -ms1))));
                wgmma_wait<0>();
                mbar_arrive_if(bar_ve + 8 * ((it - 1) & 1), lane0);
                float sum[4] = {0.f, 0.f, 0.f, 0.f};
#pragma unroll
                for (int i = 0; i < 64; i++) { sacc[i] = ex2f(fmaf(sacc[i], sc, (i & 2) ? -ms1 : -ms0)); sum[i & 3] += sacc[i]; }
                lrow0 = sum[0] + sum[1]; lrow1 = sum[2] + sum[3];
                pack_p();
                epilogue(item, t, l0, l1);
            }
            t = tn;
        }
        TS_END(1);
    }
}

__device__ __forceinline__ uint32_t cluster_ctarank() {
    uint32_t r; asm volatile("mov.u32 %0, %%cluster_ctarank;" : "=r"(r)); return r;
}
__device__ __forceinline__ uint32_t mapa_u32(uint32_t addr, uint32_t rank) {
    uint32_t r; asm volatile("mapa.shared::cluster.u32 %0, %1, %2;" : "=r"(r) : "r"(addr), "r"(rank)); return r;
}
__device__ __forceinline__ void cluster_sync_all() {
    asm volatile("barrier.cluster.arrive.release.aligned;\nbarrier.cluster.wait.acquire.aligned;" ::: "memory");
}
__device__ __forceinline__ void cluster_sync_relaxed() {
    asm volatile("barrier.cluster.arrive.relaxed.aligned;\nbarrier.cluster.wait.aligned;" ::: "memory");
}
__device__ __forceinline__ void st_async_v4(uint32_t addr, uint32_t a, uint32_t b, uint32_t c, uint32_t d, uint32_t mbar) {
    asm volatile("st.async.weak.shared::cluster.mbarrier::complete_tx::bytes.v4.b32 [%0], {%1, %2, %3, %4}, [%5];"
                 :: "r"(addr), "r"(a), "r"(b), "r"(c), "r"(d), "r"(mbar) : "memory");
}
__device__ __forceinline__ void st_async_v2(uint32_t addr, uint32_t a, uint32_t b, uint32_t mbar) {
    asm volatile("st.async.weak.shared::cluster.mbarrier::complete_tx::bytes.v2.b32 [%0], {%1, %2}, [%3];"
                 :: "r"(addr), "r"(a), "r"(b), "r"(mbar) : "memory");
}
__device__ __forceinline__ void st_async_b32(uint32_t addr, uint32_t a, uint32_t mbar) {
    asm volatile("st.async.weak.shared::cluster.mbarrier::complete_tx::bytes.b32 [%0], %1, [%2];" :: "r"(addr), "r"(a), "r"(mbar) : "memory");
}
__device__ __forceinline__ void pace(int cycles) {
    if (cycles > 0) {
        uint32_t t0, t;
        asm volatile("mov.u32 %0, %%clock;" : "=r"(t0));
        do { asm volatile("mov.u32 %0, %%clock;" : "=r"(t)); } while (t - t0 < (uint32_t)cycles);
    }
}
__device__ __forceinline__ void mbar_wait_cl(uint32_t bar, uint32_t parity) {
    uint32_t done = 0;
    for (int it = 0; it < (1 << 22) && !done; it++) {
        asm volatile(
            "{\n.reg .pred p;\n"
            "mbarrier.try_wait.parity.shared::cta.b64 p, [%1], %2;\n"
            "selp.u32 %0, 1, 0, p;\n}\n" : "=r"(done) : "r"(bar), "r"(parity) : "memory");
    }
}
__device__ __forceinline__ void ldmatrix_x4(uint32_t& r0, uint32_t& r1, uint32_t& r2, uint32_t& r3, uint32_t addr) {
    asm volatile("ldmatrix.sync.aligned.m8n8.x4.shared.b16 {%0,%1,%2,%3}, [%4];"
                 : "=r"(r0), "=r"(r1), "=r"(r2), "=r"(r3) : "r"(addr));
}
__device__ __forceinline__ void cp_async16(uint32_t dst, const void* src) {
    asm volatile("cp.async.cg.shared.global [%0], [%1], 16;" :: "r"(dst), "l"(src) : "memory");
}

#define DBG(i)
#define DBGW(i, w)
__device__ __forceinline__ void tma_load_2d_mc(uint32_t dst, const CUtensorMap* map, uint32_t bar, int c0, int c1, uint16_t mask) {
    asm volatile(
        "cp.async.bulk.tensor.2d.shared::cluster.global.mbarrier::complete_tx::bytes.multicast::cluster [%0], [%1, {%3, %4}], [%2], %5;"
        :: "r"(dst), "l"((uint64_t)map), "r"(bar), "r"(c0), "r"(c1), "h"(mask) : "memory");
}
__device__ __forceinline__ void bulk_s2s(uint32_t dst_cl, uint32_t src, uint32_t bytes, uint32_t bar_cl) {
    asm volatile("cp.async.bulk.shared::cluster.shared::cta.mbarrier::complete_tx::bytes [%0], [%1], %2, [%3];"
                 :: "r"(dst_cl), "r"(src), "r"(bytes), "r"(bar_cl) : "memory");
}
__device__ __forceinline__ bool elect_one() {
    uint32_t p;
    asm volatile("{\n.reg .pred p;\nelect.sync _|p, 0xffffffff;\nselp.u32 %0, 1, 0, p;\n}" : "=r"(p));
    return p;
}
__device__ __forceinline__ void fence_async_smem() { asm volatile("fence.proxy.async.shared::cta;" ::: "memory"); }
template <int ID, int N> __device__ __forceinline__ void bar_sync() { asm volatile("bar.sync %0, %1;" :: "n"(ID), "n"(N) : "memory"); }
template <int ID, int N> __device__ __forceinline__ void bar_arrive() { asm volatile("bar.arrive %0, %1;" :: "n"(ID), "n"(N) : "memory"); }
__device__ __forceinline__ void sts32(uint32_t a, uint32_t v) { asm volatile("st.shared.u32 [%0], %1;" :: "r"(a), "r"(v) : "memory"); }
__device__ __forceinline__ void ldsm_x4(uint32_t* r, uint32_t addr) {
    asm volatile("ldmatrix.sync.aligned.m8n8.x4.shared.b16 {%0,%1,%2,%3}, [%4];" : "=r"(r[0]), "=r"(r[1]), "=r"(r[2]), "=r"(r[3]) : "r"(addr) : "memory");
}
__device__ __forceinline__ uint32_t pin(uint32_t v) { asm volatile("" : "+r"(v)); return v; }
constexpr uint32_t DHI128 = 0x40000040u, DHI32 = 0xC0000010u;
#define ACC16(d) "+f"(d[0]), "+f"(d[1]), "+f"(d[2]), "+f"(d[3]), "+f"(d[4]), "+f"(d[5]), "+f"(d[6]), "+f"(d[7]), "+f"(d[8]), "+f"(d[9]), "+f"(d[10]), \
    "+f"(d[11]), "+f"(d[12]), "+f"(d[13]), "+f"(d[14]), "+f"(d[15])
#define ACC20(d) ACC16(d), "+f"(d[16]), "+f"(d[17]), "+f"(d[18]), "+f"(d[19])
__device__ __forceinline__ void wgmma_rs(float (&d)[16], const uint32_t (&a)[4], uint32_t db_lo) {
    asm volatile(
        "{\n.reg .b64 db;\nmov.b64 db, {%20, %21};\n"
        "wgmma.mma_async.sync.aligned.m64n32k16.f32.bf16.bf16 {%0,%1,%2,%3,%4,%5,%6,%7,%8,%9,%10,%11,%12,%13,%14,%15}, {%16,%17,%18,%19}, db, 1, 1, 1, 0;\n}\n"
        : ACC16(d) : "r"(a[0]), "r"(a[1]), "r"(a[2]), "r"(a[3]), "r"(db_lo), "n"(DHI128));
}
__device__ __forceinline__ void wgmma_rs(float (&d)[20], const uint32_t (&a)[4], uint32_t db_lo) {
    asm volatile(
        "{\n.reg .b64 db;\nmov.b64 db, {%24, %25};\n"
        "wgmma.mma_async.sync.aligned.m64n40k16.f32.bf16.bf16 {%0,%1,%2,%3,%4,%5,%6,%7,%8,%9,%10,%11,%12,%13,%14,%15,%16,%17,%18,%19}, {%20,%21,%22,%23}, db, 1, 1, 1, 0;\n}\n"
        : ACC20(d) : "r"(a[0]), "r"(a[1]), "r"(a[2]), "r"(a[3]), "r"(db_lo), "n"(DHI128));
}
template <uint32_t AHI, uint32_t BHI>
__device__ __forceinline__ void wgmma_ss(float (&d)[16], uint32_t da_lo, uint32_t db_lo) {
    asm volatile(
        "{\n.reg .b64 da, db;\nmov.b64 da, {%16, %18};\nmov.b64 db, {%17, %19};\n"
        "wgmma.mma_async.sync.aligned.m64n32k16.f32.bf16.bf16 {%0,%1,%2,%3,%4,%5,%6,%7,%8,%9,%10,%11,%12,%13,%14,%15}, da, db, 1, 1, 1, 0, 0;\n}\n"
        : ACC16(d) : "r"(da_lo), "r"(db_lo), "n"(AHI), "n"(BHI));
}
template <uint32_t AHI, uint32_t BHI>
__device__ __forceinline__ void wgmma_ss(float (&d)[20], uint32_t da_lo, uint32_t db_lo) {
    asm volatile(
        "{\n.reg .b64 da, db;\nmov.b64 da, {%20, %22};\nmov.b64 db, {%21, %23};\n"
        "wgmma.mma_async.sync.aligned.m64n40k16.f32.bf16.bf16 {%0,%1,%2,%3,%4,%5,%6,%7,%8,%9,%10,%11,%12,%13,%14,%15,%16,%17,%18,%19}, da, db, 1, 1, 1, 0, 0;\n}\n"
        : ACC20(d) : "r"(da_lo), "r"(db_lo), "n"(AHI), "n"(BHI));
}
template <uint32_t AHI, uint32_t BHI>
__device__ __forceinline__ void wgmma_ss0(float (&d)[20], uint32_t da_lo, uint32_t db_lo) {
    asm volatile(
        "{\n.reg .b64 da, db;\nmov.b64 da, {%20, %22};\nmov.b64 db, {%21, %23};\n"
        "wgmma.mma_async.sync.aligned.m64n40k16.f32.bf16.bf16 {%0,%1,%2,%3,%4,%5,%6,%7,%8,%9,%10,%11,%12,%13,%14,%15,%16,%17,%18,%19}, da, db, 0, 1, 1, 0, 0;\n}\n"
        : "=f"(d[0]), "=f"(d[1]), "=f"(d[2]), "=f"(d[3]), "=f"(d[4]), "=f"(d[5]), "=f"(d[6]), "=f"(d[7]), "=f"(d[8]), "=f"(d[9]), "=f"(d[10]),
          "=f"(d[11]), "=f"(d[12]), "=f"(d[13]), "=f"(d[14]), "=f"(d[15]), "=f"(d[16]), "=f"(d[17]), "=f"(d[18]), "=f"(d[19])
        : "r"(da_lo), "r"(db_lo), "n"(AHI), "n"(BHI));
}
__device__ __forceinline__ void wgmma_ss_n8(float (&d)[4], uint32_t da_lo, uint32_t db_lo) {
    asm volatile(
        "{\n.reg .b64 da, db;\nmov.b64 da, {%4, %6};\nmov.b64 db, {%5, %7};\n"
        "wgmma.mma_async.sync.aligned.m64n8k16.f32.bf16.bf16 {%0,%1,%2,%3}, da, db, 1, 1, 1, 1, 0;\n}\n"
        : "+f"(d[0]), "+f"(d[1]), "+f"(d[2]), "+f"(d[3]) : "r"(da_lo), "r"(db_lo), "n"(DHI128), "n"(DHI32));
}

constexpr uint32_t C2_WO = 0;
constexpr uint32_t C2_XB = 65536;
constexpr uint32_t C2_XS = 40960;
constexpr uint32_t C2_QX = C2_XB + 2 * C2_XS;
constexpr uint32_t C2_KX = C2_QX + 4096;
constexpr uint32_t C2_VT = C2_KX + 5120;
constexpr uint32_t C2_OB = C2_VT + 12288;
constexpr uint32_t C2_QM = C2_OB + 8192;
constexpr uint32_t C2_SC = C2_QM + 1024;
constexpr uint32_t C2_PB = C2_SC + 2560;
constexpr uint32_t C2_BAR = C2_PB + 768;
constexpr uint32_t C2_PX = C2_BAR + 256;
constexpr uint32_t C2_SX = C2_PX + 3072;
#define C2_NS 4
constexpr uint32_t C2_WS = C2_SX + 20480;
constexpr int C2_SMEM = C2_WS + 3 * C2_NS * 2048;
static_assert(C2_PX % 256 == 0 && C2_WS % 256 == 0 && C2_SMEM <= 232448, "smem map");
#define CH_PF 0
#define CH_PFD 3000
#define CH_WOT 1
#define CH_B4E 0
#define CH_NCH 4
#define CH_TS 0
#define CH_TSK 608
#define CH_TSW 2
#define CH_NQ1 12
#define CH_TSC 0
__device__ __align__(256) uint32_t g_tsend[64];
#define CH_POLL_DELAY 600

__device__ __forceinline__ uint32_t c2_stage(int wg, int i) { return wg < 2 ? C2_XB + C2_XS + (wg * 4 + i) * 8192 : ((C2_PX + 1023) & ~1023u) + i * 8192; }
static_assert(C2_XB + C2_XS + 8 * 8192 <= C2_BAR && ((C2_PX + 1023) & ~1023u) + 4 * 8192 <= C2_SMEM && (C2_XB + C2_XS) % 1024 == 0, "staging");
__device__ __forceinline__ void c2_stage_load(const CUtensorMap* map, uint32_t sb, int wg, int rank, int col0, int round) {
    const uint32_t bar = sb + C2_BAR + 176 + (wg * 2 + round) * 8;
    mbar_expect_tx(bar, 32768);
    for (int i = 0; i < 4; i++) tma_load_2d(sb + c2_stage(wg, i), map, bar, col0, ((rank - round * 4 - i) & 7) * 64);
}
__device__ __forceinline__ void c2_load_w(uint32_t (&w)[32][4], const CUtensorMap* map, int wg, int rank, int col0, uint32_t t128, uint32_t ws, uint32_t sb) {
#pragma unroll
    for (int r = 0; r < 2; r++) {
        mbar_wait(sb + C2_BAR + 176 + (wg * 2 + r) * 8, 0);
#pragma unroll
        for (int e = 0; e < 16; e++) {
            const uint32_t a = sb + c2_stage(wg, 0) + e * 2048;
            uint32_t w0, w1, w2, w3;
            asm volatile("ld.shared.b32 %0, [%1];" : "=r"(w0) : "r"(a + t128) : "memory");
            asm volatile("ld.shared.b32 %0, [%1];" : "=r"(w1) : "r"(a + (t128 ^ 16) + 128) : "memory");
            asm volatile("ld.shared.b32 %0, [%1];" : "=r"(w2) : "r"(a + t128 + 1024) : "memory");
            asm volatile("ld.shared.b32 %0, [%1];" : "=r"(w3) : "r"(a + (t128 ^ 16) + 1152) : "memory");
            uint32_t* d = w[r * 16 + e];
            d[0] = __byte_perm(w0, w1, 0x5410); d[1] = __byte_perm(w0, w1, 0x7632);
            d[2] = __byte_perm(w2, w3, 0x5410); d[3] = __byte_perm(w2, w3, 0x7632);
        }
        if (r == 0) {
            asm volatile("bar.sync %0, 128;" :: "r"(8 + wg) : "memory");
            if ((threadIdx.x & 127) == 32) c2_stage_load(map, sb, wg, rank, col0, 1);
            mbar_wait(sb + C2_BAR + 168, 0);
#pragma unroll 2
            for (int i = threadIdx.x; i < 2048; i += 384) {
                const int k = i >> 2, b = i & 3;
                const uint32_t a0 = sb + C2_WO + k * 128 + (((2 * b) ^ (k & 7)) << 4), a1 = a0 ^ 16;
                uint4 u, v;
                asm volatile("ld.shared.v4.b32 {%0, %1, %2, %3}, [%4];" : "=r"(u.x), "=r"(u.y), "=r"(u.z), "=r"(u.w) : "r"(a0) : "memory");
                asm volatile("ld.shared.v4.b32 {%0, %1, %2, %3}, [%4];" : "=r"(v.x), "=r"(v.y), "=r"(v.z), "=r"(v.w) : "r"(a1) : "memory");
                asm volatile("st.shared.v4.b32 [%0], {%1, %2, %3, %4};" :: "r"(a0), "r"(__byte_perm(u.x, u.y, 0x5410)),
                             "r"(__byte_perm(u.z, u.w, 0x5410)), "r"(__byte_perm(v.x, v.y, 0x5410)), "r"(__byte_perm(v.z, v.w, 0x5410)) : "memory");
                asm volatile("st.shared.v4.b32 [%0], {%1, %2, %3, %4};" :: "r"(a1), "r"(__byte_perm(u.x, u.y, 0x7632)),
                             "r"(__byte_perm(u.z, u.w, 0x7632)), "r"(__byte_perm(v.x, v.y, 0x7632)), "r"(__byte_perm(v.z, v.w, 0x7632)) : "memory");
            }
        }
    }
    cluster_sync_relaxed();
#pragma unroll
    for (int e = 0; e < C2_NS; e++) stmatrix_x4(ws + e * 2048, w[e][0], w[e][1], w[e][2], w[e][3]);
    for (int i = threadIdx.x; i < 2 * 512 + 256; i += 384)
        sts32(sb + (i < 1024 ? C2_VT + (i >> 9) * 6144 + 4096 + (i & 511) * 4 : C2_PX + 2048 + (i - 1024) * 4), 0u);
    fence_async_smem();
    asm volatile("bar.sync %0, 128;" :: "r"(8 + wg) : "memory");
}
template <int E0, int E1, int NA>
__device__ __forceinline__ void c2_xstream(float (&acc)[NA], const uint32_t (&w)[32][4], uint32_t xlo, uint32_t rank, uint32_t wslo) {
    if (E0 == 0)
#pragma unroll
        for (int i = 0; i < NA; i++) acc[i] = 0.f;
    wgmma_fence();
#pragma unroll
    for (int e = E0; e < E1; e++) {
        if (e < C2_NS) wgmma_ss<DHI32, DHI128>(acc, wslo + e * 128, xlo + ((rank - (e >> 2)) & 7) * 320 + (e & 3) * 2);
        else wgmma_rs(acc, w[e], xlo + ((rank - (e >> 2)) & 7) * 320 + (e & 3) * 2);
    }
    wgmma_commit();
}
__device__ __forceinline__ constexpr int c2_grp(int i) { return i < 2 ? i : 1 + (i >> 1); }

struct ChainParams {
    CUtensorMap mapX;
    CUtensorMap mapM;
    CUtensorMap mapW[3];
    CUtensorMap mapWo;
};
__global__ void __cluster_dims__(8, 1, 1) __launch_bounds__(384, 1)
chain_kernel(const __grid_constant__ ChainParams P) {
    const CUtensorMap& mapX = P.mapX;
    extern __shared__ __align__(1024) uint8_t smem_chain[];
    const uint32_t sb = smem_u32(smem_chain);
    const uint32_t dlo = ((sb & 0x3FFFF) >> 4) | (1u << 16);
    const int tid = __shfl_sync(0xffffffff, threadIdx.x, threadIdx.x & 31), lane = tid & 31;
    const int warp = __shfl_sync(0xffffffff, tid >> 5, 0), wg = warp >> 2, w4 = warp & 3;
    const uint32_t rank = cluster_ctarank();
    const int C = blockIdx.x >> 3;
    const int h = C * 4 + (rank >> 1);
    const int g = lane >> 2, qc = lane & 3;
    pdl_launch_dependents();
    TS_BEGIN(2);
    const uint32_t bar_m = sb + C2_BAR, bar_o = bar_m + 64, bar_sc = bar_m + 128, bar_x = bar_m + 136, bar_sx = bar_m + 152;
    const uint32_t bar_w = bar_m + 168;
    const int col0 = h * HD + (rank & 1) * 64;
    if (tid == 0) {
        for (int j = 0; j < 5; j++) { mbar_init(bar_m + 8 * j, j ? 1 : 4); mbar_init(bar_o + 8 * j, j ? 1 : 4); }
        for (int j = 0; j < 12; j++) mbar_init(bar_sc + 8 * j, 1);
        asm volatile("fence.mbarrier_init.release.cluster;" ::: "memory");
    }
    __syncwarp();
    cluster_sync_relaxed();
    if (tid == 0) {
        mbar_expect_tx(bar_x, 32768 + 8192);
        tma_load_2d_mc(sb + C2_XB + rank * 5120, &mapX, bar_x, rank * 64, 0, (uint16_t)0xff);
        for (int j = 0; j < 8; j++) tma_load_2d(sb + C2_XB + j * 5120 + 4096, &P.mapM, bar_x, j * 64, 0);
        pace(CH_PFD);
        mbar_expect_tx(bar_w, 65536);
        for (int j = 0; j < 8; j++) tma_load_2d(sb + C2_WO + j * 8192, &P.mapWo, bar_w, rank * 64, C * 512 + ((rank - j) & 7) * 64);
    }
    if ((tid & 127) == 32) {
        pace(CH_PFD);
        c2_stage_load(&P.mapW[wg], sb, wg, rank, col0, 0);
        if (CH_PF)
            for (int i = 4; i < 8; i++)
                asm volatile("cp.async.bulk.prefetch.tensor.2d.L2.global [%0, {%1, %2}];" :: "l"((uint64_t)&P.mapW[wg]), "r"(col0), "r"((int)((rank - i) & 7) * 64) : "memory");
    }
    __syncwarp();

    const uint32_t t32 = w4 * 256 + qc * 64 + (((g >> 2) ^ (qc >> 1)) << 4) + (g & 3) * 4;
    const uint32_t t128 = qc * 256 + (((2 * w4 + (g >> 2)) ^ (2 * qc)) << 4) + (g & 3) * 4;
    const uint32_t a32 = (w4 * 16 + (lane & 15)) * 32 + (((lane >> 4) ^ ((lane >> 2) & 1)) << 4);
    const uint32_t ws = sb + C2_WS + wg * (C2_NS * 2048) + a32;
    uint32_t w[32][4];
    static_assert(C2_NS == 4, "slot 0");
    auto proj_mem = [&](float (&a)[CH_NCH][4], int s, uint32_t l128) {
        uint32_t b[4][8];
#pragma unroll
        for (int i = 0; i < 4 * CH_NCH; i++) a[i >> 2][i & 3] = 0.f;
        const uint32_t par = (s & 1) ^ 1;
        const uint32_t mb = sb + C2_XB + (s & 1) * C2_XS + 4096;
        auto L = [&](int i) {
            ldsm_x4(b[i & 3], mb + ((rank - i) & 7) * 5120 + l128);
            ldsm_x4(b[i & 3] + 4, mb + ((rank - i) & 7) * 5120 + (l128 ^ 64));
        };
        auto H = [&](int i) {
#pragma unroll
            for (int kk = 0; kk < 4; kk++) {
                const uint32_t* f = i ? w[i * 4 + kk] : &b[2 + (kk >> 1)][(kk & 1) * 4];
                mma_16816(a[(i * 4 + kk) % CH_NCH], f[0], f[1], f[2], f[3], b[i & 3][2 * kk], b[i & 3][2 * kk + 1]);
            }
        };
#pragma unroll
        for (int e = 0; e < 4; e++) ldsm_x4(&b[2 + (e >> 1)][(e & 1) * 4], ws + e * 2048);
        mbar_wait(bar_m, par);
        L(0);
        H(0);
        mbar_wait(bar_m + 8, par);
        DBGW(1 + 16 * wg, 0);
        L(1);
        mbar_wait(bar_m + 16, par);
        uint32_t nxt = mbar_test(bar_m + 24, par);
        L(2); L(3);
        H(1);
        if (__builtin_expect(!nxt, 0)) mbar_wait(bar_m + 24, par);
        nxt = mbar_test(bar_m + 32, par);
        L(4); L(5);
        H(2); H(3);
        if (__builtin_expect(!nxt, 0)) mbar_wait(bar_m + 32, par);
        DBGW(2 + 16 * wg, 0);
        L(6); L(7);
        H(4); H(5); H(6); H(7);
#pragma unroll
        for (int i = 0; i < 4; i++) a[0][i] = CH_NCH == 4 ? (a[0][i] + a[1][i]) + (a[2][i] + a[3 % CH_NCH][i]) : CH_NCH == 3 ? a[0][i] + a[1][i] + a[2 % CH_NCH][i] : a[0][i] + a[1][i];
    };
    auto store_x = [&](const float (&acc)[16], uint32_t base) {
#pragma unroll
        for (int j = 0; j < 4; j++) {
            sts32(base + t128 + j * 1024, pack_bf16(acc[4 * j], acc[4 * j + 2]));
            sts32(base + (t128 ^ 16) + 128 + j * 1024, pack_bf16(acc[4 * j + 1], acc[4 * j + 3]));
        }
    };
    const float scale = 0.08838834764831845f, l2e = 1.4426950408889634f;

    if (wg == 0) {
        c2_load_w(w, &P.mapW[0], 0, rank, col0, t128, ws, sb);
        TS_END(6);
        TS_BEGIN(5);
#pragma unroll 1
        for (int s = -1;;) {
            float qx[16];
            uint32_t* dst = reinterpret_cast<uint32_t*>(g_xbuf + (((s & 1) * 8 + rank) * 8 + C) * 128) + qc * 64 + w4 * 8 + g;
            asm volatile("" : "+l"(dst));
            mbar_wait(bar_x + 8 * ((s + 1) & 1), ((s + 1) >> 1) & 1);
            if (s >= 0) bar_sync<6, 384>();
            c2_xstream<0, CH_NQ1>(qx, w, dlo + ((C2_XB + ((s + 1) & 1) * C2_XS) >> 4), rank, dlo + (C2_WS >> 4));
            if (s >= 0) {
                float acc[4] = {0.f, 0.f, 0.f, 0.f};
                const uint32_t tag = ((s >> 1) & 1) ^ 1;
                uint32_t nxt = 0;
#pragma unroll
                for (int i = 0; i < 8; i++) {
                    if (i < 2 || !(i & 1)) {
                        if (i < 2 || __builtin_expect(!nxt, 0)) mbar_wait(bar_o + 8 * c2_grp(i), s & 1);
                        if (i == 0) DBGW(7, 0);
                        if (i == 1) DBGW(8, 0);
                        if (i == 6) DBGW(9, 0);
                        wgmma_fence();
                    }
#pragma unroll
                    for (int kk = 0; kk < 4; kk++) {
                        if ((i & 1) && i < 7 && kk == CH_WOT) nxt = mbar_test(bar_o + 8 * c2_grp(i + 1), s & 1);
                        wgmma_ss_n8(acc, dlo + ((C2_WO + i * 8192 + kk * 2048) >> 4), dlo + ((C2_OB + i * 1024 + kk * 256) >> 4));
                    }
                }
                wgmma_commit();
                if (CH_B4E) bar_arrive<4, 256>();
                if (!CH_TS) bar_arrive<11, 256>();
                wgmma_wait<0>();
                asm volatile("st.relaxed.gpu.global.u32 [%0], %1;" :: "l"(dst), "r"((pack_bf16(acc[0], acc[2]) & ~1u) | tag) : "memory");
                asm volatile("st.relaxed.gpu.global.u32 [%0 + 128], %1;" :: "l"(dst), "r"((pack_bf16(acc[1], acc[3]) & ~1u) | tag) : "memory");
                if (!CH_B4E) bar_arrive<4, 256>();
                DBGW(10, 0);
            }
            s++;
            c2_xstream<CH_NQ1, 32>(qx, w, dlo + ((C2_XB + (s & 1) * C2_XS) >> 4), rank, dlo + (C2_WS >> 4));
            const uint32_t sca = pin(w4 < 2 ? sb + C2_SC + w4 * 512 + lane * 16 : sb + C2_SC + 1024 + lane * 8);
            const uint32_t krow = w4 * 16 + (lane & 15);
            const uint32_t ka0 = pin(sb + C2_KX + krow * 128 + (((lane >> 4) ^ (krow & 7)) << 4));
            const uint32_t l32 = pin(sb + C2_QM + (lane >> 4) * 256 + (lane & 7) * 32 + ((((lane >> 3) & 1) ^ ((lane >> 2) & 1)) << 4));
            const uint32_t qst = pin(sb + C2_QM + t32);
            const uint32_t l128 = pin((lane & 7) * 128 + (((lane >> 3) ^ (lane & 7)) << 4));
            if (s > 0) bar_sync<5, 256>();
            wgmma_wait<0>();
            store_x(qx, sb + C2_QX);
            DBGW(0, 0);
            if (s == NSEG - 1) break;
            {
                float a[CH_NCH][4];
                proj_mem(a, s, l128);
                sts32(qst, pack_bf16(a[0][0], a[0][2]));
                sts32(qst + 32, pack_bf16(a[0][1], a[0][3]));
            }
            DBGW(3, 0);
            if (w4 < 3) {
                uint32_t ka[4][4], qb[8];
                float c[4] = {0.f, 0.f, 0.f, 0.f}, c2[4] = {0.f, 0.f, 0.f, 0.f};
                const uint32_t sc_peer = pin(mapa_u32(sca + 1280, rank ^ 1)), sc_own = pin(mapa_u32(sca, rank));
                bar_sync<1, 384>();
                ldsm_x4(qb, l32);
                ldsm_x4(ka[0], ka0);
                ldsm_x4(ka[1], ka0 ^ 32);
                ldsm_x4(qb + 4, l32 + 512);
                ldsm_x4(ka[2], ka0 ^ 64);
                ldsm_x4(ka[3], ka0 ^ 96);
                mma_16816(c, ka[0][0], ka[0][1], ka[0][2], ka[0][3], qb[0], qb[1]);
                mma_16816(c2, ka[1][0], ka[1][1], ka[1][2], ka[1][3], qb[2], qb[3]);
                mma_16816(c, ka[2][0], ka[2][1], ka[2][2], ka[2][3], qb[4], qb[5]);
                mma_16816(c2, ka[3][0], ka[3][1], ka[3][2], ka[3][3], qb[6], qb[7]);
                const uint32_t u0 = __float_as_uint(c[0] + c2[0]), u1 = __float_as_uint(c[1] + c2[1]);
                const uint32_t u2 = __float_as_uint(c[2] + c2[2]), u3 = __float_as_uint(c[3] + c2[3]);
                asm volatile(
                    "{\n.reg .pred p;\nsetp.lt.u32 p, %8, 2;\n"
                    "@p st.async.weak.shared::cluster.mbarrier::complete_tx::bytes.v4.b32 [%0], {%4, %5, %6, %7}, [%1];\n"
                    "@!p st.async.weak.shared::cluster.mbarrier::complete_tx::bytes.v2.b32 [%0], {%4, %5}, [%1];\n"
                    "@p st.async.weak.shared::cluster.mbarrier::complete_tx::bytes.v4.b32 [%2], {%4, %5, %6, %7}, [%3];\n"
                    "@!p st.async.weak.shared::cluster.mbarrier::complete_tx::bytes.v2.b32 [%2], {%4, %5}, [%3];\n}"
                    :: "r"(sc_peer), "r"(mapa_u32(bar_sc, rank ^ 1)), "r"(sc_own), "r"(mapa_u32(bar_sc, rank)), "r"(u0), "r"(u1), "r"(u2), "r"(u3), "r"(w4) : "memory");
                bar_arrive<2, 224>();
                fence_async_smem();
                if (s >= 4 * CB_FIRST + 5 && (s & 3) == 1 && tid == 0) signal_ctr(CT_CB + ((s - 5) >> 2));
                __syncwarp();
                DBGW(4, 2);
            } else {
                bar_arrive<1, 384>();
                fence_async_smem();
                const uint32_t a = pin(sb + C2_SC + lane * 16), a2 = pin(sb + C2_SC + 1024 + lane * 8), pa = pin(sb + C2_PB + lane * 4);
                mbar_wait(bar_sc, s & 1);
                DBG(5);
                float v[10];
                {
                    float4 x0, x1, y0, y1; float2 x2, y2;
                    asm volatile("ld.shared.v4.f32 {%0, %1, %2, %3}, [%4];" : "=f"(x0.x), "=f"(x0.y), "=f"(x0.z), "=f"(x0.w) : "r"(a) : "memory");
                    asm volatile("ld.shared.v4.f32 {%0, %1, %2, %3}, [%4];" : "=f"(y0.x), "=f"(y0.y), "=f"(y0.z), "=f"(y0.w) : "r"(a + 1280) : "memory");
                    asm volatile("ld.shared.v4.f32 {%0, %1, %2, %3}, [%4];" : "=f"(x1.x), "=f"(x1.y), "=f"(x1.z), "=f"(x1.w) : "r"(a + 512) : "memory");
                    asm volatile("ld.shared.v4.f32 {%0, %1, %2, %3}, [%4];" : "=f"(y1.x), "=f"(y1.y), "=f"(y1.z), "=f"(y1.w) : "r"(a + 1792) : "memory");
                    asm volatile("ld.shared.v2.f32 {%0, %1}, [%2];" : "=f"(x2.x), "=f"(x2.y) : "r"(a2) : "memory");
                    asm volatile("ld.shared.v2.f32 {%0, %1}, [%2];" : "=f"(y2.x), "=f"(y2.y) : "r"(a2 + 1280) : "memory");
                    v[0] = x0.x + y0.x; v[1] = x0.y + y0.y; v[2] = x0.z + y0.z; v[3] = x0.w + y0.w;
                    v[4] = x1.x + y1.x; v[5] = x1.y + y1.y; v[6] = x1.z + y1.z; v[7] = x1.w + y1.w;
                    v[8] = x2.x + y2.x; v[9] = x2.y + y2.y;
                }
                float m0 = fmaxf(fmaxf(fmaxf(v[0], v[2]), fmaxf(v[4], v[6])), v[8]);
                float m1 = fmaxf(fmaxf(fmaxf(v[1], v[3]), fmaxf(v[5], v[7])), v[9]);
#pragma unroll
                for (int o = 4; o < 32; o <<= 1) {
                    m0 = fmaxf(m0, __shfl_xor_sync(0xffffffff, m0, o));
                    m1 = fmaxf(m1, __shfl_xor_sync(0xffffffff, m1, o));
                }
                const float sl = scale * l2e;
                m0 *= sl; m1 *= sl;
#pragma unroll
                for (int j = 0; j < 5; j++)
                    sts32(pa + j * 128, pack_bf16(ex2f(fmaf(v[2 * j], sl, -m0)), ex2f(fmaf(v[2 * j + 1], sl, -m1))));
                bar_arrive<3, 160>();
                DBG(6);
            }
            uint32_t now;
            asm volatile("mov.u32 %0, %%globaltimer_lo;" : "=r"(now) :: "memory");
            if (CH_TS) asm volatile("{\n.reg .pred p;\nsetp.eq.u32 p, %2, %3;\n@p st.relaxed.gpu.global.u32 [%0], %1;\n}" :: "l"(g_tsend + rank * 8 + C), "r"(now), "r"(tid), "n"(CH_TSW * 32) : "memory");
        }
        bar_sync<1, 384>();
        fence_async_smem();
        bar_arrive<6, 384>();
        bar_arrive<4, 256>();
    } else if (wg == 1) {
        c2_load_w(w, &P.mapW[1], 1, rank, col0, t128, ws, sb);
#pragma unroll 1
        for (int s = -1;;) {
            if (s > 0) {
                mbar_wait(bar_sx + 8 * ((s - 1) & 1), ((s - 1) >> 1) & 1);
                const uint32_t a = sb + C2_SX + ((s - 1) & 1) * 10240 + w4 * 1280 + lane * 8;
                float v[10];
                const int lim = 8 * w4 + g - 2 * qc;
#pragma unroll
                for (int j = 0; j < 5; j++) {
                    float2 x, y;
                    asm volatile("ld.shared.v2.f32 {%0, %1}, [%2];" : "=f"(x.x), "=f"(x.y) : "r"(a + j * 256) : "memory");
                    asm volatile("ld.shared.v2.f32 {%0, %1}, [%2];" : "=f"(y.x), "=f"(y.y) : "r"(a + 5120 + j * 256) : "memory");
                    v[2 * j] = (j < 4 && 8 * j > lim) ? -INFINITY : x.x + y.x;
                    v[2 * j + 1] = (j < 4 && 8 * j + 1 > lim) ? -INFINITY : x.y + y.y;
                }
                float mx = fmaxf(fmaxf(fmaxf(v[0], v[1]), fmaxf(v[2], v[3])), fmaxf(fmaxf(v[4], v[5]), fmaxf(v[6], v[7])));
                mx = fmaxf(mx, fmaxf(v[8], v[9]));
                mx = fmaxf(mx, __shfl_xor_sync(0xffffffff, mx, 1));
                mx = fmaxf(mx, __shfl_xor_sync(0xffffffff, mx, 2));
                const float sl = scale * l2e;
                mx *= sl;
#pragma unroll
                for (int j = 0; j < 10; j++) v[j] = ex2f(fmaf(v[j], sl, -mx));
                float sm = ((v[0] + v[1]) + (v[2] + v[3])) + ((v[4] + v[5]) + (v[6] + v[7])) + (v[8] + v[9]);
                sm += __shfl_xor_sync(0xffffffff, sm, 1);
                sm += __shfl_xor_sync(0xffffffff, sm, 2);
                float inv;
                asm("rcp.approx.ftz.f32 %0, %1;" : "=f"(inv) : "f"(sm));
                const uint32_t pa = sb + C2_PX + w4 * 256 + g * 32 + ((g >> 2) << 4) + qc * 4;
#pragma unroll
                for (int j = 0; j < 5; j++) sts32((pa ^ ((j & 1) << 4)) + (j >> 1) * 1024, pack_bf16(v[2 * j] * inv, v[2 * j + 1] * inv));
            }
            if (s >= 0) {
                fence_async_smem();
                if (s < NSEG) bar_sync<6, 384>(); else bar_sync<7, 256>();
                DBGW(20, 0);
                uint32_t cp[8];
                {
                    float cx[16];
#pragma unroll
                    for (int i = 0; i < 16; i++) cx[i] = 0.f;
                    wgmma_fence();
#pragma unroll
                    for (int kk = 0; kk < 3; kk++)
                        wgmma_ss<DHI32, DHI32>(cx, dlo + ((C2_VT + ((s - 1) & 1) * 6144 + kk * 2048) >> 4), dlo + ((C2_PX + kk * 1024) >> 4));
                    wgmma_commit();
                    wgmma_wait<0>();
#pragma unroll
                    for (int j = 0; j < 4; j++) { cp[2 * j] = pack_bf16(cx[4 * j], cx[4 * j + 2]); cp[2 * j + 1] = pack_bf16(cx[4 * j + 1], cx[4 * j + 3]); }
                    asm volatile("{\n.reg .pred p;\nsetp.gt.u32 p, %0, 99;\n@p st.shared.v4.b32 [%0], {%1, %2, %3, %4};\n@p st.shared.v4.b32 [%0], {%5, %6, %7, %8};\n}"
                                 :: "r"(rank), "r"(cp[0]), "r"(cp[1]), "r"(cp[2]), "r"(cp[3]), "r"(cp[4]), "r"(cp[5]), "r"(cp[6]), "r"(cp[7]) : "memory");
                }
                float sx[20];
                wgmma_fence();
                wgmma_ss0<DHI128, DHI128>(sx, dlo + (C2_QX >> 4), dlo + (C2_KX >> 4));
#pragma unroll
                for (int kk = 1; kk < 4; kk++) wgmma_ss<DHI128, DHI128>(sx, dlo + (C2_QX >> 4) + kk * 2, dlo + (C2_KX >> 4) + kk * 2);
                wgmma_commit();
                wgmma_wait<0>();
                if (s < NSEG - 1) bar_arrive<5, 256>();
                if (s > 0) {
                    uint32_t* dst = reinterpret_cast<uint32_t*>(g_ctxB + ((size_t)h * SEQ + (s - 1) * SEGL + 2 * qc) * HD + (rank & 1) * 64 + w4 * 16 + 2 * g);
#pragma unroll
                    for (int j = 0; j < 4; j++) {
                        asm volatile("st.global.u32 [%0], %1;" :: "l"(dst + j * 8 * (HD / 2)), "r"(cp[2 * j]) : "memory");
                        asm volatile("st.global.u32 [%0], %1;" :: "l"(dst + (j * 8 + 1) * (HD / 2)), "r"(cp[2 * j + 1]) : "memory");
                    }
                }
                DBGW(22, 0);
                if (s == NSEG) break;
                const uint32_t a = sb + C2_SX + (s & 1) * 10240 + w4 * 2560 + lane * 8;
                if (w4 < 2) {
#pragma unroll
                    for (int j = 0; j < 5; j++) {
                        asm volatile("st.shared.v2.f32 [%0], {%1, %2};" :: "r"(a + j * 256), "f"(sx[4 * j]), "f"(sx[4 * j + 1]) : "memory");
                        asm volatile("st.shared.v2.f32 [%0], {%1, %2};" :: "r"(a + 1280 + j * 256), "f"(sx[4 * j + 2]), "f"(sx[4 * j + 3]) : "memory");
                    }
                }
                if (s < NSEG - 1) mbar_wait(bar_x + 8 * ((s + 1) & 1), ((s + 1) >> 1) & 1);
                const uint32_t pa = mapa_u32(a + 5120, rank ^ 1), pb = mapa_u32(bar_sx + 8 * (s & 1), rank ^ 1);
                bar_sync<4, 256>();
                if (w4 < 2) {
#pragma unroll
                    for (int j = 0; j < 5; j++) {
                        st_async_v2(pa + j * 256, __float_as_uint(sx[4 * j]), __float_as_uint(sx[4 * j + 1]), pb);
                        st_async_v2(pa + 1280 + j * 256, __float_as_uint(sx[4 * j + 2]), __float_as_uint(sx[4 * j + 3]), pb);
                    }
                }
            } else mbar_wait(bar_x, 0);
            s++;
            if (s < NSEG) {
                float acc[16];
                c2_xstream<0, 32>(acc, w, dlo + ((C2_XB + (s & 1) * C2_XS) >> 4), rank, dlo + ((C2_WS + C2_NS * 2048) >> 4));
                const uint32_t kst = pin(sb + C2_KX + 4096 + t128);
                const uint32_t l128 = pin((lane & 7) * 128 + (((lane >> 3) ^ (lane & 7)) << 4));
                wgmma_wait<0>();
                store_x(acc, sb + C2_KX);
                DBGW(16, 0);
                float a[CH_NCH][4];
                proj_mem(a, s, l128);
                sts32(kst, pack_bf16(a[0][0], a[0][2]));
                sts32((kst ^ 16) + 128, pack_bf16(a[0][1], a[0][3]));
                bar_arrive<1, 384>();
                DBGW(19, 0);
                if (w4 == 0) {
                    if (s < NSEG - 1) {
                        if (lane == 0) mbar_expect_tx(bar_sc, 2560);
                        if (lane < 16 && (lane & 7) >= 1 && (lane & 7) < 5) mbar_expect_tx(bar_m + 8 * lane, (lane & 7) == 1 ? 1024 : 2048);
                        if (lane == 8) {
                            mbar_expect_tx(bar_x + 8 * ((s + 1) & 1), 32768);
                            tma_load_2d_mc(sb + C2_XB + ((s + 1) & 1) * C2_XS + rank * 5120, &mapX, bar_x + 8 * ((s + 1) & 1), rank * 64, (s + 1) * SEGL, (uint16_t)0xff);
                            if (s + 2 < NSEG)
                                asm volatile("cp.async.bulk.prefetch.tensor.2d.L2.global [%0, {%1, %2}];" :: "l"((uint64_t)&mapX), "r"(rank * 64), "r"((s + 2) * SEGL) : "memory");
                        }
                    }
                    if (lane == 16) mbar_expect_tx(bar_sx + 8 * (s & 1), 5120);
                    __syncwarp();
                }
            }
        }
        bar_sync<9, 128>();
        if (tid == 128) signal_ctr(CT_CB + 15);
    } else {
        c2_load_w(w, &P.mapW[2], 2, rank, col0, t128, ws, sb);
        uint32_t va[5][2] = {};
        auto store_vt = [&](int s) {
            const uint32_t a = sb + C2_VT + (s & 1) * 6144 + a32;
            stmatrix_x4(a, va[0][0], va[0][1], va[1][0], va[1][1]);
            stmatrix_x4(a + 2048, va[2][0], va[2][1], va[3][0], va[3][1]);
            asm volatile("stmatrix.sync.aligned.m8n8.x2.shared.b16 [%0], {%1, %2};" :: "r"(a + 4096), "r"(va[4][0]), "r"(va[4][1]) : "memory");
        };
#pragma unroll 1
        for (int s = -1;;) {
            if (s >= 0) {
                const int t = tid - 256;
                const uint2* src = g_xbuf + ((s & 1) * 8 + rank) * 1024 + t;
                asm volatile("" : "+l"(src));
                const uint32_t ma = sb + C2_XB + ((s + 1) & 1) * C2_XS + rank * 5120 + 4096 + (t >> 4) * 128 + ((((t >> 1) & 7) ^ (t >> 4)) << 4) + (t & 1) * 8;
                uint32_t ra[8], rb[8];
#pragma unroll
                for (int i = 1; i < 8; i++) {
                    const uint32_t d = (rank + i) & 7;
                    ra[i] = pin(mapa_u32(ma, d)); rb[i] = pin(mapa_u32(bar_m + 8 * c2_grp(i), d));
                }
                if (s == NSEG - 1) break;
                bar_sync<11, 256>();
                DBGW(29, 0);
                pace(CH_POLL_DELAY);
                const uint32_t tag = ((s >> 1) & 1) ^ 1;
                uint32_t p[8][2], m0, m1;
                auto issue = [&](uint32_t (&x)[8][2]) {
#pragma unroll
                    for (int k = 0; k < 8; k++)
                        asm volatile("ld.relaxed.gpu.global.v2.u32 {%0, %1}, [%2];" : "=r"(x[k][0]), "=r"(x[k][1]) : "l"(src + k * 128) : "memory");
                };
                auto check = [&](const uint32_t (&x)[8][2]) {
                    uint32_t bad = 0, bad2 = 0;
                    float r[4];
#pragma unroll
                    for (int k = 0; k < 8; k++) {
                        asm("lop3.b32 %0, %0, %1, %2, 0xf6;" : "+r"(bad) : "r"(x[k][0]), "r"(tag));
                        asm("lop3.b32 %0, %0, %1, %2, 0xf6;" : "+r"(bad2) : "r"(x[k][1]), "r"(tag));
#pragma unroll
                        for (int e = 0; e < 2; e++) {
                            const float lo = __uint_as_float(x[k][e] << 16), hi = __uint_as_float(x[k][e] & 0xffff0000u);
                            r[2 * e] = k ? r[2 * e] + lo : lo;
                            r[2 * e + 1] = k ? r[2 * e + 1] + hi : hi;
                        }
                    }
                    m0 = pack_bf16(r[0], r[1]); m1 = pack_bf16(r[2], r[3]);
                    asm volatile("" : "+r"(m0), "+r"(m1));
                    return __all_sync(0xffffffff, ((bad | bad2) & 1u) == 0u);
                };
                for (int it = 0; it < (1 << 20); it++) {
                    issue(p);
                    if (check(p)) break;
                }
                DBGW(30, 0);
                st_async_v2(ra[1], m0, m1, rb[1]);
                asm volatile("st.shared.v2.b32 [%0], {%1, %2};" :: "r"(ma), "r"(m0), "r"(m1) : "memory");
                __syncwarp();
                if (lane == 0) mbar_arrive(bar_m);
#pragma unroll
                for (int i = 2; i < 8; i++) st_async_v2(ra[i], m0, m1, rb[i]);
                DBGW(31, 0);
                store_vt(s);
            }
            s++;
            const uint32_t ost = pin(sb + C2_OB + t32), pla = pin(sb + C2_PB + lane * 16), plb = pin(sb + C2_PB + 512 + (lane & 7) * 16);
            bar_sync<1, 384>();
            fence_async_smem();
            DBGW(24, 0);
            if (s < NSEG - 1) bar_sync<2, 224>();
            {
                float acc[20];
                c2_xstream<0, 32>(acc, w, dlo + ((C2_XB + (s & 1) * C2_XS) >> 4), rank, dlo + ((C2_WS + 2 * C2_NS * 2048) >> 4));
                wgmma_wait<0>();
#pragma unroll
                for (int j = 0; j < 5; j++) { va[j][0] = pack_bf16(acc[4 * j], acc[4 * j + 1]); va[j][1] = pack_bf16(acc[4 * j + 2], acc[4 * j + 3]); }
            }
            DBGW(26, 0);
            if (s < NSEG - 1) {
                uint32_t p[5];
                bar_sync<3, 160>();
                DBGW(27, 0);
                ldmatrix_x4_trans(p[0], p[1], p[2], p[3], pla);
                asm volatile("ldmatrix.sync.aligned.m8n8.x1.trans.shared.b16 {%0}, [%1];" : "=r"(p[4]) : "r"(plb) : "memory");
                float oa[4] = {0.f, 0.f, 0.f, 0.f}, ob[4] = {0.f, 0.f, 0.f, 0.f}, sa[4] = {0.f, 0.f, 0.f, 0.f}, sc[4] = {0.f, 0.f, 0.f, 0.f};
                const uint32_t one = 0x3f803f80u;
                mma_16816(sa, one, one, one, one, p[0], p[1]);
                mma_16816(oa, va[0][0], va[0][1], va[1][0], va[1][1], p[0], p[1]);
                mma_16816(sc, one, one, one, one, p[2], p[3]);
                mma_16816(ob, va[2][0], va[2][1], va[3][0], va[3][1], p[2], p[3]);
                mma_16816(sa, one, one, one, one, p[4], 0u);
                mma_16816(oa, va[4][0], va[4][1], 0u, 0u, p[4], 0u);
                bar_arrive<6, 384>();
                float i0, i1;
                asm("rcp.approx.ftz.f32 %0, %1;" : "=f"(i0) : "f"(sa[0] + sc[0]));
                asm("rcp.approx.ftz.f32 %0, %1;" : "=f"(i1) : "f"(sa[1] + sc[1]));
                sts32(ost, pack_bf16((oa[0] + ob[0]) * i0, (oa[2] + ob[2]) * i0));
                sts32(ost + 32, pack_bf16((oa[1] + ob[1]) * i1, (oa[3] + ob[3]) * i1));
                fence_async_smem();
                __syncwarp();
                if (elect_one()) {
#pragma unroll
                    for (int i = 1; i < 8; i++) {
                        const uint32_t d = (rank + i) & 7;
                        bulk_s2s(mapa_u32(sb + C2_OB + i * 1024 + w4 * 256, d), sb + C2_OB + w4 * 256, 256, mapa_u32(bar_o + 8 * c2_grp(i), d));
                        if (i == 1) mbar_arrive(bar_o);
                    }
                }
                __syncwarp();
                DBGW(28, 0);
            } else bar_arrive<6, 384>();
        }
        store_vt(NSEG - 1);
        fence_async_smem();
        bar_arrive<7, 256>();
        g_xbuf[((8 + rank) * 8 + C) * 128 + (tid - 256)] = make_uint2(0u, 0u);
    }
    cluster_sync_relaxed();
    TS_END(2);
}

struct Proj2Params {
    CUtensorMap mapA[2];
    CUtensorMap mapW[3];
    bf16* out[3];
};
#define P2T(i)
#define P2_NOMMA 0
#define P2_NOLOAD 0
constexpr int P2_STAGES = 6;
constexpr int P2_SMEM = 131072 + P2_STAGES * 16384 + 1024 + 1024;
constexpr int P2_ITEMS = 168 + 48;
__device__ __forceinline__ int p2_reps(int t) { return t >= 168 ? 1 : 2; }
__device__ __forceinline__ void p2_tile(int t, int w, int& z, int& mp, int& head) {
    if (t >= 168) { w += ((t - 168) & 1) * 2; t = 168 + ((t - 168) >> 1); }
    const int hq = t / 24, v = t % 24;
    mp = v & 7;
    if (v < 16) { head = hq * 4 + (v >> 3) * 2 + (w >> 1); z = 1 + (w & 1); }
    else { head = hq * 4 + w; z = 0; }
}
__device__ __forceinline__ void mbar_arrive_remote(uint32_t bar_cluster_addr) {
    asm volatile("mbarrier.arrive.release.cluster.shared::cluster.b64 _, [%0];" :: "r"(bar_cluster_addr) : "memory");
}
__device__ __forceinline__ void mbar_arrive_cl(uint32_t bar_cluster_addr) {
    asm volatile("mbarrier.arrive.shared::cluster.b64 _, [%0];" :: "r"(bar_cluster_addr) : "memory");
}
__device__ __forceinline__ void mbar_wait_acq_cluster(uint32_t bar, uint32_t parity) {
    asm volatile(
        "{\n"
        ".reg .pred p, q;\n"
        ".reg .u32 c;\n"
        "mov.u32 c, 0;\n"
        "WAIT_LOOP_C:\n"
        "mbarrier.try_wait.parity.acquire.cluster.shared::cta.b64 p, [%0], %1;\n"
        "@p bra WAIT_DONE_C;\n"
        "add.u32 c, c, 1;\n"
        "setp.lt.u32 q, c, 4000000;\n"
        "@q bra WAIT_LOOP_C;\n"
        "WAIT_DONE_C:\n"
        "}\n" :: "r"(bar), "r"(parity) : "memory");
}
__device__ __forceinline__ uint4 quad_transpose(uint32_t p0, uint32_t p1, uint32_t p2, uint32_t p3, int lane) {
    const bool o1 = lane & 1, o2 = lane & 2;
    uint32_t s0 = o1 ? p0 : p1, s1 = o1 ? p2 : p3;
    s0 = __shfl_xor_sync(0xffffffff, s0, 1); s1 = __shfl_xor_sync(0xffffffff, s1, 1);
    const uint32_t a_lo = o1 ? s0 : p0, a_hi = o1 ? p1 : s0, b_lo = o1 ? s1 : p2, b_hi = o1 ? p3 : s1;
    uint32_t t0 = o2 ? a_lo : b_lo, t1 = o2 ? a_hi : b_hi;
    t0 = __shfl_xor_sync(0xffffffff, t0, 2); t1 = __shfl_xor_sync(0xffffffff, t1, 2);
    return o2 ? make_uint4(t0, t1, b_lo, b_hi) : make_uint4(a_lo, a_hi, t0, t1);
}
#define P2_PACE 35
#define P2_PACE2 0
template <bool PERM, int PACE = 0>
__device__ __forceinline__ void store_frag_128(const float (&acc)[64], bf16* obase, int lane) {
#pragma unroll
    for (int rr = 0; rr < 2; rr++)
#pragma unroll
        for (int g = 0; g < 4; g++) {
            const float* a = &acc[g * 16 + rr * 2];
            const uint32_t p0 = pack_bf16(a[0], a[1]), p1 = pack_bf16(a[4], a[5]), p2 = pack_bf16(a[8], a[9]), p3 = pack_bf16(a[12], a[13]);
            *reinterpret_cast<uint4*>(obase + (size_t)(rr * 8) * HD + g * 32) = PERM ? make_uint4(p0, p1, p2, p3) : quad_transpose(p0, p1, p2, p3, lane);
            pace(PACE);
        }
}
__global__ void __cluster_dims__(2, 1, 1) __launch_bounds__(384, 1) proj2_kernel(const __grid_constant__ Proj2Params P) {
    extern __shared__ uint8_t smem_raw[];
    const uint32_t sbase = (smem_u32(smem_raw) + 1023) & ~1023u;
    const uint32_t sA = sbase, sB = sbase + 131072, sC = sB + P2_STAGES * 16384;
    const uint32_t bars = sC;
    const uint32_t a_full = bars, a_empty = bars + 64, b_full = bars + 128, b_empty = b_full + 8 * P2_STAGES;
    const uint32_t item_bar = b_empty + 8 * P2_STAGES, item_in = item_bar + 16, slot = item_in + 16;
    const uint32_t note_bar = slot + 16, note_free = note_bar + 64, note = note_free + 64;
    const int warp = threadIdx.x >> 5, lane = threadIdx.x & 31;
    const uint32_t rank = cluster_ctarank();
    TS_BEGIN(0);
    if (threadIdx.x == 0) {
        for (int i = 0; i < 8; i++) { mbar_init(a_full + 8 * i, 1); mbar_init(a_empty + 8 * i, 2); }
        for (int i = 0; i < P2_STAGES; i++) { mbar_init(b_full + 8 * i, 1); mbar_init(b_empty + 8 * i, 2); }
        mbar_init(item_bar, 1); mbar_init(item_bar + 8, 1); mbar_init(item_in, 2); mbar_init(item_in + 8, 2);
        for (int i = 0; i < 8; i++) { mbar_init(note_bar + 8 * i, 1); mbar_init(note_free + 8 * i, 1); }
        asm volatile("fence.mbarrier_init.release.cluster;" ::: "memory");
    }
    __syncwarp();
    cluster_sync_relaxed();
    pdl_launch_dependents();
    if (warp == 9) {
        if (lane == 0) {
            for (int n = 0;; n++) {
                const int e = (n & 1) * 4 + ((n >> 1) & 3);
                mbar_wait(note_bar + 8 * e, (n >> 3) & 1);
                int m;
                asm volatile("ld.shared.s32 %0, [%1];" : "=r"(m) : "r"(note + e * 4) : "memory");
                mbar_arrive(note_free + 8 * e);
                if (m < 0) break;
                signal_ctr(m);
            }
        }
    } else if (warp == 10) {
        if (lane == 0) {
            auto publish = [&](int ic, int tq) {
                const int t = tq < P2_ITEMS ? tq : -1;
                asm volatile("st.shared.s32 [%0], %1;" :: "r"(slot + (ic & 3) * 4), "r"(t) : "memory");
                mbar_arrive(item_bar + 8 * (ic & 1));
                st_async_b32(mapa_u32(slot + (ic & 3) * 4, 1), (uint32_t)t, mapa_u32(item_bar + 8 * (ic & 1), 1));
            };
            const int npair = (int)(gridDim.x >> 1), pair = (int)(blockIdx.x >> 1);
            if (rank == 0) publish(0, pair);
            for (int ic = 0;; ic++) {
                if (rank == 1) mbar_expect_tx(item_bar + 8 * (ic & 1), 4);
                mbar_wait(item_bar + 8 * (ic & 1), (ic >> 1) & 1);
                int t;
                asm volatile("ld.shared.s32 %0, [%1];" : "=r"(t) : "r"(slot + (ic & 3) * 4) : "memory");
                if (t < 0) break;
                int z0, mp, h0;
                p2_tile(t, 0, z0, mp, h0);
                const int aidx = z0 >= 1 ? 1 : 0;
                const int m0 = (2 * mp + (int)rank) * 128;
                for (int k = 0; k < 8; k++) {
                    mbar_wait(a_empty + 8 * k, (ic & 1) ^ 1);
                    if (P2_NOLOAD) mbar_arrive(a_full + 8 * k); else {
                    mbar_expect_tx(a_full + 8 * k, 16384);
                    tma_load_2d(sA + k * 16384, &P.mapA[aidx], a_full + 8 * k, k * 64, m0); }
                }
                if (rank == 0) {
                    mbar_wait(item_in + 8 * (ic & 1), (ic >> 1) & 1);
                    publish(ic + 1, ic == 0 ? npair + pair : 2 * npair + (int)atomicAdd(&g_ctr[CT_PROJ], 1u));
                }
            }
        }
    } else if (warp == 8 || warp == 11) {
        if (lane == 0) {
            const int par2 = warp == 8 ? 0 : 1;
            int it = 0; uint32_t bph = 0;
            for (int ic = 0;; ic++) {
                mbar_wait(item_bar + 8 * (ic & 1), (ic >> 1) & 1);
                int t;
                asm volatile("ld.shared.s32 %0, [%1];" : "=r"(t) : "r"(slot + (ic & 3) * 4) : "memory");
                if (t < 0) break;
                const int nt = 2 * p2_reps(t);
                for (int w = 0; w < nt; w++) {
                    int z, mp, hd;
                    p2_tile(t, w, z, mp, hd);
                    for (int k = 0; k < 8; k++) {
                        const int s = it; const uint32_t phb = bph;
                        if (++it == P2_STAGES) { it = 0; bph ^= 1; }
                        if ((k & 1) != par2) continue;
                        mbar_wait(b_empty + 8 * s, phb ^ 1);
                        if (P2_NOLOAD) { mbar_arrive(b_full + 8 * s); continue; }
                        mbar_expect_tx(b_full + 8 * s, 16384);
                        tma_load_2d_mc(sB + s * 16384 + rank * 8192, &P.mapW[z], b_full + 8 * s, hd * 128 + (int)rank * 64, k * 64, (uint16_t)3);
                    }
                }
            }
        }
    } else {
        const int wg = warp >> 2;
        float acc[2][64];
        const uint32_t a_lo = desc_lo(sA, 16), b_lo0 = desc_lo(sB, 8192);
        const bool elected = (threadIdx.x & 127) == 0;
        int s = (wg * 8) % P2_STAGES;
        uint32_t ph = ((wg * 8) / P2_STAGES) & 1;
        int nnote = 0;
        if (wg == 1) asm volatile("bar.arrive 3, 256;" ::: "memory");
        for (int ic = 0;; ic++) {
            mbar_wait(item_bar + 8 * (ic & 1), (ic >> 1) & 1);
            int t;
            asm volatile("ld.shared.s32 %0, [%1];" : "=r"(t) : "r"(slot + (ic & 3) * 4) : "memory");
            P2T(7);
            if (wg == 0 && t < 0) {
                if (elected) {
                    const int e = nnote & 3;
                    mbar_wait(note_free + 8 * e, ((nnote >> 2) & 1) ^ 1);
                    asm volatile("st.shared.s32 [%0], %1;" :: "r"(note + e * 4), "r"(-1) : "memory");
                    mbar_arrive(note_bar + 8 * e);
                }
            }
            if (t < 0) break;
            const int reps = p2_reps(t);
#pragma unroll 1
            for (int rp = 0; rp < reps; rp++) {
            const bool first = rp == 0, last = rp == reps - 1;
            int z, mp, head;
            p2_tile(t, rp * 2 + wg, z, mp, head);
            asm volatile("bar.sync %0, 256;" :: "r"(3 + wg) : "memory");
            P2T(0);
            if (wg == 1 && last && elected) mbar_arrive_cl(mapa_u32(item_in + 8 * (ic & 1), 0));
            int sprev = 0;
#pragma unroll
            for (int k = 0; k < 8; k++) {
                if (k == 0) P2T(5);
                if (wg == 0 && first) mbar_wait(a_full + 8 * k, ic & 1);
                if (k == 0) P2T(6);
                mbar_wait(b_full + 8 * s, ph);
                if (k == 7) asm volatile("bar.arrive %0, 256;" :: "r"(4 - wg) : "memory");
                if (k == 0) P2T(1);
                if (k == 7) P2T(2);
                const uint32_t b_lo = b_lo0 + s * 1024;
                wgmma_fence();
#pragma unroll
                for (int kk = 0; kk < (P2_NOMMA ? 1 : 4); kk++) {
                    wgmma_ss_n128_lo<1>(acc[0], a_lo + k * 1024 + kk * 2, b_lo + kk * 128, (k | kk) != 0);
                    wgmma_ss_n128_lo<1>(acc[1], a_lo + k * 1024 + 512 + kk * 2, b_lo + kk * 128, (k | kk) != 0);
                }
                wgmma_commit();
                if (k > 0) {
                    wgmma_wait<1>();
                    if (elected) {
                        const uint32_t e = b_empty + 8 * sprev;
                        mbar_arrive_cl(mapa_u32(e, 0)); mbar_arrive_cl(mapa_u32(e, 1));
                        if (last) mbar_arrive(a_empty + 8 * (k - 1));
                    }
                }
                sprev = s;
                if (++s == P2_STAGES) { s = 0; ph ^= 1; }
            }
            wgmma_wait<0>();
            P2T(3);
            if (elected) {
                const uint32_t e = b_empty + 8 * sprev;
                mbar_arrive_cl(mapa_u32(e, 0)); mbar_arrive_cl(mapa_u32(e, 1));
                if (last) mbar_arrive(a_empty + 8 * 7);
            }
            s += 8 % P2_STAGES; ph ^= (8 / P2_STAGES) & 1;
            if (s >= P2_STAGES) { s -= P2_STAGES; ph ^= 1; }
            const int m0 = (2 * mp + (int)rank) * 128;
            bf16* obase = P.out[z] + ((size_t)head * SEQ + m0 + (warp & 3) * 16 + (lane >> 2)) * HD + (lane & 3) * 8;
            store_frag_128<true, P2_PACE>(acc[0], obase, lane); store_frag_128<true, P2_PACE>(acc[1], obase + (size_t)64 * HD, lane);
            P2T(4);
            {
                asm volatile("bar.sync %0, 128;" :: "r"(1 + wg) : "memory");
                if (elected) {
                    const int e = wg * 4 + (nnote & 3);
                    mbar_wait(note_free + 8 * e, ((nnote >> 2) & 1) ^ 1);
                    asm volatile("st.shared.s32 [%0], %1;" :: "r"(note + e * 4), "r"(CT_AP + (head >> 1)) : "memory");
                    mbar_arrive(note_bar + 8 * e);
                }
                nnote++;
            }
            }
        }
        TS_END(0);
    }
    __syncwarp();
    cluster_sync_relaxed();
}

struct OutParams {
    CUtensorMap mapCtx[2];
    CUtensorMap mapWo[2];
    CUtensorMap mapOut;
};
__device__ uint4 g_part[4 * 32 * 8 * 16 * 32];

#define OT(i)
#define OTP(i)
#define O3_LK 32
#define O3_LK15 32
#define O3_D 5
constexpr int O3_E = 68, O3_GRID = O3_E + 64;
constexpr int O2_SMEM = 196608 + 1024 + 256;

__global__ void __cluster_dims__(2, 1, 1) __launch_bounds__(352, 1) out3_kernel(const __grid_constant__ OutParams P) {
    extern __shared__ uint8_t smem_raw[];
    const uint32_t sbase = (smem_u32(smem_raw) + 1023) & ~1023u;
    const uint32_t bar_full = sbase + 196608, bar_empty = bar_full + 64;
    const int warp = threadIdx.x >> 5, lane = threadIdx.x & 31;
    const uint32_t rank = cluster_ctarank();
    const int pair = blockIdx.x >> 1;
    const bool early = pair < O3_E / 2;
    constexpr int EB = 64 - O3_LK, EB15 = 64 - O3_LK15;
    int mt, part, a0, na, b0, nb;
    if (pair < 30) {
        part = pair >= 15; mt = part ? 29 - pair : pair;
        const int d = (14 - mt) * O3_D / 14;
        a0 = part ? 32 + d : 0; na = part ? 32 - d : 32 + d;
        b0 = part ? EB / 2 : 0; nb = part ? EB - EB / 2 : EB / 2;
    } else if (early) {
        part = pair - 30; mt = 15;
        a0 = part * 16; na = 16;
        b0 = part * EB15 / 4; nb = (part + 1) * EB15 / 4 - b0;
    } else {
        part = (pair - O3_E / 2) & 1; mt = (pair - O3_E / 2) >> 1;
        a0 = 0; na = 0; b0 = mt == 15 ? EB15 : EB; nb = 64 - b0;
    }
    const int m0 = mt * 128, nk = na + nb;
    const int n0 = early ? (int)rank * 256 : part * 256 + (int)rank * 128;
    const int nst = early ? 4 : 6;
    const uint32_t ssz = early ? 49152 : 32768;
    TS_BEGIN(4);
    OT(0);
    if (threadIdx.x == 0) {
        for (int i = 0; i < 6; i++) { mbar_init(bar_full + 8 * i, 1); mbar_init(bar_empty + 8 * i, 4); }
        asm volatile("fence.mbarrier_init.release.cluster;" ::: "memory");
    }
    if (threadIdx.x == 256) asm volatile("prefetch.tensormap [%0];" :: "l"((uint64_t)&P.mapCtx[early ? 0 : 1]) : "memory");
    if (threadIdx.x == 288) asm volatile("prefetch.tensormap [%0];" :: "l"((uint64_t)&P.mapWo[early ? 0 : 1]) : "memory");
    if (warp == 0 || warp > 8) asm volatile("bar.sync 1, 96;" ::: "memory");
    __syncwarp();
    asm volatile("barrier.cluster.arrive.relaxed.aligned;" ::: "memory");
    if (warp > 8) {
        if (lane == 0) {
            int s = 0; uint32_t ph = 0;
            for (int i = 0; i < nk; i++) {
                if (i >= nst) mbar_wait(bar_empty + 8 * s, ph ^ 1);
                const uint32_t sa = sbase + s * ssz + 16384;
                const int b = i >= na, k = b ? b0 + i - na : a0 + i;
                if (early) {
                    tma_load_2d(sa + (warp - 9) * 16384, &P.mapWo[b], bar_full + 8 * s, n0 + (warp - 9) * 128, k * 64);
                    tma_load_2d(sa + (warp - 9) * 16384 + 8192, &P.mapWo[b], bar_full + 8 * s, n0 + (warp - 9) * 128 + 64, k * 64);
                } else tma_load_2d(sa + (warp - 9) * 8192, &P.mapWo[1], bar_full + 8 * s, n0 + (warp - 9) * 64, k * 64);
                if (++s == nst) { s = 0; ph ^= 1; }
            }
        }
        __syncwarp();
        asm volatile("barrier.cluster.wait.acquire.aligned;" ::: "memory");
    } else if (warp == 8) {
        if (lane == 0) {
            if (early) wait_ctr(CT_CA + mt * 2, 2u * O2_HE); else wait_ctr(CT_CB + max(mt, CB_FIRST), 64u);
            OTP(3);
        }
        __syncwarp();
        asm volatile("barrier.cluster.wait.acquire.aligned;" ::: "memory");
        if (lane == 0) {
            OTP(7);
            int s = 0; uint32_t ph = 0;
            bool late_a = false;
            for (int i = 0; i < nk; i++) {
                const int b = i >= na, k = b ? b0 + i - na : a0 + i;
                if (!b && k >= 2 * O2_HE && !late_a) { wait_ctr(CT_CA + mt * 2 + 1, 2u * (NH - O2_HE)); late_a = true; }
                if (i == na && early) wait_ctr(CT_CB + max(mt, CB_FIRST), 64u);
                if (i >= nst) mbar_wait(bar_empty + 8 * s, ph ^ 1);
                mbar_expect_tx(bar_full + 8 * s, ssz);
                tma_load_2d_mc(sbase + s * ssz + rank * 8192, &P.mapCtx[b], bar_full + 8 * s, (k & 1) * 64, (k >> 1) * SEQ + m0 + (int)rank * 64, (uint16_t)3);
                if (++s == nst) { s = 0; ph ^= 1; }
            }
        }
    } else {
        asm volatile("barrier.cluster.wait.acquire.aligned;" ::: "memory");
        const int wg = warp >> 2;
        const bool elected = (threadIdx.x & 127) == 0;
        const int row = (warp & 3) * 16 + (lane >> 2);
        const int mrow = (warp & 3) * 16 + (lane & 15);
        const uint32_t moff = mrow * 128, mx = (lane >> 4) ^ (mrow & 7);
        float g0, g1;
        int s = 0, sprev = 0; uint32_t ph = 0;
        {
            unsigned int v; int it = 0;
            do { asm volatile("ld.acquire.gpu.global.u32 %0, [%1];" : "=r"(v) : "l"(&g_ctr[CT_G]) : "memory"); } while (v < FA_GRID && ++it < (1 << 22));
        }
        asm volatile("ld.relaxed.gpu.global.f32 %0, [%1];" : "=f"(g0) : "l"(g_gate + m0 + wg * 64 + row) : "memory");
        asm volatile("ld.relaxed.gpu.global.f32 %0, [%1];" : "=f"(g1) : "l"(g_gate + m0 + wg * 64 + row + 8) : "memory");
        auto release = [&](int st) {
            if (elected) { const uint32_t e = bar_empty + 8 * st; mbar_arrive_cl(mapa_u32(e, 0)); mbar_arrive_cl(mapa_u32(e, 1)); }
        };
        if (early) {
            float acc[128];
#pragma unroll 1
            for (int i = 0; i < nk; i++) {
                mbar_wait(bar_full + 8 * s, ph);
                if (i == 8) OT(2);
                if (i == na) {
                    wgmma_wait<0>();
                    const float r0 = g0 / fmaxf(1.f - g0, 0x1p-40f), r1 = g1 / fmaxf(1.f - g1, 0x1p-40f);
#pragma unroll
                    for (int j = 0; j < 32; j++) { acc[4 * j] *= r0; acc[4 * j + 1] *= r0; acc[4 * j + 2] *= r1; acc[4 * j + 3] *= r1; }
                }
                const uint32_t sa = sbase + s * 49152 + wg * 8192, sb = sbase + s * 49152 + 16384;
                wgmma_fence();
#pragma unroll
                for (int kk = 0; kk < 4; kk++)
                    wgmma_ss_n256_tb(acc, make_desc(sa + kk * 32, 16, 1024), make_desc(sb + kk * 2048, 8192, 1024), (i | kk) != 0);
                wgmma_commit();
                if (i > 0) { wgmma_wait<1>(); release(sprev); }
                sprev = s;
                if (++s == 4) { s = 0; ph ^= 1; }
            }
            wgmma_wait<0>();
            OT(4);
            const float w0 = fmaxf(1.f - g0, 0x1p-40f), w1 = fmaxf(1.f - g1, 0x1p-40f);
            uint4* dst = g_part + (((part * 32 + mt * 2 + (int)rank) * 8 + warp) * 16) * 32 + lane;
#pragma unroll
            for (int j = 0; j < 16; j++) {
                const float* a = &acc[8 * j];
                dst[j * 32] = make_uint4(pack_bf16(a[0] * w0, a[1] * w0), pack_bf16(a[2] * w1, a[3] * w1), pack_bf16(a[4] * w0, a[5] * w0), pack_bf16(a[6] * w1, a[7] * w1));
            }
            __syncwarp();
            OT(5);
            if (lane == 0) signal_ctr_generic(CT_OP + (mt * 2 + (int)rank) * 8 + warp);
            OT(6);
        } else {
            float acc[64];
            const uint32_t a_lo = desc_lo(sbase + wg * 8192, 16), b_lo = desc_lo(sbase + 16384, 8192);
#pragma unroll 1
            for (int i = 0; i < nk; i++) {
                mbar_wait(bar_full + 8 * s, ph);
                if (i == 8) OT(2);
                wgmma_fence();
#pragma unroll
                for (int kk = 0; kk < 4; kk++) wgmma_ss_n128_lo<1>(acc, a_lo + s * 2048 + kk * 2, b_lo + s * 2048 + kk * 128, (i | kk) != 0);
                wgmma_commit();
                if (i > 0) { wgmma_wait<1>(); release(sprev); }
                sprev = s;
                if (++s == 6) { s = 0; ph ^= 1; }
            }
            const int np = mt == 15 ? 4 : 2;
            wait_ctr(CT_OP + (mt * 2 + part) * 8 + warp, np);
            const uint4* src = g_part + (((mt * 2 + part) * 8 + warp) * 16 + (int)rank * 8) * 32 + lane;
            uint4 u[2][8];
            auto load_parts = [&](int p) {
#pragma unroll
                for (int i = 0; i < 16; i++)
                    asm volatile("ld.relaxed.gpu.global.v4.u32 {%0, %1, %2, %3}, [%4];" : "=r"(u[i >> 3][i & 7].x), "=r"(u[i >> 3][i & 7].y), "=r"(u[i >> 3][i & 7].z),
                                 "=r"(u[i >> 3][i & 7].w) : "l"(src + (p + (i >> 3)) * (32 * 8 * 16 * 32) + (i & 7) * 32) : "memory");
            };
            auto add_parts = [&]() {
#pragma unroll
                for (int i = 0; i < 16; i++) {
                    const uint32_t v[4] = {u[i >> 3][i & 7].x, u[i >> 3][i & 7].y, u[i >> 3][i & 7].z, u[i >> 3][i & 7].w};
#pragma unroll
                    for (int e = 0; e < 4; e++) {
                        acc[8 * (i & 7) + 2 * e] += __uint_as_float(v[e] << 16);
                        acc[8 * (i & 7) + 2 * e + 1] += __uint_as_float(v[e] & 0xffff0000u);
                    }
                }
            };
            load_parts(0);
            wgmma_wait<0>();
            OT(4);
            const float w0 = 1.f - g0, w1 = 1.f - g1;
#pragma unroll
            for (int j = 0; j < 16; j++) { acc[4 * j] *= w0; acc[4 * j + 1] *= w0; acc[4 * j + 2] *= w1; acc[4 * j + 3] *= w1; }
            add_parts();
            if (np == 4) { load_parts(2); add_parts(); }
            OT(5);
            mbar_wait(bar_empty + 8 * s, ph ^ 1);
            const uint32_t stg = sbase + s * 32768 + wg * 16384;
#pragma unroll
            for (int j = 0; j < 8; j++) {
                const float* a = &acc[8 * j];
                stmatrix_x4(stg + (j >> 2) * 8192 + moff + ((mx ^ ((j & 3) * 2)) << 4), pack_bf16(a[0], a[1]), pack_bf16(a[2], a[3]), pack_bf16(a[4], a[5]), pack_bf16(a[6], a[7]));
            }
            fence_async_smem();
            asm volatile("bar.sync %0, 128;" :: "r"(2 + wg) : "memory");
            if (elected) {
                tma_store_2d(&P.mapOut, stg, n0, m0 + wg * 64);
                tma_store_2d(&P.mapOut, stg + 8192, n0 + 64, m0 + wg * 64);
                asm volatile("cp.async.bulk.commit_group;" ::: "memory");
                asm volatile("cp.async.bulk.wait_group 0;" ::: "memory");
            }
            OT(6);
        }
    }
    __syncthreads();
    asm volatile("barrier.cluster.arrive.relaxed.aligned;" ::: "memory");
    if (warp == 0) {
        unsigned int tk = 0;
        if (lane == 0) tk = atomicAdd(&g_ctr[CT_FIN], 1u);
        tk = __shfl_sync(0xffffffff, tk, 0);
        if (tk == gridDim.x - 1)
            for (int i = lane; i < CT_N; i += 32) g_ctr[i] = 0u;
    }
    asm volatile("barrier.cluster.wait.acquire.aligned;" ::: "memory");
    TS_END(4);
}

typedef CUresult (*PFN_encodeTiled)(CUtensorMap*, CUtensorMapDataType, cuuint32_t, void*, const cuuint64_t*,
                                    const cuuint64_t*, const cuuint32_t*, const cuuint32_t*, CUtensorMapInterleave,
                                    CUtensorMapSwizzle, CUtensorMapL2promotion, CUtensorMapFloatOOBfill);
static PFN_encodeTiled g_encode = nullptr;

static void make_map(CUtensorMap* m, const void* ptr, uint64_t rows, uint64_t cols, uint32_t box_rows, bool sw64 = false) {
    cuuint64_t dims[2] = {cols, rows};
    cuuint64_t strides[1] = {cols * 2};
    cuuint32_t box[2] = {sw64 ? 32u : 64u, box_rows};
    cuuint32_t es[2] = {1, 1};
    g_encode(m, CU_TENSOR_MAP_DATA_TYPE_BFLOAT16, 2, const_cast<void*>(ptr), dims, strides, box, es,
             CU_TENSOR_MAP_INTERLEAVE_NONE, sw64 ? CU_TENSOR_MAP_SWIZZLE_64B : CU_TENSOR_MAP_SWIZZLE_128B, CU_TENSOR_MAP_L2_PROMOTION_L2_256B,
             CU_TENSOR_MAP_FLOAT_OOB_FILL_NONE);
}

template <typename... KArgs, typename... Args>
static void launch_pdl(void (*kernel)(KArgs...), int grid, int block, size_t smem, cudaStream_t st, bool pdl, Args... args) {
    cudaLaunchConfig_t cfg = {};
    cfg.gridDim = dim3(grid); cfg.blockDim = dim3(block); cfg.dynamicSmemBytes = smem; cfg.stream = st;
    cudaLaunchAttribute at[1];
    at[0].id = cudaLaunchAttributeProgrammaticStreamSerialization;
    at[0].val.programmaticStreamSerializationAllowed = 1;
    cfg.attrs = at; cfg.numAttrs = pdl ? 1 : 0;
    cudaLaunchKernelEx(&cfg, kernel, KArgs(args)...);
}

extern "C" void kernel_launch(void* const* d_in, const int* in_sizes, int n_in, void* d_out, int out_size) {
    const bf16* x = (const bf16*)d_in[0];
    const bf16* ckv = (const bf16*)d_in[1];
    const bf16* wq = (const bf16*)d_in[2];
    const bf16* wuk = (const bf16*)d_in[3];
    const bf16* wuv = (const bf16*)d_in[4];
    const bf16* wo = (const bf16*)d_in[5];
    const bf16* mem0 = (const bf16*)d_in[7];
    const bf16* Wq = (const bf16*)d_in[8];
    const bf16* Wk = (const bf16*)d_in[9];
    const bf16* Wv = (const bf16*)d_in[10];
    const bf16* Wo = (const bf16*)d_in[11];
    const bf16* gate_w = (const bf16*)d_in[13];
    bf16* out = (bf16*)d_out;

    static Proj2Params P2;
    static ChainParams CP;
    static AttnParams AP;
    static OutParams OP;
    static bool init = false;
    static const void* last_in[15];
    bool same = init;
    for (int i = 0; i < 14 && same; i++) same = last_in[i] == d_in[i];
    same = same && last_in[14] == d_out;
    if (!init) {
        cudaDriverEntryPointQueryResult qr;
        cudaGetDriverEntryPoint("cuTensorMapEncodeTiled", (void**)&g_encode, cudaEnableDefault, &qr);
        cudaFuncSetAttribute(proj2_kernel, cudaFuncAttributeMaxDynamicSharedMemorySize, P2_SMEM);
        cudaFuncSetAttribute(attn_kernel, cudaFuncAttributeMaxDynamicSharedMemorySize, FA_SMEM);
        cudaFuncSetAttribute(chain_kernel, cudaFuncAttributeMaxDynamicSharedMemorySize, C2_SMEM);
        cudaFuncSetAttribute(out3_kernel, cudaFuncAttributeMaxDynamicSharedMemorySize, O2_SMEM);
        init = true;
    }
    if (!same) {
        for (int i = 0; i < 14; i++) last_in[i] = d_in[i];
        last_in[14] = d_out;
        void *pQA, *pKA, *pVA, *pCA, *pCB;
        cudaGetSymbolAddress(&pQA, g_QA); cudaGetSymbolAddress(&pKA, g_KA); cudaGetSymbolAddress(&pVA, g_VA);
        cudaGetSymbolAddress(&pCA, g_ctxA); cudaGetSymbolAddress(&pCB, g_ctxB);
        make_map(&P2.mapA[0], x, SEQ, DM, 128);
        make_map(&P2.mapA[1], ckv, SEQ, DM, 128);
        const void* ws[3] = {wq, wuk, wuv};
        void* cs[3] = {pQA, pKA, pVA};
        for (int i = 0; i < 3; i++) { make_map(&P2.mapW[i], ws[i], DM, NQ, 64); P2.out[i] = (bf16*)cs[i]; }
        make_map(&CP.mapX, x, SEQ, DM, SEGL);
        make_map(&CP.mapM, mem0, NMEM, DM, NMEM);
        make_map(&CP.mapW[0], Wq, DM, NQ, 64);
        make_map(&CP.mapW[1], Wk, DM, NQ, 64);
        make_map(&CP.mapW[2], Wv, DM, NQ, 64);
        make_map(&CP.mapWo, Wo, NQ, DM, 64);
        make_map(&AP.mapQ, pQA, NH * SEQ, HD, 128);
        make_map(&AP.mapK, pKA, NH * SEQ, HD, 128);
        make_map(&AP.mapV, pVA, NH * SEQ, HD, 128);
        make_map(&AP.mapO, pCA, NH * SEQ, HD, 64);
        make_map(&OP.mapCtx[0], pCA, NH * SEQ, HD, 64);
        make_map(&OP.mapCtx[1], pCB, NH * SEQ, HD, 64);
        make_map(&OP.mapWo[0], wo, NQ, DM, 64);
        make_map(&OP.mapWo[1], Wo, NQ, DM, 64);
        make_map(&OP.mapOut, out, SEQ, DM, 64);
        AP.x = x; AP.gate_w = gate_w;
    }
    cudaStream_t s1 = cudaStreamPerThread;
    const bool pdl = true;
    launch_pdl(chain_kernel, 64, 384, C2_SMEM, s1, false, CP);
    launch_pdl(proj2_kernel, 68, 384, P2_SMEM, s1, pdl, P2);
    launch_pdl(attn_kernel, FA_GRID, 384, FA_SMEM, s1, pdl, AP);
    launch_pdl(out3_kernel, O3_GRID, 352, O2_SMEM, s1, pdl, OP);
}
```

```cpp
#include <cuda_runtime.h>
#include <cuda_bf16.h>
#include <cuda.h>
#include <stdint.h>
#include <type_traits>

constexpr int SEQ = 2048;
constexpr int DM = 512;
constexpr int NH = 32;
constexpr int HD = 128;
constexpr int NQ = NH * HD;
constexpr int SEGL = 32;
constexpr int NMEM = 8;
constexpr int NSEG = SEQ / SEGL;

typedef __nv_bfloat16 bf16;

__device__ bf16 g_QA[SEQ * NQ];
__device__ bf16 g_KA[SEQ * NQ];
__device__ bf16 g_VA[SEQ * NQ];
__device__ bf16 g_ctxA[SEQ * NQ];
__device__ bf16 g_ctxB[SEQ * NQ];
constexpr int CT_PROJ = 0, CT_ATTN = 1, CT_FIN = 5;
constexpr int CT_P = 48;
constexpr int CT_G = 32;
constexpr int CT_AP = 64;
#define O2_HE 24
constexpr int CT_CA = 128;
constexpr int CT_CB = 160;
#define CB_FIRST 11
constexpr int CT_N = 192;
__device__ unsigned int g_ctr[CT_N];
__device__ float g_gate[SEQ];
constexpr int PART_A15 = 58 * 4096, PART_TAIL = 74 * 4096, PART_N = 90 * 4096;
__device__ uint4 g_part[PART_N];
__device__ uint2 g_xbuf[2 * 8 * 8 * 128];

#define FA_GRID 68

#define P2_MARK 0
#define TS_MARK(id, tid)
#define TS_MARK2(id, tid)
#define TS_BEGIN(id)
#define TS_END(id)
#define TS_BEGIN_T(id, tid)
#define TS_END_T(id, tid)
__device__ __forceinline__ void pdl_launch_dependents() { asm volatile("griddepcontrol.launch_dependents;" ::: "memory"); }
__device__ __forceinline__ void wait_ctr(int idx, unsigned int n) {
    unsigned int v; int it = 0;
    do { asm volatile("ld.acquire.gpu.global.u32 %0, [%1];" : "=r"(v) : "l"(&g_ctr[idx]) : "memory"); } while (v < n && ++it < (1 << 22));
}
__device__ __forceinline__ void signal_ctr(int idx) {
    asm volatile("fence.proxy.async.global;" ::: "memory");
    asm volatile("red.release.gpu.global.add.u32 [%0], 1;" :: "l"(&g_ctr[idx]) : "memory");
}
__device__ __forceinline__ void signal_ctr_generic(int idx) {
    asm volatile("red.release.gpu.global.add.u32 [%0], 1;" :: "l"(&g_ctr[idx]) : "memory");
}
__device__ __forceinline__ void finish_launch(int lane) {
    unsigned int tk = 0;
    if (lane == 0) tk = atomicAdd(&g_ctr[CT_FIN], 1u);
    tk = __shfl_sync(0xffffffff, tk, 0);
    if (tk == 64 + 68 - 1)
#pragma unroll 1
        for (int i = lane; i < CT_N; i += 32) g_ctr[i] = 0u;
}
__device__ __forceinline__ uint4 quad_transpose(uint32_t p0, uint32_t p1, uint32_t p2, uint32_t p3, int lane) {
    const bool o1 = lane & 1, o2 = lane & 2;
    uint32_t s0 = o1 ? p0 : p1, s1 = o1 ? p2 : p3;
    s0 = __shfl_xor_sync(0xffffffff, s0, 1); s1 = __shfl_xor_sync(0xffffffff, s1, 1);
    const uint32_t a_lo = o1 ? s0 : p0, a_hi = o1 ? p1 : s0, b_lo = o1 ? s1 : p2, b_hi = o1 ? p3 : s1;
    uint32_t t0 = o2 ? a_lo : b_lo, t1 = o2 ? a_hi : b_hi;
    t0 = __shfl_xor_sync(0xffffffff, t0, 2); t1 = __shfl_xor_sync(0xffffffff, t1, 2);
    return o2 ? make_uint4(t0, t1, b_lo, b_hi) : make_uint4(a_lo, a_hi, t0, t1);
}
__device__ __forceinline__ uint32_t smem_u32(const void* p) {
    return (uint32_t)__cvta_generic_to_shared(p);
}
__device__ __forceinline__ void mbar_init(uint32_t bar, uint32_t count) {
    asm volatile("mbarrier.init.shared::cta.b64 [%0], %1;" :: "r"(bar), "r"(count));
}
__device__ __forceinline__ void mbar_expect_tx(uint32_t bar, uint32_t bytes) {
    asm volatile("mbarrier.arrive.expect_tx.shared::cta.b64 _, [%0], %1;" :: "r"(bar), "r"(bytes) : "memory");
}
__device__ __forceinline__ void mbar_arrive(uint32_t bar) {
    asm volatile("mbarrier.arrive.shared::cta.b64 _, [%0];" :: "r"(bar) : "memory");
}
__device__ __forceinline__ void mbar_wait(uint32_t bar, uint32_t parity) {
    asm volatile(
        "{\n"
        ".reg .pred p, q;\n"
        ".reg .u32 c;\n"
        "mov.u32 c, 0;\n"
        "WAIT_LOOP:\n"
        "mbarrier.try_wait.parity.shared::cta.b64 p, [%0], %1;\n"
        "@p bra WAIT_DONE;\n"
        "add.u32 c, c, 1;\n"
        "setp.lt.u32 q, c, 4000000;\n"
        "@q bra WAIT_LOOP;\n"
        "WAIT_DONE:\n"
        "}\n" :: "r"(bar), "r"(parity) : "memory");
}
__device__ __forceinline__ void tma_load_2d(uint32_t dst, const CUtensorMap* map, uint32_t bar, int c0, int c1) {
    asm volatile(
        "cp.async.bulk.tensor.2d.shared::cluster.global.mbarrier::complete_tx::bytes [%0], [%1, {%3, %4}], [%2];"
        :: "r"(dst), "l"((uint64_t)map), "r"(bar), "r"(c0), "r"(c1) : "memory");
}
__device__ __forceinline__ void wgmma_fence() { asm volatile("wgmma.fence.sync.aligned;" ::: "memory"); }
__device__ __forceinline__ void wgmma_commit() { asm volatile("wgmma.commit_group.sync.aligned;" ::: "memory"); }
template <int N> __device__ __forceinline__ void wgmma_wait() {
    asm volatile("wgmma.wait_group.sync.aligned %0;" :: "n"(N) : "memory");
}
__device__ __forceinline__ uint64_t make_desc(uint32_t addr, uint32_t lbo, uint32_t sbo) {
    uint64_t d = 0;
    d |= (uint64_t)((addr & 0x3FFFF) >> 4);
    d |= (uint64_t)((lbo >> 4) & 0x3FFF) << 16;
    d |= (uint64_t)((sbo >> 4) & 0x3FFF) << 32;
    d |= (uint64_t)1 << 62;
    return d;
}

#define ACC64(d) \
    "+f"(d[0]), "+f"(d[1]), "+f"(d[2]), "+f"(d[3]), "+f"(d[4]), "+f"(d[5]), "+f"(d[6]), "+f"(d[7]), \
    "+f"(d[8]), "+f"(d[9]), "+f"(d[10]), "+f"(d[11]), "+f"(d[12]), "+f"(d[13]), "+f"(d[14]), "+f"(d[15]), \
    "+f"(d[16]), "+f"(d[17]), "+f"(d[18]), "+f"(d[19]), "+f"(d[20]), "+f"(d[21]), "+f"(d[22]), "+f"(d[23]), \
    "+f"(d[24]), "+f"(d[25]), "+f"(d[26]), "+f"(d[27]), "+f"(d[28]), "+f"(d[29]), "+f"(d[30]), "+f"(d[31]), \
    "+f"(d[32]), "+f"(d[33]), "+f"(d[34]), "+f"(d[35]), "+f"(d[36]), "+f"(d[37]), "+f"(d[38]), "+f"(d[39]), \
    "+f"(d[40]), "+f"(d[41]), "+f"(d[42]), "+f"(d[43]), "+f"(d[44]), "+f"(d[45]), "+f"(d[46]), "+f"(d[47]), \
    "+f"(d[48]), "+f"(d[49]), "+f"(d[50]), "+f"(d[51]), "+f"(d[52]), "+f"(d[53]), "+f"(d[54]), "+f"(d[55]), \
    "+f"(d[56]), "+f"(d[57]), "+f"(d[58]), "+f"(d[59]), "+f"(d[60]), "+f"(d[61]), "+f"(d[62]), "+f"(d[63])
#define ACC64_STR \
    "{%0, %1, %2, %3, %4, %5, %6, %7, %8, %9, %10, %11, %12, %13, %14, %15, " \
    "%16, %17, %18, %19, %20, %21, %22, %23, %24, %25, %26, %27, %28, %29, %30, %31, " \
    "%32, %33, %34, %35, %36, %37, %38, %39, %40, %41, %42, %43, %44, %45, %46, %47, " \
    "%48, %49, %50, %51, %52, %53, %54, %55, %56, %57, %58, %59, %60, %61, %62, %63}"

template <int TB>
__device__ __forceinline__ void wgmma_ss_n128(float (&d)[64], uint64_t da, uint64_t db, int scale_d) {
    asm volatile(
        "{\n.reg .pred p;\nsetp.ne.b32 p, %66, 0;\n"
        "wgmma.mma_async.sync.aligned.m64n128k16.f32.bf16.bf16 " ACC64_STR ", %64, %65, p, 1, 1, 0, %67;\n}\n"
        : ACC64(d) : "l"(da), "l"(db), "r"(scale_d), "n"(TB));
}
__device__ __forceinline__ uint32_t desc_lo(uint32_t addr, uint32_t lbo) { return ((addr & 0x3FFFF) >> 4) | ((lbo >> 4) << 16); }
template <int TB>
__device__ __forceinline__ void wgmma_ss_n128_lo(float (&d)[64], uint32_t da_lo, uint32_t db_lo, int scale_d) {
    asm volatile(
        "{\n.reg .pred p;\n.reg .b64 da, db;\nsetp.ne.b32 p, %66, 0;\n"
        "mov.b64 da, {%64, 0x40000040};\nmov.b64 db, {%65, 0x40000040};\n"
        "wgmma.mma_async.sync.aligned.m64n128k16.f32.bf16.bf16 " ACC64_STR ", da, db, p, 1, 1, 0, %67;\n}\n"
        : ACC64(d) : "r"(da_lo), "r"(db_lo), "r"(scale_d), "n"(TB));
}
__device__ __forceinline__ void wgmma_rs_n128_tb(float (&d)[64], uint32_t a0, uint32_t a1, uint32_t a2, uint32_t a3,
                                                 uint64_t db, int scale_d) {
    asm volatile(
        "{\n.reg .pred p;\nsetp.ne.b32 p, %69, 0;\n"
        "wgmma.mma_async.sync.aligned.m64n128k16.f32.bf16.bf16 " ACC64_STR ", {%64, %65, %66, %67}, %68, p, 1, 1, 1;\n}\n"
        : ACC64(d) : "r"(a0), "r"(a1), "r"(a2), "r"(a3), "l"(db), "r"(scale_d));
}
__device__ __forceinline__ void wgmma_rs_n80(float (&d)[40], const uint32_t (&a)[4], uint32_t db_lo, int scale_d) {
    asm volatile(
        "{\n.reg .pred p;\n.reg .b64 db;\nsetp.ne.b32 p, %45, 0;\nmov.b64 db, {%44, 0x40000040};\n"
        "wgmma.mma_async.sync.aligned.m64n80k16.f32.bf16.bf16 "
        "{%0, %1, %2, %3, %4, %5, %6, %7, %8, %9, %10, %11, %12, %13, %14, %15, %16, %17, %18, %19, %20, %21, %22, %23, %24, %25, %26, %27, %28, %29, %30, %31, %32, %33, %34, %35, %36, %37, %38, %39}, "
        "{%40, %41, %42, %43}, db, p, 1, 1, 0;\n}\n"
        : "+f"(d[0]), "+f"(d[1]), "+f"(d[2]), "+f"(d[3]), "+f"(d[4]), "+f"(d[5]), "+f"(d[6]), "+f"(d[7]), "+f"(d[8]), "+f"(d[9]), "+f"(d[10]), "+f"(d[11]), "+f"(d[12]), "+f"(d[13]), "+f"(d[14]), "+f"(d[15]), "+f"(d[16]), "+f"(d[17]), "+f"(d[18]), "+f"(d[19]), "+f"(d[20]), "+f"(d[21]), "+f"(d[22]), "+f"(d[23]), "+f"(d[24]), "+f"(d[25]), "+f"(d[26]), "+f"(d[27]), "+f"(d[28]), "+f"(d[29]), "+f"(d[30]), "+f"(d[31]), "+f"(d[32]), "+f"(d[33]), "+f"(d[34]), "+f"(d[35]), "+f"(d[36]), "+f"(d[37]), "+f"(d[38]), "+f"(d[39])
        : "r"(a[0]), "r"(a[1]), "r"(a[2]), "r"(a[3]), "r"(db_lo), "r"(scale_d));
}
__device__ __forceinline__ void wgmma_ss_n256_tb(float (&d)[128], uint64_t da, uint64_t db, int scale_d) {
    asm volatile(
        "{\n.reg .pred p;\nsetp.ne.b32 p, %130, 0;\n"
        "wgmma.mma_async.sync.aligned.m64n256k16.f32.bf16.bf16 {%0, %1, %2, %3, %4, %5, %6, %7, %8, %9, %10, %11, %12, %13, %14, %15, %16, %17, %18, %19, %20, %21, %22, %23, %24, %25, %26, %27, %28, %29, %30, %31, %32, %33, %34, %35, %36, %37, %38, %39, %40, %41, %42, %43, %44, %45, %46, %47, %48, %49, %50, %51, %52, %53, %54, %55, %56, %57, %58, %59, %60, %61, %62, %63, %64, %65, %66, %67, %68, %69, %70, %71, %72, %73, %74, %75, %76, %77, %78, %79, %80, %81, %82, %83, %84, %85, %86, %87, %88, %89, %90, %91, %92, %93, %94, %95, %96, %97, %98, %99, %100, %101, %102, %103, %104, %105, %106, %107, %108, %109, %110, %111, %112, %113, %114, %115, %116, %117, %118, %119, %120, %121, %122, %123, %124, %125, %126, %127}, %128, %129, p, 1, 1, 0, 1;\n}\n"
        : "+f"(d[0]), "+f"(d[1]), "+f"(d[2]), "+f"(d[3]), "+f"(d[4]), "+f"(d[5]), "+f"(d[6]), "+f"(d[7]), "+f"(d[8]), "+f"(d[9]), "+f"(d[10]), "+f"(d[11]), "+f"(d[12]), "+f"(d[13]), "+f"(d[14]), "+f"(d[15]), "+f"(d[16]), "+f"(d[17]), "+f"(d[18]), "+f"(d[19]), "+f"(d[20]), "+f"(d[21]), "+f"(d[22]), "+f"(d[23]), "+f"(d[24]), "+f"(d[25]), "+f"(d[26]), "+f"(d[27]), "+f"(d[28]), "+f"(d[29]), "+f"(d[30]), "+f"(d[31]), "+f"(d[32]), "+f"(d[33]), "+f"(d[34]), "+f"(d[35]), "+f"(d[36]), "+f"(d[37]), "+f"(d[38]), "+f"(d[39]), "+f"(d[40]), "+f"(d[41]), "+f"(d[42]), "+f"(d[43]), "+f"(d[44]), "+f"(d[45]), "+f"(d[46]), "+f"(d[47]), "+f"(d[48]), "+f"(d[49]), "+f"(d[50]), "+f"(d[51]), "+f"(d[52]), "+f"(d[53]), "+f"(d[54]), "+f"(d[55]), "+f"(d[56]), "+f"(d[57]), "+f"(d[58]), "+f"(d[59]), "+f"(d[60]), "+f"(d[61]), "+f"(d[62]), "+f"(d[63]), "+f"(d[64]), "+f"(d[65]), "+f"(d[66]), "+f"(d[67]), "+f"(d[68]), "+f"(d[69]), "+f"(d[70]), "+f"(d[71]), "+f"(d[72]), "+f"(d[73]), "+f"(d[74]), "+f"(d[75]), "+f"(d[76]), "+f"(d[77]), "+f"(d[78]), "+f"(d[79]), "+f"(d[80]), "+f"(d[81]), "+f"(d[82]), "+f"(d[83]), "+f"(d[84]), "+f"(d[85]), "+f"(d[86]), "+f"(d[87]), "+f"(d[88]), "+f"(d[89]), "+f"(d[90]), "+f"(d[91]), "+f"(d[92]), "+f"(d[93]), "+f"(d[94]), "+f"(d[95]), "+f"(d[96]), "+f"(d[97]), "+f"(d[98]), "+f"(d[99]), "+f"(d[100]), "+f"(d[101]), "+f"(d[102]), "+f"(d[103]), "+f"(d[104]), "+f"(d[105]), "+f"(d[106]), "+f"(d[107]), "+f"(d[108]), "+f"(d[109]), "+f"(d[110]), "+f"(d[111]), "+f"(d[112]), "+f"(d[113]), "+f"(d[114]), "+f"(d[115]), "+f"(d[116]), "+f"(d[117]), "+f"(d[118]), "+f"(d[119]), "+f"(d[120]), "+f"(d[121]), "+f"(d[122]), "+f"(d[123]), "+f"(d[124]), "+f"(d[125]), "+f"(d[126]), "+f"(d[127])
        : "l"(da), "l"(db), "r"(scale_d));
}
__device__ __forceinline__ void stmatrix_x4(uint32_t addr, uint32_t r0, uint32_t r1, uint32_t r2, uint32_t r3) {
    asm volatile("stmatrix.sync.aligned.m8n8.x4.shared.b16 [%0], {%1, %2, %3, %4};" :: "r"(addr), "r"(r0), "r"(r1), "r"(r2), "r"(r3) : "memory");
}
__device__ __forceinline__ void tma_store_2d(const CUtensorMap* map, uint32_t src, int c0, int c1) {
    asm volatile("cp.async.bulk.tensor.2d.global.shared::cta.bulk_group [%0, {%2, %3}], [%1];"
                 :: "l"((uint64_t)map), "r"(src), "r"(c0), "r"(c1) : "memory");
}
__device__ __forceinline__ float ex2f(float x) { float y; asm("ex2.approx.ftz.f32 %0, %1;" : "=f"(y) : "f"(x)); return y; }
__device__ __forceinline__ uint32_t pack_bf16(float lo, float hi) {
    __nv_bfloat162 v = __floats2bfloat162_rn(lo, hi);
    return *reinterpret_cast<uint32_t*>(&v);
}
__device__ __forceinline__ float bf16r(float x) { return __uint_as_float(pack_bf16(0.f, x) & 0xffff0000u); }
__device__ __forceinline__ void mma_16816(float (&c)[4], uint32_t a0, uint32_t a1, uint32_t a2, uint32_t a3,
                                          uint32_t b0, uint32_t b1) {
    asm volatile(
        "mma.sync.aligned.m16n8k16.row.col.f32.bf16.bf16.f32 {%0,%1,%2,%3}, {%4,%5,%6,%7}, {%8,%9}, {%0,%1,%2,%3};"
        : "+f"(c[0]), "+f"(c[1]), "+f"(c[2]), "+f"(c[3])
        : "r"(a0), "r"(a1), "r"(a2), "r"(a3), "r"(b0), "r"(b1));
}
__device__ __forceinline__ void ldmatrix_x4_trans(uint32_t& r0, uint32_t& r1, uint32_t& r2, uint32_t& r3, uint32_t addr) {
    asm volatile("ldmatrix.sync.aligned.m8n8.x4.trans.shared.b16 {%0,%1,%2,%3}, [%4];"
                 : "=r"(r0), "=r"(r1), "=r"(r2), "=r"(r3) : "r"(addr));
}

struct AttnParams {
    CUtensorMap mapQ, mapK, mapV;
    CUtensorMap mapO;
    const bf16 *x, *gate_w;
};
constexpr uint32_t FA_Q = 0, FA_KV = 65536, FA_O = 196608, FA_BAR = 229376;
constexpr int FA_SMEM = FA_BAR + 256;
constexpr int FA_ITEMS = 16 * NH;
__device__ __forceinline__ int fa_qt(int t) { return 15 - ((t & 127) >> 3); }
__device__ __forceinline__ int fa_head(int t) { return (t >> 7) * 8 + (t & 7); }
__device__ __forceinline__ uint32_t mbar_test(uint32_t bar, uint32_t parity) {
    uint32_t done;
    asm volatile(
        "{\n.reg .pred p;\n"
        "mbarrier.test_wait.parity.shared::cta.b64 p, [%1], %2;\n"
        "selp.u32 %0, 1, 0, p;\n}\n" : "=r"(done) : "r"(bar), "r"(parity) : "memory");
    return done;
}
__device__ __forceinline__ void mbar_arrive_if(uint32_t bar, bool c) {
    asm volatile("{\n.reg .pred p;\nsetp.ne.u32 p, %1, 0;\n@p mbarrier.arrive.shared::cta.b64 _, [%0];\n}" :: "r"(bar), "r"((uint32_t)c) : "memory");
}
__device__ __forceinline__ void wgmma_rs_n128_tb_lo(float (&d)[64], const uint32_t* a, uint32_t db_lo, int scale_d) {
    asm volatile(
        "{\n.reg .pred p;\n.reg .b64 db;\nsetp.ne.b32 p, %69, 0;\nmov.b64 db, {%68, 0x40000040};\n"
        "wgmma.mma_async.sync.aligned.m64n128k16.f32.bf16.bf16 " ACC64_STR ", {%64, %65, %66, %67}, db, p, 1, 1, 1;\n}\n"
        : ACC64(d) : "r"(a[0]), "r"(a[1]), "r"(a[2]), "r"(a[3]), "r"(db_lo), "r"(scale_d));
}
#define FA_TEST 48
#define FA_PIN 32

__device__ __forceinline__ void wgmma_ss_n64_lo(float (&d)[64], uint32_t da_lo, uint32_t db_lo, int scale_d) {
    asm volatile(
        "{\n.reg .pred p;\n.reg .b64 da, db;\nsetp.ne.b32 p, %34, 0;\n"
        "mov.b64 da, {%32, 0x40000040};\nmov.b64 db, {%33, 0x40000040};\n"
        "wgmma.mma_async.sync.aligned.m64n64k16.f32.bf16.bf16 {%0, %1, %2, %3, %4, %5, %6, %7, %8, %9, %10, %11, %12, %13, %14, %15, "
        "%16, %17, %18, %19, %20, %21, %22, %23, %24, %25, %26, %27, %28, %29, %30, %31}, da, db, p, 1, 1, 0, 0;\n}\n"
        : "+f"(d[0]), "+f"(d[1]), "+f"(d[2]), "+f"(d[3]), "+f"(d[4]), "+f"(d[5]), "+f"(d[6]), "+f"(d[7]), "+f"(d[8]), "+f"(d[9]), "+f"(d[10]),
          "+f"(d[11]), "+f"(d[12]), "+f"(d[13]), "+f"(d[14]), "+f"(d[15]), "+f"(d[16]), "+f"(d[17]), "+f"(d[18]), "+f"(d[19]), "+f"(d[20]),
          "+f"(d[21]), "+f"(d[22]), "+f"(d[23]), "+f"(d[24]), "+f"(d[25]), "+f"(d[26]), "+f"(d[27]), "+f"(d[28]), "+f"(d[29]), "+f"(d[30]), "+f"(d[31])
        : "r"(da_lo), "r"(db_lo), "r"(scale_d));
}
#define FA_CLR 0
#define FA_NOFB 0
#define FA_DPIN 16
#define FA_RLO 40
#define FA_RHI 232
#define FA_LIM 0x1p40f
__device__ __forceinline__ void attn_consumer(const uint32_t sb, const int wg, const int w4, const int lane) {
    const uint32_t bar_q = sb + FA_BAR, bar_of = bar_q + 96, bar_oe = bar_q + 112, oslot = bar_q + 144;
    const bool lane0 = lane == 0;
    float o[64], sacc[64];
    uint32_t pa[32];
    float ms0 = 0.f, ms1 = 0.f, lrow0 = 1.f, lrow1 = 1.f;
    const float sc = 0.08838834764831845f * 1.4426950408889634f;
    const uint32_t q_lo = desc_lo(sb + FA_Q + wg * 8192, 16), k_lo = desc_lo(sb + FA_KV, 16), v_lo = desc_lo(sb + FA_KV + 32768, 16384);
    uint32_t qd = q_lo + 2048, kd = k_lo + 4096, vd = v_lo, bs = bar_q + 8, bi = bar_q + 8;
    auto issue_qk = [&](uint32_t a, bool half) {
        const uint32_t b = kd;
#pragma unroll
        for (int kk = 0; kk < 8; kk++) {
            if (half) wgmma_ss_n64_lo(sacc, a + (kk >> 2) * 1024 + (kk & 3) * 2, b + (kk >> 2) * 1024 + (kk & 3) * 2, kk != 0);
            else wgmma_ss_n128_lo<0>(sacc, a + (kk >> 2) * 1024 + (kk & 3) * 2, b + (kk >> 2) * 1024 + (kk & 3) * 2, kk != 0);
        }
        wgmma_commit();
    };
    auto issue_pv = [&](bool acc) {
        const uint32_t b = vd;
#pragma unroll
        for (int kk = 0; kk < 8; kk++) wgmma_rs_n128_tb_lo(o, &pa[kk * 4], b + kk * 128, kk != 0 || acc);
        wgmma_commit();
    };
    auto turn_wait = [&]() { asm volatile("bar.sync %0, 256;" :: "r"(1 + wg) : "memory"); };
    auto turn_pass = [&]() { asm volatile("bar.arrive %0, 256;" :: "r"(2 - wg) : "memory"); };
    int item = -1, it = -1, j = 0, nkv = 1, t = 0;
    auto redo = [&](float& l0, float& l1) {
        const size_t row0 = (size_t)fa_head(t) * SEQ + (lane >> 2);
        const uint32_t* qg = reinterpret_cast<const uint32_t*>(g_QA + (row0 + (nkv - 1) * 128 + wg * 64 + w4 * 16) * HD) + (lane & 3);
        const uint32_t* kg = reinterpret_cast<const uint32_t*>(g_KA + (row0 + (nkv - 1 - j) * 128) * HD) + (lane & 3);
        auto ldg = [](const uint32_t* p) { uint32_t v; asm volatile("ld.relaxed.gpu.global.u32 %0, [%1];" : "=r"(v) : "l"(p) : "memory"); return v; };
        const int r0 = j ? 1 << 20 : wg * 64 + w4 * 16 + (lane >> 2) - (lane & 3) * 2;
        float mx0 = -INFINITY, mx1 = -INFINITY;
        const float m0 = ms0, m1 = ms1;
        uint4 tmp[8];
        l0 = 0.f; l1 = 0.f;
#pragma unroll 1
        for (int ps = 0; ps < 32; ps++) {
            const int nb = ps & 15;
            float c[4] = {0.f, 0.f, 0.f, 0.f};
#pragma unroll 1
            for (int kk = 0; kk < 64; kk += 8)
                mma_16816(c, ldg(qg + kk), ldg(qg + kk + 8 * 64), ldg(qg + kk + 4), ldg(qg + kk + 8 * 64 + 4), ldg(kg + nb * 8 * 64 + kk), ldg(kg + nb * 8 * 64 + kk + 4));
#pragma unroll
            for (int i = 0; i < 4; i++)
                if (nb * 8 + (i & 1) - ((i & 2) ? 8 : 0) > r0) c[i] = -INFINITY;
            mx0 = fmaxf(mx0, fmaxf(c[0], c[1])); mx1 = fmaxf(mx1, fmaxf(c[2], c[3]));
#pragma unroll
            for (int i = 0; i < 4; i++) c[i] = ex2f(fmaf(c[i], sc, (i & 2) ? ms1 : ms0));
            l0 += c[0] + c[1]; l1 += c[2] + c[3];
            reinterpret_cast<uint2*>(tmp)[nb] = make_uint2(pack_bf16(c[0], c[1]), pack_bf16(c[2], c[3]));
            if (ps == 15) {
                mx0 = fmaxf(mx0, __shfl_xor_sync(0xffffffff, mx0, 1)); mx1 = fmaxf(mx1, __shfl_xor_sync(0xffffffff, mx1, 1));
                mx0 = fmaxf(mx0, __shfl_xor_sync(0xffffffff, mx0, 2)); mx1 = fmaxf(mx1, __shfl_xor_sync(0xffffffff, mx1, 2));
                ms0 = fminf(-mx0 * sc, ms0); ms1 = fminf(-mx1 * sc, ms1);
                l0 = 0.f; l1 = 0.f;
            }
        }
        const float a0 = ex2f(ms0 - m0), a1 = ex2f(ms1 - m1);
        lrow0 *= a0; lrow1 *= a1;
#pragma unroll
        for (int i = 0; i < 64; i++) o[i] *= (i & 2) ? a1 : a0;
#pragma unroll
        for (int i = 0; i < 8; i++) { pa[4 * i] = tmp[i].x; pa[4 * i + 1] = tmp[i].y; pa[4 * i + 2] = tmp[i].z; pa[4 * i + 3] = tmp[i].w; }
    };
    auto pin_after = [&](float v) {
        asm volatile("{\n.reg .pred p;\nsetp.eq.f32 p, %1, %2;\n@p st.shared.f32 [%0], %1;\n}" :: "r"(oslot + 16), "f"(v), "f"(ms0) : "memory");
    };
    uint32_t ok = 0, okq = 0;
    int tn = 0;
    auto tests = [&]() {
        ok = mbar_test(bs + 48, (it >> 1) & 1);
        asm volatile("ld.shared.s32 %0, [%1];" : "=r"(tn) : "r"((bi ^ 8) + 128) : "memory");
        ok &= mbar_test((bs ^ 8) + 32, ((it + 1) >> 1) & 1);
        okq = mbar_test(bi ^ 8, ((item + 1) >> 1) & 1);
    };
    auto epilogue = [&](int tag, bool real) {
        float l0 = lrow0, l1 = lrow1;
        l0 += __shfl_xor_sync(0xffffffff, l0, 1); l1 += __shfl_xor_sync(0xffffffff, l1, 1);
        l0 += __shfl_xor_sync(0xffffffff, l0, 2); l1 += __shfl_xor_sync(0xffffffff, l1, 2);
        float i0, i1;
        asm("rcp.approx.ftz.f32 %0, %1;" : "=f"(i0) : "f"(l0));
        asm("rcp.approx.ftz.f32 %0, %1;" : "=f"(i1) : "f"(l1));
        const int row = w4 * 16 + (lane >> 2);
        const uint32_t stg = sb + FA_O + wg * 16384 + row * 128;
#pragma unroll
        for (int i = 0; i < 4; i++) {
            const int ch = i * 4 + (lane & 3);
            const uint32_t a = stg + (ch >> 3) * 8192 + (((ch & 7) ^ (row & 7)) << 4);
            const float* q = &o[i * 16];
            asm volatile("st.shared.v4.b32 [%0], {%1, %2, %3, %4};" :: "r"(a), "r"(pack_bf16(q[0] * i0, q[1] * i0)), "r"(pack_bf16(q[4] * i0, q[5] * i0)),
                         "r"(pack_bf16(q[8] * i0, q[9] * i0)), "r"(pack_bf16(q[12] * i0, q[13] * i0)) : "memory");
            asm volatile("st.shared.v4.b32 [%0], {%1, %2, %3, %4};" :: "r"(a + 1024), "r"(pack_bf16(q[2] * i1, q[3] * i1)), "r"(pack_bf16(q[6] * i1, q[7] * i1)),
                         "r"(pack_bf16(q[10] * i1, q[11] * i1)), "r"(pack_bf16(q[14] * i1, q[15] * i1)) : "memory");
        }
        asm volatile("st.shared.s32 [%0], %1;" :: "r"(oslot + wg * 4), "r"(tag) : "memory");
        __syncwarp();
        mbar_arrive_if(bar_of + 8 * wg, lane0 && real);
    };
    auto transition = [&](auto wgc, float& l0, float& l1) {
        constexpr int WG = decltype(wgc)::value;
        constexpr int NE = WG == 0 ? 32 : 64;
        turn_wait();
        wgmma_fence();
        issue_qk(qd, WG == 0);
        issue_pv(nkv > 1);
        turn_pass();
        const int tc = t;
        t = __shfl_sync(0xffffffff, tn, 0);
        nkv = fa_qt(t) + 1;
        mbar_wait(bar_oe + 8 * wg, (max(item, 0) & 1) ^ 1);
        item++; bi ^= 8;
        wgmma_wait<1>();
        mbar_arrive_if(bs + 64, lane0);
        mbar_arrive_if(bi + 16, lane0 && nkv == 1);
        ms0 = -sc * __shfl_sync(0xffffffff, sacc[0], lane & 28); ms1 = -sc * __shfl_sync(0xffffffff, sacc[2], lane & 28);
        const int r0 = w4 * 16 + (lane >> 2) - (lane & 3) * 2;
#pragma unroll
        for (int i = 0; i < 32; i++)
            if ((i >> 2) * 8 + (i & 1) - ((i & 2) ? 8 : 0) > r0) sacc[WG * 32 + i] = -INFINITY;
        float sum[4];
#pragma unroll
        for (int i = 0; i < FA_DPIN; i++) { sacc[i] = ex2f(fmaf(sacc[i], sc, (i & 2) ? ms1 : ms0)); sum[i & 3] = i < 4 ? sacc[i] : sum[i & 3] + sacc[i]; }
        pin_after((sum[0] + sum[1]) + (sum[2] + sum[3]));
        wgmma_wait<0>();
        mbar_arrive_if((bs ^ 8) + 80, lane0 && item > 0);
        epilogue(tc, item > 0);
#pragma unroll
        for (int i = 0; i < NE; i++) {
            if (i >= FA_DPIN) { sacc[i] = ex2f(fmaf(sacc[i], sc, (i & 2) ? ms1 : ms0)); sum[i & 3] += sacc[i]; }
            if (i & 1) pa[i >> 1] = pack_bf16(sacc[i - 1], sacc[i]);
            if (i == NE - 16) { pin_after(sum[0]); tests(); }
        }
        if (NE == 32)
#pragma unroll
            for (int i = 16; i < 32; i++) asm volatile("mov.u32 %0, 0;" : "=r"(pa[i]));
        l0 = sum[0] + sum[1]; l1 = sum[2] + sum[3];
    };
#pragma unroll
    for (int i = 0; i < 32; i++) pa[i] = 0u;
    if (wg == 1) asm volatile("bar.arrive 1, 256;" ::: "memory");
#pragma unroll 1
    for (;;) {
        float l0, l1;
        it++;
        kd = 2 * k_lo + 4096 - kd; vd = 2 * v_lo + 4096 - vd; bs ^= 8;
        if (++j < nkv) {
            if (__builtin_expect(!ok, 0)) {
                mbar_wait(bs + 32, (it >> 1) & 1);
                mbar_wait((bs ^ 8) + 48, ((it - 1) >> 1) & 1);
            }
            turn_wait();
            wgmma_fence();
            issue_qk(qd, false);
            issue_pv(j > 1);
            turn_pass();
            wgmma_wait<1>();
            mbar_arrive_if(bs + 64, lane0);
            mbar_arrive_if(bi + 16, lane0 && j == nkv - 1);
            float sum[4];
#pragma unroll
            for (int i = 0; i < FA_PIN; i++) { sacc[i] = ex2f(fmaf(sacc[i], sc, (i & 2) ? ms1 : ms0)); sum[i & 3] = i < 4 ? sacc[i] : sum[i & 3] + sacc[i]; }
            pin_after((sum[0] + sum[1]) + (sum[2] + sum[3]));
            wgmma_wait<0>();
            mbar_arrive_if((bs ^ 8) + 80, lane0);
#pragma unroll
            for (int i = 0; i < 64; i++) {
                if (i >= FA_PIN) { sacc[i] = ex2f(fmaf(sacc[i], sc, (i & 2) ? ms1 : ms0)); sum[i & 3] = i < 4 ? sacc[i] : sum[i & 3] + sacc[i]; }
                if (i & 1) pa[i >> 1] = pack_bf16(sacc[i - 1], sacc[i]);
                if (i == FA_TEST) { pin_after(sum[0]); tests(); }
            }
            l0 = sum[0] + sum[1]; l1 = sum[2] + sum[3];
        } else {
            if (__builtin_expect(!(ok & okq), 0)) {
                mbar_wait(bi ^ 8, ((item + 1) >> 1) & 1);
                asm volatile("ld.shared.s32 %0, [%1];" : "=r"(tn) : "r"((bi ^ 8) + 128) : "memory");
                mbar_wait((bs ^ 8) + 48, ((it - 1) >> 1) & 1);
                if (tn < 0) break;
                mbar_wait(bs + 32, (it >> 1) & 1);
            }
            qd = 2 * q_lo + 2048 - qd;
            if (wg == 0) transition(std::integral_constant<int, 0>(), l0, l1); else transition(std::integral_constant<int, 1>(), l0, l1);
            j = 0;
            lrow0 = 0.f; lrow1 = 0.f;
        }
        if (!FA_NOFB && __builtin_expect(__any_sync(0xffffffff, !(l0 + l1 < FA_LIM)), 0)) redo(l0, l1);
        lrow0 += l0; lrow1 += l1;
    }
    wgmma_fence();
    issue_pv(nkv > 1);
    mbar_wait(bar_oe + 8 * wg, (item & 1) ^ 1);
    wgmma_wait<0>();
    epilogue(t | 0x80000000, true);
}

__global__ void __launch_bounds__(384, 1) attn_kernel(const __grid_constant__ AttnParams P) {
    extern __shared__ __align__(1024) uint8_t smem_attn[];
    const uint32_t sb = smem_u32(smem_attn);
    const uint32_t bar_q = sb + FA_BAR, bar_qe = bar_q + 16, bar_kf = bar_q + 32, bar_vf = bar_q + 48, bar_ke = bar_q + 64, bar_ve = bar_q + 80,
                   bar_of = bar_q + 96, bar_oe = bar_q + 112, slot = bar_q + 128, oslot = bar_q + 144;
    const int warp = __shfl_sync(0xffffffff, threadIdx.x >> 5, 0);
    const int lane = threadIdx.x & 31;
    if (threadIdx.x == 0) {
        for (int i = 0; i < 2; i++) {
            mbar_init(bar_q + 8 * i, 1); mbar_init(bar_qe + 8 * i, 8); mbar_init(bar_kf + 8 * i, 1); mbar_init(bar_vf + 8 * i, 1);
            mbar_init(bar_ke + 8 * i, 8); mbar_init(bar_ve + 8 * i, 8); mbar_init(bar_of + 8 * i, 4); mbar_init(bar_oe + 8 * i, 1);
        }
        asm volatile("fence.mbarrier_init.release.cluster;" ::: "memory");
    }
    if (threadIdx.x == 256) wait_ctr(CT_AP + (fa_head(blockIdx.x) >> 1), 96u);
    __syncthreads();
    pdl_launch_dependents();
    if (warp >= 8) {
        asm volatile("setmaxnreg.dec.sync.aligned.u32 %0;" :: "n"(FA_RLO));
        if (warp == 11) {
            const uint4 gv0 = __ldg(reinterpret_cast<const uint4*>(P.gate_w) + lane), gv1 = __ldg(reinterpret_cast<const uint4*>(P.gate_w) + 32 + lane);
            const uint32_t gw[8] = {gv0.x, gv0.y, gv0.z, gv0.w, gv1.x, gv1.y, gv1.z, gv1.w};
#pragma unroll 1
            for (int r = blockIdx.x; r < SEQ; r += gridDim.x) {
                const uint4 x0 = __ldg(reinterpret_cast<const uint4*>(P.x + (size_t)r * DM) + lane), x1 = __ldg(reinterpret_cast<const uint4*>(P.x + (size_t)r * DM) + 32 + lane);
                const uint32_t xw[8] = {x0.x, x0.y, x0.z, x0.w, x1.x, x1.y, x1.z, x1.w};
                float sum = 0.f;
#pragma unroll
                for (int e = 0; e < 8; e++) {
                    const uint32_t pr = pack_bf16(__uint_as_float(xw[e] << 16) * __uint_as_float(gw[e] << 16), __uint_as_float(xw[e] & 0xffff0000u) * __uint_as_float(gw[e] & 0xffff0000u));
                    sum += __uint_as_float(pr << 16) + __uint_as_float(pr & 0xffff0000u);
                }
#pragma unroll
                for (int o = 16; o; o >>= 1) sum += __shfl_xor_sync(0xffffffff, sum, o);
                if (lane == 0) g_gate[r] = bf16r(__fdividef(1.f, 1.f + __expf(-bf16r(sum))));
            }
#pragma unroll 1
            for (int i = blockIdx.x * 32 + lane; i < FA_CLR; i += gridDim.x * 32) g_part[i] = make_uint4(~0u, ~0u, ~0u, ~0u);
            __syncwarp();
            if (lane == 0) signal_ctr_generic(CT_G);
        } else if (warp > 8) {
            if (lane == 0) {
                const int wg = warp - 9;
                const uint32_t stg = sb + FA_O + wg * 16384;
                TS_BEGIN_T(1, 320);
                for (int n = 0;; n++) {
                    mbar_wait(bar_of + 8 * wg, n & 1);
                    int t;
                    asm volatile("ld.shared.s32 %0, [%1];" : "=r"(t) : "r"(oslot + wg * 4) : "memory");
                    asm volatile("fence.proxy.async.shared::cta;" ::: "memory");
                    const bool last = t < 0;
                    t &= 0xffff;
                    const int qt = fa_qt(t), h = fa_head(t);
                    tma_store_2d(&P.mapO, stg, 0, h * SEQ + qt * 128 + wg * 64);
                    tma_store_2d(&P.mapO, stg + 8192, 64, h * SEQ + qt * 128 + wg * 64);
                    asm volatile("cp.async.bulk.commit_group;" ::: "memory");
                    asm volatile("cp.async.bulk.wait_group.read 0;" ::: "memory");
                    mbar_arrive(bar_oe + 8 * wg);
                    asm volatile("cp.async.bulk.wait_group 0;" ::: "memory");
                    signal_ctr(CT_CA + qt * 2 + (h >= O2_HE));
                    if (last) break;
                }
                TS_END_T(1, 320);
            }
        } else if (lane == 0) {
            int it = 0, t = blockIdx.x, hp_ready = 1 << (fa_head(t) >> 1);
            auto load_q = [&](int item, int t) {
                const uint32_t b = bar_q + 8 * (item & 1);
                asm volatile("st.shared.s32 [%0], %1;" :: "r"(slot + (item & 1) * 8), "r"(t) : "memory");
                if (t < 0) { mbar_arrive(b); return; }
                const int row = fa_head(t) * SEQ + fa_qt(t) * 128;
                mbar_expect_tx(b, 32768);
                tma_load_2d(sb + FA_Q + (item & 1) * 32768, &P.mapQ, b, 0, row);
                tma_load_2d(sb + FA_Q + (item & 1) * 32768 + 16384, &P.mapQ, b, 64, row);
            };
            auto load_v = [&](int it, int row) {
                const int s = it & 1;
                const uint32_t sv = sb + FA_KV + s * 65536 + 32768;
                mbar_wait(bar_ve + 8 * s, ((it >> 1) & 1) ^ 1);
                mbar_expect_tx(bar_vf + 8 * s, 32768);
                tma_load_2d(sv, &P.mapV, bar_vf + 8 * s, 0, row);
                tma_load_2d(sv + 16384, &P.mapV, bar_vf + 8 * s, 64, row);
            };
            int vrow = 0;
            load_q(0, t);
            for (int item = 0; t >= 0; item++) {
                const int h = fa_head(t);
                for (int j = fa_qt(t); j >= 0; j--, it++) {
                    const int s = it & 1;
                    const uint32_t ph = ((it >> 1) & 1) ^ 1;
                    const uint32_t sk = sb + FA_KV + s * 65536;
                    if (j == 0) t = (int)(gridDim.x + atomicAdd(&g_ctr[CT_ATTN], 1u));
                    mbar_wait(bar_ke + 8 * s, ph);
                    mbar_expect_tx(bar_kf + 8 * s, 32768);
                    tma_load_2d(sk, &P.mapK, bar_kf + 8 * s, 0, h * SEQ + j * 128);
                    tma_load_2d(sk + 16384, &P.mapK, bar_kf + 8 * s, 64, h * SEQ + j * 128);
                    if (it > 0) load_v(it - 1, vrow);
                    vrow = h * SEQ + j * 128;
                    if (j == 0) {
                        if (t >= FA_ITEMS) t = -1;
                        else {
                            const int hp = fa_head(t) >> 1;
                            if (!((hp_ready >> hp) & 1)) { wait_ctr(CT_AP + hp, 96u); hp_ready |= 1 << hp; }
                        }
                        mbar_wait(bar_qe + 8 * ((item + 1) & 1), (((item + 1) >> 1) & 1) ^ 1);
                        load_q(item + 1, t);
                    }
                }
            }
            load_v(it - 1, vrow);
        }
    } else {
        asm volatile("setmaxnreg.inc.sync.aligned.u32 %0;" :: "n"(FA_RHI));
        attn_consumer(sb, warp >> 2, warp & 3, lane);
    }
}

__device__ __forceinline__ uint32_t cluster_ctarank() {
    uint32_t r; asm volatile("mov.u32 %0, %%cluster_ctarank;" : "=r"(r)); return r;
}
__device__ __forceinline__ uint32_t mapa_u32(uint32_t addr, uint32_t rank) {
    uint32_t r; asm volatile("mapa.shared::cluster.u32 %0, %1, %2;" : "=r"(r) : "r"(addr), "r"(rank)); return r;
}
__device__ __forceinline__ void cluster_sync_all() {
    asm volatile("barrier.cluster.arrive.release.aligned;\nbarrier.cluster.wait.acquire.aligned;" ::: "memory");
}
__device__ __forceinline__ void cluster_sync_relaxed() {
    asm volatile("barrier.cluster.arrive.relaxed.aligned;\nbarrier.cluster.wait.aligned;" ::: "memory");
}
__device__ __forceinline__ void st_async_v4(uint32_t addr, uint32_t a, uint32_t b, uint32_t c, uint32_t d, uint32_t mbar) {
    asm volatile("st.async.weak.shared::cluster.mbarrier::complete_tx::bytes.v4.b32 [%0], {%1, %2, %3, %4}, [%5];"
                 :: "r"(addr), "r"(a), "r"(b), "r"(c), "r"(d), "r"(mbar) : "memory");
}
__device__ __forceinline__ void st_async_v2(uint32_t addr, uint32_t a, uint32_t b, uint32_t mbar) {
    asm volatile("st.async.weak.shared::cluster.mbarrier::complete_tx::bytes.v2.b32 [%0], {%1, %2}, [%3];"
                 :: "r"(addr), "r"(a), "r"(b), "r"(mbar) : "memory");
}
__device__ __forceinline__ void st_async_b32(uint32_t addr, uint32_t a, uint32_t mbar) {
    asm volatile("st.async.weak.shared::cluster.mbarrier::complete_tx::bytes.b32 [%0], %1, [%2];" :: "r"(addr), "r"(a), "r"(mbar) : "memory");
}
__device__ __forceinline__ void pace(int cycles) {
    if (cycles > 0) {
        uint32_t t0, t;
        asm volatile("mov.u32 %0, %%clock;" : "=r"(t0));
        do { asm volatile("mov.u32 %0, %%clock;" : "=r"(t)); } while (t - t0 < (uint32_t)cycles);
    }
}
__device__ __forceinline__ void mbar_wait_cl(uint32_t bar, uint32_t parity) {
    uint32_t done = 0;
    for (int it = 0; it < (1 << 22) && !done; it++) {
        asm volatile(
            "{\n.reg .pred p;\n"
            "mbarrier.try_wait.parity.shared::cta.b64 p, [%1], %2;\n"
            "selp.u32 %0, 1, 0, p;\n}\n" : "=r"(done) : "r"(bar), "r"(parity) : "memory");
    }
}
__device__ __forceinline__ void ldmatrix_x4(uint32_t& r0, uint32_t& r1, uint32_t& r2, uint32_t& r3, uint32_t addr) {
    asm volatile("ldmatrix.sync.aligned.m8n8.x4.shared.b16 {%0,%1,%2,%3}, [%4];"
                 : "=r"(r0), "=r"(r1), "=r"(r2), "=r"(r3) : "r"(addr));
}
__device__ __forceinline__ void cp_async16(uint32_t dst, const void* src) {
    asm volatile("cp.async.cg.shared.global [%0], [%1], 16;" :: "r"(dst), "l"(src) : "memory");
}

#define DBG(i)
#define DBGW(i, w)
__device__ __forceinline__ void tma_load_2d_mc(uint32_t dst, const CUtensorMap* map, uint32_t bar, int c0, int c1, uint16_t mask) {
    asm volatile(
        "cp.async.bulk.tensor.2d.shared::cluster.global.mbarrier::complete_tx::bytes.multicast::cluster [%0], [%1, {%3, %4}], [%2], %5;"
        :: "r"(dst), "l"((uint64_t)map), "r"(bar), "r"(c0), "r"(c1), "h"(mask) : "memory");
}
__device__ __forceinline__ void bulk_s2s(uint32_t dst_cl, uint32_t src, uint32_t bytes, uint32_t bar_cl) {
    asm volatile("cp.async.bulk.shared::cluster.shared::cta.mbarrier::complete_tx::bytes [%0], [%1], %2, [%3];"
                 :: "r"(dst_cl), "r"(src), "r"(bytes), "r"(bar_cl) : "memory");
}
__device__ __forceinline__ bool elect_one() {
    uint32_t p;
    asm volatile("{\n.reg .pred p;\nelect.sync _|p, 0xffffffff;\nselp.u32 %0, 1, 0, p;\n}" : "=r"(p));
    return p;
}
__device__ __forceinline__ void fence_async_smem() { asm volatile("fence.proxy.async.shared::cta;" ::: "memory"); }
template <int ID, int N> __device__ __forceinline__ void bar_sync() { asm volatile("bar.sync %0, %1;" :: "n"(ID), "n"(N) : "memory"); }
template <int ID, int N> __device__ __forceinline__ void bar_arrive() { asm volatile("bar.arrive %0, %1;" :: "n"(ID), "n"(N) : "memory"); }
__device__ __forceinline__ void sts32(uint32_t a, uint32_t v) { asm volatile("st.shared.u32 [%0], %1;" :: "r"(a), "r"(v) : "memory"); }
__device__ __forceinline__ void ldsm_x4(uint32_t* r, uint32_t addr) {
    asm volatile("ldmatrix.sync.aligned.m8n8.x4.shared.b16 {%0,%1,%2,%3}, [%4];" : "=r"(r[0]), "=r"(r[1]), "=r"(r[2]), "=r"(r[3]) : "r"(addr) : "memory");
}
__device__ __forceinline__ uint32_t pin(uint32_t v) { asm volatile("" : "+r"(v)); return v; }
constexpr uint32_t DHI128 = 0x40000040u, DHI32 = 0xC0000010u;
#define ACC16(d) "+f"(d[0]), "+f"(d[1]), "+f"(d[2]), "+f"(d[3]), "+f"(d[4]), "+f"(d[5]), "+f"(d[6]), "+f"(d[7]), "+f"(d[8]), "+f"(d[9]), "+f"(d[10]), \
    "+f"(d[11]), "+f"(d[12]), "+f"(d[13]), "+f"(d[14]), "+f"(d[15])
#define ACC20(d) ACC16(d), "+f"(d[16]), "+f"(d[17]), "+f"(d[18]), "+f"(d[19])
__device__ __forceinline__ void wgmma_rs(float (&d)[16], const uint32_t (&a)[4], uint32_t db_lo) {
    asm volatile(
        "{\n.reg .b64 db;\nmov.b64 db, {%20, %21};\n"
        "wgmma.mma_async.sync.aligned.m64n32k16.f32.bf16.bf16 {%0,%1,%2,%3,%4,%5,%6,%7,%8,%9,%10,%11,%12,%13,%14,%15}, {%16,%17,%18,%19}, db, 1, 1, 1, 0;\n}\n"
        : ACC16(d) : "r"(a[0]), "r"(a[1]), "r"(a[2]), "r"(a[3]), "r"(db_lo), "n"(DHI128));
}
__device__ __forceinline__ void wgmma_rs(float (&d)[20], const uint32_t (&a)[4], uint32_t db_lo) {
    asm volatile(
        "{\n.reg .b64 db;\nmov.b64 db, {%24, %25};\n"
        "wgmma.mma_async.sync.aligned.m64n40k16.f32.bf16.bf16 {%0,%1,%2,%3,%4,%5,%6,%7,%8,%9,%10,%11,%12,%13,%14,%15,%16,%17,%18,%19}, {%20,%21,%22,%23}, db, 1, 1, 1, 0;\n}\n"
        : ACC20(d) : "r"(a[0]), "r"(a[1]), "r"(a[2]), "r"(a[3]), "r"(db_lo), "n"(DHI128));
}
template <uint32_t AHI, uint32_t BHI>
__device__ __forceinline__ void wgmma_ss(float (&d)[16], uint32_t da_lo, uint32_t db_lo) {
    asm volatile(
        "{\n.reg .b64 da, db;\nmov.b64 da, {%16, %18};\nmov.b64 db, {%17, %19};\n"
        "wgmma.mma_async.sync.aligned.m64n32k16.f32.bf16.bf16 {%0,%1,%2,%3,%4,%5,%6,%7,%8,%9,%10,%11,%12,%13,%14,%15}, da, db, 1, 1, 1, 0, 0;\n}\n"
        : ACC16(d) : "r"(da_lo), "r"(db_lo), "n"(AHI), "n"(BHI));
}
template <uint32_t AHI, uint32_t BHI>
__device__ __forceinline__ void wgmma_ss(float (&d)[20], uint32_t da_lo, uint32_t db_lo) {
    asm volatile(
        "{\n.reg .b64 da, db;\nmov.b64 da, {%20, %22};\nmov.b64 db, {%21, %23};\n"
        "wgmma.mma_async.sync.aligned.m64n40k16.f32.bf16.bf16 {%0,%1,%2,%3,%4,%5,%6,%7,%8,%9,%10,%11,%12,%13,%14,%15,%16,%17,%18,%19}, da, db, 1, 1, 1, 0, 0;\n}\n"
        : ACC20(d) : "r"(da_lo), "r"(db_lo), "n"(AHI), "n"(BHI));
}
template <uint32_t AHI, uint32_t BHI>
__device__ __forceinline__ void wgmma_ss0(float (&d)[20], uint32_t da_lo, uint32_t db_lo) {
    asm volatile(
        "{\n.reg .b64 da, db;\nmov.b64 da, {%20, %22};\nmov.b64 db, {%21, %23};\n"
        "wgmma.mma_async.sync.aligned.m64n40k16.f32.bf16.bf16 {%0,%1,%2,%3,%4,%5,%6,%7,%8,%9,%10,%11,%12,%13,%14,%15,%16,%17,%18,%19}, da, db, 0, 1, 1, 0, 0;\n}\n"
        : "=f"(d[0]), "=f"(d[1]), "=f"(d[2]), "=f"(d[3]), "=f"(d[4]), "=f"(d[5]), "=f"(d[6]), "=f"(d[7]), "=f"(d[8]), "=f"(d[9]), "=f"(d[10]),
          "=f"(d[11]), "=f"(d[12]), "=f"(d[13]), "=f"(d[14]), "=f"(d[15]), "=f"(d[16]), "=f"(d[17]), "=f"(d[18]), "=f"(d[19])
        : "r"(da_lo), "r"(db_lo), "n"(AHI), "n"(BHI));
}
__device__ __forceinline__ void wgmma_ss_n8(float (&d)[4], uint32_t da_lo, uint32_t db_lo) {
    asm volatile(
        "{\n.reg .b64 da, db;\nmov.b64 da, {%4, %6};\nmov.b64 db, {%5, %7};\n"
        "wgmma.mma_async.sync.aligned.m64n8k16.f32.bf16.bf16 {%0,%1,%2,%3}, da, db, 1, 1, 1, 1, 0;\n}\n"
        : "+f"(d[0]), "+f"(d[1]), "+f"(d[2]), "+f"(d[3]) : "r"(da_lo), "r"(db_lo), "n"(DHI128), "n"(DHI32));
}

__device__ __forceinline__ void wgmma_ss_n32_ta(float (&d)[16], uint32_t da_lo, uint32_t db_lo) {
    asm volatile(
        "{\n.reg .b64 da, db;\nmov.b64 da, {%16, %18};\nmov.b64 db, {%17, %18};\n"
        "wgmma.mma_async.sync.aligned.m64n32k16.f32.bf16.bf16 {%0,%1,%2,%3,%4,%5,%6,%7,%8,%9,%10,%11,%12,%13,%14,%15}, da, db, 1, 1, 1, 1, 0;\n}\n"
        : ACC16(d) : "r"(da_lo), "r"(db_lo), "n"(DHI128));
}

constexpr uint32_t C2_WO = 0;
constexpr uint32_t C2_XB = 65536;
constexpr uint32_t C2_XS = 40960;
constexpr uint32_t C2_QX = C2_XB + 2 * C2_XS;
constexpr uint32_t C2_KX = C2_QX + 4096;
constexpr uint32_t C2_VT = C2_KX + 5120;
constexpr uint32_t C2_OB = C2_VT + 12288;
constexpr uint32_t C2_QM = C2_OB + 8192;
constexpr uint32_t C2_SC = C2_QM + 1024;
constexpr uint32_t C2_PB = C2_SC + 2560;
constexpr uint32_t C2_BAR = C2_PB + 768;
constexpr uint32_t C2_PX = C2_BAR + 256;
constexpr uint32_t C2_SX = C2_PX + 3072;
#define C2_NS 4
constexpr uint32_t C2_WS = C2_SX + 20480;
constexpr int C2_SMEM = C2_WS + 3 * C2_NS * 2048;
static_assert(C2_PX % 256 == 0 && C2_WS % 256 == 0 && C2_SMEM <= 232448, "smem map");
#define CH_PF 0
#define CH_PFD 1000
#define CH_PT 1260
#define CH_PT1 CH_PT
#define CH_WOT 1
#define CH_B4E 0
#define CH_NCH 4
#define CH_TS 0
#define CH_TSK 608
#define CH_TSW 2
#define CH_NQ1 12
#define CH_TSC 0
__device__ __align__(256) uint32_t g_tsend[64];
#define CH_POLL_DELAY 600

__device__ __forceinline__ uint32_t c2_stage(int wg, int i) { return wg < 2 ? C2_XB + C2_XS + (wg * 4 + i) * 8192 : ((C2_PX + 1023) & ~1023u) + i * 8192; }
static_assert(C2_XB + C2_XS + 8 * 8192 <= C2_BAR && ((C2_PX + 1023) & ~1023u) + 4 * 8192 <= C2_SMEM && (C2_XB + C2_XS) % 1024 == 0, "staging");
__device__ __forceinline__ void c2_stage_load(const CUtensorMap* map, uint32_t sb, int wg, int rank, int col0, int round) {
    const uint32_t bar = sb + C2_BAR + 176 + (wg * 2 + round) * 8;
    mbar_expect_tx(bar, 32768);
#pragma unroll 1
    for (int i = 0; i < 4; i++) {
        tma_load_2d(sb + c2_stage(wg, i), map, bar, col0, ((rank - round * 4 - i) & 7) * 64);
        if (i < 3) pace(round ? CH_PT1 : CH_PT);
    }
}
__device__ __forceinline__ void c2_load_w(uint32_t (&w)[32][4], const CUtensorMap* map, int wg, int rank, int col0, uint32_t t128, uint32_t ws, uint32_t sb) {
    const uint32_t s0 = pin(sb + c2_stage(wg, 0) + t128), s1 = pin(sb + c2_stage(wg, 0) + (t128 ^ 16) + 128);
#pragma unroll
    for (int r = 0; r < 2; r++) {
        mbar_wait(sb + C2_BAR + 176 + (wg * 2 + r) * 8, 0);
#pragma unroll
        for (int e = 0; e < 16; e++) {
            uint32_t w0, w1, w2, w3;
            asm volatile("ld.shared.b32 %0, [%1];" : "=r"(w0) : "r"(s0 + e * 2048) : "memory");
            asm volatile("ld.shared.b32 %0, [%1];" : "=r"(w1) : "r"(s1 + e * 2048) : "memory");
            asm volatile("ld.shared.b32 %0, [%1];" : "=r"(w2) : "r"(s0 + e * 2048 + 1024) : "memory");
            asm volatile("ld.shared.b32 %0, [%1];" : "=r"(w3) : "r"(s1 + e * 2048 + 1024) : "memory");
            uint32_t* d = w[r * 16 + e];
            d[0] = __byte_perm(w0, w1, 0x5410); d[1] = __byte_perm(w0, w1, 0x7632);
            d[2] = __byte_perm(w2, w3, 0x5410); d[3] = __byte_perm(w2, w3, 0x7632);
        }
        if (r == 0) {
            asm volatile("bar.sync %0, 128;" :: "r"(8 + wg) : "memory");
            if ((threadIdx.x & 127) == 32) c2_stage_load(map, sb, wg, rank, col0, 1);
            mbar_wait(sb + C2_BAR + 168, 0);
#pragma unroll 1
            for (int i = threadIdx.x; i < 2048; i += 384) {
                const int k = i >> 2, b = i & 3;
                const uint32_t a0 = sb + C2_WO + k * 128 + (((2 * b) ^ (k & 7)) << 4), a1 = a0 ^ 16;
                uint4 u, v;
                asm volatile("ld.shared.v4.b32 {%0, %1, %2, %3}, [%4];" : "=r"(u.x), "=r"(u.y), "=r"(u.z), "=r"(u.w) : "r"(a0) : "memory");
                asm volatile("ld.shared.v4.b32 {%0, %1, %2, %3}, [%4];" : "=r"(v.x), "=r"(v.y), "=r"(v.z), "=r"(v.w) : "r"(a1) : "memory");
                asm volatile("st.shared.v4.b32 [%0], {%1, %2, %3, %4};" :: "r"(a0), "r"(__byte_perm(u.x, u.y, 0x5410)),
                             "r"(__byte_perm(u.z, u.w, 0x5410)), "r"(__byte_perm(v.x, v.y, 0x5410)), "r"(__byte_perm(v.z, v.w, 0x5410)) : "memory");
                asm volatile("st.shared.v4.b32 [%0], {%1, %2, %3, %4};" :: "r"(a1), "r"(__byte_perm(u.x, u.y, 0x7632)),
                             "r"(__byte_perm(u.z, u.w, 0x7632)), "r"(__byte_perm(v.x, v.y, 0x7632)), "r"(__byte_perm(v.z, v.w, 0x7632)) : "memory");
            }
        }
    }
    cluster_sync_relaxed();
#pragma unroll
    for (int e = 0; e < C2_NS; e++) stmatrix_x4(ws + e * 2048, w[e][0], w[e][1], w[e][2], w[e][3]);
#pragma unroll 1
    for (int i = threadIdx.x; i < 2 * 512 + 256; i += 384)
        sts32(sb + (i < 1024 ? C2_VT + (i >> 9) * 6144 + 4096 + (i & 511) * 4 : C2_PX + 2048 + (i - 1024) * 4), 0u);
    fence_async_smem();
    asm volatile("bar.sync %0, 128;" :: "r"(8 + wg) : "memory");
}
template <int E0, int E1, int NA>
__device__ __forceinline__ void c2_xstream(float (&acc)[NA], const uint32_t (&w)[32][4], uint32_t xlo, uint32_t rank, uint32_t wslo) {
    if (E0 == 0)
#pragma unroll
        for (int i = 0; i < NA; i++) acc[i] = 0.f;
    wgmma_fence();
#pragma unroll
    for (int e = E0; e < E1; e++) {
        if (e < C2_NS) wgmma_ss<DHI32, DHI128>(acc, wslo + e * 128, xlo + ((rank - (e >> 2)) & 7) * 320 + (e & 3) * 2);
        else wgmma_rs(acc, w[e], xlo + ((rank - (e >> 2)) & 7) * 320 + (e & 3) * 2);
    }
    wgmma_commit();
}
__device__ __forceinline__ constexpr uint32_t c2_tslot(int i) { return i == 0 ? C2_QX : i < 4 ? C2_OB + (i - 1) * 4096 : ((C2_WS + 1023) & ~1023u) + (i - 4) * 4096; }
static_assert(C2_QX % 1024 == 0 && C2_OB % 1024 == 0 && c2_tslot(3) + 4096 <= C2_BAR && c2_tslot(7) + 4096 <= C2_SMEM, "tail slots");
__device__ __forceinline__ constexpr int c2_grp(int i) { return i < 2 ? i : 1 + (i >> 1); }

struct ChainParams {
    CUtensorMap mapX;
    CUtensorMap mapM;
    CUtensorMap mapW[3];
    CUtensorMap mapWo;
    CUtensorMap mapC;
    bf16* out;
};
__global__ void __cluster_dims__(8, 1, 1) __launch_bounds__(384, 1)
chain_kernel(const __grid_constant__ ChainParams P) {
    const CUtensorMap& mapX = P.mapX;
    extern __shared__ __align__(1024) uint8_t smem_chain[];
    const uint32_t sb = smem_u32(smem_chain);
    const uint32_t dlo = ((sb & 0x3FFFF) >> 4) | (1u << 16);
    const int tid = __shfl_sync(0xffffffff, threadIdx.x, threadIdx.x & 31), lane = tid & 31;
    const int warp = __shfl_sync(0xffffffff, tid >> 5, 0), wg = warp >> 2, w4 = warp & 3;
    const uint32_t rank = cluster_ctarank();
    const int C = blockIdx.x >> 3;
    const int h = C * 4 + (rank >> 1);
    const int g = lane >> 2, qc = lane & 3;
    pdl_launch_dependents();
    TS_BEGIN(2);
    const uint32_t bar_m = sb + C2_BAR, bar_o = bar_m + 64, bar_sc = bar_m + 128, bar_x = bar_m + 136, bar_sx = bar_m + 152;
    const uint32_t bar_w = bar_m + 168, bar_h = bar_m + 40;
    const int col0 = h * HD + (rank & 1) * 64;
    if (tid == 0) {
        for (int j = 0; j < 5; j++) { mbar_init(bar_m + 8 * j, j ? 1 : 4); mbar_init(bar_o + 8 * j, j ? 1 : 4); }
        for (int j = 0; j < 12; j++) mbar_init(bar_sc + 8 * j, 1);
        mbar_init(bar_h, 32); mbar_init(bar_h + 8, 32);
        asm volatile("fence.mbarrier_init.release.cluster;" ::: "memory");
    }
    __syncwarp();
    cluster_sync_relaxed();
    if (tid == 0) {
        mbar_expect_tx(bar_x, 32768 + 8192);
        tma_load_2d_mc(sb + C2_XB + rank * 5120, &mapX, bar_x, rank * 64, 0, (uint16_t)0xff);
#pragma unroll 1
        for (int j = 0; j < 8; j++) tma_load_2d(sb + C2_XB + j * 5120 + 4096, &P.mapM, bar_x, j * 64, 0);
        mbar_expect_tx(bar_w, 65536);
    }
    if ((tid & 127) == 32) {
        pace(CH_PFD);
        c2_stage_load(&P.mapW[wg], sb, wg, rank, col0, 0);
#pragma unroll 1
        for (int j = wg; j < 8; j += 3) {
            pace(CH_PT1);
            tma_load_2d(sb + C2_WO + j * 8192, &P.mapWo, bar_w, rank * 64, C * 512 + ((rank - j) & 7) * 64);
        }
    }
    __syncwarp();

    const uint32_t t32 = w4 * 256 + qc * 64 + (((g >> 2) ^ (qc >> 1)) << 4) + (g & 3) * 4;
    const uint32_t t128 = qc * 256 + (((2 * w4 + (g >> 2)) ^ (2 * qc)) << 4) + (g & 3) * 4;
    const uint32_t a32 = (w4 * 16 + (lane & 15)) * 32 + (((lane >> 4) ^ ((lane >> 2) & 1)) << 4);
    const uint32_t ws = sb + C2_WS + wg * (C2_NS * 2048) + a32;
    uint32_t w[32][4];
    static_assert(C2_NS == 4, "slot 0");
    auto proj_mem = [&](float (&a)[CH_NCH][4], int s, uint32_t l128) {
        uint32_t b[4][8];
#pragma unroll
        for (int i = 0; i < 4 * CH_NCH; i++) a[i >> 2][i & 3] = 0.f;
        const uint32_t par = (s & 1) ^ 1;
        const uint32_t mb = sb + C2_XB + (s & 1) * C2_XS + 4096;
        auto L = [&](int i) {
            ldsm_x4(b[i & 3], mb + ((rank - i) & 7) * 5120 + l128);
            ldsm_x4(b[i & 3] + 4, mb + ((rank - i) & 7) * 5120 + (l128 ^ 64));
        };
        auto H = [&](int i) {
#pragma unroll
            for (int kk = 0; kk < 4; kk++) {
                const uint32_t* f = i ? w[i * 4 + kk] : &b[2 + (kk >> 1)][(kk & 1) * 4];
                mma_16816(a[(i * 4 + kk) % CH_NCH], f[0], f[1], f[2], f[3], b[i & 3][2 * kk], b[i & 3][2 * kk + 1]);
            }
        };
#pragma unroll
        for (int e = 0; e < 4; e++) ldsm_x4(&b[2 + (e >> 1)][(e & 1) * 4], ws + e * 2048);
        mbar_wait(bar_m, par);
        L(0);
        H(0);
        mbar_wait(bar_m + 8, par);
        DBGW(1 + 16 * wg, 0);
        L(1);
        mbar_wait(bar_m + 16, par);
        uint32_t nxt = mbar_test(bar_m + 24, par);
        L(2); L(3);
        H(1);
        if (__builtin_expect(!nxt, 0)) mbar_wait(bar_m + 24, par);
        nxt = mbar_test(bar_m + 32, par);
        L(4); L(5);
        H(2); H(3);
        if (__builtin_expect(!nxt, 0)) mbar_wait(bar_m + 32, par);
        DBGW(2 + 16 * wg, 0);
        L(6); L(7);
        H(4); H(5); H(6); H(7);
#pragma unroll
        for (int i = 0; i < 4; i++) a[0][i] = CH_NCH == 4 ? (a[0][i] + a[1][i]) + (a[2][i] + a[3 % CH_NCH][i]) : CH_NCH == 3 ? a[0][i] + a[1][i] + a[2 % CH_NCH][i] : a[0][i] + a[1][i];
    };
    auto store_x = [&](const float (&acc)[16], uint32_t base) {
#pragma unroll
        for (int j = 0; j < 4; j++) {
            sts32(base + t128 + j * 1024, pack_bf16(acc[4 * j], acc[4 * j + 2]));
            sts32(base + (t128 ^ 16) + 128 + j * 1024, pack_bf16(acc[4 * j + 1], acc[4 * j + 3]));
        }
    };
    auto tail_load = [&](int q, int b) {
        if (q == 2) asm volatile("fence.acq_rel.gpu;" ::: "memory");
        asm volatile("fence.proxy.async.global;" ::: "memory");
        mbar_expect_tx(bar_x + 8 * b, 32768);
        tma_load_2d_mc(sb + C2_XB + b * C2_XS + rank * 5120, &P.mapC, bar_x + 8 * b, (rank & 1) * 64, h * SEQ + (NSEG - 4 + q) * SEGL, (uint16_t)0xff);
    };
    auto fresh_lane = [&]() { uint32_t l; asm volatile("mov.u32 %0, %%laneid;" : "=r"(l)); return l; };
    auto tail_arrive = [&](int i) {
        const uint32_t lane = fresh_lane();
        if (lane < 8) asm volatile("mbarrier.arrive.relaxed.cluster.shared::cluster.b64 _, [%0];" :: "r"(mapa_u32(bar_h + 8 * i, lane)) : "memory");
        __syncwarp();
    };
    const float scale = 0.08838834764831845f, l2e = 1.4426950408889634f;
    c2_load_w(w, &P.mapW[wg], wg, rank, col0, t128, ws, sb);
    TS_END(6);
    TS_BEGIN(5);

    if (wg == 0) {
#pragma unroll 1
        for (int s = -1;;) {
            float qx[16];
            uint32_t* dst = reinterpret_cast<uint32_t*>(g_xbuf + (((s & 1) * 8 + rank) * 8 + C) * 128) + qc * 64 + w4 * 8 + g;
            asm volatile("" : "+l"(dst));
            mbar_wait(bar_x + 8 * ((s + 1) & 1), ((s + 1) >> 1) & 1);
            if (s >= 0) bar_sync<6, 384>();
            c2_xstream<0, CH_NQ1>(qx, w, dlo + ((C2_XB + ((s + 1) & 1) * C2_XS) >> 4), rank, dlo + (C2_WS >> 4));
            if (s >= 0) {
                float acc[4] = {0.f, 0.f, 0.f, 0.f};
                const uint32_t tag = ((s >> 1) & 1) ^ 1;
                uint32_t nxt = 0;
#pragma unroll
                for (int i = 0; i < 8; i++) {
                    if (i < 2 || !(i & 1)) {
                        if (i < 2 || __builtin_expect(!nxt, 0)) mbar_wait(bar_o + 8 * c2_grp(i), s & 1);
                        if (i == 0) DBGW(7, 0);
                        if (i == 1) DBGW(8, 0);
                        if (i == 6) DBGW(9, 0);
                        wgmma_fence();
                    }
#pragma unroll
                    for (int kk = 0; kk < 4; kk++) {
                        if ((i & 1) && i < 7 && kk == CH_WOT) nxt = mbar_test(bar_o + 8 * c2_grp(i + 1), s & 1);
                        wgmma_ss_n8(acc, dlo + ((C2_WO + i * 8192 + kk * 2048) >> 4), dlo + ((C2_OB + i * 1024 + kk * 256) >> 4));
                    }
                }
                wgmma_commit();
                if (CH_B4E) bar_arrive<4, 256>();
                if (!CH_TS) bar_arrive<11, 256>();
                wgmma_wait<0>();
                asm volatile("st.relaxed.gpu.global.u32 [%0], %1;" :: "l"(dst), "r"((pack_bf16(acc[0], acc[2]) & ~1u) | tag) : "memory");
                asm volatile("st.relaxed.gpu.global.u32 [%0 + 128], %1;" :: "l"(dst), "r"((pack_bf16(acc[1], acc[3]) & ~1u) | tag) : "memory");
                if (!CH_B4E) bar_arrive<4, 256>();
                DBGW(10, 0);
            }
            s++;
            c2_xstream<CH_NQ1, 32>(qx, w, dlo + ((C2_XB + (s & 1) * C2_XS) >> 4), rank, dlo + (C2_WS >> 4));
            const uint32_t sca = pin(w4 < 2 ? sb + C2_SC + w4 * 512 + lane * 16 : sb + C2_SC + 1024 + lane * 8);
            const uint32_t krow = w4 * 16 + (lane & 15);
            const uint32_t ka0 = pin(sb + C2_KX + krow * 128 + (((lane >> 4) ^ (krow & 7)) << 4));
            const uint32_t l32 = pin(sb + C2_QM + (lane >> 4) * 256 + (lane & 7) * 32 + ((((lane >> 3) & 1) ^ ((lane >> 2) & 1)) << 4));
            const uint32_t qst = pin(sb + C2_QM + t32);
            const uint32_t l128 = pin((lane & 7) * 128 + (((lane >> 3) ^ (lane & 7)) << 4));
            if (s > 0) bar_sync<5, 256>();
            wgmma_wait<0>();
            store_x(qx, sb + C2_QX);
            DBGW(0, 0);
            if (s == NSEG - 1) break;
            {
                float a[CH_NCH][4];
                proj_mem(a, s, l128);
                sts32(qst, pack_bf16(a[0][0], a[0][2]));
                sts32(qst + 32, pack_bf16(a[0][1], a[0][3]));
            }
            DBGW(3, 0);
            if (w4 < 3) {
                uint32_t ka[4][4], qb[8];
                float c[4] = {0.f, 0.f, 0.f, 0.f}, c2[4] = {0.f, 0.f, 0.f, 0.f};
                const uint32_t sc_peer = pin(mapa_u32(sca + 1280, rank ^ 1)), sc_own = pin(mapa_u32(sca, rank));
                bar_sync<1, 384>();
                ldsm_x4(qb, l32);
                ldsm_x4(ka[0], ka0);
                ldsm_x4(ka[1], ka0 ^ 32);
                ldsm_x4(qb + 4, l32 + 512);
                ldsm_x4(ka[2], ka0 ^ 64);
                ldsm_x4(ka[3], ka0 ^ 96);
                mma_16816(c, ka[0][0], ka[0][1], ka[0][2], ka[0][3], qb[0], qb[1]);
                mma_16816(c2, ka[1][0], ka[1][1], ka[1][2], ka[1][3], qb[2], qb[3]);
                mma_16816(c, ka[2][0], ka[2][1], ka[2][2], ka[2][3], qb[4], qb[5]);
                mma_16816(c2, ka[3][0], ka[3][1], ka[3][2], ka[3][3], qb[6], qb[7]);
                const uint32_t u0 = __float_as_uint(c[0] + c2[0]), u1 = __float_as_uint(c[1] + c2[1]);
                const uint32_t u2 = __float_as_uint(c[2] + c2[2]), u3 = __float_as_uint(c[3] + c2[3]);
                asm volatile(
                    "{\n.reg .pred p;\nsetp.lt.u32 p, %8, 2;\n"
                    "@p st.async.weak.shared::cluster.mbarrier::complete_tx::bytes.v4.b32 [%0], {%4, %5, %6, %7}, [%1];\n"
                    "@!p st.async.weak.shared::cluster.mbarrier::complete_tx::bytes.v2.b32 [%0], {%4, %5}, [%1];\n"
                    "@p st.async.weak.shared::cluster.mbarrier::complete_tx::bytes.v4.b32 [%2], {%4, %5, %6, %7}, [%3];\n"
                    "@!p st.async.weak.shared::cluster.mbarrier::complete_tx::bytes.v2.b32 [%2], {%4, %5}, [%3];\n}"
                    :: "r"(sc_peer), "r"(mapa_u32(bar_sc, rank ^ 1)), "r"(sc_own), "r"(mapa_u32(bar_sc, rank)), "r"(u0), "r"(u1), "r"(u2), "r"(u3), "r"(w4) : "memory");
                bar_arrive<2, 224>();
                fence_async_smem();
                if (s >= 4 * CB_FIRST + 5 && (s & 3) == 1 && tid == 0) signal_ctr(CT_CB + ((s - 5) >> 2));
                __syncwarp();
                DBGW(4, 2);
            } else {
                bar_arrive<1, 384>();
                fence_async_smem();
                const uint32_t a = pin(sb + C2_SC + lane * 16), a2 = pin(sb + C2_SC + 1024 + lane * 8), pa = pin(sb + C2_PB + lane * 4);
                mbar_wait(bar_sc, s & 1);
                DBG(5);
                float v[10];
                {
                    float4 x0, x1, y0, y1; float2 x2, y2;
                    asm volatile("ld.shared.v4.f32 {%0, %1, %2, %3}, [%4];" : "=f"(x0.x), "=f"(x0.y), "=f"(x0.z), "=f"(x0.w) : "r"(a) : "memory");
                    asm volatile("ld.shared.v4.f32 {%0, %1, %2, %3}, [%4];" : "=f"(y0.x), "=f"(y0.y), "=f"(y0.z), "=f"(y0.w) : "r"(a + 1280) : "memory");
                    asm volatile("ld.shared.v4.f32 {%0, %1, %2, %3}, [%4];" : "=f"(x1.x), "=f"(x1.y), "=f"(x1.z), "=f"(x1.w) : "r"(a + 512) : "memory");
                    asm volatile("ld.shared.v4.f32 {%0, %1, %2, %3}, [%4];" : "=f"(y1.x), "=f"(y1.y), "=f"(y1.z), "=f"(y1.w) : "r"(a + 1792) : "memory");
                    asm volatile("ld.shared.v2.f32 {%0, %1}, [%2];" : "=f"(x2.x), "=f"(x2.y) : "r"(a2) : "memory");
                    asm volatile("ld.shared.v2.f32 {%0, %1}, [%2];" : "=f"(y2.x), "=f"(y2.y) : "r"(a2 + 1280) : "memory");
                    v[0] = x0.x + y0.x; v[1] = x0.y + y0.y; v[2] = x0.z + y0.z; v[3] = x0.w + y0.w;
                    v[4] = x1.x + y1.x; v[5] = x1.y + y1.y; v[6] = x1.z + y1.z; v[7] = x1.w + y1.w;
                    v[8] = x2.x + y2.x; v[9] = x2.y + y2.y;
                }
                float m0 = fmaxf(fmaxf(fmaxf(v[0], v[2]), fmaxf(v[4], v[6])), v[8]);
                float m1 = fmaxf(fmaxf(fmaxf(v[1], v[3]), fmaxf(v[5], v[7])), v[9]);
#pragma unroll
                for (int o = 4; o < 32; o <<= 1) {
                    m0 = fmaxf(m0, __shfl_xor_sync(0xffffffff, m0, o));
                    m1 = fmaxf(m1, __shfl_xor_sync(0xffffffff, m1, o));
                }
                const float sl = scale * l2e;
                m0 *= sl; m1 *= sl;
#pragma unroll
                for (int j = 0; j < 5; j++)
                    sts32(pa + j * 128, pack_bf16(ex2f(fmaf(v[2 * j], sl, -m0)), ex2f(fmaf(v[2 * j + 1], sl, -m1))));
                bar_arrive<3, 160>();
                DBG(6);
            }
            uint32_t now;
            asm volatile("mov.u32 %0, %%globaltimer_lo;" : "=r"(now) :: "memory");
            if (CH_TS) asm volatile("{\n.reg .pred p;\nsetp.eq.u32 p, %2, %3;\n@p st.relaxed.gpu.global.u32 [%0], %1;\n}" :: "l"(g_tsend + rank * 8 + C), "r"(now), "r"(tid), "n"(CH_TSW * 32) : "memory");
        }
        bar_arrive<1, 384>();
        fence_async_smem();
        bar_arrive<6, 384>();
        TS_MARK(8, 0);
    } else if (wg == 1) {
#pragma unroll 1
        for (int s = -1;;) {
            if (s > 0) {
                mbar_wait(bar_sx + 8 * ((s - 1) & 1), ((s - 1) >> 1) & 1);
                const uint32_t a = sb + C2_SX + ((s - 1) & 1) * 10240 + w4 * 1280 + lane * 8;
                float v[10];
                const int lim = 8 * w4 + g - 2 * qc;
#pragma unroll
                for (int j = 0; j < 5; j++) {
                    float2 x, y;
                    asm volatile("ld.shared.v2.f32 {%0, %1}, [%2];" : "=f"(x.x), "=f"(x.y) : "r"(a + j * 256) : "memory");
                    asm volatile("ld.shared.v2.f32 {%0, %1}, [%2];" : "=f"(y.x), "=f"(y.y) : "r"(a + 5120 + j * 256) : "memory");
                    v[2 * j] = (j < 4 && 8 * j > lim) ? -INFINITY : x.x + y.x;
                    v[2 * j + 1] = (j < 4 && 8 * j + 1 > lim) ? -INFINITY : x.y + y.y;
                }
                float mx = fmaxf(fmaxf(fmaxf(v[0], v[1]), fmaxf(v[2], v[3])), fmaxf(fmaxf(v[4], v[5]), fmaxf(v[6], v[7])));
                mx = fmaxf(mx, fmaxf(v[8], v[9]));
                mx = fmaxf(mx, __shfl_xor_sync(0xffffffff, mx, 1));
                mx = fmaxf(mx, __shfl_xor_sync(0xffffffff, mx, 2));
                const float sl = scale * l2e;
                mx *= sl;
#pragma unroll
                for (int j = 0; j < 10; j++) v[j] = ex2f(fmaf(v[j], sl, -mx));
                float sm = ((v[0] + v[1]) + (v[2] + v[3])) + ((v[4] + v[5]) + (v[6] + v[7])) + (v[8] + v[9]);
                sm += __shfl_xor_sync(0xffffffff, sm, 1);
                sm += __shfl_xor_sync(0xffffffff, sm, 2);
                float inv;
                asm("rcp.approx.ftz.f32 %0, %1;" : "=f"(inv) : "f"(sm));
                const uint32_t pa = sb + C2_PX + w4 * 256 + g * 32 + ((g >> 2) << 4) + qc * 4;
#pragma unroll
                for (int j = 0; j < 5; j++) sts32((pa ^ ((j & 1) << 4)) + (j >> 1) * 1024, pack_bf16(v[2 * j] * inv, v[2 * j + 1] * inv));
            }
            if (s >= 0) {
                fence_async_smem();
                if (s < NSEG) bar_sync<6, 384>(); else bar_sync<7, 256>();
                DBGW(20, 0);
                uint32_t cp[8];
                {
                    float cx[16];
#pragma unroll
                    for (int i = 0; i < 16; i++) cx[i] = 0.f;
                    wgmma_fence();
#pragma unroll
                    for (int kk = 0; kk < 3; kk++)
                        wgmma_ss<DHI32, DHI32>(cx, dlo + ((C2_VT + ((s - 1) & 1) * 6144 + kk * 2048) >> 4), dlo + ((C2_PX + kk * 1024) >> 4));
                    wgmma_commit();
                    wgmma_wait<0>();
#pragma unroll
                    for (int j = 0; j < 4; j++) { cp[2 * j] = pack_bf16(cx[4 * j], cx[4 * j + 2]); cp[2 * j + 1] = pack_bf16(cx[4 * j + 1], cx[4 * j + 3]); }
                    asm volatile("{\n.reg .pred p;\nsetp.gt.u32 p, %0, 99;\n@p st.shared.v4.b32 [%0], {%1, %2, %3, %4};\n@p st.shared.v4.b32 [%0], {%5, %6, %7, %8};\n}"
                                 :: "r"(rank), "r"(cp[0]), "r"(cp[1]), "r"(cp[2]), "r"(cp[3]), "r"(cp[4]), "r"(cp[5]), "r"(cp[6]), "r"(cp[7]) : "memory");
                }
                if (s == NSEG) {
#pragma unroll
                    for (int j = 0; j < 4; j++) {
                        sts32(sb + C2_QX + t128 + j * 1024, cp[2 * j]);
                        sts32(sb + C2_QX + (t128 ^ 16) + 128 + j * 1024, cp[2 * j + 1]);
                    }
                    break;
                }
                float sx[20];
                wgmma_fence();
                wgmma_ss0<DHI128, DHI128>(sx, dlo + (C2_QX >> 4), dlo + (C2_KX >> 4));
#pragma unroll
                for (int kk = 1; kk < 4; kk++) wgmma_ss<DHI128, DHI128>(sx, dlo + (C2_QX >> 4) + kk * 2, dlo + (C2_KX >> 4) + kk * 2);
                wgmma_commit();
                wgmma_wait<0>();
                if (s < NSEG - 1) bar_arrive<5, 256>();
                if (s > 0) {
                    uint32_t* dst = reinterpret_cast<uint32_t*>(g_ctxB + ((size_t)h * SEQ + (s - 1) * SEGL + 2 * qc) * HD + (rank & 1) * 64 + w4 * 16 + 2 * g);
#pragma unroll
                    for (int j = 0; j < 4; j++) {
                        asm volatile("st.global.u32 [%0], %1;" :: "l"(dst + j * 8 * (HD / 2)), "r"(cp[2 * j]) : "memory");
                        asm volatile("st.global.u32 [%0], %1;" :: "l"(dst + (j * 8 + 1) * (HD / 2)), "r"(cp[2 * j + 1]) : "memory");
                    }
                }
                DBGW(22, 0);
                if (s >= NSEG - 2) asm volatile("bar.arrive %0, 160;" :: "r"(s - (NSEG - 2) + 12) : "memory");
                const uint32_t a = sb + C2_SX + (s & 1) * 10240 + w4 * 2560 + lane * 8;
                if (w4 < 2) {
#pragma unroll
                    for (int j = 0; j < 5; j++) {
                        asm volatile("st.shared.v2.f32 [%0], {%1, %2};" :: "r"(a + j * 256), "f"(sx[4 * j]), "f"(sx[4 * j + 1]) : "memory");
                        asm volatile("st.shared.v2.f32 [%0], {%1, %2};" :: "r"(a + 1280 + j * 256), "f"(sx[4 * j + 2]), "f"(sx[4 * j + 3]) : "memory");
                    }
                }
                if (s < NSEG - 1) mbar_wait(bar_x + 8 * ((s + 1) & 1), ((s + 1) >> 1) & 1);
                const uint32_t pa = mapa_u32(a + 5120, rank ^ 1), pb = mapa_u32(bar_sx + 8 * (s & 1), rank ^ 1);
                if (s < NSEG - 1) bar_sync<4, 256>();
                if (w4 < 2) {
#pragma unroll
                    for (int j = 0; j < 5; j++) {
                        st_async_v2(pa + j * 256, __float_as_uint(sx[4 * j]), __float_as_uint(sx[4 * j + 1]), pb);
                        st_async_v2(pa + 1280 + j * 256, __float_as_uint(sx[4 * j + 2]), __float_as_uint(sx[4 * j + 3]), pb);
                    }
                }
            } else mbar_wait(bar_x, 0);
            s++;
            if (s < NSEG) {
                float acc[16];
                c2_xstream<0, 32>(acc, w, dlo + ((C2_XB + (s & 1) * C2_XS) >> 4), rank, dlo + ((C2_WS + C2_NS * 2048) >> 4));
                const uint32_t kst = pin(sb + C2_KX + 4096 + t128);
                const uint32_t l128 = pin((lane & 7) * 128 + (((lane >> 3) ^ (lane & 7)) << 4));
                wgmma_wait<0>();
                store_x(acc, sb + C2_KX);
                DBGW(16, 0);
                float a[CH_NCH][4];
                proj_mem(a, s, l128);
                sts32(kst, pack_bf16(a[0][0], a[0][2]));
                sts32((kst ^ 16) + 128, pack_bf16(a[0][1], a[0][3]));
                bar_arrive<1, 384>();
                DBGW(19, 0);
                if (w4 == 0) {
                    if (s < NSEG - 1) {
                        if (lane == 0) mbar_expect_tx(bar_sc, 2560);
                        if (lane < 16 && (lane & 7) >= 1 && (lane & 7) < 5) mbar_expect_tx(bar_m + 8 * lane, (lane & 7) == 1 ? 1024 : 2048);
                        if (lane == 8) {
                            mbar_expect_tx(bar_x + 8 * ((s + 1) & 1), 32768);
                            tma_load_2d_mc(sb + C2_XB + ((s + 1) & 1) * C2_XS + rank * 5120, &mapX, bar_x + 8 * ((s + 1) & 1), rank * 64, (s + 1) * SEGL, (uint16_t)0xff);
                            if (s + 2 < NSEG)
                                asm volatile("cp.async.bulk.prefetch.tensor.2d.L2.global [%0, {%1, %2}];" :: "l"((uint64_t)&mapX), "r"(rank * 64), "r"((s + 2) * SEGL) : "memory");
                        }
                    }
                    else if (lane >= 1 && lane < 5) mbar_expect_tx(bar_o + 8 * lane, lane == 1 ? 4096 : 8192);
                    if (lane == 16) mbar_expect_tx(bar_sx + 8 * (s & 1), 5120);
                    __syncwarp();
                }
            }
        }
        fence_async_smem();
        TS_MARK(12, 128);
        mbar_wait(bar_h + 8, 0);
        bar_sync<9, 128>();
        if (elect_one()) {
            mbar_arrive(bar_o);
#pragma unroll 1
            for (int i = 1; i < 8; i++) {
                const uint32_t d = (rank + i) & 7;
                bulk_s2s(mapa_u32(sb + c2_tslot(i) + w4 * 1024, d), sb + C2_QX + w4 * 1024, 1024, mapa_u32(bar_o + 8 * c2_grp(i), d));
            }
        }
        __syncwarp();
    } else {
        uint32_t va[5][2] = {};
        auto store_vt = [&](int s) {
            const uint32_t a = sb + C2_VT + (s & 1) * 6144 + a32;
            stmatrix_x4(a, va[0][0], va[0][1], va[1][0], va[1][1]);
            stmatrix_x4(a + 2048, va[2][0], va[2][1], va[3][0], va[3][1]);
            asm volatile("stmatrix.sync.aligned.m8n8.x2.shared.b16 [%0], {%1, %2};" :: "r"(a + 4096), "r"(va[4][0]), "r"(va[4][1]) : "memory");
        };
#pragma unroll 1
        for (int s = -1;;) {
            if (s >= 0) {
                const int t = tid - 256;
                const uint2* src = g_xbuf + ((s & 1) * 8 + rank) * 1024 + t;
                asm volatile("" : "+l"(src));
                const uint32_t ma = sb + C2_XB + ((s + 1) & 1) * C2_XS + rank * 5120 + 4096 + (t >> 4) * 128 + ((((t >> 1) & 7) ^ (t >> 4)) << 4) + (t & 1) * 8;
                uint32_t ra[8], rb[8];
#pragma unroll
                for (int i = 1; i < 8; i++) {
                    const uint32_t d = (rank + i) & 7;
                    ra[i] = pin(mapa_u32(ma, d)); rb[i] = pin(mapa_u32(bar_m + 8 * c2_grp(i), d));
                }
                if (s == NSEG - 1) break;
                bar_sync<11, 256>();
                DBGW(29, 0);
                {
                    uint32_t t0, t1;
                    asm volatile("mov.u32 %0, %%clock;" : "=r"(t0));
                    if (s == NSEG - 2 && w4 == 0 && elect_one()) tail_load(0, 0);
                    __syncwarp();
                    do { asm volatile("mov.u32 %0, %%clock;" : "=r"(t1)); } while (t1 - t0 < (uint32_t)CH_POLL_DELAY);
                }
                const uint32_t tag = ((s >> 1) & 1) ^ 1;
                uint32_t p[8][2], m0, m1;
                auto issue = [&](uint32_t (&x)[8][2]) {
#pragma unroll
                    for (int k = 0; k < 8; k++)
                        asm volatile("ld.relaxed.gpu.global.v2.u32 {%0, %1}, [%2];" : "=r"(x[k][0]), "=r"(x[k][1]) : "l"(src + k * 128) : "memory");
                };
                auto check = [&](const uint32_t (&x)[8][2]) {
                    uint32_t bad = 0, bad2 = 0;
                    float r[4];
#pragma unroll
                    for (int k = 0; k < 8; k++) {
                        asm("lop3.b32 %0, %0, %1, %2, 0xf6;" : "+r"(bad) : "r"(x[k][0]), "r"(tag));
                        asm("lop3.b32 %0, %0, %1, %2, 0xf6;" : "+r"(bad2) : "r"(x[k][1]), "r"(tag));
#pragma unroll
                        for (int e = 0; e < 2; e++) {
                            const float lo = __uint_as_float(x[k][e] << 16), hi = __uint_as_float(x[k][e] & 0xffff0000u);
                            r[2 * e] = k ? r[2 * e] + lo : lo;
                            r[2 * e + 1] = k ? r[2 * e + 1] + hi : hi;
                        }
                    }
                    m0 = pack_bf16(r[0], r[1]); m1 = pack_bf16(r[2], r[3]);
                    asm volatile("" : "+r"(m0), "+r"(m1));
                    return __all_sync(0xffffffff, ((bad | bad2) & 1u) == 0u);
                };
                for (int it = 0; it < (1 << 20); it++) {
                    issue(p);
                    if (check(p)) break;
                }
                DBGW(30, 0);
                st_async_v2(ra[1], m0, m1, rb[1]);
                asm volatile("st.shared.v2.b32 [%0], {%1, %2};" :: "r"(ma), "r"(m0), "r"(m1) : "memory");
                __syncwarp();
                if (lane == 0) mbar_arrive(bar_m);
#pragma unroll
                for (int i = 2; i < 8; i++) st_async_v2(ra[i], m0, m1, rb[i]);
                DBGW(31, 0);
                store_vt(s);
            }
            s++;
            const uint32_t ost = pin(sb + C2_OB + t32), pla = pin(sb + C2_PB + lane * 16), plb = pin(sb + C2_PB + 512 + (lane & 7) * 16);
            bar_sync<1, 384>();
            fence_async_smem();
            DBGW(24, 0);
            if (s < NSEG - 1) bar_sync<2, 224>();
            {
                float acc[20];
                c2_xstream<0, 32>(acc, w, dlo + ((C2_XB + (s & 1) * C2_XS) >> 4), rank, dlo + ((C2_WS + 2 * C2_NS * 2048) >> 4));
                wgmma_wait<0>();
#pragma unroll
                for (int j = 0; j < 5; j++) { va[j][0] = pack_bf16(acc[4 * j], acc[4 * j + 1]); va[j][1] = pack_bf16(acc[4 * j + 2], acc[4 * j + 3]); }
            }
            DBGW(26, 0);
            if (s < NSEG - 1) {
                uint32_t p[5];
                bar_sync<3, 160>();
                DBGW(27, 0);
                ldmatrix_x4_trans(p[0], p[1], p[2], p[3], pla);
                asm volatile("ldmatrix.sync.aligned.m8n8.x1.trans.shared.b16 {%0}, [%1];" : "=r"(p[4]) : "r"(plb) : "memory");
                float oa[4] = {0.f, 0.f, 0.f, 0.f}, ob[4] = {0.f, 0.f, 0.f, 0.f}, sa[4] = {0.f, 0.f, 0.f, 0.f}, sc[4] = {0.f, 0.f, 0.f, 0.f};
                const uint32_t one = 0x3f803f80u;
                mma_16816(sa, one, one, one, one, p[0], p[1]);
                mma_16816(oa, va[0][0], va[0][1], va[1][0], va[1][1], p[0], p[1]);
                mma_16816(sc, one, one, one, one, p[2], p[3]);
                mma_16816(ob, va[2][0], va[2][1], va[3][0], va[3][1], p[2], p[3]);
                mma_16816(sa, one, one, one, one, p[4], 0u);
                mma_16816(oa, va[4][0], va[4][1], 0u, 0u, p[4], 0u);
                bar_arrive<6, 384>();
                float i0, i1;
                asm("rcp.approx.ftz.f32 %0, %1;" : "=f"(i0) : "f"(sa[0] + sc[0]));
                asm("rcp.approx.ftz.f32 %0, %1;" : "=f"(i1) : "f"(sa[1] + sc[1]));
                sts32(ost, pack_bf16((oa[0] + ob[0]) * i0, (oa[2] + ob[2]) * i0));
                sts32(ost + 32, pack_bf16((oa[1] + ob[1]) * i1, (oa[3] + ob[3]) * i1));
                fence_async_smem();
                __syncwarp();
                if (elect_one()) {
#pragma unroll
                    for (int i = 1; i < 8; i++) {
                        const uint32_t d = (rank + i) & 7;
                        bulk_s2s(mapa_u32(sb + C2_OB + i * 1024 + w4 * 256, d), sb + C2_OB + w4 * 256, 256, mapa_u32(bar_o + 8 * c2_grp(i), d));
                        if (i == 1) mbar_arrive(bar_o);
                    }
                }
                __syncwarp();
                DBGW(28, 0);
            } else bar_arrive<6, 384>();
        }
        store_vt(NSEG - 1);
        fence_async_smem();
        bar_arrive<7, 256>();
        g_xbuf[((8 + rank) * 8 + C) * 128 + w4 * 32 + fresh_lane()] = make_uint2(0u, 0u);
    }
    if (wg != 1) {
        const uint32_t lane = fresh_lane(), g = lane >> 2, qc = lane & 3;
        const int row = w4 * 32 + C * 4 + (lane >> 3);
        float r[8], wb = 1.f;
#pragma unroll
        for (int i = 0; i < 8; i++) r[i] = 0.f;
#pragma unroll 1
        for (int q = wg;; q += 1 + (q & 1)) {
            if (q == 1 || q == 2) {
                tail_arrive(q - 1);
                if (w4 == 0) {
                    asm volatile("bar.sync %0, 160;" :: "r"(11 + q) : "memory");
                    mbar_wait(bar_h + 8 * (q - 1), 0);
                    if (elect_one()) tail_load(q, q - 1);
                    __syncwarp();
                }
            }
            if (wg == 2) {
                if (q == 2) wait_ctr(CT_P, 104u);
                const uint4* src = q == 2 ? g_part + PART_A15 + (rank >> 2) * 4096 + (row >> 4) * 512 + ((rank & 3) * 4 + ((lane >> 1) & 2) + ((row >> 3) & 1)) * 32 + (row & 7) * 4 + qc
                                          : g_part + PART_TAIL + (rank * 128 + row) * 64 + (lane & 7);
                const uint32_t step = q == 2 ? 8192 : 8;
                uint4 u[8];
                for (int it = 0; it < (1 << 20); it++) {
                    uint32_t mx = 0;
#pragma unroll
                    for (int k = 0; k < 8; k++)
                        asm volatile("ld.relaxed.gpu.global.v4.u32 {%0, %1, %2, %3}, [%4];" : "=r"(u[k].x), "=r"(u[k].y), "=r"(u[k].z), "=r"(u[k].w) : "l"(src + k * step) : "memory");
#pragma unroll
                    for (int k = 0; k < 8; k++) mx = max(max(mx, max(u[k].x, u[k].y)), max(u[k].z, u[k].w));
                    if (__all_sync(0xffffffff, mx != ~0u)) break;
                }
#pragma unroll
                for (int k = 0; k < 8; k++) {
                    const uint32_t v[4] = {u[k].x, u[k].y, u[k].z, u[k].w};
#pragma unroll
                    for (int e = 0; e < 4; e++) {
                        r[2 * e] = fmaf(wb, __uint_as_float(v[e] << 16), r[2 * e]);
                        r[2 * e + 1] = fmaf(wb, __uint_as_float(v[e] & 0xffff0000u), r[2 * e + 1]);
                    }
                }
                if (q == 3) {
                    *reinterpret_cast<uint4*>(P.out + (size_t)(SEQ - 128 + row) * DM + rank * 64 + (lane & 7) * 8) =
                        quad_transpose(pack_bf16(r[0], r[1]), pack_bf16(r[2], r[3]), pack_bf16(r[4], r[5]), pack_bf16(r[6], r[7]), lane);
                    TS_MARK(15, 256 + 96);
                    break;
                }
                asm volatile("ld.relaxed.gpu.global.f32 %0, [%1];" : "=f"(wb) : "l"(g_gate + SEQ - 128 + row) : "memory");
                wb = 1.f - wb;
                TS_MARK(13, 256);
            }
            float acc[16];
#pragma unroll
            for (int i = 0; i < 16; i++) acc[i] = 0.f;
            uint32_t da = dlo + (C2_WO >> 4), db = dlo + (q < 3 ? ((C2_XB + (q >> 1) * C2_XS) >> 4) + rank * 320 : c2_tslot(0) >> 4);
            uint32_t bar = q < 3 ? bar_x + 8 * (q >> 1) : bar_o;
            const uint32_t d0 = q < 3 ? -320 : 256, k1 = q < 3 ? rank : 0, d1 = q < 3 ? 2240 : (c2_tslot(1) - c2_tslot(0)) >> 4;
            const uint32_t k2 = q < 3 ? 8 : 3, bm = q < 3 ? 0 : 0x2b << 3;
#pragma unroll 1
            for (uint32_t i = 0; i < 8; i++) {
                mbar_wait(bar, q & 1);
                wgmma_fence();
#pragma unroll
                for (int kk = 0; kk < 4; kk++) wgmma_ss_n32_ta(acc, da + kk * 128, db + kk * 2);
                wgmma_commit();
                da += 512;
                db += i == k1 ? d1 : i == k2 ? (c2_tslot(4) - c2_tslot(3)) >> 4 : d0;
                bar += (bm >> i) & 8;
            }
            if (q == 0) wait_ctr(CT_P, 104u);
            wgmma_wait<0>();
            uint32_t* dst = reinterpret_cast<uint32_t*>(g_part + PART_TAIL + ((rank * 128 + q * 32 + 2 * qc) * 8 + C) * 8 + (w4 >> 1) * 4 + (g & 3)) + (w4 & 1) * 2 + (g >> 2);
#pragma unroll
            for (int j = 0; j < 4; j++) {
                asm volatile("st.relaxed.gpu.global.u32 [%0], %1;" :: "l"(dst + j * 8 * 256), "r"(pack_bf16(acc[4 * j], acc[4 * j + 2])) : "memory");
                asm volatile("st.relaxed.gpu.global.u32 [%0], %1;" :: "l"(dst + (j * 8 + 1) * 256), "r"(pack_bf16(acc[4 * j + 1], acc[4 * j + 3])) : "memory");
            }
            TS_MARK(q == 2 ? 14 : q == 3 ? 11 : 9 + q, q == 2 ? 256 : 0);
            if (q == 3) break;
        }
    }
    cluster_sync_relaxed();
    if (warp == 0) finish_launch(fresh_lane());
    TS_END(2);
}

struct Proj2Params {
    CUtensorMap mapA[2];
    CUtensorMap mapW[3];
    bf16* out[3];
};
#define P2T(i)
#define P2_NOMMA 0
#define P2_NOLOAD 0
constexpr int P2_STAGES = 6;
constexpr int P2_SMEM = 131072 + P2_STAGES * 16384 + 1024 + 1024;
constexpr int P2_ITEMS = 168 + 48;
__device__ __forceinline__ int p2_reps(int t) { return t >= 168 ? 1 : 2; }
__device__ __forceinline__ void p2_tile(int t, int w, int& z, int& mp, int& head) {
    if (t >= 168) { w += ((t - 168) & 1) * 2; t = 168 + ((t - 168) >> 1); }
    const int hq = t / 24, v = t % 24;
    mp = v & 7;
    if (v < 16) { head = hq * 4 + (v >> 3) * 2 + (w >> 1); z = 1 + (w & 1); }
    else { head = hq * 4 + w; z = 0; }
}
__device__ __forceinline__ void mbar_arrive_remote(uint32_t bar_cluster_addr) {
    asm volatile("mbarrier.arrive.release.cluster.shared::cluster.b64 _, [%0];" :: "r"(bar_cluster_addr) : "memory");
}
__device__ __forceinline__ void mbar_arrive_cl(uint32_t bar_cluster_addr) {
    asm volatile("mbarrier.arrive.shared::cluster.b64 _, [%0];" :: "r"(bar_cluster_addr) : "memory");
}
__device__ __forceinline__ void mbar_wait_acq_cluster(uint32_t bar, uint32_t parity) {
    asm volatile(
        "{\n"
        ".reg .pred p, q;\n"
        ".reg .u32 c;\n"
        "mov.u32 c, 0;\n"
        "WAIT_LOOP_C:\n"
        "mbarrier.try_wait.parity.acquire.cluster.shared::cta.b64 p, [%0], %1;\n"
        "@p bra WAIT_DONE_C;\n"
        "add.u32 c, c, 1;\n"
        "setp.lt.u32 q, c, 4000000;\n"
        "@q bra WAIT_LOOP_C;\n"
        "WAIT_DONE_C:\n"
        "}\n" :: "r"(bar), "r"(parity) : "memory");
}
#define P2_PACE 35
#define P2_PACE2 0
template <bool PERM, int PACE = 0>
__device__ __forceinline__ void store_frag_128(const float (&acc)[64], bf16* obase, int lane) {
#pragma unroll
    for (int rr = 0; rr < 2; rr++)
#pragma unroll
        for (int g = 0; g < 4; g++) {
            const float* a = &acc[g * 16 + rr * 2];
            const uint32_t p0 = pack_bf16(a[0], a[1]), p1 = pack_bf16(a[4], a[5]), p2 = pack_bf16(a[8], a[9]), p3 = pack_bf16(a[12], a[13]);
            *reinterpret_cast<uint4*>(obase + (size_t)(rr * 8) * HD + g * 32) = PERM ? make_uint4(p0, p1, p2, p3) : quad_transpose(p0, p1, p2, p3, lane);
            pace(PACE);
        }
}
__global__ void __cluster_dims__(2, 1, 1) __launch_bounds__(384, 1) proj2_kernel(const __grid_constant__ Proj2Params P) {
    extern __shared__ uint8_t smem_raw[];
    const uint32_t sbase = (smem_u32(smem_raw) + 1023) & ~1023u;
    const uint32_t sA = sbase, sB = sbase + 131072, sC = sB + P2_STAGES * 16384;
    const uint32_t bars = sC;
    const uint32_t a_full = bars, a_empty = bars + 64, b_full = bars + 128, b_empty = b_full + 8 * P2_STAGES;
    const uint32_t item_bar = b_empty + 8 * P2_STAGES, item_in = item_bar + 16, slot = item_in + 16;
    const uint32_t note_bar = slot + 16, note_free = note_bar + 64, note = note_free + 64;
    const int warp = threadIdx.x >> 5, lane = threadIdx.x & 31;
    const uint32_t rank = cluster_ctarank();
    TS_BEGIN(0);
    if (threadIdx.x == 0) {
        for (int i = 0; i < 8; i++) { mbar_init(a_full + 8 * i, 1); mbar_init(a_empty + 8 * i, 2); }
        for (int i = 0; i < P2_STAGES; i++) { mbar_init(b_full + 8 * i, 1); mbar_init(b_empty + 8 * i, 2); }
        mbar_init(item_bar, 1); mbar_init(item_bar + 8, 1); mbar_init(item_in, 2); mbar_init(item_in + 8, 2);
        for (int i = 0; i < 8; i++) { mbar_init(note_bar + 8 * i, 1); mbar_init(note_free + 8 * i, 1); }
        asm volatile("fence.mbarrier_init.release.cluster;" ::: "memory");
    }
    __syncwarp();
    cluster_sync_relaxed();
    pdl_launch_dependents();
    if (warp == 9) {
        if (lane == 0) {
            if (P2_MARK == 4) {
                for (int k = 0; k < 4; k++) { mbar_wait(a_full + 8 * (2 * k + 1), 0); TS_MARK2(8 + k, 288); }
                for (int k = 0; k < 4; k++) { mbar_wait(b_full + 8 * (k + 2), 0); TS_MARK2(12 + k, 288); }
            }
            for (int n = 0;; n++) {
                const int e = (n & 1) * 4 + ((n >> 1) & 3);
                mbar_wait(note_bar + 8 * e, (n >> 3) & 1);
                int m;
                asm volatile("ld.shared.s32 %0, [%1];" : "=r"(m) : "r"(note + e * 4) : "memory");
                mbar_arrive(note_free + 8 * e);
                if (m < 0) break;
                signal_ctr(m);
            }
        }
    } else if (warp == 10) {
        if (lane == 0) {
            auto publish = [&](int ic, int tq) {
                const int t = tq < P2_ITEMS ? tq : -1;
                asm volatile("st.shared.s32 [%0], %1;" :: "r"(slot + (ic & 3) * 4), "r"(t) : "memory");
                mbar_arrive(item_bar + 8 * (ic & 1));
                st_async_b32(mapa_u32(slot + (ic & 3) * 4, 1), (uint32_t)t, mapa_u32(item_bar + 8 * (ic & 1), 1));
            };
            const int npair = (int)(gridDim.x >> 1), pair = (int)(blockIdx.x >> 1);
            if (rank == 0) publish(0, pair);
            for (int ic = 0;; ic++) {
                if (rank == 1) mbar_expect_tx(item_bar + 8 * (ic & 1), 4);
                mbar_wait(item_bar + 8 * (ic & 1), (ic >> 1) & 1);
                int t;
                asm volatile("ld.shared.s32 %0, [%1];" : "=r"(t) : "r"(slot + (ic & 3) * 4) : "memory");
                if (t < 0) break;
                int z0, mp, h0;
                p2_tile(t, 0, z0, mp, h0);
                const int aidx = z0 >= 1 ? 1 : 0;
                const int m0 = (2 * mp + (int)rank) * 128;
                for (int k = 0; k < 8; k++) {
                    mbar_wait(a_empty + 8 * k, (ic & 1) ^ 1);
                    if (P2_NOLOAD) mbar_arrive(a_full + 8 * k); else {
                    mbar_expect_tx(a_full + 8 * k, 16384);
                    tma_load_2d(sA + k * 16384, &P.mapA[aidx], a_full + 8 * k, k * 64, m0); }
                }
                if (rank == 0) {
                    mbar_wait(item_in + 8 * (ic & 1), (ic >> 1) & 1);
                    publish(ic + 1, ic == 0 ? npair + pair : 2 * npair + (int)atomicAdd(&g_ctr[CT_PROJ], 1u));
                }
            }
        }
    } else if (warp == 8 || warp == 11) {
        if (lane == 0) {
            const int par2 = warp == 8 ? 0 : 1;
            int it = 0; uint32_t bph = 0;
            for (int ic = 0;; ic++) {
                mbar_wait(item_bar + 8 * (ic & 1), (ic >> 1) & 1);
                int t;
                asm volatile("ld.shared.s32 %0, [%1];" : "=r"(t) : "r"(slot + (ic & 3) * 4) : "memory");
                if (t < 0) break;
                const int nt = 2 * p2_reps(t);
                for (int w = 0; w < nt; w++) {
                    int z, mp, hd;
                    p2_tile(t, w, z, mp, hd);
                    for (int k = 0; k < 8; k++) {
                        const int s = it; const uint32_t phb = bph;
                        if (++it == P2_STAGES) { it = 0; bph ^= 1; }
                        if ((k & 1) != par2) continue;
                        mbar_wait(b_empty + 8 * s, phb ^ 1);
                        if (P2_NOLOAD) { mbar_arrive(b_full + 8 * s); continue; }
                        mbar_expect_tx(b_full + 8 * s, 16384);
                        tma_load_2d_mc(sB + s * 16384 + rank * 8192, &P.mapW[z], b_full + 8 * s, hd * 128 + (int)rank * 64, k * 64, (uint16_t)3);
                    }
                }
            }
        }
    } else {
        const int wg = warp >> 2;
        float acc[2][64];
        const uint32_t a_lo = desc_lo(sA, 16), b_lo0 = desc_lo(sB, 8192);
        const bool elected = (threadIdx.x & 127) == 0;
        int s = (wg * 8) % P2_STAGES;
        uint32_t ph = ((wg * 8) / P2_STAGES) & 1;
        int nnote = 0;
        if (wg == 1) asm volatile("bar.arrive 3, 256;" ::: "memory");
        for (int ic = 0;; ic++) {
            mbar_wait(item_bar + 8 * (ic & 1), (ic >> 1) & 1);
            int t;
            asm volatile("ld.shared.s32 %0, [%1];" : "=r"(t) : "r"(slot + (ic & 3) * 4) : "memory");
            P2T(7);
            if (wg == 0 && t < 0) {
                if (elected) {
                    const int e = nnote & 3;
                    mbar_wait(note_free + 8 * e, ((nnote >> 2) & 1) ^ 1);
                    asm volatile("st.shared.s32 [%0], %1;" :: "r"(note + e * 4), "r"(-1) : "memory");
                    mbar_arrive(note_bar + 8 * e);
                }
            }
            if (t < 0) break;
            const int reps = p2_reps(t);
#pragma unroll 1
            for (int rp = 0; rp < reps; rp++) {
            const bool first = rp == 0, last = rp == reps - 1;
            int z, mp, head;
            p2_tile(t, rp * 2 + wg, z, mp, head);
            asm volatile("bar.sync %0, 256;" :: "r"(3 + wg) : "memory");
            P2T(0);
            if (wg == 1 && last && elected) mbar_arrive_cl(mapa_u32(item_in + 8 * (ic & 1), 0));
            int sprev = 0;
#pragma unroll
            for (int k = 0; k < 8; k++) {
                if (k == 0) P2T(5);
                if (wg == 0 && first) mbar_wait(a_full + 8 * k, ic & 1);
                if (k == 0) P2T(6);
                if (P2_MARK == 1 && k == 0 && ic == 0 && first) TS_MARK2(8, 0);
                if (P2_MARK == 3 && ic == 0 && first) TS_MARK2(8 + k, 0);
                mbar_wait(b_full + 8 * s, ph);
                if (k == 7) asm volatile("bar.arrive %0, 256;" :: "r"(4 - wg) : "memory");
                if (k == 0) P2T(1);
                if (P2_MARK == 1 && k == 0 && ic == 0 && first) TS_MARK2(9, 0);
                if (P2_MARK == 2 && ic == 0 && first) TS_MARK2(8 + k, 0);
                if (k == 7) P2T(2);
                const uint32_t b_lo = b_lo0 + s * 1024;
                wgmma_fence();
#pragma unroll
                for (int kk = 0; kk < (P2_NOMMA ? 1 : 4); kk++) {
                    wgmma_ss_n128_lo<1>(acc[0], a_lo + k * 1024 + kk * 2, b_lo + kk * 128, (k | kk) != 0);
                    wgmma_ss_n128_lo<1>(acc[1], a_lo + k * 1024 + 512 + kk * 2, b_lo + kk * 128, (k | kk) != 0);
                }
                wgmma_commit();
                if (k > 0) {
                    wgmma_wait<1>();
                    if (elected) {
                        const uint32_t e = b_empty + 8 * sprev;
                        mbar_arrive_cl(mapa_u32(e, 0)); mbar_arrive_cl(mapa_u32(e, 1));
                        if (last) mbar_arrive(a_empty + 8 * (k - 1));
                    }
                }
                sprev = s;
                if (++s == P2_STAGES) { s = 0; ph ^= 1; }
            }
            wgmma_wait<0>();
            P2T(3);
            if (P2_MARK == 1 && ic == 0 && first) TS_MARK2(10, 0);
            if (P2_MARK == 1 && ic < 4 && last) TS_MARK2(12 + ic, 128);
            if (elected) {
                const uint32_t e = b_empty + 8 * sprev;
                mbar_arrive_cl(mapa_u32(e, 0)); mbar_arrive_cl(mapa_u32(e, 1));
                if (last) mbar_arrive(a_empty + 8 * 7);
            }
            s += 8 % P2_STAGES; ph ^= (8 / P2_STAGES) & 1;
            if (s >= P2_STAGES) { s -= P2_STAGES; ph ^= 1; }
            const int m0 = (2 * mp + (int)rank) * 128;
            bf16* obase = P.out[z] + ((size_t)head * SEQ + m0 + (warp & 3) * 16 + (lane >> 2)) * HD + (lane & 3) * 8;
            store_frag_128<true, P2_PACE>(acc[0], obase, lane); store_frag_128<true, P2_PACE>(acc[1], obase + (size_t)64 * HD, lane);
            P2T(4);
            if (P2_MARK == 1 && ic == 0 && first) TS_MARK2(11, 0);
            {
                asm volatile("bar.sync %0, 128;" :: "r"(1 + wg) : "memory");
                if (elected) {
                    const int e = wg * 4 + (nnote & 3);
                    mbar_wait(note_free + 8 * e, ((nnote >> 2) & 1) ^ 1);
                    asm volatile("st.shared.s32 [%0], %1;" :: "r"(note + e * 4), "r"(CT_AP + (head >> 1)) : "memory");
                    mbar_arrive(note_bar + 8 * e);
                }
                nnote++;
            }
            }
        }
        TS_END(0);
    }
    __syncwarp();
    cluster_sync_relaxed();
}

struct OutParams {
    CUtensorMap mapCtx[2];
    CUtensorMap mapWo[2];
    bf16* out;
};
#define OT(i)
#define OTP(i)
#define O4_D 2
#define O4_CD 2000
#define O4_CP 0
constexpr int O4_GRID = 68;
constexpr int O2_SMEM = 196608 + 1024 + 256;
struct OutJob { int mt, a0, na, b0, nb, member; };
__device__ __forceinline__ OutJob out_job(int pair, int j) {
    OutJob J;
    if (pair < 26) {
        J.member = pair >= 13; J.mt = J.member ? 25 - pair : pair;
        const int d = (12 - J.mt) * O4_D / 12;
        J.a0 = J.member ? 32 + d : 0; J.na = J.member ? 32 - d : 32 + d;
        J.b0 = J.member * 32; J.nb = 32;
    } else {
        J.member = pair - 26; J.mt = j ? 12 + j : 15;
        J.a0 = J.b0 = J.member * 8; J.na = 8; J.nb = j ? 8 : 0;
    }
    return J;
}
__device__ __forceinline__ void tma_load_3d(uint32_t dst, const CUtensorMap* map, uint32_t bar, int c0, int c1, int c2) {
    asm volatile(
        "cp.async.bulk.tensor.3d.shared::cluster.global.mbarrier::complete_tx::bytes [%0], [%1, {%3, %4, %5}], [%2];"
        :: "r"(dst), "l"((uint64_t)map), "r"(bar), "r"(c0), "r"(c1), "r"(c2) : "memory");
}
__device__ __forceinline__ void out_weights(const OutParams& P, uint32_t sbase, uint32_t bar_full, uint32_t bar_empty, int pair, int rank, bool fresh) {
    int s = 0, n = 0; uint32_t ph = 0;
#pragma unroll 1
    for (int j = 0; j < (pair < 26 ? 1 : 3); j++) {
        const OutJob J = out_job(pair, j);
#pragma unroll 1
        for (int i = 0; i < J.na + J.nb; i++, n++) {
            if (!fresh) mbar_wait(bar_empty + 8 * s, ph);
            else if (n >= 4) mbar_wait(bar_empty + 8 * s, ph ^ 1);
            const int b = i >= J.na, k = b ? J.b0 + i - J.na : J.a0 + i;
            const int h = pair < 26 ? J.member * 2 : 0;
            tma_load_3d(sbase + s * 49152 + 16384, &P.mapWo[b], bar_full + 8 * s, 0, k * 64, rank * 4 + h);
            tma_load_3d(sbase + s * 49152 + 32768, &P.mapWo[b], bar_full + 8 * s, 0, k * 64, rank * 4 + 2 - h);
            if (++s == 4) { s = 0; ph ^= 1; }
        }
    }
}
__device__ __forceinline__ void out_ctx(const OutParams& P, uint32_t sbase, uint32_t bar_full, uint32_t bar_empty, int pair, int rank, bool fresh) {
    int s = 0, n = 0; uint32_t ph = 0;
#pragma unroll 1
    for (int j = 0; j < (pair < 26 ? 1 : 3); j++) {
        const OutJob J = out_job(pair, j);
#pragma unroll 1
        for (int i = 0; i < J.na + J.nb; i++, n++) {
            const int b = i >= J.na, k = b ? J.b0 + i - J.na : J.a0 + i;
            if (i == 0 && k < 2 * O2_HE) wait_ctr(CT_CA + J.mt * 2, 2u * O2_HE);
            if (!b && (i == 0 ? k >= 2 * O2_HE : k == 2 * O2_HE)) wait_ctr(CT_CA + J.mt * 2 + 1, 2u * (NH - O2_HE));
            if (i == J.na) wait_ctr(CT_CB + max(J.mt, CB_FIRST), 64u);
            if (!fresh) mbar_wait(bar_empty + 8 * s, ph);
            else if (n >= 4) mbar_wait(bar_empty + 8 * s, ph ^ 1);
            mbar_expect_tx(bar_full + 8 * s, 49152);
            tma_load_2d_mc(sbase + s * 49152 + rank * 8192, &P.mapCtx[b], bar_full + 8 * s, (k & 1) * 64, (k >> 1) * SEQ + J.mt * 128 + rank * 64, (uint16_t)3);
            if (++s == 4) { s = 0; ph ^= 1; }
        }
    }
}
__device__ __forceinline__ void out_consumer(const OutParams& P, uint32_t sbase, uint32_t bar_full, uint32_t bar_empty, int pair, int rank, int warp, int lane) {
    const int wg = warp >> 2;
    const bool elected = (warp & 3) == 0 && lane == 0;
    const int row = warp * 16 + (lane >> 2);
    int s = 0, sprev = 0; uint32_t ph = 0;
    auto release = [&](int st) {
        if (elected) { const uint32_t e = bar_empty + 8 * st; mbar_arrive_cl(mapa_u32(e, 0)); mbar_arrive_cl(mapa_u32(e, 1)); }
    };
    wait_ctr(CT_G, FA_GRID);
#pragma unroll 1
    for (int j = 0; j < (pair < 26 ? 1 : 3); j++) {
        const OutJob J = out_job(pair, j);
        float g0, g1, acc[128];
        asm volatile("ld.relaxed.gpu.global.f32 %0, [%1];" : "=f"(g0) : "l"(g_gate + J.mt * 128 + row) : "memory");
        asm volatile("ld.relaxed.gpu.global.f32 %0, [%1];" : "=f"(g1) : "l"(g_gate + J.mt * 128 + row + 8) : "memory");
#pragma unroll
        for (int e = 0; e < 128; e++) acc[e] = 0.f;
#pragma unroll 1
        for (int i = 0; i < J.na + J.nb; i++) {
            mbar_wait(bar_full + 8 * s, ph);
            if (i == 0) OT(1);
            if (i == J.na) {
                OT(2);
                wgmma_wait<0>();
                const float w0 = fmaxf(1.f - g0, 0x1p-40f), w1 = fmaxf(1.f - g1, 0x1p-40f);
                const float r0 = __fdividef(g0, w0), r1 = __fdividef(g1, w1);
                g0 = w0; g1 = w1;
#pragma unroll
                for (int e = 0; e < 32; e++) { acc[4 * e] *= r0; acc[4 * e + 1] *= r0; acc[4 * e + 2] *= r1; acc[4 * e + 3] *= r1; }
            }
            const uint32_t sa = sbase + s * 49152 + wg * 8192, sb = sbase + s * 49152 + 16384;
            wgmma_fence();
#pragma unroll
            for (int kk = 0; kk < 4; kk++)
                wgmma_ss_n256_tb(acc, make_desc(sa + kk * 32, 16, 1024), make_desc(sb + kk * 2048, 8192, 1024), 1);
            wgmma_commit();
            if (i > 0) { wgmma_wait<1>(); release(sprev); }
            sprev = s;
            if (++s == 4) { s = 0; ph ^= 1; }
        }
        if (j == 0) wait_ctr(CT_P, 104u);
        wgmma_wait<0>();
        release(sprev);
        OT(4);
        uint32_t p[16][4];
#pragma unroll
        for (int e = 0; e < 16; e++)
#pragma unroll
            for (int i = 0; i < 4; i++) {
                const float* a = &acc[(e >> 1) * 16 + (e & 1) * 2 + 4 * i];
                p[e][i] = pack_bf16(a[0] * ((e & 1) ? g1 : g0), a[1] * ((e & 1) ? g1 : g0));
            }
        const bool two = pair < 26;
        const uint4* part = g_part + (two ? (J.mt * 2 + rank) * 4096 + warp * 256 : (26 + (J.mt - 13) * 16 + rank) * 4096 + warp * 512) + lane;
        {
            const uint4* dst = part + (two ? J.member * 2048 - 256 : J.member * 8192);
#pragma unroll
            for (int e = 15; e >= 0; e--) {
                if (e == 7 && two) break;
                asm volatile("st.relaxed.gpu.global.v4.u32 [%0], {%1, %2, %3, %4};" :: "l"(dst + e * 32), "r"(p[e][0]), "r"(p[e][1]), "r"(p[e][2]), "r"(p[e][3]) : "memory");
            }
        }
        OT(5);
        bf16* dst = P.out + (size_t)(J.mt * 128 + row) * DM + rank * 256 + J.member * (two ? 128 : 32) + (lane & 3) * 8;
        const uint32_t step = two ? 32 : 8192;
        part += two ? 2048 - J.member * 2048 : J.member * 64;
#pragma unroll 1
        for (int c = 0; c < (J.nb ? 2 : 0); c++) {
            uint32_t u[8][4];
            for (int it = 0; it < (1 << 20); it++) {
                uint32_t mx = 0;
#pragma unroll
                for (int i = 0; i < 8; i++)
                    asm volatile("ld.relaxed.gpu.global.v4.u32 {%0, %1, %2, %3}, [%4];" : "=r"(u[i][0]), "=r"(u[i][1]), "=r"(u[i][2]), "=r"(u[i][3]) : "l"(part + c * 32 + i * step) : "memory");
#pragma unroll
                for (int i = 0; i < 8; i++) mx = max(max(mx, max(u[i][0], u[i][1])), max(u[i][2], u[i][3]));
                if (__all_sync(0xffffffff, mx != ~0u)) break;
            }
            if (two) {
#pragma unroll
                for (int e = 0; e < 8; e++) {
#pragma unroll
                    for (int i = 0; i < 4; i++) asm("add.rn.bf16x2 %0, %0, %1;" : "+r"(u[e][i]) : "r"(p[e][i]));
                    *reinterpret_cast<uint4*>(dst + (e & 1) * 8 * DM + (e >> 1) * 32) = quad_transpose(u[e][0], u[e][1], u[e][2], u[e][3], lane);
                }
                break;
            }
            float r[8];
#pragma unroll
            for (int m = 0; m < 8; m++)
#pragma unroll
                for (int i = 0; i < 4; i++) {
                    const float lo = __uint_as_float(u[m][i] << 16), hi = __uint_as_float(u[m][i] & 0xffff0000u);
                    r[2 * i] = m ? r[2 * i] + lo : lo; r[2 * i + 1] = m ? r[2 * i + 1] + hi : hi;
                }
            *reinterpret_cast<uint4*>(dst + c * 8 * DM) = quad_transpose(pack_bf16(r[0], r[1]), pack_bf16(r[2], r[3]), pack_bf16(r[4], r[5]), pack_bf16(r[6], r[7]), lane);
        }
        OT(6);
        if (j == 0) OT(3);
        if (j == 1) OT(7);
    }
}

__global__ void __cluster_dims__(2, 1, 1) __launch_bounds__(384, 1) out4_kernel(const __grid_constant__ OutParams P) {
    extern __shared__ uint8_t smem_raw[];
    const uint32_t sbase = (smem_u32(smem_raw) + 1023) & ~1023u;
    const uint32_t bar_full = sbase + 196608, bar_empty = bar_full + 64;
    const int warp = __shfl_sync(0xffffffff, threadIdx.x >> 5, 0), lane = threadIdx.x & 31;
    const int rank = (int)cluster_ctarank(), pair = blockIdx.x >> 1;
    TS_BEGIN(4);
    OT(0);
    if (threadIdx.x == 0) {
        for (int i = 0; i < 4; i++) { mbar_init(bar_full + 8 * i, 1); mbar_init(bar_empty + 8 * i, 4); }
        asm volatile("fence.mbarrier_init.release.cluster;" ::: "memory");
    }
    if (threadIdx.x == 256) asm volatile("prefetch.tensormap [%0];" :: "l"((uint64_t)&P.mapCtx[0]) : "memory");
    if (threadIdx.x == 352) asm volatile("prefetch.tensormap [%0];" :: "l"((uint64_t)&P.mapWo[0]) : "memory");
    if (warp == 0 || warp == 11) asm volatile("bar.sync 1, 64;" ::: "memory");
    __syncwarp();
    asm volatile("barrier.cluster.arrive.relaxed.aligned;" ::: "memory");
    if (warp == 11) {
        if (lane == 0) out_weights(P, sbase, bar_full, bar_empty, pair, rank, true);
        __syncwarp();
        asm volatile("barrier.cluster.wait.acquire.aligned;" ::: "memory");
    } else {
        asm volatile("barrier.cluster.wait.acquire.aligned;" ::: "memory");
        if (warp == 8 && lane == 0) out_ctx(P, sbase, bar_full, bar_empty, pair, rank, true);
        if (warp > 8 && pair < 26) {
            pace(O4_CD);
#pragma unroll 1
            for (int i = (blockIdx.x * 2 + warp - 9) * 32 + lane; i < PART_N; i += 104 * 32) { g_part[PART_N - 1 - i] = make_uint4(~0u, ~0u, ~0u, ~0u); if (O4_CP) pace(O4_CP); }
            wait_ctr(CT_G, FA_GRID);
            __syncwarp();
            if (lane == 0) signal_ctr_generic(CT_P);
        }
        if (warp < 8) out_consumer(P, sbase, bar_full, bar_empty, pair, rank, warp, lane);
    }
    __syncthreads();
    asm volatile("barrier.cluster.arrive.relaxed.aligned;" ::: "memory");
    if (warp == 0) finish_launch(lane);
    asm volatile("barrier.cluster.wait.acquire.aligned;" ::: "memory");
    TS_END(4);
}

typedef CUresult (*PFN_encodeTiled)(CUtensorMap*, CUtensorMapDataType, cuuint32_t, void*, const cuuint64_t*,
                                    const cuuint64_t*, const cuuint32_t*, const cuuint32_t*, CUtensorMapInterleave,
                                    CUtensorMapSwizzle, CUtensorMapL2promotion, CUtensorMapFloatOOBfill);
static PFN_encodeTiled g_encode = nullptr;

static void make_map(CUtensorMap* m, const void* ptr, uint64_t rows, uint64_t cols, uint32_t box_rows, bool sw64 = false) {
    cuuint64_t dims[2] = {cols, rows};
    cuuint64_t strides[1] = {cols * 2};
    cuuint32_t box[2] = {sw64 ? 32u : 64u, box_rows};
    cuuint32_t es[2] = {1, 1};
    g_encode(m, CU_TENSOR_MAP_DATA_TYPE_BFLOAT16, 2, const_cast<void*>(ptr), dims, strides, box, es,
             CU_TENSOR_MAP_INTERLEAVE_NONE, sw64 ? CU_TENSOR_MAP_SWIZZLE_64B : CU_TENSOR_MAP_SWIZZLE_128B, CU_TENSOR_MAP_L2_PROMOTION_L2_256B,
             CU_TENSOR_MAP_FLOAT_OOB_FILL_NONE);
}

static void make_map3(CUtensorMap* m, const void* ptr, uint64_t rows, uint64_t cols, uint32_t box_rows, uint32_t nblk) {
    cuuint64_t dims[3] = {64, rows, cols / 64};
    cuuint64_t strides[2] = {cols * 2, 128};
    cuuint32_t box[3] = {64u, box_rows, nblk};
    cuuint32_t es[3] = {1, 1, 1};
    g_encode(m, CU_TENSOR_MAP_DATA_TYPE_BFLOAT16, 3, const_cast<void*>(ptr), dims, strides, box, es,
             CU_TENSOR_MAP_INTERLEAVE_NONE, CU_TENSOR_MAP_SWIZZLE_128B, CU_TENSOR_MAP_L2_PROMOTION_L2_256B, CU_TENSOR_MAP_FLOAT_OOB_FILL_NONE);
}

template <typename... KArgs, typename... Args>
static void launch_pdl(void (*kernel)(KArgs...), int grid, int block, size_t smem, cudaStream_t st, bool pdl, Args... args) {
    cudaLaunchConfig_t cfg = {};
    cfg.gridDim = dim3(grid); cfg.blockDim = dim3(block); cfg.dynamicSmemBytes = smem; cfg.stream = st;
    cudaLaunchAttribute at[1];
    at[0].id = cudaLaunchAttributeProgrammaticStreamSerialization;
    at[0].val.programmaticStreamSerializationAllowed = 1;
    cfg.attrs = at; cfg.numAttrs = pdl ? 1 : 0;
    cudaLaunchKernelEx(&cfg, kernel, KArgs(args)...);
}

extern "C" void kernel_launch(void* const* d_in, const int* in_sizes, int n_in, void* d_out, int out_size) {
    const bf16* x = (const bf16*)d_in[0];
    const bf16* ckv = (const bf16*)d_in[1];
    const bf16* wq = (const bf16*)d_in[2];
    const bf16* wuk = (const bf16*)d_in[3];
    const bf16* wuv = (const bf16*)d_in[4];
    const bf16* wo = (const bf16*)d_in[5];
    const bf16* mem0 = (const bf16*)d_in[7];
    const bf16* Wq = (const bf16*)d_in[8];
    const bf16* Wk = (const bf16*)d_in[9];
    const bf16* Wv = (const bf16*)d_in[10];
    const bf16* Wo = (const bf16*)d_in[11];
    const bf16* gate_w = (const bf16*)d_in[13];
    bf16* out = (bf16*)d_out;

    static Proj2Params P2;
    static ChainParams CP;
    static AttnParams AP;
    static OutParams OP;
    static bool init = false;
    static const void* last_in[15];
    bool same = init;
    for (int i = 0; i < 14 && same; i++) same = last_in[i] == d_in[i];
    same = same && last_in[14] == d_out;
    if (!init) {
        cudaDriverEntryPointQueryResult qr;
        cudaGetDriverEntryPoint("cuTensorMapEncodeTiled", (void**)&g_encode, cudaEnableDefault, &qr);
        cudaFuncSetAttribute(proj2_kernel, cudaFuncAttributeMaxDynamicSharedMemorySize, P2_SMEM);
        cudaFuncSetAttribute(attn_kernel, cudaFuncAttributeMaxDynamicSharedMemorySize, FA_SMEM);
        cudaFuncSetAttribute(chain_kernel, cudaFuncAttributeMaxDynamicSharedMemorySize, C2_SMEM);
        cudaFuncSetAttribute(out4_kernel, cudaFuncAttributeMaxDynamicSharedMemorySize, O2_SMEM);
        init = true;
    }
    if (!same) {
        for (int i = 0; i < 14; i++) last_in[i] = d_in[i];
        last_in[14] = d_out;
        void *pQA, *pKA, *pVA, *pCA, *pCB;
        cudaGetSymbolAddress(&pQA, g_QA); cudaGetSymbolAddress(&pKA, g_KA); cudaGetSymbolAddress(&pVA, g_VA);
        cudaGetSymbolAddress(&pCA, g_ctxA); cudaGetSymbolAddress(&pCB, g_ctxB);
        make_map(&P2.mapA[0], x, SEQ, DM, 128);
        make_map(&P2.mapA[1], ckv, SEQ, DM, 128);
        const void* ws[3] = {wq, wuk, wuv};
        void* cs[3] = {pQA, pKA, pVA};
        for (int i = 0; i < 3; i++) { make_map(&P2.mapW[i], ws[i], DM, NQ, 64); P2.out[i] = (bf16*)cs[i]; }
        make_map(&CP.mapX, x, SEQ, DM, SEGL);
        make_map(&CP.mapM, mem0, NMEM, DM, NMEM);
        make_map(&CP.mapW[0], Wq, DM, NQ, 64);
        make_map(&CP.mapW[1], Wk, DM, NQ, 64);
        make_map(&CP.mapW[2], Wv, DM, NQ, 64);
        make_map(&CP.mapWo, Wo, NQ, DM, 64);
        make_map(&AP.mapQ, pQA, NH * SEQ, HD, 128);
        make_map(&AP.mapK, pKA, NH * SEQ, HD, 128);
        make_map(&AP.mapV, pVA, NH * SEQ, HD, 128);
        make_map(&AP.mapO, pCA, NH * SEQ, HD, 64);
        make_map(&OP.mapCtx[0], pCA, NH * SEQ, HD, 64);
        make_map(&OP.mapCtx[1], pCB, NH * SEQ, HD, 64);
        make_map3(&OP.mapWo[0], wo, NQ, DM, 64, 2);
        make_map3(&OP.mapWo[1], Wo, NQ, DM, 64, 2);
        OP.out = out;
        make_map(&CP.mapC, pCB, NH * SEQ, HD, SEGL);
        CP.out = out;
        AP.x = x; AP.gate_w = gate_w;
    }
    cudaStream_t s1 = cudaStreamPerThread;
    const bool pdl = true;
    launch_pdl(chain_kernel, 64, 384, C2_SMEM, s1, false, CP);
    launch_pdl(proj2_kernel, 68, 384, P2_SMEM, s1, pdl, P2);
    launch_pdl(attn_kernel, FA_GRID, 384, FA_SMEM, s1, pdl, AP);
    launch_pdl(out4_kernel, O4_GRID, 384, O2_SMEM, s1, pdl, OP);
}
```

```cpp
#include <cuda_runtime.h>
#include <cuda_bf16.h>
#include <cuda.h>
#include <stdint.h>
#include <type_traits>

constexpr int SEQ = 2048;
constexpr int DM = 512;
constexpr int NH = 32;
constexpr int HD = 128;
constexpr int NQ = NH * HD;
constexpr int SEGL = 32;
constexpr int NMEM = 8;
constexpr int NSEG = SEQ / SEGL;

typedef __nv_bfloat16 bf16;

__device__ bf16 g_QA[SEQ * NQ];
__device__ bf16 g_KA[SEQ * NQ];
__device__ bf16 g_VA[SEQ * NQ];
__device__ bf16 g_ctxA[SEQ * NQ];
__device__ bf16 g_ctxB[SEQ * NQ];
constexpr int CT_ATTN = 1, CT_FIN = 5;
constexpr int CT_P = 48;
constexpr int CT_G = 32;
constexpr int CT_AP = 64;
#define O2_HE 24
constexpr int CT_CA = 128;
constexpr int CT_CB = 160;
#define CB_FIRST 11
constexpr int CT_N = 192;
__device__ unsigned int g_ctr[CT_N];
__device__ float g_gate[SEQ];
constexpr int PART_A15 = 58 * 4096, PART_TAIL = 74 * 4096, PART_N = 90 * 4096;
__device__ uint4 g_part[PART_N];
__device__ uint2 g_xbuf[2 * 8 * 8 * 128];

#define FA_GRID 68

#define P2_MARK 0
#define TS_MARK(id, tid)
#define TS_MARK2(id, tid)
#define TS_BEGIN(id)
#define TS_END(id)
#define TS_BEGIN_T(id, tid)
#define TS_END_T(id, tid)
__device__ __forceinline__ void pdl_launch_dependents() { asm volatile("griddepcontrol.launch_dependents;" ::: "memory"); }
__device__ __forceinline__ void wait_ctr(int idx, unsigned int n) {
    unsigned int v; int it = 0;
    do { asm volatile("ld.acquire.gpu.global.u32 %0, [%1];" : "=r"(v) : "l"(&g_ctr[idx]) : "memory"); } while (v < n && ++it < (1 << 22));
}
__device__ __forceinline__ void signal_ctr(int idx) {
    asm volatile("fence.proxy.async.global;" ::: "memory");
    asm volatile("red.release.gpu.global.add.u32 [%0], 1;" :: "l"(&g_ctr[idx]) : "memory");
}
__device__ __forceinline__ void signal_ctr_generic(int idx) {
    asm volatile("red.release.gpu.global.add.u32 [%0], 1;" :: "l"(&g_ctr[idx]) : "memory");
}
__device__ __forceinline__ void finish_launch(int lane) {
    unsigned int tk = 0;
    if (lane == 0) tk = atomicAdd(&g_ctr[CT_FIN], 1u);
    tk = __shfl_sync(0xffffffff, tk, 0);
    if (tk == 64 + 68 - 1)
#pragma unroll 1
        for (int i = lane; i < CT_N; i += 32) g_ctr[i] = 0u;
}
__device__ __forceinline__ uint4 quad_transpose(uint32_t p0, uint32_t p1, uint32_t p2, uint32_t p3, int lane) {
    const bool o1 = lane & 1, o2 = lane & 2;
    uint32_t s0 = o1 ? p0 : p1, s1 = o1 ? p2 : p3;
    s0 = __shfl_xor_sync(0xffffffff, s0, 1); s1 = __shfl_xor_sync(0xffffffff, s1, 1);
    const uint32_t a_lo = o1 ? s0 : p0, a_hi = o1 ? p1 : s0, b_lo = o1 ? s1 : p2, b_hi = o1 ? p3 : s1;
    uint32_t t0 = o2 ? a_lo : b_lo, t1 = o2 ? a_hi : b_hi;
    t0 = __shfl_xor_sync(0xffffffff, t0, 2); t1 = __shfl_xor_sync(0xffffffff, t1, 2);
    return o2 ? make_uint4(t0, t1, b_lo, b_hi) : make_uint4(a_lo, a_hi, t0, t1);
}
__device__ __forceinline__ uint32_t smem_u32(const void* p) {
    return (uint32_t)__cvta_generic_to_shared(p);
}
__device__ __forceinline__ void mbar_init(uint32_t bar, uint32_t count) {
    asm volatile("mbarrier.init.shared::cta.b64 [%0], %1;" :: "r"(bar), "r"(count));
}
__device__ __forceinline__ void mbar_expect_tx(uint32_t bar, uint32_t bytes) {
    asm volatile("mbarrier.arrive.expect_tx.shared::cta.b64 _, [%0], %1;" :: "r"(bar), "r"(bytes) : "memory");
}
__device__ __forceinline__ void mbar_arrive(uint32_t bar) {
    asm volatile("mbarrier.arrive.shared::cta.b64 _, [%0];" :: "r"(bar) : "memory");
}
__device__ __forceinline__ void mbar_wait(uint32_t bar, uint32_t parity) {
    asm volatile(
        "{\n"
        ".reg .pred p, q;\n"
        ".reg .u32 c;\n"
        "mov.u32 c, 0;\n"
        "WAIT_LOOP:\n"
        "mbarrier.try_wait.parity.shared::cta.b64 p, [%0], %1;\n"
        "@p bra WAIT_DONE;\n"
        "add.u32 c, c, 1;\n"
        "setp.lt.u32 q, c, 4000000;\n"
        "@q bra WAIT_LOOP;\n"
        "WAIT_DONE:\n"
        "}\n" :: "r"(bar), "r"(parity) : "memory");
}
__device__ __forceinline__ void tma_load_2d(uint32_t dst, const CUtensorMap* map, uint32_t bar, int c0, int c1) {
    asm volatile(
        "cp.async.bulk.tensor.2d.shared::cluster.global.mbarrier::complete_tx::bytes [%0], [%1, {%3, %4}], [%2];"
        :: "r"(dst), "l"((uint64_t)map), "r"(bar), "r"(c0), "r"(c1) : "memory");
}
__device__ __forceinline__ void wgmma_fence() { asm volatile("wgmma.fence.sync.aligned;" ::: "memory"); }
__device__ __forceinline__ void wgmma_commit() { asm volatile("wgmma.commit_group.sync.aligned;" ::: "memory"); }
template <int N> __device__ __forceinline__ void wgmma_wait() {
    asm volatile("wgmma.wait_group.sync.aligned %0;" :: "n"(N) : "memory");
}
__device__ __forceinline__ uint64_t make_desc(uint32_t addr, uint32_t lbo, uint32_t sbo) {
    uint64_t d = 0;
    d |= (uint64_t)((addr & 0x3FFFF) >> 4);
    d |= (uint64_t)((lbo >> 4) & 0x3FFF) << 16;
    d |= (uint64_t)((sbo >> 4) & 0x3FFF) << 32;
    d |= (uint64_t)1 << 62;
    return d;
}

#define ACC64(d) \
    "+f"(d[0]), "+f"(d[1]), "+f"(d[2]), "+f"(d[3]), "+f"(d[4]), "+f"(d[5]), "+f"(d[6]), "+f"(d[7]), \
    "+f"(d[8]), "+f"(d[9]), "+f"(d[10]), "+f"(d[11]), "+f"(d[12]), "+f"(d[13]), "+f"(d[14]), "+f"(d[15]), \
    "+f"(d[16]), "+f"(d[17]), "+f"(d[18]), "+f"(d[19]), "+f"(d[20]), "+f"(d[21]), "+f"(d[22]), "+f"(d[23]), \
    "+f"(d[24]), "+f"(d[25]), "+f"(d[26]), "+f"(d[27]), "+f"(d[28]), "+f"(d[29]), "+f"(d[30]), "+f"(d[31]), \
    "+f"(d[32]), "+f"(d[33]), "+f"(d[34]), "+f"(d[35]), "+f"(d[36]), "+f"(d[37]), "+f"(d[38]), "+f"(d[39]), \
    "+f"(d[40]), "+f"(d[41]), "+f"(d[42]), "+f"(d[43]), "+f"(d[44]), "+f"(d[45]), "+f"(d[46]), "+f"(d[47]), \
    "+f"(d[48]), "+f"(d[49]), "+f"(d[50]), "+f"(d[51]), "+f"(d[52]), "+f"(d[53]), "+f"(d[54]), "+f"(d[55]), \
    "+f"(d[56]), "+f"(d[57]), "+f"(d[58]), "+f"(d[59]), "+f"(d[60]), "+f"(d[61]), "+f"(d[62]), "+f"(d[63])
#define ACC64_STR \
    "{%0, %1, %2, %3, %4, %5, %6, %7, %8, %9, %10, %11, %12, %13, %14, %15, " \
    "%16, %17, %18, %19, %20, %21, %22, %23, %24, %25, %26, %27, %28, %29, %30, %31, " \
    "%32, %33, %34, %35, %36, %37, %38, %39, %40, %41, %42, %43, %44, %45, %46, %47, " \
    "%48, %49, %50, %51, %52, %53, %54, %55, %56, %57, %58, %59, %60, %61, %62, %63}"

template <int TB>
__device__ __forceinline__ void wgmma_ss_n128(float (&d)[64], uint64_t da, uint64_t db, int scale_d) {
    asm volatile(
        "{\n.reg .pred p;\nsetp.ne.b32 p, %66, 0;\n"
        "wgmma.mma_async.sync.aligned.m64n128k16.f32.bf16.bf16 " ACC64_STR ", %64, %65, p, 1, 1, 0, %67;\n}\n"
        : ACC64(d) : "l"(da), "l"(db), "r"(scale_d), "n"(TB));
}
__device__ __forceinline__ uint32_t desc_lo(uint32_t addr, uint32_t lbo) { return ((addr & 0x3FFFF) >> 4) | ((lbo >> 4) << 16); }
template <int TB>
__device__ __forceinline__ void wgmma_ss_n128_lo(float (&d)[64], uint32_t da_lo, uint32_t db_lo, int scale_d) {
    asm volatile(
        "{\n.reg .pred p;\n.reg .b64 da, db;\nsetp.ne.b32 p, %66, 0;\n"
        "mov.b64 da, {%64, 0x40000040};\nmov.b64 db, {%65, 0x40000040};\n"
        "wgmma.mma_async.sync.aligned.m64n128k16.f32.bf16.bf16 " ACC64_STR ", da, db, p, 1, 1, 0, %67;\n}\n"
        : ACC64(d) : "r"(da_lo), "r"(db_lo), "r"(scale_d), "n"(TB));
}
__device__ __forceinline__ void wgmma_rs_n128_tb(float (&d)[64], uint32_t a0, uint32_t a1, uint32_t a2, uint32_t a3,
                                                 uint64_t db, int scale_d) {
    asm volatile(
        "{\n.reg .pred p;\nsetp.ne.b32 p, %69, 0;\n"
        "wgmma.mma_async.sync.aligned.m64n128k16.f32.bf16.bf16 " ACC64_STR ", {%64, %65, %66, %67}, %68, p, 1, 1, 1;\n}\n"
        : ACC64(d) : "r"(a0), "r"(a1), "r"(a2), "r"(a3), "l"(db), "r"(scale_d));
}
__device__ __forceinline__ void wgmma_rs_n80(float (&d)[40], const uint32_t (&a)[4], uint32_t db_lo, int scale_d) {
    asm volatile(
        "{\n.reg .pred p;\n.reg .b64 db;\nsetp.ne.b32 p, %45, 0;\nmov.b64 db, {%44, 0x40000040};\n"
        "wgmma.mma_async.sync.aligned.m64n80k16.f32.bf16.bf16 "
        "{%0, %1, %2, %3, %4, %5, %6, %7, %8, %9, %10, %11, %12, %13, %14, %15, %16, %17, %18, %19, %20, %21, %22, %23, %24, %25, %26, %27, %28, %29, %30, %31, %32, %33, %34, %35, %36, %37, %38, %39}, "
        "{%40, %41, %42, %43}, db, p, 1, 1, 0;\n}\n"
        : "+f"(d[0]), "+f"(d[1]), "+f"(d[2]), "+f"(d[3]), "+f"(d[4]), "+f"(d[5]), "+f"(d[6]), "+f"(d[7]), "+f"(d[8]), "+f"(d[9]), "+f"(d[10]), "+f"(d[11]), "+f"(d[12]), "+f"(d[13]), "+f"(d[14]), "+f"(d[15]), "+f"(d[16]), "+f"(d[17]), "+f"(d[18]), "+f"(d[19]), "+f"(d[20]), "+f"(d[21]), "+f"(d[22]), "+f"(d[23]), "+f"(d[24]), "+f"(d[25]), "+f"(d[26]), "+f"(d[27]), "+f"(d[28]), "+f"(d[29]), "+f"(d[30]), "+f"(d[31]), "+f"(d[32]), "+f"(d[33]), "+f"(d[34]), "+f"(d[35]), "+f"(d[36]), "+f"(d[37]), "+f"(d[38]), "+f"(d[39])
        : "r"(a[0]), "r"(a[1]), "r"(a[2]), "r"(a[3]), "r"(db_lo), "r"(scale_d));
}
__device__ __forceinline__ void wgmma_ss_n256_tb(float (&d)[128], uint64_t da, uint64_t db, int scale_d) {
    asm volatile(
        "{\n.reg .pred p;\nsetp.ne.b32 p, %130, 0;\n"
        "wgmma.mma_async.sync.aligned.m64n256k16.f32.bf16.bf16 {%0, %1, %2, %3, %4, %5, %6, %7, %8, %9, %10, %11, %12, %13, %14, %15, %16, %17, %18, %19, %20, %21, %22, %23, %24, %25, %26, %27, %28, %29, %30, %31, %32, %33, %34, %35, %36, %37, %38, %39, %40, %41, %42, %43, %44, %45, %46, %47, %48, %49, %50, %51, %52, %53, %54, %55, %56, %57, %58, %59, %60, %61, %62, %63, %64, %65, %66, %67, %68, %69, %70, %71, %72, %73, %74, %75, %76, %77, %78, %79, %80, %81, %82, %83, %84, %85, %86, %87, %88, %89, %90, %91, %92, %93, %94, %95, %96, %97, %98, %99, %100, %101, %102, %103, %104, %105, %106, %107, %108, %109, %110, %111, %112, %113, %114, %115, %116, %117, %118, %119, %120, %121, %122, %123, %124, %125, %126, %127}, %128, %129, p, 1, 1, 0, 1;\n}\n"
        : "+f"(d[0]), "+f"(d[1]), "+f"(d[2]), "+f"(d[3]), "+f"(d[4]), "+f"(d[5]), "+f"(d[6]), "+f"(d[7]), "+f"(d[8]), "+f"(d[9]), "+f"(d[10]), "+f"(d[11]), "+f"(d[12]), "+f"(d[13]), "+f"(d[14]), "+f"(d[15]), "+f"(d[16]), "+f"(d[17]), "+f"(d[18]), "+f"(d[19]), "+f"(d[20]), "+f"(d[21]), "+f"(d[22]), "+f"(d[23]), "+f"(d[24]), "+f"(d[25]), "+f"(d[26]), "+f"(d[27]), "+f"(d[28]), "+f"(d[29]), "+f"(d[30]), "+f"(d[31]), "+f"(d[32]), "+f"(d[33]), "+f"(d[34]), "+f"(d[35]), "+f"(d[36]), "+f"(d[37]), "+f"(d[38]), "+f"(d[39]), "+f"(d[40]), "+f"(d[41]), "+f"(d[42]), "+f"(d[43]), "+f"(d[44]), "+f"(d[45]), "+f"(d[46]), "+f"(d[47]), "+f"(d[48]), "+f"(d[49]), "+f"(d[50]), "+f"(d[51]), "+f"(d[52]), "+f"(d[53]), "+f"(d[54]), "+f"(d[55]), "+f"(d[56]), "+f"(d[57]), "+f"(d[58]), "+f"(d[59]), "+f"(d[60]), "+f"(d[61]), "+f"(d[62]), "+f"(d[63]), "+f"(d[64]), "+f"(d[65]), "+f"(d[66]), "+f"(d[67]), "+f"(d[68]), "+f"(d[69]), "+f"(d[70]), "+f"(d[71]), "+f"(d[72]), "+f"(d[73]), "+f"(d[74]), "+f"(d[75]), "+f"(d[76]), "+f"(d[77]), "+f"(d[78]), "+f"(d[79]), "+f"(d[80]), "+f"(d[81]), "+f"(d[82]), "+f"(d[83]), "+f"(d[84]), "+f"(d[85]), "+f"(d[86]), "+f"(d[87]), "+f"(d[88]), "+f"(d[89]), "+f"(d[90]), "+f"(d[91]), "+f"(d[92]), "+f"(d[93]), "+f"(d[94]), "+f"(d[95]), "+f"(d[96]), "+f"(d[97]), "+f"(d[98]), "+f"(d[99]), "+f"(d[100]), "+f"(d[101]), "+f"(d[102]), "+f"(d[103]), "+f"(d[104]), "+f"(d[105]), "+f"(d[106]), "+f"(d[107]), "+f"(d[108]), "+f"(d[109]), "+f"(d[110]), "+f"(d[111]), "+f"(d[112]), "+f"(d[113]), "+f"(d[114]), "+f"(d[115]), "+f"(d[116]), "+f"(d[117]), "+f"(d[118]), "+f"(d[119]), "+f"(d[120]), "+f"(d[121]), "+f"(d[122]), "+f"(d[123]), "+f"(d[124]), "+f"(d[125]), "+f"(d[126]), "+f"(d[127])
        : "l"(da), "l"(db), "r"(scale_d));
}
__device__ __forceinline__ void stmatrix_x4(uint32_t addr, uint32_t r0, uint32_t r1, uint32_t r2, uint32_t r3) {
    asm volatile("stmatrix.sync.aligned.m8n8.x4.shared.b16 [%0], {%1, %2, %3, %4};" :: "r"(addr), "r"(r0), "r"(r1), "r"(r2), "r"(r3) : "memory");
}
__device__ __forceinline__ void tma_store_2d(const CUtensorMap* map, uint32_t src, int c0, int c1) {
    asm volatile("cp.async.bulk.tensor.2d.global.shared::cta.bulk_group [%0, {%2, %3}], [%1];"
                 :: "l"((uint64_t)map), "r"(src), "r"(c0), "r"(c1) : "memory");
}
__device__ __forceinline__ float ex2f(float x) { float y; asm("ex2.approx.ftz.f32 %0, %1;" : "=f"(y) : "f"(x)); return y; }
__device__ __forceinline__ uint32_t pack_bf16(float lo, float hi) {
    __nv_bfloat162 v = __floats2bfloat162_rn(lo, hi);
    return *reinterpret_cast<uint32_t*>(&v);
}
__device__ __forceinline__ float bf16r(float x) { return __uint_as_float(pack_bf16(0.f, x) & 0xffff0000u); }
__device__ __forceinline__ void mma_16816(float (&c)[4], uint32_t a0, uint32_t a1, uint32_t a2, uint32_t a3,
                                          uint32_t b0, uint32_t b1) {
    asm volatile(
        "mma.sync.aligned.m16n8k16.row.col.f32.bf16.bf16.f32 {%0,%1,%2,%3}, {%4,%5,%6,%7}, {%8,%9}, {%0,%1,%2,%3};"
        : "+f"(c[0]), "+f"(c[1]), "+f"(c[2]), "+f"(c[3])
        : "r"(a0), "r"(a1), "r"(a2), "r"(a3), "r"(b0), "r"(b1));
}
__device__ __forceinline__ void ldmatrix_x4_trans(uint32_t& r0, uint32_t& r1, uint32_t& r2, uint32_t& r3, uint32_t addr) {
    asm volatile("ldmatrix.sync.aligned.m8n8.x4.trans.shared.b16 {%0,%1,%2,%3}, [%4];"
                 : "=r"(r0), "=r"(r1), "=r"(r2), "=r"(r3) : "r"(addr));
}

struct AttnParams {
    CUtensorMap mapQ, mapK, mapV;
    CUtensorMap mapO;
    const bf16 *x, *gate_w;
};
constexpr uint32_t FA_Q = 0, FA_KV = 65536, FA_O = 196608, FA_BAR = 229376;
constexpr int FA_SMEM = FA_BAR + 256;
constexpr int FA_ITEMS = 16 * NH;
__device__ __forceinline__ int fa_qt(int t) { return 15 - ((t & 127) >> 3); }
__device__ __forceinline__ int fa_head(int t) { return (t >> 7) * 8 + (t & 7); }
__device__ __forceinline__ uint32_t mbar_test(uint32_t bar, uint32_t parity) {
    uint32_t done;
    asm volatile(
        "{\n.reg .pred p;\n"
        "mbarrier.test_wait.parity.shared::cta.b64 p, [%1], %2;\n"
        "selp.u32 %0, 1, 0, p;\n}\n" : "=r"(done) : "r"(bar), "r"(parity) : "memory");
    return done;
}
__device__ __forceinline__ void mbar_arrive_if(uint32_t bar, bool c) {
    asm volatile("{\n.reg .pred p;\nsetp.ne.u32 p, %1, 0;\n@p mbarrier.arrive.shared::cta.b64 _, [%0];\n}" :: "r"(bar), "r"((uint32_t)c) : "memory");
}
__device__ __forceinline__ void wgmma_rs_n128_tb_lo(float (&d)[64], const uint32_t* a, uint32_t db_lo, int scale_d) {
    asm volatile(
        "{\n.reg .pred p;\n.reg .b64 db;\nsetp.ne.b32 p, %69, 0;\nmov.b64 db, {%68, 0x40000040};\n"
        "wgmma.mma_async.sync.aligned.m64n128k16.f32.bf16.bf16 " ACC64_STR ", {%64, %65, %66, %67}, db, p, 1, 1, 1;\n}\n"
        : ACC64(d) : "r"(a[0]), "r"(a[1]), "r"(a[2]), "r"(a[3]), "r"(db_lo), "r"(scale_d));
}
#define FA_TEST 48
#define FA_PIN 32

__device__ __forceinline__ void wgmma_ss_n64_lo(float (&d)[64], uint32_t da_lo, uint32_t db_lo, int scale_d) {
    asm volatile(
        "{\n.reg .pred p;\n.reg .b64 da, db;\nsetp.ne.b32 p, %34, 0;\n"
        "mov.b64 da, {%32, 0x40000040};\nmov.b64 db, {%33, 0x40000040};\n"
        "wgmma.mma_async.sync.aligned.m64n64k16.f32.bf16.bf16 {%0, %1, %2, %3, %4, %5, %6, %7, %8, %9, %10, %11, %12, %13, %14, %15, "
        "%16, %17, %18, %19, %20, %21, %22, %23, %24, %25, %26, %27, %28, %29, %30, %31}, da, db, p, 1, 1, 0, 0;\n}\n"
        : "+f"(d[0]), "+f"(d[1]), "+f"(d[2]), "+f"(d[3]), "+f"(d[4]), "+f"(d[5]), "+f"(d[6]), "+f"(d[7]), "+f"(d[8]), "+f"(d[9]), "+f"(d[10]),
          "+f"(d[11]), "+f"(d[12]), "+f"(d[13]), "+f"(d[14]), "+f"(d[15]), "+f"(d[16]), "+f"(d[17]), "+f"(d[18]), "+f"(d[19]), "+f"(d[20]),
          "+f"(d[21]), "+f"(d[22]), "+f"(d[23]), "+f"(d[24]), "+f"(d[25]), "+f"(d[26]), "+f"(d[27]), "+f"(d[28]), "+f"(d[29]), "+f"(d[30]), "+f"(d[31])
        : "r"(da_lo), "r"(db_lo), "r"(scale_d));
}
#define FA_CLR 0
#define FA_NOFB 0
#define FA_DPIN 16
#define FA_RLO 40
#define FA_RHI 232
#define FA_LIM 0x1p40f
__device__ __forceinline__ void attn_consumer(const uint32_t sb, const int wg, const int w4, const int lane) {
    const uint32_t bar_q = sb + FA_BAR, bar_of = bar_q + 96, bar_oe = bar_q + 112, oslot = bar_q + 144;
    const bool lane0 = lane == 0;
    float o[64], sacc[64];
    uint32_t pa[32];
    float ms0 = 0.f, ms1 = 0.f, lrow0 = 1.f, lrow1 = 1.f;
    const float sc = 0.08838834764831845f * 1.4426950408889634f;
    const uint32_t q_lo = desc_lo(sb + FA_Q + wg * 8192, 16), k_lo = desc_lo(sb + FA_KV, 16), v_lo = desc_lo(sb + FA_KV + 32768, 16384);
    uint32_t qd = q_lo + 2048, kd = k_lo + 4096, vd = v_lo, bs = bar_q + 8, bi = bar_q + 8;
    auto issue_qk = [&](uint32_t a, bool half) {
        const uint32_t b = kd;
#pragma unroll
        for (int kk = 0; kk < 8; kk++) {
            if (half) wgmma_ss_n64_lo(sacc, a + (kk >> 2) * 1024 + (kk & 3) * 2, b + (kk >> 2) * 1024 + (kk & 3) * 2, kk != 0);
            else wgmma_ss_n128_lo<0>(sacc, a + (kk >> 2) * 1024 + (kk & 3) * 2, b + (kk >> 2) * 1024 + (kk & 3) * 2, kk != 0);
        }
        wgmma_commit();
    };
    auto issue_pv = [&](bool acc) {
        const uint32_t b = vd;
#pragma unroll
        for (int kk = 0; kk < 8; kk++) wgmma_rs_n128_tb_lo(o, &pa[kk * 4], b + kk * 128, kk != 0 || acc);
        wgmma_commit();
    };
    auto turn_wait = [&]() { asm volatile("bar.sync %0, 256;" :: "r"(1 + wg) : "memory"); };
    auto turn_pass = [&]() { asm volatile("bar.arrive %0, 256;" :: "r"(2 - wg) : "memory"); };
    int item = -1, it = -1, j = 0, nkv = 1, t = 0;
    auto redo = [&](float& l0, float& l1) {
        const size_t row0 = (size_t)fa_head(t) * SEQ + (lane >> 2);
        const uint32_t* qg = reinterpret_cast<const uint32_t*>(g_QA + (row0 + (nkv - 1) * 128 + wg * 64 + w4 * 16) * HD) + (lane & 3);
        const uint32_t* kg = reinterpret_cast<const uint32_t*>(g_KA + (row0 + (nkv - 1 - j) * 128) * HD) + (lane & 3);
        auto ldg = [](const uint32_t* p) { uint32_t v; asm volatile("ld.relaxed.gpu.global.u32 %0, [%1];" : "=r"(v) : "l"(p) : "memory"); return v; };
        const int r0 = j ? 1 << 20 : wg * 64 + w4 * 16 + (lane >> 2) - (lane & 3) * 2;
        float mx0 = -INFINITY, mx1 = -INFINITY;
        const float m0 = ms0, m1 = ms1;
        uint4 tmp[8];
        l0 = 0.f; l1 = 0.f;
#pragma unroll 1
        for (int ps = 0; ps < 32; ps++) {
            const int nb = ps & 15;
            float c[4] = {0.f, 0.f, 0.f, 0.f};
#pragma unroll 1
            for (int kk = 0; kk < 64; kk += 8)
                mma_16816(c, ldg(qg + kk), ldg(qg + kk + 8 * 64), ldg(qg + kk + 4), ldg(qg + kk + 8 * 64 + 4), ldg(kg + nb * 8 * 64 + kk), ldg(kg + nb * 8 * 64 + kk + 4));
#pragma unroll
            for (int i = 0; i < 4; i++)
                if (nb * 8 + (i & 1) - ((i & 2) ? 8 : 0) > r0) c[i] = -INFINITY;
            mx0 = fmaxf(mx0, fmaxf(c[0], c[1])); mx1 = fmaxf(mx1, fmaxf(c[2], c[3]));
#pragma unroll
            for (int i = 0; i < 4; i++) c[i] = ex2f(fmaf(c[i], sc, (i & 2) ? ms1 : ms0));
            l0 += c[0] + c[1]; l1 += c[2] + c[3];
            reinterpret_cast<uint2*>(tmp)[nb] = make_uint2(pack_bf16(c[0], c[1]), pack_bf16(c[2], c[3]));
            if (ps == 15) {
                mx0 = fmaxf(mx0, __shfl_xor_sync(0xffffffff, mx0, 1)); mx1 = fmaxf(mx1, __shfl_xor_sync(0xffffffff, mx1, 1));
                mx0 = fmaxf(mx0, __shfl_xor_sync(0xffffffff, mx0, 2)); mx1 = fmaxf(mx1, __shfl_xor_sync(0xffffffff, mx1, 2));
                ms0 = fminf(-mx0 * sc, ms0); ms1 = fminf(-mx1 * sc, ms1);
                l0 = 0.f; l1 = 0.f;
            }
        }
        const float a0 = ex2f(ms0 - m0), a1 = ex2f(ms1 - m1);
        lrow0 *= a0; lrow1 *= a1;
#pragma unroll
        for (int i = 0; i < 64; i++) o[i] *= (i & 2) ? a1 : a0;
#pragma unroll
        for (int i = 0; i < 8; i++) { pa[4 * i] = tmp[i].x; pa[4 * i + 1] = tmp[i].y; pa[4 * i + 2] = tmp[i].z; pa[4 * i + 3] = tmp[i].w; }
    };
    auto pin_after = [&](float v) {
        asm volatile("{\n.reg .pred p;\nsetp.eq.f32 p, %1, %2;\n@p st.shared.f32 [%0], %1;\n}" :: "r"(oslot + 16), "f"(v), "f"(ms0) : "memory");
    };
    uint32_t ok = 0, okq = 0;
    int tn = 0;
    auto tests = [&]() {
        ok = mbar_test(bs + 48, (it >> 1) & 1);
        asm volatile("ld.shared.s32 %0, [%1];" : "=r"(tn) : "r"((bi ^ 8) + 128) : "memory");
        ok &= mbar_test((bs ^ 8) + 32, ((it + 1) >> 1) & 1);
        okq = mbar_test(bi ^ 8, ((item + 1) >> 1) & 1);
    };
    auto epilogue = [&](int tag, bool real) {
        float l0 = lrow0, l1 = lrow1;
        l0 += __shfl_xor_sync(0xffffffff, l0, 1); l1 += __shfl_xor_sync(0xffffffff, l1, 1);
        l0 += __shfl_xor_sync(0xffffffff, l0, 2); l1 += __shfl_xor_sync(0xffffffff, l1, 2);
        float i0, i1;
        asm("rcp.approx.ftz.f32 %0, %1;" : "=f"(i0) : "f"(l0));
        asm("rcp.approx.ftz.f32 %0, %1;" : "=f"(i1) : "f"(l1));
        const int row = w4 * 16 + (lane >> 2);
        const uint32_t stg = sb + FA_O + wg * 16384 + row * 128;
#pragma unroll
        for (int i = 0; i < 4; i++) {
            const int ch = i * 4 + (lane & 3);
            const uint32_t a = stg + (ch >> 3) * 8192 + (((ch & 7) ^ (row & 7)) << 4);
            const float* q = &o[i * 16];
            asm volatile("st.shared.v4.b32 [%0], {%1, %2, %3, %4};" :: "r"(a), "r"(pack_bf16(q[0] * i0, q[1] * i0)), "r"(pack_bf16(q[4] * i0, q[5] * i0)),
                         "r"(pack_bf16(q[8] * i0, q[9] * i0)), "r"(pack_bf16(q[12] * i0, q[13] * i0)) : "memory");
            asm volatile("st.shared.v4.b32 [%0], {%1, %2, %3, %4};" :: "r"(a + 1024), "r"(pack_bf16(q[2] * i1, q[3] * i1)), "r"(pack_bf16(q[6] * i1, q[7] * i1)),
                         "r"(pack_bf16(q[10] * i1, q[11] * i1)), "r"(pack_bf16(q[14] * i1, q[15] * i1)) : "memory");
        }
        asm volatile("st.shared.s32 [%0], %1;" :: "r"(oslot + wg * 4), "r"(tag) : "memory");
        __syncwarp();
        mbar_arrive_if(bar_of + 8 * wg, lane0 && real);
    };
    auto transition = [&](auto wgc, float& l0, float& l1) {
        constexpr int WG = decltype(wgc)::value;
        constexpr int NE = WG == 0 ? 32 : 64;
        turn_wait();
        wgmma_fence();
        issue_qk(qd, WG == 0);
        issue_pv(nkv > 1);
        turn_pass();
        const int tc = t;
        t = __shfl_sync(0xffffffff, tn, 0);
        nkv = fa_qt(t) + 1;
        mbar_wait(bar_oe + 8 * wg, (max(item, 0) & 1) ^ 1);
        item++; bi ^= 8;
        wgmma_wait<1>();
        mbar_arrive_if(bs + 64, lane0);
        mbar_arrive_if(bi + 16, lane0 && nkv == 1);
        ms0 = -sc * __shfl_sync(0xffffffff, sacc[0], lane & 28); ms1 = -sc * __shfl_sync(0xffffffff, sacc[2], lane & 28);
        const int r0 = w4 * 16 + (lane >> 2) - (lane & 3) * 2;
#pragma unroll
        for (int i = 0; i < 32; i++)
            if ((i >> 2) * 8 + (i & 1) - ((i & 2) ? 8 : 0) > r0) sacc[WG * 32 + i] = -INFINITY;
        float sum[4];
#pragma unroll
        for (int i = 0; i < FA_DPIN; i++) { sacc[i] = ex2f(fmaf(sacc[i], sc, (i & 2) ? ms1 : ms0)); sum[i & 3] = i < 4 ? sacc[i] : sum[i & 3] + sacc[i]; }
        pin_after((sum[0] + sum[1]) + (sum[2] + sum[3]));
        wgmma_wait<0>();
        mbar_arrive_if((bs ^ 8) + 80, lane0 && item > 0);
        epilogue(tc, item > 0);
#pragma unroll
        for (int i = 0; i < NE; i++) {
            if (i >= FA_DPIN) { sacc[i] = ex2f(fmaf(sacc[i], sc, (i & 2) ? ms1 : ms0)); sum[i & 3] += sacc[i]; }
            if (i & 1) pa[i >> 1] = pack_bf16(sacc[i - 1], sacc[i]);
            if (i == NE - 16) { pin_after(sum[0]); tests(); }
        }
        if (NE == 32)
#pragma unroll
            for (int i = 16; i < 32; i++) asm volatile("mov.u32 %0, 0;" : "=r"(pa[i]));
        l0 = sum[0] + sum[1]; l1 = sum[2] + sum[3];
    };
#pragma unroll
    for (int i = 0; i < 32; i++) pa[i] = 0u;
    if (wg == 1) asm volatile("bar.arrive 1, 256;" ::: "memory");
#pragma unroll 1
    for (;;) {
        float l0, l1;
        it++;
        kd = 2 * k_lo + 4096 - kd; vd = 2 * v_lo + 4096 - vd; bs ^= 8;
        if (++j < nkv) {
            if (__builtin_expect(!ok, 0)) {
                mbar_wait(bs + 32, (it >> 1) & 1);
                mbar_wait((bs ^ 8) + 48, ((it - 1) >> 1) & 1);
            }
            turn_wait();
            wgmma_fence();
            issue_qk(qd, false);
            issue_pv(j > 1);
            turn_pass();
            wgmma_wait<1>();
            mbar_arrive_if(bs + 64, lane0);
            mbar_arrive_if(bi + 16, lane0 && j == nkv - 1);
            float sum[4];
#pragma unroll
            for (int i = 0; i < FA_PIN; i++) { sacc[i] = ex2f(fmaf(sacc[i], sc, (i & 2) ? ms1 : ms0)); sum[i & 3] = i < 4 ? sacc[i] : sum[i & 3] + sacc[i]; }
            pin_after((sum[0] + sum[1]) + (sum[2] + sum[3]));
            wgmma_wait<0>();
            mbar_arrive_if((bs ^ 8) + 80, lane0);
#pragma unroll
            for (int i = 0; i < 64; i++) {
                if (i >= FA_PIN) { sacc[i] = ex2f(fmaf(sacc[i], sc, (i & 2) ? ms1 : ms0)); sum[i & 3] = i < 4 ? sacc[i] : sum[i & 3] + sacc[i]; }
                if (i & 1) pa[i >> 1] = pack_bf16(sacc[i - 1], sacc[i]);
                if (i == FA_TEST) { pin_after(sum[0]); tests(); }
            }
            l0 = sum[0] + sum[1]; l1 = sum[2] + sum[3];
        } else {
            if (__builtin_expect(!(ok & okq), 0)) {
                mbar_wait(bi ^ 8, ((item + 1) >> 1) & 1);
                asm volatile("ld.shared.s32 %0, [%1];" : "=r"(tn) : "r"((bi ^ 8) + 128) : "memory");
                mbar_wait((bs ^ 8) + 48, ((it - 1) >> 1) & 1);
                if (tn < 0) break;
                mbar_wait(bs + 32, (it >> 1) & 1);
            }
            qd = 2 * q_lo + 2048 - qd;
            if (wg == 0) transition(std::integral_constant<int, 0>(), l0, l1); else transition(std::integral_constant<int, 1>(), l0, l1);
            j = 0;
            lrow0 = 0.f; lrow1 = 0.f;
        }
        if (!FA_NOFB && __builtin_expect(__any_sync(0xffffffff, !(l0 + l1 < FA_LIM)), 0)) redo(l0, l1);
        lrow0 += l0; lrow1 += l1;
    }
    wgmma_fence();
    issue_pv(nkv > 1);
    mbar_wait(bar_oe + 8 * wg, (item & 1) ^ 1);
    wgmma_wait<0>();
    epilogue(t | 0x80000000, true);
}

__global__ void __launch_bounds__(384, 1) attn_kernel(const __grid_constant__ AttnParams P) {
    extern __shared__ __align__(1024) uint8_t smem_attn[];
    const uint32_t sb = smem_u32(smem_attn);
    const uint32_t bar_q = sb + FA_BAR, bar_qe = bar_q + 16, bar_kf = bar_q + 32, bar_vf = bar_q + 48, bar_ke = bar_q + 64, bar_ve = bar_q + 80,
                   bar_of = bar_q + 96, bar_oe = bar_q + 112, slot = bar_q + 128, oslot = bar_q + 144;
    const int warp = __shfl_sync(0xffffffff, threadIdx.x >> 5, 0);
    const int lane = threadIdx.x & 31;
    if (threadIdx.x == 0) {
        for (int i = 0; i < 2; i++) {
            mbar_init(bar_q + 8 * i, 1); mbar_init(bar_qe + 8 * i, 8); mbar_init(bar_kf + 8 * i, 1); mbar_init(bar_vf + 8 * i, 1);
            mbar_init(bar_ke + 8 * i, 8); mbar_init(bar_ve + 8 * i, 8); mbar_init(bar_of + 8 * i, 4); mbar_init(bar_oe + 8 * i, 1);
        }
        asm volatile("fence.mbarrier_init.release.cluster;" ::: "memory");
    }
    if (threadIdx.x == 256) wait_ctr(CT_AP + (fa_head(blockIdx.x) >> 1), 192u);
    __syncthreads();
    pdl_launch_dependents();
    if (warp >= 8) {
        asm volatile("setmaxnreg.dec.sync.aligned.u32 %0;" :: "n"(FA_RLO));
        if (warp == 11) {
            const uint4 gv0 = __ldg(reinterpret_cast<const uint4*>(P.gate_w) + lane), gv1 = __ldg(reinterpret_cast<const uint4*>(P.gate_w) + 32 + lane);
            const uint32_t gw[8] = {gv0.x, gv0.y, gv0.z, gv0.w, gv1.x, gv1.y, gv1.z, gv1.w};
#pragma unroll 1
            for (int r = blockIdx.x; r < SEQ; r += gridDim.x) {
                const uint4 x0 = __ldg(reinterpret_cast<const uint4*>(P.x + (size_t)r * DM) + lane), x1 = __ldg(reinterpret_cast<const uint4*>(P.x + (size_t)r * DM) + 32 + lane);
                const uint32_t xw[8] = {x0.x, x0.y, x0.z, x0.w, x1.x, x1.y, x1.z, x1.w};
                float sum = 0.f;
#pragma unroll
                for (int e = 0; e < 8; e++) {
                    const uint32_t pr = pack_bf16(__uint_as_float(xw[e] << 16) * __uint_as_float(gw[e] << 16), __uint_as_float(xw[e] & 0xffff0000u) * __uint_as_float(gw[e] & 0xffff0000u));
                    sum += __uint_as_float(pr << 16) + __uint_as_float(pr & 0xffff0000u);
                }
#pragma unroll
                for (int o = 16; o; o >>= 1) sum += __shfl_xor_sync(0xffffffff, sum, o);
                if (lane == 0) g_gate[r] = bf16r(__fdividef(1.f, 1.f + __expf(-bf16r(sum))));
            }
#pragma unroll 1
            for (int i = blockIdx.x * 32 + lane; i < FA_CLR; i += gridDim.x * 32) g_part[i] = make_uint4(~0u, ~0u, ~0u, ~0u);
            __syncwarp();
            if (lane == 0) signal_ctr_generic(CT_G);
        } else if (warp > 8) {
            if (lane == 0) {
                const int wg = warp - 9;
                const uint32_t stg = sb + FA_O + wg * 16384;
                TS_BEGIN_T(1, 320);
                for (int n = 0;; n++) {
                    mbar_wait(bar_of + 8 * wg, n & 1);
                    int t;
                    asm volatile("ld.shared.s32 %0, [%1];" : "=r"(t) : "r"(oslot + wg * 4) : "memory");
                    asm volatile("fence.proxy.async.shared::cta;" ::: "memory");
                    const bool last = t < 0;
                    t &= 0xffff;
                    const int qt = fa_qt(t), h = fa_head(t);
                    tma_store_2d(&P.mapO, stg, 0, h * SEQ + qt * 128 + wg * 64);
                    tma_store_2d(&P.mapO, stg + 8192, 64, h * SEQ + qt * 128 + wg * 64);
                    asm volatile("cp.async.bulk.commit_group;" ::: "memory");
                    asm volatile("cp.async.bulk.wait_group.read 0;" ::: "memory");
                    mbar_arrive(bar_oe + 8 * wg);
                    asm volatile("cp.async.bulk.wait_group 0;" ::: "memory");
                    signal_ctr(CT_CA + qt * 2 + (h >= O2_HE));
                    if (last) break;
                }
                TS_END_T(1, 320);
            }
        } else if (lane == 0) {
            int it = 0, t = blockIdx.x, hp_ready = 1 << (fa_head(t) >> 1);
            auto load_q = [&](int item, int t) {
                const uint32_t b = bar_q + 8 * (item & 1);
                asm volatile("st.shared.s32 [%0], %1;" :: "r"(slot + (item & 1) * 8), "r"(t) : "memory");
                if (t < 0) { mbar_arrive(b); return; }
                const int row = fa_head(t) * SEQ + fa_qt(t) * 128;
                mbar_expect_tx(b, 32768);
                tma_load_2d(sb + FA_Q + (item & 1) * 32768, &P.mapQ, b, 0, row);
                tma_load_2d(sb + FA_Q + (item & 1) * 32768 + 16384, &P.mapQ, b, 64, row);
            };
            auto load_v = [&](int it, int row) {
                const int s = it & 1;
                const uint32_t sv = sb + FA_KV + s * 65536 + 32768;
                mbar_wait(bar_ve + 8 * s, ((it >> 1) & 1) ^ 1);
                mbar_expect_tx(bar_vf + 8 * s, 32768);
                tma_load_2d(sv, &P.mapV, bar_vf + 8 * s, 0, row);
                tma_load_2d(sv + 16384, &P.mapV, bar_vf + 8 * s, 64, row);
            };
            int vrow = 0;
            load_q(0, t);
            for (int item = 0; t >= 0; item++) {
                const int h = fa_head(t);
                for (int j = fa_qt(t); j >= 0; j--, it++) {
                    const int s = it & 1;
                    const uint32_t ph = ((it >> 1) & 1) ^ 1;
                    const uint32_t sk = sb + FA_KV + s * 65536;
                    if (j == 0) t = (int)(gridDim.x + atomicAdd(&g_ctr[CT_ATTN], 1u));
                    mbar_wait(bar_ke + 8 * s, ph);
                    mbar_expect_tx(bar_kf + 8 * s, 32768);
                    tma_load_2d(sk, &P.mapK, bar_kf + 8 * s, 0, h * SEQ + j * 128);
                    tma_load_2d(sk + 16384, &P.mapK, bar_kf + 8 * s, 64, h * SEQ + j * 128);
                    if (it > 0) load_v(it - 1, vrow);
                    vrow = h * SEQ + j * 128;
                    if (j == 0) {
                        if (t >= FA_ITEMS) t = -1;
                        else {
                            const int hp = fa_head(t) >> 1;
                            if (!((hp_ready >> hp) & 1)) { wait_ctr(CT_AP + hp, 192u); hp_ready |= 1 << hp; }
                        }
                        mbar_wait(bar_qe + 8 * ((item + 1) & 1), (((item + 1) >> 1) & 1) ^ 1);
                        load_q(item + 1, t);
                    }
                }
            }
            load_v(it - 1, vrow);
        }
    } else {
        asm volatile("setmaxnreg.inc.sync.aligned.u32 %0;" :: "n"(FA_RHI));
        attn_consumer(sb, warp >> 2, warp & 3, lane);
    }
}

__device__ __forceinline__ uint32_t cluster_ctarank() {
    uint32_t r; asm volatile("mov.u32 %0, %%cluster_ctarank;" : "=r"(r)); return r;
}
__device__ __forceinline__ uint32_t mapa_u32(uint32_t addr, uint32_t rank) {
    uint32_t r; asm volatile("mapa.shared::cluster.u32 %0, %1, %2;" : "=r"(r) : "r"(addr), "r"(rank)); return r;
}
__device__ __forceinline__ void cluster_sync_all() {
    asm volatile("barrier.cluster.arrive.release.aligned;\nbarrier.cluster.wait.acquire.aligned;" ::: "memory");
}
__device__ __forceinline__ void cluster_sync_relaxed() {
    asm volatile("barrier.cluster.arrive.relaxed.aligned;\nbarrier.cluster.wait.aligned;" ::: "memory");
}
__device__ __forceinline__ void st_async_v4(uint32_t addr, uint32_t a, uint32_t b, uint32_t c, uint32_t d, uint32_t mbar) {
    asm volatile("st.async.weak.shared::cluster.mbarrier::complete_tx::bytes.v4.b32 [%0], {%1, %2, %3, %4}, [%5];"
                 :: "r"(addr), "r"(a), "r"(b), "r"(c), "r"(d), "r"(mbar) : "memory");
}
__device__ __forceinline__ void st_async_v2(uint32_t addr, uint32_t a, uint32_t b, uint32_t mbar) {
    asm volatile("st.async.weak.shared::cluster.mbarrier::complete_tx::bytes.v2.b32 [%0], {%1, %2}, [%3];"
                 :: "r"(addr), "r"(a), "r"(b), "r"(mbar) : "memory");
}
__device__ __forceinline__ void st_async_b32(uint32_t addr, uint32_t a, uint32_t mbar) {
    asm volatile("st.async.weak.shared::cluster.mbarrier::complete_tx::bytes.b32 [%0], %1, [%2];" :: "r"(addr), "r"(a), "r"(mbar) : "memory");
}
__device__ __forceinline__ void pace(int cycles) {
    if (cycles > 0) {
        uint32_t t0, t;
        asm volatile("mov.u32 %0, %%clock;" : "=r"(t0));
        do { asm volatile("mov.u32 %0, %%clock;" : "=r"(t)); } while (t - t0 < (uint32_t)cycles);
    }
}
__device__ __forceinline__ void mbar_wait_cl(uint32_t bar, uint32_t parity) {
    uint32_t done = 0;
    for (int it = 0; it < (1 << 22) && !done; it++) {
        asm volatile(
            "{\n.reg .pred p;\n"
            "mbarrier.try_wait.parity.shared::cta.b64 p, [%1], %2;\n"
            "selp.u32 %0, 1, 0, p;\n}\n" : "=r"(done) : "r"(bar), "r"(parity) : "memory");
    }
}
__device__ __forceinline__ void ldmatrix_x4(uint32_t& r0, uint32_t& r1, uint32_t& r2, uint32_t& r3, uint32_t addr) {
    asm volatile("ldmatrix.sync.aligned.m8n8.x4.shared.b16 {%0,%1,%2,%3}, [%4];"
                 : "=r"(r0), "=r"(r1), "=r"(r2), "=r"(r3) : "r"(addr));
}
__device__ __forceinline__ void cp_async16(uint32_t dst, const void* src) {
    asm volatile("cp.async.cg.shared.global [%0], [%1], 16;" :: "r"(dst), "l"(src) : "memory");
}

#define DBG(i)
#define DBGW(i, w)
#define CYC(i)
#define TM(i)
__device__ __forceinline__ void tma_load_2d_mc(uint32_t dst, const CUtensorMap* map, uint32_t bar, int c0, int c1, uint16_t mask) {
    asm volatile(
        "cp.async.bulk.tensor.2d.shared::cluster.global.mbarrier::complete_tx::bytes.multicast::cluster [%0], [%1, {%3, %4}], [%2], %5;"
        :: "r"(dst), "l"((uint64_t)map), "r"(bar), "r"(c0), "r"(c1), "h"(mask) : "memory");
}
__device__ __forceinline__ void bulk_s2s(uint32_t dst_cl, uint32_t src, uint32_t bytes, uint32_t bar_cl) {
    asm volatile("cp.async.bulk.shared::cluster.shared::cta.mbarrier::complete_tx::bytes [%0], [%1], %2, [%3];"
                 :: "r"(dst_cl), "r"(src), "r"(bytes), "r"(bar_cl) : "memory");
}
__device__ __forceinline__ bool elect_one() {
    uint32_t p;
    asm volatile("{\n.reg .pred p;\nelect.sync _|p, 0xffffffff;\nselp.u32 %0, 1, 0, p;\n}" : "=r"(p));
    return p;
}
__device__ __forceinline__ void fence_async_smem() { asm volatile("fence.proxy.async.shared::cta;" ::: "memory"); }
template <int ID, int N> __device__ __forceinline__ void bar_sync() { asm volatile("bar.sync %0, %1;" :: "n"(ID), "n"(N) : "memory"); }
template <int ID, int N> __device__ __forceinline__ void bar_arrive() { asm volatile("bar.arrive %0, %1;" :: "n"(ID), "n"(N) : "memory"); }
__device__ __forceinline__ void sts32(uint32_t a, uint32_t v) { asm volatile("st.shared.u32 [%0], %1;" :: "r"(a), "r"(v) : "memory"); }
__device__ __forceinline__ void ldsm_x4(uint32_t* r, uint32_t addr) {
    asm volatile("ldmatrix.sync.aligned.m8n8.x4.shared.b16 {%0,%1,%2,%3}, [%4];" : "=r"(r[0]), "=r"(r[1]), "=r"(r[2]), "=r"(r[3]) : "r"(addr) : "memory");
}
__device__ __forceinline__ uint32_t pin(uint32_t v) { asm volatile("" : "+r"(v)); return v; }
constexpr uint32_t DHI128 = 0x40000040u, DHI32 = 0xC0000010u;
#define ACC16(d) "+f"(d[0]), "+f"(d[1]), "+f"(d[2]), "+f"(d[3]), "+f"(d[4]), "+f"(d[5]), "+f"(d[6]), "+f"(d[7]), "+f"(d[8]), "+f"(d[9]), "+f"(d[10]), \
    "+f"(d[11]), "+f"(d[12]), "+f"(d[13]), "+f"(d[14]), "+f"(d[15])
#define ACC20(d) ACC16(d), "+f"(d[16]), "+f"(d[17]), "+f"(d[18]), "+f"(d[19])
__device__ __forceinline__ void wgmma_rs(float (&d)[16], const uint32_t (&a)[4], uint32_t db_lo) {
    asm volatile(
        "{\n.reg .b64 db;\nmov.b64 db, {%20, %21};\n"
        "wgmma.mma_async.sync.aligned.m64n32k16.f32.bf16.bf16 {%0,%1,%2,%3,%4,%5,%6,%7,%8,%9,%10,%11,%12,%13,%14,%15}, {%16,%17,%18,%19}, db, 1, 1, 1, 0;\n}\n"
        : ACC16(d) : "r"(a[0]), "r"(a[1]), "r"(a[2]), "r"(a[3]), "r"(db_lo), "n"(DHI128));
}
__device__ __forceinline__ void wgmma_rs(float (&d)[20], const uint32_t (&a)[4], uint32_t db_lo) {
    asm volatile(
        "{\n.reg .b64 db;\nmov.b64 db, {%24, %25};\n"
        "wgmma.mma_async.sync.aligned.m64n40k16.f32.bf16.bf16 {%0,%1,%2,%3,%4,%5,%6,%7,%8,%9,%10,%11,%12,%13,%14,%15,%16,%17,%18,%19}, {%20,%21,%22,%23}, db, 1, 1, 1, 0;\n}\n"
        : ACC20(d) : "r"(a[0]), "r"(a[1]), "r"(a[2]), "r"(a[3]), "r"(db_lo), "n"(DHI128));
}
template <uint32_t AHI, uint32_t BHI>
__device__ __forceinline__ void wgmma_ss(float (&d)[16], uint32_t da_lo, uint32_t db_lo) {
    asm volatile(
        "{\n.reg .b64 da, db;\nmov.b64 da, {%16, %18};\nmov.b64 db, {%17, %19};\n"
        "wgmma.mma_async.sync.aligned.m64n32k16.f32.bf16.bf16 {%0,%1,%2,%3,%4,%5,%6,%7,%8,%9,%10,%11,%12,%13,%14,%15}, da, db, 1, 1, 1, 0, 0;\n}\n"
        : ACC16(d) : "r"(da_lo), "r"(db_lo), "n"(AHI), "n"(BHI));
}
template <uint32_t AHI, uint32_t BHI>
__device__ __forceinline__ void wgmma_ss(float (&d)[20], uint32_t da_lo, uint32_t db_lo) {
    asm volatile(
        "{\n.reg .b64 da, db;\nmov.b64 da, {%20, %22};\nmov.b64 db, {%21, %23};\n"
        "wgmma.mma_async.sync.aligned.m64n40k16.f32.bf16.bf16 {%0,%1,%2,%3,%4,%5,%6,%7,%8,%9,%10,%11,%12,%13,%14,%15,%16,%17,%18,%19}, da, db, 1, 1, 1, 0, 0;\n}\n"
        : ACC20(d) : "r"(da_lo), "r"(db_lo), "n"(AHI), "n"(BHI));
}
template <uint32_t AHI, uint32_t BHI>
__device__ __forceinline__ void wgmma_ss0(float (&d)[20], uint32_t da_lo, uint32_t db_lo) {
    asm volatile(
        "{\n.reg .b64 da, db;\nmov.b64 da, {%20, %22};\nmov.b64 db, {%21, %23};\n"
        "wgmma.mma_async.sync.aligned.m64n40k16.f32.bf16.bf16 {%0,%1,%2,%3,%4,%5,%6,%7,%8,%9,%10,%11,%12,%13,%14,%15,%16,%17,%18,%19}, da, db, 0, 1, 1, 0, 0;\n}\n"
        : "=f"(d[0]), "=f"(d[1]), "=f"(d[2]), "=f"(d[3]), "=f"(d[4]), "=f"(d[5]), "=f"(d[6]), "=f"(d[7]), "=f"(d[8]), "=f"(d[9]), "=f"(d[10]),
          "=f"(d[11]), "=f"(d[12]), "=f"(d[13]), "=f"(d[14]), "=f"(d[15]), "=f"(d[16]), "=f"(d[17]), "=f"(d[18]), "=f"(d[19])
        : "r"(da_lo), "r"(db_lo), "n"(AHI), "n"(BHI));
}
__device__ __forceinline__ void wgmma_ss_n8(float (&d)[4], uint32_t da_lo, uint32_t db_lo) {
    asm volatile(
        "{\n.reg .b64 da, db;\nmov.b64 da, {%4, %6};\nmov.b64 db, {%5, %7};\n"
        "wgmma.mma_async.sync.aligned.m64n8k16.f32.bf16.bf16 {%0,%1,%2,%3}, da, db, 1, 1, 1, 1, 0;\n}\n"
        : "+f"(d[0]), "+f"(d[1]), "+f"(d[2]), "+f"(d[3]) : "r"(da_lo), "r"(db_lo), "n"(DHI128), "n"(DHI32));
}

__device__ __forceinline__ void wgmma_ss_n32_ta(float (&d)[16], uint32_t da_lo, uint32_t db_lo) {
    asm volatile(
        "{\n.reg .b64 da, db;\nmov.b64 da, {%16, %18};\nmov.b64 db, {%17, %18};\n"
        "wgmma.mma_async.sync.aligned.m64n32k16.f32.bf16.bf16 {%0,%1,%2,%3,%4,%5,%6,%7,%8,%9,%10,%11,%12,%13,%14,%15}, da, db, 1, 1, 1, 1, 0;\n}\n"
        : ACC16(d) : "r"(da_lo), "r"(db_lo), "n"(DHI128));
}

constexpr uint32_t C2_WO = 0;
constexpr uint32_t C2_XB = 65536;
constexpr uint32_t C2_XS = 40960;
constexpr uint32_t C2_QX = C2_XB + 2 * C2_XS;
constexpr uint32_t C2_KX = C2_QX + 4096;
constexpr uint32_t C2_VT = C2_KX + 5120;
constexpr uint32_t C2_OB = C2_VT + 12288;
constexpr uint32_t C2_QM = C2_OB + 8192;
constexpr uint32_t C2_SC = C2_QM + 1024;
constexpr uint32_t C2_PB = C2_SC + 2560;
constexpr uint32_t C2_BAR = C2_PB + 768;
constexpr uint32_t C2_PX = C2_BAR + 256;
constexpr uint32_t C2_SX = C2_PX + 3072;
#define C2_NS 4
constexpr uint32_t C2_WS = C2_SX + 20480;
constexpr int C2_SMEM = C2_WS + 3 * C2_NS * 2048;
static_assert(C2_PX % 256 == 0 && C2_WS % 256 == 0 && C2_SMEM <= 232448, "smem map");
#define CH_PFD 1000
#define CH_PT 1260
#define CH_PT1 CH_PT
#define CH_WOT 1
#define CH_NCH 4
#define CH_NQ1 12
#define CH_POLL_DELAY 600

__device__ __forceinline__ uint32_t c2_stage(int wg, int i) { return wg < 2 ? C2_XB + C2_XS + (wg * 4 + i) * 8192 : ((C2_PX + 1023) & ~1023u) + i * 8192; }
static_assert(C2_XB + C2_XS + 8 * 8192 <= C2_BAR && ((C2_PX + 1023) & ~1023u) + 4 * 8192 <= C2_SMEM && (C2_XB + C2_XS) % 1024 == 0, "staging");
__device__ __forceinline__ void c2_stage_load(const CUtensorMap* map, uint32_t sb, int wg, int rank, int col0, int round) {
    const uint32_t bar = sb + C2_BAR + 176 + (wg * 2 + round) * 8;
    mbar_expect_tx(bar, 32768);
#pragma unroll 1
    for (int i = 0; i < 4; i++) {
        tma_load_2d(sb + c2_stage(wg, i), map, bar, col0, ((rank - round * 4 - i) & 7) * 64);
        if (i < 3) pace(round ? CH_PT1 : CH_PT);
    }
}
__device__ __forceinline__ void c2_load_w(uint32_t (&w)[32][4], const CUtensorMap* map, int wg, int rank, int col0, uint32_t t128, uint32_t ws, uint32_t sb) {
    const uint32_t s0 = pin(sb + c2_stage(wg, 0) + t128), s1 = pin(sb + c2_stage(wg, 0) + (t128 ^ 16) + 128);
#pragma unroll
    for (int r = 0; r < 2; r++) {
        mbar_wait(sb + C2_BAR + 176 + (wg * 2 + r) * 8, 0);
#pragma unroll
        for (int e = 0; e < 16; e++) {
            uint32_t w0, w1, w2, w3;
            asm volatile("ld.shared.b32 %0, [%1];" : "=r"(w0) : "r"(s0 + e * 2048) : "memory");
            asm volatile("ld.shared.b32 %0, [%1];" : "=r"(w1) : "r"(s1 + e * 2048) : "memory");
            asm volatile("ld.shared.b32 %0, [%1];" : "=r"(w2) : "r"(s0 + e * 2048 + 1024) : "memory");
            asm volatile("ld.shared.b32 %0, [%1];" : "=r"(w3) : "r"(s1 + e * 2048 + 1024) : "memory");
            uint32_t* d = w[r * 16 + e];
            d[0] = __byte_perm(w0, w1, 0x5410); d[1] = __byte_perm(w0, w1, 0x7632);
            d[2] = __byte_perm(w2, w3, 0x5410); d[3] = __byte_perm(w2, w3, 0x7632);
        }
        if (r == 0) {
            asm volatile("bar.sync %0, 128;" :: "r"(8 + wg) : "memory");
            if ((threadIdx.x & 127) == 32) c2_stage_load(map, sb, wg, rank, col0, 1);
            mbar_wait(sb + C2_BAR + 168, 0);
#pragma unroll 1
            for (int i = threadIdx.x; i < 2048; i += 384) {
                const int k = i >> 2, b = i & 3;
                const uint32_t a0 = sb + C2_WO + k * 128 + (((2 * b) ^ (k & 7)) << 4), a1 = a0 ^ 16;
                uint4 u, v;
                asm volatile("ld.shared.v4.b32 {%0, %1, %2, %3}, [%4];" : "=r"(u.x), "=r"(u.y), "=r"(u.z), "=r"(u.w) : "r"(a0) : "memory");
                asm volatile("ld.shared.v4.b32 {%0, %1, %2, %3}, [%4];" : "=r"(v.x), "=r"(v.y), "=r"(v.z), "=r"(v.w) : "r"(a1) : "memory");
                asm volatile("st.shared.v4.b32 [%0], {%1, %2, %3, %4};" :: "r"(a0), "r"(__byte_perm(u.x, u.y, 0x5410)),
                             "r"(__byte_perm(u.z, u.w, 0x5410)), "r"(__byte_perm(v.x, v.y, 0x5410)), "r"(__byte_perm(v.z, v.w, 0x5410)) : "memory");
                asm volatile("st.shared.v4.b32 [%0], {%1, %2, %3, %4};" :: "r"(a1), "r"(__byte_perm(u.x, u.y, 0x7632)),
                             "r"(__byte_perm(u.z, u.w, 0x7632)), "r"(__byte_perm(v.x, v.y, 0x7632)), "r"(__byte_perm(v.z, v.w, 0x7632)) : "memory");
            }
        }
    }
    cluster_sync_relaxed();
#pragma unroll
    for (int e = 0; e < C2_NS; e++) stmatrix_x4(ws + e * 2048, w[e][0], w[e][1], w[e][2], w[e][3]);
#pragma unroll 1
    for (int i = threadIdx.x; i < 2 * 512 + 256; i += 384)
        sts32(sb + (i < 1024 ? C2_VT + (i >> 9) * 6144 + 4096 + (i & 511) * 4 : C2_PX + 2048 + (i - 1024) * 4), 0u);
    fence_async_smem();
    asm volatile("bar.sync %0, 128;" :: "r"(8 + wg) : "memory");
}
template <int E0, int E1, int NA>
__device__ __forceinline__ void c2_xstream(float (&acc)[NA], const uint32_t (&w)[32][4], uint32_t xlo, uint32_t rank, uint32_t wslo) {
    if (E0 == 0)
#pragma unroll
        for (int i = 0; i < NA; i++) acc[i] = 0.f;
    wgmma_fence();
#pragma unroll
    for (int e = E0; e < E1; e++) {
        if (e < C2_NS) wgmma_ss<DHI32, DHI128>(acc, wslo + e * 128, xlo + ((rank - (e >> 2)) & 7) * 320 + (e & 3) * 2);
        else wgmma_rs(acc, w[e], xlo + ((rank - (e >> 2)) & 7) * 320 + (e & 3) * 2);
    }
    wgmma_commit();
}
__device__ __forceinline__ constexpr uint32_t c2_tslot(int i) { return i == 0 ? C2_QX : i < 4 ? C2_OB + (i - 1) * 4096 : ((C2_WS + 1023) & ~1023u) + (i - 4) * 4096; }
static_assert(C2_QX % 1024 == 0 && C2_OB % 1024 == 0 && c2_tslot(3) + 4096 <= C2_BAR && c2_tslot(7) + 4096 <= C2_SMEM, "tail slots");
__device__ __forceinline__ constexpr int c2_grp(int i) { return i < 2 ? i : 1 + (i >> 1); }

struct ChainParams {
    CUtensorMap mapX;
    CUtensorMap mapM;
    CUtensorMap mapW[3];
    CUtensorMap mapWo;
    CUtensorMap mapC;
    bf16* out;
};
__global__ void __cluster_dims__(8, 1, 1) __launch_bounds__(384, 1)
chain_kernel(const __grid_constant__ ChainParams P) {
    const CUtensorMap& mapX = P.mapX;
    extern __shared__ __align__(1024) uint8_t smem_chain[];
    const uint32_t sb = smem_u32(smem_chain);
    const uint32_t dlo = ((sb & 0x3FFFF) >> 4) | (1u << 16);
    const int tid = __shfl_sync(0xffffffff, threadIdx.x, threadIdx.x & 31), lane = tid & 31;
    const int warp = __shfl_sync(0xffffffff, tid >> 5, 0), wg = warp >> 2, w4 = warp & 3;
    const uint32_t rank = cluster_ctarank();
    const int C = blockIdx.x >> 3;
    const int h = C * 4 + (rank >> 1);
    const int g = lane >> 2, qc = lane & 3;
    pdl_launch_dependents();
    TS_BEGIN(2);
    CYC(0);
    const uint32_t bar_m = sb + C2_BAR, bar_o = bar_m + 64, bar_sc = bar_m + 128, bar_x = bar_m + 136, bar_sx = bar_m + 152;
    const uint32_t bar_w = bar_m + 168, bar_h = bar_m + 40;
    const int col0 = h * HD + (rank & 1) * 64;
    if (tid == 0) {
        for (int j = 0; j < 5; j++) { mbar_init(bar_m + 8 * j, j ? 1 : 4); mbar_init(bar_o + 8 * j, j ? 1 : 4); }
        for (int j = 0; j < 12; j++) mbar_init(bar_sc + 8 * j, 1);
        mbar_init(bar_h, 32); mbar_init(bar_h + 8, 32);
        asm volatile("fence.mbarrier_init.release.cluster;" ::: "memory");
    }
    __syncwarp();
    cluster_sync_relaxed();
    if (tid == 0) {
        mbar_expect_tx(bar_x, 32768 + 8192);
        tma_load_2d_mc(sb + C2_XB + rank * 5120, &mapX, bar_x, rank * 64, 0, (uint16_t)0xff);
#pragma unroll 1
        for (int j = 0; j < 8; j++) tma_load_2d(sb + C2_XB + j * 5120 + 4096, &P.mapM, bar_x, j * 64, 0);
        mbar_expect_tx(bar_w, 65536);
    }
    if ((tid & 127) == 32) {
        pace(CH_PFD);
        c2_stage_load(&P.mapW[wg], sb, wg, rank, col0, 0);
#pragma unroll 1
        for (int j = wg; j < 8; j += 3) {
            pace(CH_PT1);
            tma_load_2d(sb + C2_WO + j * 8192, &P.mapWo, bar_w, rank * 64, C * 512 + ((rank - j) & 7) * 64);
        }
    }
    __syncwarp();

    const uint32_t t32 = w4 * 256 + qc * 64 + (((g >> 2) ^ (qc >> 1)) << 4) + (g & 3) * 4;
    const uint32_t t128 = qc * 256 + (((2 * w4 + (g >> 2)) ^ (2 * qc)) << 4) + (g & 3) * 4;
    const uint32_t a32 = (w4 * 16 + (lane & 15)) * 32 + (((lane >> 4) ^ ((lane >> 2) & 1)) << 4);
    const uint32_t ws = sb + C2_WS + wg * (C2_NS * 2048) + a32;
    uint32_t w[32][4];
    static_assert(C2_NS == 4, "slot 0");
    auto proj_mem = [&](float (&a)[CH_NCH][4], int s, uint32_t l128) {
        uint32_t b[4][8];
#pragma unroll
        for (int i = 0; i < 4 * CH_NCH; i++) a[i >> 2][i & 3] = 0.f;
        const uint32_t par = (s & 1) ^ 1;
        const uint32_t mb = sb + C2_XB + (s & 1) * C2_XS + 4096;
        auto L = [&](int i) {
            ldsm_x4(b[i & 3], mb + ((rank - i) & 7) * 5120 + l128);
            ldsm_x4(b[i & 3] + 4, mb + ((rank - i) & 7) * 5120 + (l128 ^ 64));
        };
        auto H = [&](int i) {
#pragma unroll
            for (int kk = 0; kk < 4; kk++) {
                const uint32_t* f = i ? w[i * 4 + kk] : &b[2 + (kk >> 1)][(kk & 1) * 4];
                mma_16816(a[(i * 4 + kk) % CH_NCH], f[0], f[1], f[2], f[3], b[i & 3][2 * kk], b[i & 3][2 * kk + 1]);
            }
        };
#pragma unroll
        for (int e = 0; e < 4; e++) ldsm_x4(&b[2 + (e >> 1)][(e & 1) * 4], ws + e * 2048);
        mbar_wait(bar_m, par);
        L(0);
        H(0);
        mbar_wait(bar_m + 8, par);
        DBGW(1 + 16 * wg, 0);
        L(1);
        mbar_wait(bar_m + 16, par);
        uint32_t nxt = mbar_test(bar_m + 24, par);
        L(2); L(3);
        H(1);
        if (__builtin_expect(!nxt, 0)) mbar_wait(bar_m + 24, par);
        nxt = mbar_test(bar_m + 32, par);
        L(4); L(5);
        H(2); H(3);
        if (__builtin_expect(!nxt, 0)) mbar_wait(bar_m + 32, par);
        DBGW(2 + 16 * wg, 0);
        L(6); L(7);
        H(4); H(5); H(6); H(7);
#pragma unroll
        for (int i = 0; i < 4; i++) a[0][i] = CH_NCH == 4 ? (a[0][i] + a[1][i]) + (a[2][i] + a[3 % CH_NCH][i]) : CH_NCH == 3 ? a[0][i] + a[1][i] + a[2 % CH_NCH][i] : a[0][i] + a[1][i];
    };
    auto store_x = [&](const float (&acc)[16], uint32_t base) {
#pragma unroll
        for (int j = 0; j < 4; j++) {
            sts32(base + t128 + j * 1024, pack_bf16(acc[4 * j], acc[4 * j + 2]));
            sts32(base + (t128 ^ 16) + 128 + j * 1024, pack_bf16(acc[4 * j + 1], acc[4 * j + 3]));
        }
    };
    auto tail_load = [&](int q, int b) {
        if (q == 2) asm volatile("fence.acq_rel.gpu;" ::: "memory");
        asm volatile("fence.proxy.async.global;" ::: "memory");
        mbar_expect_tx(bar_x + 8 * b, 32768);
        tma_load_2d_mc(sb + C2_XB + b * C2_XS + rank * 5120, &P.mapC, bar_x + 8 * b, (rank & 1) * 64, h * SEQ + (NSEG - 4 + q) * SEGL, (uint16_t)0xff);
    };
    auto fresh_lane = [&]() { uint32_t l; asm volatile("mov.u32 %0, %%laneid;" : "=r"(l)); return l; };
    auto tail_arrive = [&](int i) {
        const uint32_t lane = fresh_lane();
        if (lane < 8) asm volatile("mbarrier.arrive.relaxed.cluster.shared::cluster.b64 _, [%0];" :: "r"(mapa_u32(bar_h + 8 * i, lane)) : "memory");
        __syncwarp();
    };
    const float scale = 0.08838834764831845f, l2e = 1.4426950408889634f;
    c2_load_w(w, &P.mapW[wg], wg, rank, col0, t128, ws, sb);
    TS_END(6);
    TS_BEGIN(5);
    CYC(1);

    if (wg == 0) {
#pragma unroll 1
        for (int s = -1;;) {
            float qx[16];
            uint32_t* dst = reinterpret_cast<uint32_t*>(g_xbuf + (((s & 1) * 8 + rank) * 8 + C) * 128) + qc * 64 + w4 * 8 + g;
            asm volatile("" : "+l"(dst));
            mbar_wait(bar_x + 8 * ((s + 1) & 1), ((s + 1) >> 1) & 1);
            if (s >= 0) bar_sync<6, 384>();
            c2_xstream<0, CH_NQ1>(qx, w, dlo + ((C2_XB + ((s + 1) & 1) * C2_XS) >> 4), rank, dlo + (C2_WS >> 4));
            if (s >= 0) {
                float acc[4] = {0.f, 0.f, 0.f, 0.f};
                const uint32_t tag = ((s >> 1) & 1) ^ 1;
                uint32_t nxt = 0;
#pragma unroll
                for (int i = 0; i < 8; i++) {
                    if (i < 2 || !(i & 1)) {
                        if (i < 2 || __builtin_expect(!nxt, 0)) mbar_wait(bar_o + 8 * c2_grp(i), s & 1);
                        if (i == 0) DBGW(7, 0);
                        if (i == 1) DBGW(8, 0);
                        if (i == 6) DBGW(9, 0);
                        wgmma_fence();
                    }
#pragma unroll
                    for (int kk = 0; kk < 4; kk++) {
                        if ((i & 1) && i < 7 && kk == CH_WOT) nxt = mbar_test(bar_o + 8 * c2_grp(i + 1), s & 1);
                        wgmma_ss_n8(acc, dlo + ((C2_WO + i * 8192 + kk * 2048) >> 4), dlo + ((C2_OB + i * 1024 + kk * 256) >> 4));
                    }
                }
                wgmma_commit();
                bar_arrive<11, 256>();
                wgmma_wait<0>();
                asm volatile("st.relaxed.gpu.global.u32 [%0], %1;" :: "l"(dst), "r"((pack_bf16(acc[0], acc[2]) & ~1u) | tag) : "memory");
                asm volatile("st.relaxed.gpu.global.u32 [%0 + 128], %1;" :: "l"(dst), "r"((pack_bf16(acc[1], acc[3]) & ~1u) | tag) : "memory");
                bar_arrive<4, 256>();
                DBGW(10, 0);
            }
            s++;
            c2_xstream<CH_NQ1, 32>(qx, w, dlo + ((C2_XB + (s & 1) * C2_XS) >> 4), rank, dlo + (C2_WS >> 4));
            const uint32_t sca = pin(w4 < 2 ? sb + C2_SC + w4 * 512 + lane * 16 : sb + C2_SC + 1024 + lane * 8);
            const uint32_t krow = w4 * 16 + (lane & 15);
            const uint32_t ka0 = pin(sb + C2_KX + krow * 128 + (((lane >> 4) ^ (krow & 7)) << 4));
            const uint32_t l32 = pin(sb + C2_QM + (lane >> 4) * 256 + (lane & 7) * 32 + ((((lane >> 3) & 1) ^ ((lane >> 2) & 1)) << 4));
            const uint32_t qst = pin(sb + C2_QM + t32);
            const uint32_t l128 = pin((lane & 7) * 128 + (((lane >> 3) ^ (lane & 7)) << 4));
            if (s > 0) bar_sync<5, 256>();
            wgmma_wait<0>();
            store_x(qx, sb + C2_QX);
            DBGW(0, 0);
            if (s == NSEG - 1) break;
            {
                float a[CH_NCH][4];
                proj_mem(a, s, l128);
                sts32(qst, pack_bf16(a[0][0], a[0][2]));
                sts32(qst + 32, pack_bf16(a[0][1], a[0][3]));
            }
            DBGW(3, 0);
            if (w4 < 3) {
                uint32_t ka[4][4], qb[8];
                float c[4] = {0.f, 0.f, 0.f, 0.f}, c2[4] = {0.f, 0.f, 0.f, 0.f};
                const uint32_t sc_peer = pin(mapa_u32(sca + 1280, rank ^ 1)), sc_own = pin(mapa_u32(sca, rank));
                bar_sync<1, 384>();
                ldsm_x4(qb, l32);
                ldsm_x4(ka[0], ka0);
                ldsm_x4(ka[1], ka0 ^ 32);
                ldsm_x4(qb + 4, l32 + 512);
                ldsm_x4(ka[2], ka0 ^ 64);
                ldsm_x4(ka[3], ka0 ^ 96);
                mma_16816(c, ka[0][0], ka[0][1], ka[0][2], ka[0][3], qb[0], qb[1]);
                mma_16816(c2, ka[1][0], ka[1][1], ka[1][2], ka[1][3], qb[2], qb[3]);
                mma_16816(c, ka[2][0], ka[2][1], ka[2][2], ka[2][3], qb[4], qb[5]);
                mma_16816(c2, ka[3][0], ka[3][1], ka[3][2], ka[3][3], qb[6], qb[7]);
                const uint32_t u0 = __float_as_uint(c[0] + c2[0]), u1 = __float_as_uint(c[1] + c2[1]);
                const uint32_t u2 = __float_as_uint(c[2] + c2[2]), u3 = __float_as_uint(c[3] + c2[3]);
                asm volatile(
                    "{\n.reg .pred p;\nsetp.lt.u32 p, %8, 2;\n"
                    "@p st.async.weak.shared::cluster.mbarrier::complete_tx::bytes.v4.b32 [%0], {%4, %5, %6, %7}, [%1];\n"
                    "@!p st.async.weak.shared::cluster.mbarrier::complete_tx::bytes.v2.b32 [%0], {%4, %5}, [%1];\n"
                    "@p st.async.weak.shared::cluster.mbarrier::complete_tx::bytes.v4.b32 [%2], {%4, %5, %6, %7}, [%3];\n"
                    "@!p st.async.weak.shared::cluster.mbarrier::complete_tx::bytes.v2.b32 [%2], {%4, %5}, [%3];\n}"
                    :: "r"(sc_peer), "r"(mapa_u32(bar_sc, rank ^ 1)), "r"(sc_own), "r"(mapa_u32(bar_sc, rank)), "r"(u0), "r"(u1), "r"(u2), "r"(u3), "r"(w4) : "memory");
                bar_arrive<2, 224>();
                fence_async_smem();
                if (s >= 4 * CB_FIRST + 5 && (s & 3) == 1 && tid == 0) signal_ctr(CT_CB + ((s - 5) >> 2));
                __syncwarp();
                DBGW(4, 2);
            } else {
                bar_arrive<1, 384>();
                fence_async_smem();
                const uint32_t a = pin(sb + C2_SC + lane * 16), a2 = pin(sb + C2_SC + 1024 + lane * 8), pa = pin(sb + C2_PB + lane * 4);
                mbar_wait(bar_sc, s & 1);
                DBG(5);
                float v[10];
                {
                    float4 x0, x1, y0, y1; float2 x2, y2;
                    asm volatile("ld.shared.v4.f32 {%0, %1, %2, %3}, [%4];" : "=f"(x0.x), "=f"(x0.y), "=f"(x0.z), "=f"(x0.w) : "r"(a) : "memory");
                    asm volatile("ld.shared.v4.f32 {%0, %1, %2, %3}, [%4];" : "=f"(y0.x), "=f"(y0.y), "=f"(y0.z), "=f"(y0.w) : "r"(a + 1280) : "memory");
                    asm volatile("ld.shared.v4.f32 {%0, %1, %2, %3}, [%4];" : "=f"(x1.x), "=f"(x1.y), "=f"(x1.z), "=f"(x1.w) : "r"(a + 512) : "memory");
                    asm volatile("ld.shared.v4.f32 {%0, %1, %2, %3}, [%4];" : "=f"(y1.x), "=f"(y1.y), "=f"(y1.z), "=f"(y1.w) : "r"(a + 1792) : "memory");
                    asm volatile("ld.shared.v2.f32 {%0, %1}, [%2];" : "=f"(x2.x), "=f"(x2.y) : "r"(a2) : "memory");
                    asm volatile("ld.shared.v2.f32 {%0, %1}, [%2];" : "=f"(y2.x), "=f"(y2.y) : "r"(a2 + 1280) : "memory");
                    v[0] = x0.x + y0.x; v[1] = x0.y + y0.y; v[2] = x0.z + y0.z; v[3] = x0.w + y0.w;
                    v[4] = x1.x + y1.x; v[5] = x1.y + y1.y; v[6] = x1.z + y1.z; v[7] = x1.w + y1.w;
                    v[8] = x2.x + y2.x; v[9] = x2.y + y2.y;
                }
                float m0 = fmaxf(fmaxf(fmaxf(v[0], v[2]), fmaxf(v[4], v[6])), v[8]);
                float m1 = fmaxf(fmaxf(fmaxf(v[1], v[3]), fmaxf(v[5], v[7])), v[9]);
#pragma unroll
                for (int o = 4; o < 32; o <<= 1) {
                    m0 = fmaxf(m0, __shfl_xor_sync(0xffffffff, m0, o));
                    m1 = fmaxf(m1, __shfl_xor_sync(0xffffffff, m1, o));
                }
                const float sl = scale * l2e;
                m0 *= sl; m1 *= sl;
#pragma unroll
                for (int j = 0; j < 5; j++)
                    sts32(pa + j * 128, pack_bf16(ex2f(fmaf(v[2 * j], sl, -m0)), ex2f(fmaf(v[2 * j + 1], sl, -m1))));
                bar_arrive<3, 160>();
                DBG(6);
            }
        }
        bar_arrive<1, 384>();
        fence_async_smem();
        bar_arrive<6, 384>();
        TS_MARK(8, 0);
        CYC(2);
        TM(0);
    } else if (wg == 1) {
#pragma unroll 1
        for (int s = -1;;) {
            if (s > 0) {
                mbar_wait(bar_sx + 8 * ((s - 1) & 1), ((s - 1) >> 1) & 1);
                const uint32_t a = sb + C2_SX + ((s - 1) & 1) * 10240 + w4 * 1280 + lane * 8;
                float v[10];
                const int lim = 8 * w4 + g - 2 * qc;
#pragma unroll
                for (int j = 0; j < 5; j++) {
                    float2 x, y;
                    asm volatile("ld.shared.v2.f32 {%0, %1}, [%2];" : "=f"(x.x), "=f"(x.y) : "r"(a + j * 256) : "memory");
                    asm volatile("ld.shared.v2.f32 {%0, %1}, [%2];" : "=f"(y.x), "=f"(y.y) : "r"(a + 5120 + j * 256) : "memory");
                    v[2 * j] = (j < 4 && 8 * j > lim) ? -INFINITY : x.x + y.x;
                    v[2 * j + 1] = (j < 4 && 8 * j + 1 > lim) ? -INFINITY : x.y + y.y;
                }
                float mx = fmaxf(fmaxf(fmaxf(v[0], v[1]), fmaxf(v[2], v[3])), fmaxf(fmaxf(v[4], v[5]), fmaxf(v[6], v[7])));
                mx = fmaxf(mx, fmaxf(v[8], v[9]));
                mx = fmaxf(mx, __shfl_xor_sync(0xffffffff, mx, 1));
                mx = fmaxf(mx, __shfl_xor_sync(0xffffffff, mx, 2));
                const float sl = scale * l2e;
                mx *= sl;
#pragma unroll
                for (int j = 0; j < 10; j++) v[j] = ex2f(fmaf(v[j], sl, -mx));
                float sm = ((v[0] + v[1]) + (v[2] + v[3])) + ((v[4] + v[5]) + (v[6] + v[7])) + (v[8] + v[9]);
                sm += __shfl_xor_sync(0xffffffff, sm, 1);
                sm += __shfl_xor_sync(0xffffffff, sm, 2);
                float inv;
                asm("rcp.approx.ftz.f32 %0, %1;" : "=f"(inv) : "f"(sm));
                const uint32_t pa = sb + C2_PX + w4 * 256 + g * 32 + ((g >> 2) << 4) + qc * 4;
#pragma unroll
                for (int j = 0; j < 5; j++) sts32((pa ^ ((j & 1) << 4)) + (j >> 1) * 1024, pack_bf16(v[2 * j] * inv, v[2 * j + 1] * inv));
            }
            if (s >= 0) {
                fence_async_smem();
                if (s < NSEG) bar_sync<6, 384>(); else bar_sync<7, 256>();
                DBGW(20, 0);
                TM(s < NSEG ? 2 : 4);
                uint32_t cp[8];
                {
                    float cx[16];
#pragma unroll
                    for (int i = 0; i < 16; i++) cx[i] = 0.f;
                    wgmma_fence();
#pragma unroll
                    for (int kk = 0; kk < 3; kk++)
                        wgmma_ss<DHI32, DHI32>(cx, dlo + ((C2_VT + ((s - 1) & 1) * 6144 + kk * 2048) >> 4), dlo + ((C2_PX + kk * 1024) >> 4));
                    wgmma_commit();
                    wgmma_wait<0>();
#pragma unroll
                    for (int j = 0; j < 4; j++) { cp[2 * j] = pack_bf16(cx[4 * j], cx[4 * j + 2]); cp[2 * j + 1] = pack_bf16(cx[4 * j + 1], cx[4 * j + 3]); }
                    asm volatile("{\n.reg .pred p;\nsetp.gt.u32 p, %0, 99;\n@p st.shared.v4.b32 [%0], {%1, %2, %3, %4};\n@p st.shared.v4.b32 [%0], {%5, %6, %7, %8};\n}"
                                 :: "r"(rank), "r"(cp[0]), "r"(cp[1]), "r"(cp[2]), "r"(cp[3]), "r"(cp[4]), "r"(cp[5]), "r"(cp[6]), "r"(cp[7]) : "memory");
                }
                if (s == NSEG) {
#pragma unroll
                    for (int j = 0; j < 4; j++) {
                        sts32(sb + C2_QX + t128 + j * 1024, cp[2 * j]);
                        sts32(sb + C2_QX + (t128 ^ 16) + 128 + j * 1024, cp[2 * j + 1]);
                    }
                    break;
                }
                float sx[20];
                wgmma_fence();
                wgmma_ss0<DHI128, DHI128>(sx, dlo + (C2_QX >> 4), dlo + (C2_KX >> 4));
#pragma unroll
                for (int kk = 1; kk < 4; kk++) wgmma_ss<DHI128, DHI128>(sx, dlo + (C2_QX >> 4) + kk * 2, dlo + (C2_KX >> 4) + kk * 2);
                wgmma_commit();
                wgmma_wait<0>();
                if (s < NSEG - 1) bar_arrive<5, 256>();
                if (s > 0) {
                    uint32_t* dst = reinterpret_cast<uint32_t*>(g_ctxB + ((size_t)h * SEQ + (s - 1) * SEGL + 2 * qc) * HD + (rank & 1) * 64 + w4 * 16 + 2 * g);
#pragma unroll
                    for (int j = 0; j < 4; j++) {
                        asm volatile("st.global.u32 [%0], %1;" :: "l"(dst + j * 8 * (HD / 2)), "r"(cp[2 * j]) : "memory");
                        asm volatile("st.global.u32 [%0], %1;" :: "l"(dst + (j * 8 + 1) * (HD / 2)), "r"(cp[2 * j + 1]) : "memory");
                    }
                }
                DBGW(22, 0);
                TM(3);
                if (s >= NSEG - 2) asm volatile("bar.arrive %0, 160;" :: "r"(s - (NSEG - 2) + 12) : "memory");
                const uint32_t a = sb + C2_SX + (s & 1) * 10240 + w4 * 2560 + lane * 8;
                if (w4 < 2) {
#pragma unroll
                    for (int j = 0; j < 5; j++) {
                        asm volatile("st.shared.v2.f32 [%0], {%1, %2};" :: "r"(a + j * 256), "f"(sx[4 * j]), "f"(sx[4 * j + 1]) : "memory");
                        asm volatile("st.shared.v2.f32 [%0], {%1, %2};" :: "r"(a + 1280 + j * 256), "f"(sx[4 * j + 2]), "f"(sx[4 * j + 3]) : "memory");
                    }
                }
                if (s < NSEG - 1) mbar_wait(bar_x + 8 * ((s + 1) & 1), ((s + 1) >> 1) & 1);
                const uint32_t pa = mapa_u32(a + 5120, rank ^ 1), pb = mapa_u32(bar_sx + 8 * (s & 1), rank ^ 1);
                if (s < NSEG - 1) bar_sync<4, 256>();
                if (w4 < 2) {
#pragma unroll
                    for (int j = 0; j < 5; j++) {
                        st_async_v2(pa + j * 256, __float_as_uint(sx[4 * j]), __float_as_uint(sx[4 * j + 1]), pb);
                        st_async_v2(pa + 1280 + j * 256, __float_as_uint(sx[4 * j + 2]), __float_as_uint(sx[4 * j + 3]), pb);
                    }
                }
            } else mbar_wait(bar_x, 0);
            s++;
            if (s < NSEG) {
                float acc[16];
                c2_xstream<0, 32>(acc, w, dlo + ((C2_XB + (s & 1) * C2_XS) >> 4), rank, dlo + ((C2_WS + C2_NS * 2048) >> 4));
                const uint32_t kst = pin(sb + C2_KX + 4096 + t128);
                const uint32_t l128 = pin((lane & 7) * 128 + (((lane >> 3) ^ (lane & 7)) << 4));
                wgmma_wait<0>();
                store_x(acc, sb + C2_KX);
                DBGW(16, 0);
                float a[CH_NCH][4];
                proj_mem(a, s, l128);
                sts32(kst, pack_bf16(a[0][0], a[0][2]));
                sts32((kst ^ 16) + 128, pack_bf16(a[0][1], a[0][3]));
                bar_arrive<1, 384>();
                TM(1);
                DBGW(19, 0);
                if (w4 == 0) {
                    if (s < NSEG - 1) {
                        if (lane == 0) mbar_expect_tx(bar_sc, 2560);
                        if (lane < 16 && (lane & 7) >= 1 && (lane & 7) < 5) mbar_expect_tx(bar_m + 8 * lane, (lane & 7) == 1 ? 1024 : 2048);
                        if (lane == 8) {
                            mbar_expect_tx(bar_x + 8 * ((s + 1) & 1), 32768);
                            tma_load_2d_mc(sb + C2_XB + ((s + 1) & 1) * C2_XS + rank * 5120, &mapX, bar_x + 8 * ((s + 1) & 1), rank * 64, (s + 1) * SEGL, (uint16_t)0xff);
                            if (s + 2 < NSEG)
                                asm volatile("cp.async.bulk.prefetch.tensor.2d.L2.global [%0, {%1, %2}];" :: "l"((uint64_t)&mapX), "r"(rank * 64), "r"((s + 2) * SEGL) : "memory");
                        }
                    }
                    else if (lane >= 1 && lane < 5) mbar_expect_tx(bar_o + 8 * lane, lane == 1 ? 4096 : 8192);
                    if (lane == 16) mbar_expect_tx(bar_sx + 8 * (s & 1), 5120);
                    __syncwarp();
                }
            }
        }
        fence_async_smem();
        TS_MARK(12, 128);
        TM(5);
        mbar_wait(bar_h + 8, 0);
        TM(6);
        bar_sync<9, 128>();
        if (elect_one()) {
            mbar_arrive(bar_o);
#pragma unroll 1
            for (int i = 1; i < 8; i++) {
                const uint32_t d = (rank + i) & 7;
                bulk_s2s(mapa_u32(sb + c2_tslot(i) + w4 * 1024, d), sb + C2_QX + w4 * 1024, 1024, mapa_u32(bar_o + 8 * c2_grp(i), d));
            }
        }
        __syncwarp();
    } else {
        uint32_t va[5][2] = {};
        auto store_vt = [&](int s) {
            const uint32_t a = sb + C2_VT + (s & 1) * 6144 + a32;
            stmatrix_x4(a, va[0][0], va[0][1], va[1][0], va[1][1]);
            stmatrix_x4(a + 2048, va[2][0], va[2][1], va[3][0], va[3][1]);
            asm volatile("stmatrix.sync.aligned.m8n8.x2.shared.b16 [%0], {%1, %2};" :: "r"(a + 4096), "r"(va[4][0]), "r"(va[4][1]) : "memory");
        };
#pragma unroll 1
        for (int s = -1;;) {
            if (s >= 0) {
                const int t = tid - 256;
                const uint2* src = g_xbuf + ((s & 1) * 8 + rank) * 1024 + t;
                asm volatile("" : "+l"(src));
                const uint32_t ma = sb + C2_XB + ((s + 1) & 1) * C2_XS + rank * 5120 + 4096 + (t >> 4) * 128 + ((((t >> 1) & 7) ^ (t >> 4)) << 4) + (t & 1) * 8;
                uint32_t ra[8], rb[8];
#pragma unroll
                for (int i = 1; i < 8; i++) {
                    const uint32_t d = (rank + i) & 7;
                    ra[i] = pin(mapa_u32(ma, d)); rb[i] = pin(mapa_u32(bar_m + 8 * c2_grp(i), d));
                }
                if (s == NSEG - 1) break;
                bar_sync<11, 256>();
                DBGW(29, 0);
                {
                    uint32_t t0, t1;
                    asm volatile("mov.u32 %0, %%clock;" : "=r"(t0));
                    if (s == NSEG - 2 && w4 == 0 && elect_one()) tail_load(0, 0);
                    __syncwarp();
                    do { asm volatile("mov.u32 %0, %%clock;" : "=r"(t1)); } while ((int)(t1 - t0) < CH_POLL_DELAY);
                }
                const uint32_t tag = ((s >> 1) & 1) ^ 1;
                uint32_t p[8][2], m0, m1;
                auto issue = [&](uint32_t (&x)[8][2]) {
#pragma unroll
                    for (int k = 0; k < 8; k++)
                        asm volatile("ld.relaxed.gpu.global.v2.u32 {%0, %1}, [%2];" : "=r"(x[k][0]), "=r"(x[k][1]) : "l"(src + k * 128) : "memory");
                };
                auto check = [&](const uint32_t (&x)[8][2]) {
                    uint32_t bad = 0, bad2 = 0;
                    float r[4];
#pragma unroll
                    for (int k = 0; k < 8; k++) {
                        asm("lop3.b32 %0, %0, %1, %2, 0xf6;" : "+r"(bad) : "r"(x[k][0]), "r"(tag));
                        asm("lop3.b32 %0, %0, %1, %2, 0xf6;" : "+r"(bad2) : "r"(x[k][1]), "r"(tag));
#pragma unroll
                        for (int e = 0; e < 2; e++) {
                            const float lo = __uint_as_float(x[k][e] << 16), hi = __uint_as_float(x[k][e] & 0xffff0000u);
                            r[2 * e] = k ? r[2 * e] + lo : lo;
                            r[2 * e + 1] = k ? r[2 * e + 1] + hi : hi;
                        }
                    }
                    m0 = pack_bf16(r[0], r[1]); m1 = pack_bf16(r[2], r[3]);
                    asm volatile("" : "+r"(m0), "+r"(m1));
                    return __all_sync(0xffffffff, ((bad | bad2) & 1u) == 0u);
                };
                for (int it = 0; it < (1 << 20); it++) {
                    issue(p);
                    if (check(p)) break;
                }
                DBGW(30, 0);
                st_async_v2(ra[1], m0, m1, rb[1]);
                asm volatile("st.shared.v2.b32 [%0], {%1, %2};" :: "r"(ma), "r"(m0), "r"(m1) : "memory");
                __syncwarp();
                if (lane == 0) mbar_arrive(bar_m);
#pragma unroll
                for (int i = 2; i < 8; i++) st_async_v2(ra[i], m0, m1, rb[i]);
                DBGW(31, 0);
                TM(8);
                store_vt(s);
            }
            s++;
            const uint32_t ost = pin(sb + C2_OB + t32), pla = pin(sb + C2_PB + lane * 16), plb = pin(sb + C2_PB + 512 + (lane & 7) * 16);
            bar_sync<1, 384>();
            fence_async_smem();
            DBGW(24, 0);
            if (s < NSEG - 1) bar_sync<2, 224>();
            {
                float acc[20];
                c2_xstream<0, 32>(acc, w, dlo + ((C2_XB + (s & 1) * C2_XS) >> 4), rank, dlo + ((C2_WS + 2 * C2_NS * 2048) >> 4));
                wgmma_wait<0>();
#pragma unroll
                for (int j = 0; j < 5; j++) { va[j][0] = pack_bf16(acc[4 * j], acc[4 * j + 1]); va[j][1] = pack_bf16(acc[4 * j + 2], acc[4 * j + 3]); }
            }
            DBGW(26, 0);
            TM(7);
            if (s < NSEG - 1) {
                uint32_t p[5];
                bar_sync<3, 160>();
                DBGW(27, 0);
                ldmatrix_x4_trans(p[0], p[1], p[2], p[3], pla);
                asm volatile("ldmatrix.sync.aligned.m8n8.x1.trans.shared.b16 {%0}, [%1];" : "=r"(p[4]) : "r"(plb) : "memory");
                float oa[4] = {0.f, 0.f, 0.f, 0.f}, ob[4] = {0.f, 0.f, 0.f, 0.f}, sa[4] = {0.f, 0.f, 0.f, 0.f}, sc[4] = {0.f, 0.f, 0.f, 0.f};
                const uint32_t one = 0x3f803f80u;
                mma_16816(sa, one, one, one, one, p[0], p[1]);
                mma_16816(oa, va[0][0], va[0][1], va[1][0], va[1][1], p[0], p[1]);
                mma_16816(sc, one, one, one, one, p[2], p[3]);
                mma_16816(ob, va[2][0], va[2][1], va[3][0], va[3][1], p[2], p[3]);
                mma_16816(sa, one, one, one, one, p[4], 0u);
                mma_16816(oa, va[4][0], va[4][1], 0u, 0u, p[4], 0u);
                bar_arrive<6, 384>();
                float i0, i1;
                asm("rcp.approx.ftz.f32 %0, %1;" : "=f"(i0) : "f"(sa[0] + sc[0]));
                asm("rcp.approx.ftz.f32 %0, %1;" : "=f"(i1) : "f"(sa[1] + sc[1]));
                sts32(ost, pack_bf16((oa[0] + ob[0]) * i0, (oa[2] + ob[2]) * i0));
                sts32(ost + 32, pack_bf16((oa[1] + ob[1]) * i1, (oa[3] + ob[3]) * i1));
                fence_async_smem();
                __syncwarp();
                if (elect_one()) {
#pragma unroll
                    for (int i = 1; i < 8; i++) {
                        const uint32_t d = (rank + i) & 7;
                        bulk_s2s(mapa_u32(sb + C2_OB + i * 1024 + w4 * 256, d), sb + C2_OB + w4 * 256, 256, mapa_u32(bar_o + 8 * c2_grp(i), d));
                        if (i == 1) mbar_arrive(bar_o);
                    }
                }
                __syncwarp();
                DBGW(28, 0);
            } else bar_arrive<6, 384>();
        }
        store_vt(NSEG - 1);
        fence_async_smem();
        bar_arrive<7, 256>();
        g_xbuf[((8 + rank) * 8 + C) * 128 + w4 * 32 + fresh_lane()] = make_uint2(0u, 0u);
    }
    if (wg != 1) {
        const uint32_t lane = fresh_lane(), g = lane >> 2, qc = lane & 3;
        const int row = w4 * 32 + C * 4 + (lane >> 3);
        float r[8], wb = 1.f;
#pragma unroll
        for (int i = 0; i < 8; i++) r[i] = 0.f;
#pragma unroll 1
        for (int q = wg;; q += 1 + (q & 1)) {
            if (q == 1 || q == 2) {
                tail_arrive(q - 1);
                if (w4 == 0) {
                    asm volatile("bar.sync %0, 160;" :: "r"(11 + q) : "memory");
                    mbar_wait(bar_h + 8 * (q - 1), 0);
                    if (elect_one()) tail_load(q, q - 1);
                    __syncwarp();
                }
            }
            if (wg == 2) {
                if (q == 2) wait_ctr(CT_P, 104u);
                const uint4* src = q == 2 ? g_part + PART_A15 + (rank >> 2) * 4096 + (row >> 4) * 512 + ((rank & 3) * 4 + ((lane >> 1) & 2) + ((row >> 3) & 1)) * 32 + (row & 7) * 4 + qc
                                          : g_part + PART_TAIL + (rank * 128 + row) * 64 + (lane & 7);
                const uint32_t step = q == 2 ? 8192 : 8;
                uint4 u[8];
                for (int it = 0; it < (1 << 20); it++) {
                    uint32_t mx = 0;
#pragma unroll
                    for (int k = 0; k < 8; k++)
                        asm volatile("ld.relaxed.gpu.global.v4.u32 {%0, %1, %2, %3}, [%4];" : "=r"(u[k].x), "=r"(u[k].y), "=r"(u[k].z), "=r"(u[k].w) : "l"(src + k * step) : "memory");
#pragma unroll
                    for (int k = 0; k < 8; k++) mx = max(max(mx, max(u[k].x, u[k].y)), max(u[k].z, u[k].w));
                    if (__all_sync(0xffffffff, mx != ~0u)) break;
                }
#pragma unroll
                for (int k = 0; k < 8; k++) {
                    const uint32_t v[4] = {u[k].x, u[k].y, u[k].z, u[k].w};
#pragma unroll
                    for (int e = 0; e < 4; e++) {
                        r[2 * e] = fmaf(wb, __uint_as_float(v[e] << 16), r[2 * e]);
                        r[2 * e + 1] = fmaf(wb, __uint_as_float(v[e] & 0xffff0000u), r[2 * e + 1]);
                    }
                }
                if (q == 3) {
                    *reinterpret_cast<uint4*>(P.out + (size_t)(SEQ - 128 + row) * DM + rank * 64 + (lane & 7) * 8) =
                        quad_transpose(pack_bf16(r[0], r[1]), pack_bf16(r[2], r[3]), pack_bf16(r[4], r[5]), pack_bf16(r[6], r[7]), lane);
                    TS_MARK(15, 256 + 96);
                    TM(21);
                    break;
                }
                asm volatile("ld.relaxed.gpu.global.f32 %0, [%1];" : "=f"(wb) : "l"(g_gate + SEQ - 128 + row) : "memory");
                wb = 1.f - wb;
                TS_MARK(13, 256);
            }
            TM(9 + q);
            float acc[16];
#pragma unroll
            for (int i = 0; i < 16; i++) acc[i] = 0.f;
            uint32_t da = dlo + (C2_WO >> 4), db = dlo + (q < 3 ? ((C2_XB + (q >> 1) * C2_XS) >> 4) + rank * 320 : c2_tslot(0) >> 4);
            uint32_t bar = q < 3 ? bar_x + 8 * (q >> 1) : bar_o;
            const uint32_t d0 = q < 3 ? -320 : 256, k1 = q < 3 ? rank : 0, d1 = q < 3 ? 2240 : (c2_tslot(1) - c2_tslot(0)) >> 4;
            const uint32_t k2 = q < 3 ? 8 : 3, bm = q < 3 ? 0 : 0x2b << 3;
#pragma unroll 1
            for (uint32_t i = 0; i < 8; i++) {
                mbar_wait(bar, q & 1);
                if (i == 0) TM(13 + q);
                if (i == 7) TM(25 + q);
                wgmma_fence();
#pragma unroll
                for (int kk = 0; kk < 4; kk++) wgmma_ss_n32_ta(acc, da + kk * 128, db + kk * 2);
                wgmma_commit();
                da += 512;
                db += i == k1 ? d1 : i == k2 ? (c2_tslot(4) - c2_tslot(3)) >> 4 : d0;
                bar += (bm >> i) & 8;
            }
            if (q == 0) wait_ctr(CT_P, 104u);
            wgmma_wait<0>();
            uint32_t* dst = reinterpret_cast<uint32_t*>(g_part + PART_TAIL + ((rank * 128 + q * 32 + 2 * qc) * 8 + C) * 8 + (w4 >> 1) * 4 + (g & 3)) + (w4 & 1) * 2 + (g >> 2);
#pragma unroll
            for (int j = 0; j < 4; j++) {
                asm volatile("st.relaxed.gpu.global.u32 [%0], %1;" :: "l"(dst + j * 8 * 256), "r"(pack_bf16(acc[4 * j], acc[4 * j + 2])) : "memory");
                asm volatile("st.relaxed.gpu.global.u32 [%0], %1;" :: "l"(dst + (j * 8 + 1) * 256), "r"(pack_bf16(acc[4 * j + 1], acc[4 * j + 3])) : "memory");
            }
            TS_MARK(q == 2 ? 14 : q == 3 ? 11 : 9 + q, q == 2 ? 256 : 0);
            TM(17 + q);
            if (q == 3) break;
        }
    }
    cluster_sync_relaxed();
    if (warp == 0) finish_launch(fresh_lane());
    TS_END(2);
    CYC(3);
    if (wg == 0) TM(23);
}

constexpr int P3_LEN = 24;
struct Proj3Params {
    CUtensorMap mapA[2];
    CUtensorMap mapW[3];
    bf16* out[3];
    uint16_t sched[34 * P3_LEN];
};
#define P3_STAGES 14
#define P3_LAG 2
#define P3_PACE 0
#define P3T(i)
constexpr int P3_SMEM = P3_STAGES * 16384 + 256 + 2 * P3_LEN * 8;
__device__ __forceinline__ void mbar_arrive_cl(uint32_t bar_cluster_addr) {
    asm volatile("mbarrier.arrive.shared::cluster.b64 _, [%0];" :: "r"(bar_cluster_addr) : "memory");
}
__global__ void __cluster_dims__(2, 1, 1) __launch_bounds__(384, 1) proj3_kernel(const __grid_constant__ Proj3Params P) {
    extern __shared__ __align__(1024) uint8_t smem_proj[];
    const uint32_t sb = smem_u32(smem_proj);
    const uint32_t full = sb + P3_STAGES * 16384, empty = full + 8 * P3_STAGES, done = full + 256;
    const int warp = __shfl_sync(0xffffffff, threadIdx.x >> 5, 0), lane = threadIdx.x & 31;
    const uint32_t rank = cluster_ctarank();
    const uint16_t* sched = P.sched + (blockIdx.x >> 1) * P3_LEN;
    TS_BEGIN(0);
    if (threadIdx.x == 0) {
#pragma unroll 1
        for (int i = 0; i < P3_STAGES; i++) { mbar_init(full + 8 * i, 1); mbar_init(empty + 8 * i, 4); }
        asm volatile("fence.mbarrier_init.release.cluster;" ::: "memory");
    }
    if ((warp == 9 || warp == 10) && lane == 0)
#pragma unroll 1
        for (int i = 0; i < P3_LEN; i++) mbar_init(done + ((warp - 9) * P3_LEN + i) * 8, 4);
    __syncthreads();
    cluster_sync_relaxed();
    pdl_launch_dependents();
    if (warp >= 8) {
        asm volatile("setmaxnreg.dec.sync.aligned.u32 40;");
        if (warp == 8 && lane == 0) {
            uint32_t so = 0, ph = 1;
#pragma unroll 1
            for (;; sched++) {
                const uint32_t e = *sched, z = (e >> 5) & 3, na = e >> 10;
                if (z == 3) break;
#pragma unroll 1
                for (int i = 1 - na; i < 16; i += 2 - na) {
                    mbar_wait(empty + so, ph);
                    mbar_expect_tx(full + so, 16384);
                    if (i & 1) tma_load_2d_mc(sb + so * 2048 + rank * 8192, &P.mapW[z], full + so, (e & 31) * 128 + rank * 64, (i >> 1) * 64, (uint16_t)3);
                    else tma_load_2d(sb + so * 2048, &P.mapA[z != 0], full + so, (i >> 1) * 64, (((e >> 7) & 7) * 2 + rank) * 128);
                    so += 8;
                    if (so == 8 * P3_STAGES) { so = 0; ph ^= 1; }
                }
            }
        } else if (warp < 11 && lane == 0) {
#pragma unroll 1
            for (uint32_t d = done + (warp - 9) * P3_LEN * 8;; d += 8, sched++) {
                const uint32_t e = *sched;
                if (((e >> 5) & 3) == 3) break;
                mbar_wait(d, 0);
                signal_ctr(CT_AP + ((e & 31) >> 1));
            }
        }
    } else {
        asm volatile("setmaxnreg.inc.sync.aligned.u32 232;");
        const int wg = warp >> 2;
        uint32_t a[32][4];
        float acc[64];
        const uint32_t b_lo = desc_lo(sb, 8192);
        const int r = warp * 16 + (lane & 15);
        const uint32_t la = sb + r * 128 + (((lane >> 4) ^ (r & 7)) << 4);
#pragma unroll
        for (int i = 0; i < 32; i++) ldsm_x4(a[i], la + i * 1024);
        const uint32_t rel = mapa_u32(empty, lane & 1);
        const int tw = threadIdx.x & 127;
        uint32_t so = 0, ph = 0;
        if (wg == 1) asm volatile("bar.arrive 1, 256;" ::: "memory");
#pragma unroll 1
        for (uint32_t d = done + wg * P3_LEN * 8;; d += 8, sched++) {
            const uint32_t e = *sched;
            if (((e >> 5) & 3) == 3) break;
            const bool na = e >> 10;
            const bool sig = tw < (na ? 4 : 2);
            uint32_t old = 0;
            auto release = [&]() { asm volatile("{\n.reg .pred p;\nsetp.ne.u32 p, %1, 0;\n@p mbarrier.arrive.shared::cluster.b64 _, [%0];\n}" :: "r"(rel + old), "r"((uint32_t)sig) : "memory"); };
            P3T(0);
            asm volatile("bar.sync %0, 256;" :: "r"(1 + wg) : "memory");
            P3T(1);
#pragma unroll
            for (int k = 0; k < 8; k++) {
                const uint32_t sa = so;
                if (na) {
                    mbar_wait(full + so, ph);
#pragma unroll
                    for (int kk = 0; kk < 4; kk++) ldsm_x4(a[k * 4 + kk], (la + so * 2048) ^ (kk * 32));
                    so += 8;
                    if (so == 8 * P3_STAGES) { so = 0; ph ^= 1; }
                }
                mbar_wait(full + so, ph);
                wgmma_fence();
#pragma unroll
                for (int kk = 0; kk < 4; kk++) wgmma_rs_n128_tb_lo(acc, a[k * 4 + kk], b_lo + so * 128 + kk * 128, (k | kk) != 0);
                wgmma_commit();
                if (k == P3_LAG) asm volatile("bar.arrive %0, 256;" :: "r"(2 - wg) : "memory");
                if (k > 0) { wgmma_wait<1>(); release(); }
                old = (lane & 2) ? sa : so;
                so += 8;
                if (so == 8 * P3_STAGES) { so = 0; ph ^= 1; }
            }
            bf16* dst = P.out[(e >> 5) & 3] + ((size_t)(e & 31) * SEQ + (((e >> 7) & 7) * 2 + rank) * 128 + warp * 16 + (lane >> 2)) * HD + (lane & 3) * 8;
            wgmma_wait<0>();
            P3T(2);
            release();
#pragma unroll
            for (int i = 0; i < 8; i++) {
                const float* c = &acc[(i >> 1) * 16 + (i & 1) * 2];
                *reinterpret_cast<uint4*>(dst + (i & 1) * 8 * HD + (i >> 1) * 32) =
                    make_uint4(pack_bf16(c[0], c[1]), pack_bf16(c[4], c[5]), pack_bf16(c[8], c[9]), pack_bf16(c[12], c[13]));
                pace(P3_PACE);
            }
            __syncwarp();
            mbar_arrive_if(d, lane == 0);
        }
        TS_END(0);
    }
    __syncwarp();
    cluster_sync_relaxed();
}

struct OutParams {
    CUtensorMap mapCtx[2];
    CUtensorMap mapWo[2];
    bf16* out;
};
#define OT(i)
#define O4_D 2
#define O4_CD 2000
#define O4_CP 0
constexpr int O4_GRID = 68;
constexpr int O2_SMEM = 196608 + 1024 + 256;
struct OutJob { int mt, a0, na, b0, nb, member; };
__device__ __forceinline__ OutJob out_job(int pair, int j) {
    OutJob J;
    if (pair < 26) {
        J.member = pair >= 13; J.mt = J.member ? 25 - pair : pair;
        const int d = (12 - J.mt) * O4_D / 12;
        J.a0 = J.member ? 32 + d : 0; J.na = J.member ? 32 - d : 32 + d;
        J.b0 = J.member * 32; J.nb = 32;
    } else {
        J.member = pair - 26; J.mt = j ? 12 + j : 15;
        J.a0 = J.b0 = J.member * 8; J.na = 8; J.nb = j ? 8 : 0;
    }
    return J;
}
__device__ __forceinline__ void tma_load_3d(uint32_t dst, const CUtensorMap* map, uint32_t bar, int c0, int c1, int c2) {
    asm volatile(
        "cp.async.bulk.tensor.3d.shared::cluster.global.mbarrier::complete_tx::bytes [%0], [%1, {%3, %4, %5}], [%2];"
        :: "r"(dst), "l"((uint64_t)map), "r"(bar), "r"(c0), "r"(c1), "r"(c2) : "memory");
}
__device__ __forceinline__ void out_weights(const OutParams& P, uint32_t sbase, uint32_t bar_full, uint32_t bar_empty, int pair, int rank, bool fresh) {
    int s = 0, n = 0; uint32_t ph = 0;
#pragma unroll 1
    for (int j = 0; j < (pair < 26 ? 1 : 3); j++) {
        const OutJob J = out_job(pair, j);
#pragma unroll 1
        for (int i = 0; i < J.na + J.nb; i++, n++) {
            if (!fresh) mbar_wait(bar_empty + 8 * s, ph);
            else if (n >= 4) mbar_wait(bar_empty + 8 * s, ph ^ 1);
            const int b = i >= J.na, k = b ? J.b0 + i - J.na : J.a0 + i;
            const int h = pair < 26 ? J.member * 2 : 0;
            tma_load_3d(sbase + s * 49152 + 16384, &P.mapWo[b], bar_full + 8 * s, 0, k * 64, rank * 4 + h);
            tma_load_3d(sbase + s * 49152 + 32768, &P.mapWo[b], bar_full + 8 * s, 0, k * 64, rank * 4 + 2 - h);
            if (++s == 4) { s = 0; ph ^= 1; }
        }
    }
}
__device__ __forceinline__ void out_ctx(const OutParams& P, uint32_t sbase, uint32_t bar_full, uint32_t bar_empty, int pair, int rank, bool fresh) {
    int s = 0, n = 0; uint32_t ph = 0;
#pragma unroll 1
    for (int j = 0; j < (pair < 26 ? 1 : 3); j++) {
        const OutJob J = out_job(pair, j);
#pragma unroll 1
        for (int i = 0; i < J.na + J.nb; i++, n++) {
            const int b = i >= J.na, k = b ? J.b0 + i - J.na : J.a0 + i;
            if (i == 0 && k < 2 * O2_HE) wait_ctr(CT_CA + J.mt * 2, 2u * O2_HE);
            if (!b && (i == 0 ? k >= 2 * O2_HE : k == 2 * O2_HE)) wait_ctr(CT_CA + J.mt * 2 + 1, 2u * (NH - O2_HE));
            if (i == J.na) wait_ctr(CT_CB + max(J.mt, CB_FIRST), 64u);
            if (!fresh) mbar_wait(bar_empty + 8 * s, ph);
            else if (n >= 4) mbar_wait(bar_empty + 8 * s, ph ^ 1);
            mbar_expect_tx(bar_full + 8 * s, 49152);
            tma_load_2d_mc(sbase + s * 49152 + rank * 8192, &P.mapCtx[b], bar_full + 8 * s, (k & 1) * 64, (k >> 1) * SEQ + J.mt * 128 + rank * 64, (uint16_t)3);
            if (++s == 4) { s = 0; ph ^= 1; }
        }
    }
}
__device__ __forceinline__ void out_consumer(const OutParams& P, uint32_t sbase, uint32_t bar_full, uint32_t bar_empty, int pair, int rank, int warp, int lane) {
    const int wg = warp >> 2;
    const bool elected = (warp & 3) == 0 && lane == 0;
    const int row = warp * 16 + (lane >> 2);
    int s = 0, sprev = 0; uint32_t ph = 0;
    auto release = [&](int st) {
        if (elected) { const uint32_t e = bar_empty + 8 * st; mbar_arrive_cl(mapa_u32(e, 0)); mbar_arrive_cl(mapa_u32(e, 1)); }
    };
    wait_ctr(CT_G, FA_GRID);
#pragma unroll 1
    for (int j = 0; j < (pair < 26 ? 1 : 3); j++) {
        const OutJob J = out_job(pair, j);
        float g0, g1, acc[128];
        asm volatile("ld.relaxed.gpu.global.f32 %0, [%1];" : "=f"(g0) : "l"(g_gate + J.mt * 128 + row) : "memory");
        asm volatile("ld.relaxed.gpu.global.f32 %0, [%1];" : "=f"(g1) : "l"(g_gate + J.mt * 128 + row + 8) : "memory");
#pragma unroll
        for (int e = 0; e < 128; e++) acc[e] = 0.f;
#pragma unroll 1
        for (int i = 0; i < J.na + J.nb; i++) {
            mbar_wait(bar_full + 8 * s, ph);
            if (i == 0) OT(1);
            if (i == J.na) {
                OT(2);
                wgmma_wait<0>();
                const float w0 = fmaxf(1.f - g0, 0x1p-40f), w1 = fmaxf(1.f - g1, 0x1p-40f);
                const float r0 = __fdividef(g0, w0), r1 = __fdividef(g1, w1);
                g0 = w0; g1 = w1;
#pragma unroll
                for (int e = 0; e < 32; e++) { acc[4 * e] *= r0; acc[4 * e + 1] *= r0; acc[4 * e + 2] *= r1; acc[4 * e + 3] *= r1; }
            }
            const uint32_t sa = sbase + s * 49152 + wg * 8192, sb = sbase + s * 49152 + 16384;
            wgmma_fence();
#pragma unroll
            for (int kk = 0; kk < 4; kk++)
                wgmma_ss_n256_tb(acc, make_desc(sa + kk * 32, 16, 1024), make_desc(sb + kk * 2048, 8192, 1024), 1);
            wgmma_commit();
            if (i > 0) { wgmma_wait<1>(); release(sprev); }
            sprev = s;
            if (++s == 4) { s = 0; ph ^= 1; }
        }
        if (j == 0) wait_ctr(CT_P, 104u);
        wgmma_wait<0>();
        release(sprev);
        OT(4);
        uint32_t p[16][4];
#pragma unroll
        for (int e = 0; e < 16; e++)
#pragma unroll
            for (int i = 0; i < 4; i++) {
                const float* a = &acc[(e >> 1) * 16 + (e & 1) * 2 + 4 * i];
                p[e][i] = pack_bf16(a[0] * ((e & 1) ? g1 : g0), a[1] * ((e & 1) ? g1 : g0));
            }
        const bool two = pair < 26;
        const uint4* part = g_part + (two ? (J.mt * 2 + rank) * 4096 + warp * 256 : (26 + (J.mt - 13) * 16 + rank) * 4096 + warp * 512) + lane;
        {
            const uint4* dst = part + (two ? J.member * 2048 - 256 : J.member * 8192);
#pragma unroll
            for (int e = 15; e >= 0; e--) {
                if (e == 7 && two) break;
                asm volatile("st.relaxed.gpu.global.v4.u32 [%0], {%1, %2, %3, %4};" :: "l"(dst + e * 32), "r"(p[e][0]), "r"(p[e][1]), "r"(p[e][2]), "r"(p[e][3]) : "memory");
            }
        }
        OT(5);
        bf16* dst = P.out + (size_t)(J.mt * 128 + row) * DM + rank * 256 + J.member * (two ? 128 : 32) + (lane & 3) * 8;
        const uint32_t step = two ? 32 : 8192;
        part += two ? 2048 - J.member * 2048 : J.member * 64;
#pragma unroll 1
        for (int c = 0; c < (J.nb ? 2 : 0); c++) {
            uint32_t u[8][4];
            for (int it = 0; it < (1 << 20); it++) {
                uint32_t mx = 0;
#pragma unroll
                for (int i = 0; i < 8; i++)
                    asm volatile("ld.relaxed.gpu.global.v4.u32 {%0, %1, %2, %3}, [%4];" : "=r"(u[i][0]), "=r"(u[i][1]), "=r"(u[i][2]), "=r"(u[i][3]) : "l"(part + c * 32 + i * step) : "memory");
#pragma unroll
                for (int i = 0; i < 8; i++) mx = max(max(mx, max(u[i][0], u[i][1])), max(u[i][2], u[i][3]));
                if (__all_sync(0xffffffff, mx != ~0u)) break;
            }
            if (c == 0) OT(3);
            if (two) {
#pragma unroll
                for (int e = 0; e < 8; e++) {
#pragma unroll
                    for (int i = 0; i < 4; i++) asm("add.rn.bf16x2 %0, %0, %1;" : "+r"(u[e][i]) : "r"(p[e][i]));
                    *reinterpret_cast<uint4*>(dst + (e & 1) * 8 * DM + (e >> 1) * 32) = quad_transpose(u[e][0], u[e][1], u[e][2], u[e][3], lane);
                }
                break;
            }
            float r[8];
#pragma unroll
            for (int m = 0; m < 8; m++)
#pragma unroll
                for (int i = 0; i < 4; i++) {
                    const float lo = __uint_as_float(u[m][i] << 16), hi = __uint_as_float(u[m][i] & 0xffff0000u);
                    r[2 * i] = m ? r[2 * i] + lo : lo; r[2 * i + 1] = m ? r[2 * i + 1] + hi : hi;
                }
            *reinterpret_cast<uint4*>(dst + c * 8 * DM) = quad_transpose(pack_bf16(r[0], r[1]), pack_bf16(r[2], r[3]), pack_bf16(r[4], r[5]), pack_bf16(r[6], r[7]), lane);
        }
        OT(6);
    }
}

__global__ void __cluster_dims__(2, 1, 1) __launch_bounds__(384, 1) out4_kernel(const __grid_constant__ OutParams P) {
    extern __shared__ uint8_t smem_raw[];
    const uint32_t sbase = (smem_u32(smem_raw) + 1023) & ~1023u;
    const uint32_t bar_full = sbase + 196608, bar_empty = bar_full + 64;
    const int warp = __shfl_sync(0xffffffff, threadIdx.x >> 5, 0), lane = threadIdx.x & 31;
    const int rank = (int)cluster_ctarank(), pair = blockIdx.x >> 1;
    TS_BEGIN(4);
    if (threadIdx.x == 0) {
        for (int i = 0; i < 4; i++) { mbar_init(bar_full + 8 * i, 1); mbar_init(bar_empty + 8 * i, 4); }
        asm volatile("fence.mbarrier_init.release.cluster;" ::: "memory");
    }
    if (threadIdx.x == 256) asm volatile("prefetch.tensormap [%0];" :: "l"((uint64_t)&P.mapCtx[0]) : "memory");
    if (threadIdx.x == 352) asm volatile("prefetch.tensormap [%0];" :: "l"((uint64_t)&P.mapWo[0]) : "memory");
    if (warp == 0 || warp == 11) asm volatile("bar.sync 1, 64;" ::: "memory");
    __syncwarp();
    asm volatile("barrier.cluster.arrive.relaxed.aligned;" ::: "memory");
    if (warp == 11) {
        if (lane == 0) out_weights(P, sbase, bar_full, bar_empty, pair, rank, true);
        __syncwarp();
        asm volatile("barrier.cluster.wait.acquire.aligned;" ::: "memory");
    } else {
        asm volatile("barrier.cluster.wait.acquire.aligned;" ::: "memory");
        if (warp == 8 && lane == 0) out_ctx(P, sbase, bar_full, bar_empty, pair, rank, true);
        if (warp > 8 && pair < 26) {
            pace(O4_CD);
#pragma unroll 1
            for (int i = (blockIdx.x * 2 + warp - 9) * 32 + lane; i < PART_N; i += 104 * 32) { g_part[PART_N - 1 - i] = make_uint4(~0u, ~0u, ~0u, ~0u); if (O4_CP) pace(O4_CP); }
            wait_ctr(CT_G, FA_GRID);
            __syncwarp();
            if (lane == 0) signal_ctr_generic(CT_P);
        }
        if (warp < 8) out_consumer(P, sbase, bar_full, bar_empty, pair, rank, warp, lane);
    }
    __syncthreads();
    asm volatile("barrier.cluster.arrive.relaxed.aligned;" ::: "memory");
    if (warp == 0) finish_launch(lane);
    asm volatile("barrier.cluster.wait.acquire.aligned;" ::: "memory");
    TS_END(4);
}

typedef CUresult (*PFN_encodeTiled)(CUtensorMap*, CUtensorMapDataType, cuuint32_t, void*, const cuuint64_t*,
                                    const cuuint64_t*, const cuuint32_t*, const cuuint32_t*, CUtensorMapInterleave,
                                    CUtensorMapSwizzle, CUtensorMapL2promotion, CUtensorMapFloatOOBfill);
static PFN_encodeTiled g_encode = nullptr;

static void make_map(CUtensorMap* m, const void* ptr, uint64_t rows, uint64_t cols, uint32_t box_rows, bool sw64 = false) {
    cuuint64_t dims[2] = {cols, rows};
    cuuint64_t strides[1] = {cols * 2};
    cuuint32_t box[2] = {sw64 ? 32u : 64u, box_rows};
    cuuint32_t es[2] = {1, 1};
    g_encode(m, CU_TENSOR_MAP_DATA_TYPE_BFLOAT16, 2, const_cast<void*>(ptr), dims, strides, box, es,
             CU_TENSOR_MAP_INTERLEAVE_NONE, sw64 ? CU_TENSOR_MAP_SWIZZLE_64B : CU_TENSOR_MAP_SWIZZLE_128B, CU_TENSOR_MAP_L2_PROMOTION_L2_256B,
             CU_TENSOR_MAP_FLOAT_OOB_FILL_NONE);
}

static void make_map3(CUtensorMap* m, const void* ptr, uint64_t rows, uint64_t cols, uint32_t box_rows, uint32_t nblk) {
    cuuint64_t dims[3] = {64, rows, cols / 64};
    cuuint64_t strides[2] = {cols * 2, 128};
    cuuint32_t box[3] = {64u, box_rows, nblk};
    cuuint32_t es[3] = {1, 1, 1};
    g_encode(m, CU_TENSOR_MAP_DATA_TYPE_BFLOAT16, 3, const_cast<void*>(ptr), dims, strides, box, es,
             CU_TENSOR_MAP_INTERLEAVE_NONE, CU_TENSOR_MAP_SWIZZLE_128B, CU_TENSOR_MAP_L2_PROMOTION_L2_256B, CU_TENSOR_MAP_FLOAT_OOB_FILL_NONE);
}

template <typename... KArgs, typename... Args>
static void launch_pdl(void (*kernel)(KArgs...), int grid, int block, size_t smem, cudaStream_t st, bool pdl, Args... args) {
    cudaLaunchConfig_t cfg = {};
    cfg.gridDim = dim3(grid); cfg.blockDim = dim3(block); cfg.dynamicSmemBytes = smem; cfg.stream = st;
    cudaLaunchAttribute at[1];
    at[0].id = cudaLaunchAttributeProgrammaticStreamSerialization;
    at[0].val.programmaticStreamSerializationAllowed = 1;
    cfg.attrs = at; cfg.numAttrs = pdl ? 1 : 0;
    cudaLaunchKernelEx(&cfg, kernel, KArgs(args)...);
}

extern "C" void kernel_launch(void* const* d_in, const int* in_sizes, int n_in, void* d_out, int out_size) {
    const bf16* x = (const bf16*)d_in[0];
    const bf16* ckv = (const bf16*)d_in[1];
    const bf16* wq = (const bf16*)d_in[2];
    const bf16* wuk = (const bf16*)d_in[3];
    const bf16* wuv = (const bf16*)d_in[4];
    const bf16* wo = (const bf16*)d_in[5];
    const bf16* mem0 = (const bf16*)d_in[7];
    const bf16* Wq = (const bf16*)d_in[8];
    const bf16* Wk = (const bf16*)d_in[9];
    const bf16* Wv = (const bf16*)d_in[10];
    const bf16* Wo = (const bf16*)d_in[11];
    const bf16* gate_w = (const bf16*)d_in[13];
    bf16* out = (bf16*)d_out;

    static Proj3Params P2;
    static ChainParams CP;
    static AttnParams AP;
    static OutParams OP;
    static bool init = false;
    static const void* last_in[15];
    bool same = init;
    for (int i = 0; i < 14 && same; i++) same = last_in[i] == d_in[i];
    same = same && last_in[14] == d_out;
    if (!init) {
        cudaDriverEntryPointQueryResult qr;
        cudaGetDriverEntryPoint("cuTensorMapEncodeTiled", (void**)&g_encode, cudaEnableDefault, &qr);
        cudaFuncSetAttribute(proj3_kernel, cudaFuncAttributeMaxDynamicSharedMemorySize, P3_SMEM);
        for (int p = 0; p < 34; p++) {
            uint16_t* t = P2.sched + p * P3_LEN;
            int n = 0, rows = -1;
            auto add = [&](int z, int mp, int head) {
                t[n++] = (uint16_t)(head | z << 5 | mp << 7 | (rows != (z ? 8 : 0) + mp) << 10);
                rows = (z ? 8 : 0) + mp;
            };
            const int mp = p & 7, kind = p >> 3;
            if (kind == 0) for (int h = 0; h < 23; h++) add(0, mp, h);
            else if (kind < 4) {
                for (int i = kind - 1; i < 54; i += 3) add(1 + (i & 1), mp, i >> 1);
                if (kind < 3) for (int h = 27; h < 32; h++) add(kind, mp, h);
                else for (int h = 23; h < 27; h++) add(0, mp, h);
            } else for (int i = 0; i < 20; i++) add(0, mp * 4 + i / 5, 27 + i % 5);
            while (n < P3_LEN) t[n++] = 3 << 5;
        }
        cudaFuncSetAttribute(attn_kernel, cudaFuncAttributeMaxDynamicSharedMemorySize, FA_SMEM);
        cudaFuncSetAttribute(chain_kernel, cudaFuncAttributeMaxDynamicSharedMemorySize, C2_SMEM);
        cudaFuncSetAttribute(out4_kernel, cudaFuncAttributeMaxDynamicSharedMemorySize, O2_SMEM);
        init = true;
    }
    if (!same) {
        for (int i = 0; i < 14; i++) last_in[i] = d_in[i];
        last_in[14] = d_out;
        void *pQA, *pKA, *pVA, *pCA, *pCB;
        cudaGetSymbolAddress(&pQA, g_QA); cudaGetSymbolAddress(&pKA, g_KA); cudaGetSymbolAddress(&pVA, g_VA);
        cudaGetSymbolAddress(&pCA, g_ctxA); cudaGetSymbolAddress(&pCB, g_ctxB);
        make_map(&P2.mapA[0], x, SEQ, DM, 128);
        make_map(&P2.mapA[1], ckv, SEQ, DM, 128);
        const void* ws[3] = {wq, wuk, wuv};
        void* cs[3] = {pQA, pKA, pVA};
        for (int i = 0; i < 3; i++) { make_map(&P2.mapW[i], ws[i], DM, NQ, 64); P2.out[i] = (bf16*)cs[i]; }
        make_map(&CP.mapX, x, SEQ, DM, SEGL);
        make_map(&CP.mapM, mem0, NMEM, DM, NMEM);
        make_map(&CP.mapW[0], Wq, DM, NQ, 64);
        make_map(&CP.mapW[1], Wk, DM, NQ, 64);
        make_map(&CP.mapW[2], Wv, DM, NQ, 64);
        make_map(&CP.mapWo, Wo, NQ, DM, 64);
        make_map(&AP.mapQ, pQA, NH * SEQ, HD, 128);
        make_map(&AP.mapK, pKA, NH * SEQ, HD, 128);
        make_map(&AP.mapV, pVA, NH * SEQ, HD, 128);
        make_map(&AP.mapO, pCA, NH * SEQ, HD, 64);
        make_map(&OP.mapCtx[0], pCA, NH * SEQ, HD, 64);
        make_map(&OP.mapCtx[1], pCB, NH * SEQ, HD, 64);
        make_map3(&OP.mapWo[0], wo, NQ, DM, 64, 2);
        make_map3(&OP.mapWo[1], Wo, NQ, DM, 64, 2);
        OP.out = out;
        make_map(&CP.mapC, pCB, NH * SEQ, HD, SEGL);
        CP.out = out;
        AP.x = x; AP.gate_w = gate_w;
    }
    cudaStream_t s1 = cudaStreamPerThread;
    const bool pdl = true;
    launch_pdl(chain_kernel, 64, 384, C2_SMEM, s1, false, CP);
    launch_pdl(proj3_kernel, 68, 384, P3_SMEM, s1, pdl, P2);
    launch_pdl(attn_kernel, FA_GRID, 384, FA_SMEM, s1, pdl, AP);
    launch_pdl(out4_kernel, O4_GRID, 384, O2_SMEM, s1, pdl, OP);
}
```

```cpp
#include <cuda_runtime.h>
#include <cuda_bf16.h>
#include <cuda.h>
#include <stdint.h>
#include <type_traits>

constexpr int SEQ = 2048;
constexpr int DM = 512;
constexpr int NH = 32;
constexpr int HD = 128;
constexpr int NQ = NH * HD;
constexpr int SEGL = 32;
constexpr int NMEM = 8;
constexpr int NSEG = SEQ / SEGL;

typedef __nv_bfloat16 bf16;

__device__ bf16 g_QA[SEQ * NQ];
__device__ bf16 g_KA[SEQ * NQ];
__device__ bf16 g_VA[SEQ * NQ];
__device__ bf16 g_ctxA[SEQ * NQ];
__device__ bf16 g_ctxB[SEQ * NQ];
constexpr int CT_ATTN = 1, CT_FIN = 5;
constexpr int CT_P = 48;
constexpr int CT_G = 32;
constexpr int CT_AP = 64;
#define O2_HE 24
constexpr int CT_CA = 128;
constexpr int CT_CB = 160;
#define CB_FIRST 11
constexpr int CT_N = 192;
__device__ unsigned int g_ctr[CT_N];
__device__ float g_gate[SEQ];
__device__ uint2 g_xbuf[2 * 8 * 8 * 128];

#define FA_GRID 68

#define P2_MARK 0
#define TS_MARK(id, tid)
#define TS_MARK2(id, tid)
#define TS_BEGIN(id)
#define TS_END(id)
#define TS_BEGIN_T(id, tid)
#define TS_END_T(id, tid)
__device__ __forceinline__ void pdl_launch_dependents() { asm volatile("griddepcontrol.launch_dependents;" ::: "memory"); }
__device__ __forceinline__ void wait_ctr(int idx, unsigned int n) {
    unsigned int v; int it = 0;
    do { asm volatile("ld.acquire.gpu.global.u32 %0, [%1];" : "=r"(v) : "l"(&g_ctr[idx]) : "memory"); } while (v < n && ++it < (1 << 22));
}
__device__ __forceinline__ void signal_ctr(int idx) {
    asm volatile("fence.proxy.async.global;" ::: "memory");
    asm volatile("red.release.gpu.global.add.u32 [%0], 1;" :: "l"(&g_ctr[idx]) : "memory");
}
__device__ __forceinline__ void signal_ctr_generic(int idx) {
    asm volatile("red.release.gpu.global.add.u32 [%0], 1;" :: "l"(&g_ctr[idx]) : "memory");
}
__device__ __forceinline__ void finish_launch(int lane) {
    unsigned int tk = 0;
    if (lane == 0) tk = atomicAdd(&g_ctr[CT_FIN], 1u);
    tk = __shfl_sync(0xffffffff, tk, 0);
    if (tk == 64 + 68 - 1)
#pragma unroll 1
        for (int i = lane; i < CT_N; i += 32) g_ctr[i] = 0u;
}
__device__ __forceinline__ uint4 quad_transpose(uint32_t p0, uint32_t p1, uint32_t p2, uint32_t p3, int lane) {
    const bool o1 = lane & 1, o2 = lane & 2;
    uint32_t s0 = o1 ? p0 : p1, s1 = o1 ? p2 : p3;
    s0 = __shfl_xor_sync(0xffffffff, s0, 1); s1 = __shfl_xor_sync(0xffffffff, s1, 1);
    const uint32_t a_lo = o1 ? s0 : p0, a_hi = o1 ? p1 : s0, b_lo = o1 ? s1 : p2, b_hi = o1 ? p3 : s1;
    uint32_t t0 = o2 ? a_lo : b_lo, t1 = o2 ? a_hi : b_hi;
    t0 = __shfl_xor_sync(0xffffffff, t0, 2); t1 = __shfl_xor_sync(0xffffffff, t1, 2);
    return o2 ? make_uint4(t0, t1, b_lo, b_hi) : make_uint4(a_lo, a_hi, t0, t1);
}
__device__ __forceinline__ uint32_t smem_u32(const void* p) {
    return (uint32_t)__cvta_generic_to_shared(p);
}
__device__ __forceinline__ void mbar_init(uint32_t bar, uint32_t count) {
    asm volatile("mbarrier.init.shared::cta.b64 [%0], %1;" :: "r"(bar), "r"(count));
}
__device__ __forceinline__ void mbar_expect_tx(uint32_t bar, uint32_t bytes) {
    asm volatile("mbarrier.arrive.expect_tx.shared::cta.b64 _, [%0], %1;" :: "r"(bar), "r"(bytes) : "memory");
}
__device__ __forceinline__ void mbar_arrive(uint32_t bar) {
    asm volatile("mbarrier.arrive.shared::cta.b64 _, [%0];" :: "r"(bar) : "memory");
}
__device__ __forceinline__ void mbar_wait(uint32_t bar, uint32_t parity) {
    asm volatile(
        "{\n"
        ".reg .pred p, q;\n"
        ".reg .u32 c;\n"
        "mov.u32 c, 0;\n"
        "WAIT_LOOP:\n"
        "mbarrier.try_wait.parity.shared::cta.b64 p, [%0], %1;\n"
        "@p bra WAIT_DONE;\n"
        "add.u32 c, c, 1;\n"
        "setp.lt.u32 q, c, 4000000;\n"
        "@q bra WAIT_LOOP;\n"
        "WAIT_DONE:\n"
        "}\n" :: "r"(bar), "r"(parity) : "memory");
}
__device__ __forceinline__ void tma_load_2d(uint32_t dst, const CUtensorMap* map, uint32_t bar, int c0, int c1) {
    asm volatile(
        "cp.async.bulk.tensor.2d.shared::cluster.global.mbarrier::complete_tx::bytes [%0], [%1, {%3, %4}], [%2];"
        :: "r"(dst), "l"((uint64_t)map), "r"(bar), "r"(c0), "r"(c1) : "memory");
}
__device__ __forceinline__ void wgmma_fence() { asm volatile("wgmma.fence.sync.aligned;" ::: "memory"); }
__device__ __forceinline__ void wgmma_commit() { asm volatile("wgmma.commit_group.sync.aligned;" ::: "memory"); }
template <int N> __device__ __forceinline__ void wgmma_wait() {
    asm volatile("wgmma.wait_group.sync.aligned %0;" :: "n"(N) : "memory");
}
__device__ __forceinline__ uint64_t make_desc(uint32_t addr, uint32_t lbo, uint32_t sbo) {
    uint64_t d = 0;
    d |= (uint64_t)((addr & 0x3FFFF) >> 4);
    d |= (uint64_t)((lbo >> 4) & 0x3FFF) << 16;
    d |= (uint64_t)((sbo >> 4) & 0x3FFF) << 32;
    d |= (uint64_t)1 << 62;
    return d;
}

#define ACC64(d) \
    "+f"(d[0]), "+f"(d[1]), "+f"(d[2]), "+f"(d[3]), "+f"(d[4]), "+f"(d[5]), "+f"(d[6]), "+f"(d[7]), \
    "+f"(d[8]), "+f"(d[9]), "+f"(d[10]), "+f"(d[11]), "+f"(d[12]), "+f"(d[13]), "+f"(d[14]), "+f"(d[15]), \
    "+f"(d[16]), "+f"(d[17]), "+f"(d[18]), "+f"(d[19]), "+f"(d[20]), "+f"(d[21]), "+f"(d[22]), "+f"(d[23]), \
    "+f"(d[24]), "+f"(d[25]), "+f"(d[26]), "+f"(d[27]), "+f"(d[28]), "+f"(d[29]), "+f"(d[30]), "+f"(d[31]), \
    "+f"(d[32]), "+f"(d[33]), "+f"(d[34]), "+f"(d[35]), "+f"(d[36]), "+f"(d[37]), "+f"(d[38]), "+f"(d[39]), \
    "+f"(d[40]), "+f"(d[41]), "+f"(d[42]), "+f"(d[43]), "+f"(d[44]), "+f"(d[45]), "+f"(d[46]), "+f"(d[47]), \
    "+f"(d[48]), "+f"(d[49]), "+f"(d[50]), "+f"(d[51]), "+f"(d[52]), "+f"(d[53]), "+f"(d[54]), "+f"(d[55]), \
    "+f"(d[56]), "+f"(d[57]), "+f"(d[58]), "+f"(d[59]), "+f"(d[60]), "+f"(d[61]), "+f"(d[62]), "+f"(d[63])
#define ACC64_STR \
    "{%0, %1, %2, %3, %4, %5, %6, %7, %8, %9, %10, %11, %12, %13, %14, %15, " \
    "%16, %17, %18, %19, %20, %21, %22, %23, %24, %25, %26, %27, %28, %29, %30, %31, " \
    "%32, %33, %34, %35, %36, %37, %38, %39, %40, %41, %42, %43, %44, %45, %46, %47, " \
    "%48, %49, %50, %51, %52, %53, %54, %55, %56, %57, %58, %59, %60, %61, %62, %63}"

template <int TB>
__device__ __forceinline__ void wgmma_ss_n128(float (&d)[64], uint64_t da, uint64_t db, int scale_d) {
    asm volatile(
        "{\n.reg .pred p;\nsetp.ne.b32 p, %66, 0;\n"
        "wgmma.mma_async.sync.aligned.m64n128k16.f32.bf16.bf16 " ACC64_STR ", %64, %65, p, 1, 1, 0, %67;\n}\n"
        : ACC64(d) : "l"(da), "l"(db), "r"(scale_d), "n"(TB));
}
__device__ __forceinline__ uint32_t desc_lo(uint32_t addr, uint32_t lbo) { return ((addr & 0x3FFFF) >> 4) | ((lbo >> 4) << 16); }
template <int TB>
__device__ __forceinline__ void wgmma_ss_n128_lo(float (&d)[64], uint32_t da_lo, uint32_t db_lo, int scale_d) {
    asm volatile(
        "{\n.reg .pred p;\n.reg .b64 da, db;\nsetp.ne.b32 p, %66, 0;\n"
        "mov.b64 da, {%64, 0x40000040};\nmov.b64 db, {%65, 0x40000040};\n"
        "wgmma.mma_async.sync.aligned.m64n128k16.f32.bf16.bf16 " ACC64_STR ", da, db, p, 1, 1, 0, %67;\n}\n"
        : ACC64(d) : "r"(da_lo), "r"(db_lo), "r"(scale_d), "n"(TB));
}
__device__ __forceinline__ void wgmma_rs_n128_tb(float (&d)[64], uint32_t a0, uint32_t a1, uint32_t a2, uint32_t a3,
                                                 uint64_t db, int scale_d) {
    asm volatile(
        "{\n.reg .pred p;\nsetp.ne.b32 p, %69, 0;\n"
        "wgmma.mma_async.sync.aligned.m64n128k16.f32.bf16.bf16 " ACC64_STR ", {%64, %65, %66, %67}, %68, p, 1, 1, 1;\n}\n"
        : ACC64(d) : "r"(a0), "r"(a1), "r"(a2), "r"(a3), "l"(db), "r"(scale_d));
}
__device__ __forceinline__ void wgmma_rs_n80(float (&d)[40], const uint32_t (&a)[4], uint32_t db_lo, int scale_d) {
    asm volatile(
        "{\n.reg .pred p;\n.reg .b64 db;\nsetp.ne.b32 p, %45, 0;\nmov.b64 db, {%44, 0x40000040};\n"
        "wgmma.mma_async.sync.aligned.m64n80k16.f32.bf16.bf16 "
        "{%0, %1, %2, %3, %4, %5, %6, %7, %8, %9, %10, %11, %12, %13, %14, %15, %16, %17, %18, %19, %20, %21, %22, %23, %24, %25, %26, %27, %28, %29, %30, %31, %32, %33, %34, %35, %36, %37, %38, %39}, "
        "{%40, %41, %42, %43}, db, p, 1, 1, 0;\n}\n"
        : "+f"(d[0]), "+f"(d[1]), "+f"(d[2]), "+f"(d[3]), "+f"(d[4]), "+f"(d[5]), "+f"(d[6]), "+f"(d[7]), "+f"(d[8]), "+f"(d[9]), "+f"(d[10]), "+f"(d[11]), "+f"(d[12]), "+f"(d[13]), "+f"(d[14]), "+f"(d[15]), "+f"(d[16]), "+f"(d[17]), "+f"(d[18]), "+f"(d[19]), "+f"(d[20]), "+f"(d[21]), "+f"(d[22]), "+f"(d[23]), "+f"(d[24]), "+f"(d[25]), "+f"(d[26]), "+f"(d[27]), "+f"(d[28]), "+f"(d[29]), "+f"(d[30]), "+f"(d[31]), "+f"(d[32]), "+f"(d[33]), "+f"(d[34]), "+f"(d[35]), "+f"(d[36]), "+f"(d[37]), "+f"(d[38]), "+f"(d[39])
        : "r"(a[0]), "r"(a[1]), "r"(a[2]), "r"(a[3]), "r"(db_lo), "r"(scale_d));
}
__device__ __forceinline__ void wgmma_ss_n256_tb(float (&d)[128], uint32_t da_lo, uint32_t db_lo, int scale_d) {
    asm volatile(
        "{\n.reg .pred p;\n.reg .b64 da, db;\nsetp.ne.b32 p, %130, 0;\nmov.b64 da, {%128, 0x40000040};\nmov.b64 db, {%129, 0x40000040};\n"
        "wgmma.mma_async.sync.aligned.m64n256k16.f32.bf16.bf16 {%0, %1, %2, %3, %4, %5, %6, %7, %8, %9, %10, %11, %12, %13, %14, %15, %16, %17, %18, %19, %20, %21, %22, %23, %24, %25, %26, %27, %28, %29, %30, %31, %32, %33, %34, %35, %36, %37, %38, %39, %40, %41, %42, %43, %44, %45, %46, %47, %48, %49, %50, %51, %52, %53, %54, %55, %56, %57, %58, %59, %60, %61, %62, %63, %64, %65, %66, %67, %68, %69, %70, %71, %72, %73, %74, %75, %76, %77, %78, %79, %80, %81, %82, %83, %84, %85, %86, %87, %88, %89, %90, %91, %92, %93, %94, %95, %96, %97, %98, %99, %100, %101, %102, %103, %104, %105, %106, %107, %108, %109, %110, %111, %112, %113, %114, %115, %116, %117, %118, %119, %120, %121, %122, %123, %124, %125, %126, %127}, da, db, p, 1, 1, 0, 1;\n}\n"
        : "+f"(d[0]), "+f"(d[1]), "+f"(d[2]), "+f"(d[3]), "+f"(d[4]), "+f"(d[5]), "+f"(d[6]), "+f"(d[7]), "+f"(d[8]), "+f"(d[9]), "+f"(d[10]), "+f"(d[11]), "+f"(d[12]), "+f"(d[13]), "+f"(d[14]), "+f"(d[15]), "+f"(d[16]), "+f"(d[17]), "+f"(d[18]), "+f"(d[19]), "+f"(d[20]), "+f"(d[21]), "+f"(d[22]), "+f"(d[23]), "+f"(d[24]), "+f"(d[25]), "+f"(d[26]), "+f"(d[27]), "+f"(d[28]), "+f"(d[29]), "+f"(d[30]), "+f"(d[31]), "+f"(d[32]), "+f"(d[33]), "+f"(d[34]), "+f"(d[35]), "+f"(d[36]), "+f"(d[37]), "+f"(d[38]), "+f"(d[39]), "+f"(d[40]), "+f"(d[41]), "+f"(d[42]), "+f"(d[43]), "+f"(d[44]), "+f"(d[45]), "+f"(d[46]), "+f"(d[47]), "+f"(d[48]), "+f"(d[49]), "+f"(d[50]), "+f"(d[51]), "+f"(d[52]), "+f"(d[53]), "+f"(d[54]), "+f"(d[55]), "+f"(d[56]), "+f"(d[57]), "+f"(d[58]), "+f"(d[59]), "+f"(d[60]), "+f"(d[61]), "+f"(d[62]), "+f"(d[63]), "+f"(d[64]), "+f"(d[65]), "+f"(d[66]), "+f"(d[67]), "+f"(d[68]), "+f"(d[69]), "+f"(d[70]), "+f"(d[71]), "+f"(d[72]), "+f"(d[73]), "+f"(d[74]), "+f"(d[75]), "+f"(d[76]), "+f"(d[77]), "+f"(d[78]), "+f"(d[79]), "+f"(d[80]), "+f"(d[81]), "+f"(d[82]), "+f"(d[83]), "+f"(d[84]), "+f"(d[85]), "+f"(d[86]), "+f"(d[87]), "+f"(d[88]), "+f"(d[89]), "+f"(d[90]), "+f"(d[91]), "+f"(d[92]), "+f"(d[93]), "+f"(d[94]), "+f"(d[95]), "+f"(d[96]), "+f"(d[97]), "+f"(d[98]), "+f"(d[99]), "+f"(d[100]), "+f"(d[101]), "+f"(d[102]), "+f"(d[103]), "+f"(d[104]), "+f"(d[105]), "+f"(d[106]), "+f"(d[107]), "+f"(d[108]), "+f"(d[109]), "+f"(d[110]), "+f"(d[111]), "+f"(d[112]), "+f"(d[113]), "+f"(d[114]), "+f"(d[115]), "+f"(d[116]), "+f"(d[117]), "+f"(d[118]), "+f"(d[119]), "+f"(d[120]), "+f"(d[121]), "+f"(d[122]), "+f"(d[123]), "+f"(d[124]), "+f"(d[125]), "+f"(d[126]), "+f"(d[127])
        : "r"(da_lo), "r"(db_lo), "r"(scale_d));
}
__device__ __forceinline__ void stmatrix_x4(uint32_t addr, uint32_t r0, uint32_t r1, uint32_t r2, uint32_t r3) {
    asm volatile("stmatrix.sync.aligned.m8n8.x4.shared.b16 [%0], {%1, %2, %3, %4};" :: "r"(addr), "r"(r0), "r"(r1), "r"(r2), "r"(r3) : "memory");
}
__device__ __forceinline__ void tma_store_2d(const CUtensorMap* map, uint32_t src, int c0, int c1) {
    asm volatile("cp.async.bulk.tensor.2d.global.shared::cta.bulk_group [%0, {%2, %3}], [%1];"
                 :: "l"((uint64_t)map), "r"(src), "r"(c0), "r"(c1) : "memory");
}
__device__ __forceinline__ float ex2f(float x) { float y; asm("ex2.approx.ftz.f32 %0, %1;" : "=f"(y) : "f"(x)); return y; }
__device__ __forceinline__ uint32_t pack_bf16(float lo, float hi) {
    __nv_bfloat162 v = __floats2bfloat162_rn(lo, hi);
    return *reinterpret_cast<uint32_t*>(&v);
}
__device__ __forceinline__ float bf16r(float x) { return __uint_as_float(pack_bf16(0.f, x) & 0xffff0000u); }
__device__ __forceinline__ void mma_16816(float (&c)[4], uint32_t a0, uint32_t a1, uint32_t a2, uint32_t a3,
                                          uint32_t b0, uint32_t b1) {
    asm volatile(
        "mma.sync.aligned.m16n8k16.row.col.f32.bf16.bf16.f32 {%0,%1,%2,%3}, {%4,%5,%6,%7}, {%8,%9}, {%0,%1,%2,%3};"
        : "+f"(c[0]), "+f"(c[1]), "+f"(c[2]), "+f"(c[3])
        : "r"(a0), "r"(a1), "r"(a2), "r"(a3), "r"(b0), "r"(b1));
}
__device__ __forceinline__ void ldmatrix_x4_trans(uint32_t& r0, uint32_t& r1, uint32_t& r2, uint32_t& r3, uint32_t addr) {
    asm volatile("ldmatrix.sync.aligned.m8n8.x4.trans.shared.b16 {%0,%1,%2,%3}, [%4];"
                 : "=r"(r0), "=r"(r1), "=r"(r2), "=r"(r3) : "r"(addr));
}

struct AttnParams {
    CUtensorMap mapQ, mapK, mapV;
    CUtensorMap mapO;
    const bf16 *x, *gate_w;
};
constexpr uint32_t FA_Q = 0, FA_KV = 65536, FA_O = 196608, FA_BAR = 229376;
constexpr int FA_SMEM = FA_BAR + 256;
constexpr int FA_ITEMS = 16 * NH;
__device__ __forceinline__ int fa_qt(int t) { return 15 - ((t & 127) >> 3); }
__device__ __forceinline__ int fa_head(int t) { return (t >> 7) * 8 + (t & 7); }
__device__ __forceinline__ uint32_t mbar_test(uint32_t bar, uint32_t parity) {
    uint32_t done;
    asm volatile(
        "{\n.reg .pred p;\n"
        "mbarrier.test_wait.parity.shared::cta.b64 p, [%1], %2;\n"
        "selp.u32 %0, 1, 0, p;\n}\n" : "=r"(done) : "r"(bar), "r"(parity) : "memory");
    return done;
}
__device__ __forceinline__ void mbar_arrive_if(uint32_t bar, bool c) {
    asm volatile("{\n.reg .pred p;\nsetp.ne.u32 p, %1, 0;\n@p mbarrier.arrive.shared::cta.b64 _, [%0];\n}" :: "r"(bar), "r"((uint32_t)c) : "memory");
}
__device__ __forceinline__ void wgmma_rs_n128_tb_lo(float (&d)[64], const uint32_t* a, uint32_t db_lo, int scale_d) {
    asm volatile(
        "{\n.reg .pred p;\n.reg .b64 db;\nsetp.ne.b32 p, %69, 0;\nmov.b64 db, {%68, 0x40000040};\n"
        "wgmma.mma_async.sync.aligned.m64n128k16.f32.bf16.bf16 " ACC64_STR ", {%64, %65, %66, %67}, db, p, 1, 1, 1;\n}\n"
        : ACC64(d) : "r"(a[0]), "r"(a[1]), "r"(a[2]), "r"(a[3]), "r"(db_lo), "r"(scale_d));
}
#define FA_TEST 48
#define FA_PIN 32

__device__ __forceinline__ void wgmma_ss_n64_lo(float (&d)[64], uint32_t da_lo, uint32_t db_lo, int scale_d) {
    asm volatile(
        "{\n.reg .pred p;\n.reg .b64 da, db;\nsetp.ne.b32 p, %34, 0;\n"
        "mov.b64 da, {%32, 0x40000040};\nmov.b64 db, {%33, 0x40000040};\n"
        "wgmma.mma_async.sync.aligned.m64n64k16.f32.bf16.bf16 {%0, %1, %2, %3, %4, %5, %6, %7, %8, %9, %10, %11, %12, %13, %14, %15, "
        "%16, %17, %18, %19, %20, %21, %22, %23, %24, %25, %26, %27, %28, %29, %30, %31}, da, db, p, 1, 1, 0, 0;\n}\n"
        : "+f"(d[0]), "+f"(d[1]), "+f"(d[2]), "+f"(d[3]), "+f"(d[4]), "+f"(d[5]), "+f"(d[6]), "+f"(d[7]), "+f"(d[8]), "+f"(d[9]), "+f"(d[10]),
          "+f"(d[11]), "+f"(d[12]), "+f"(d[13]), "+f"(d[14]), "+f"(d[15]), "+f"(d[16]), "+f"(d[17]), "+f"(d[18]), "+f"(d[19]), "+f"(d[20]),
          "+f"(d[21]), "+f"(d[22]), "+f"(d[23]), "+f"(d[24]), "+f"(d[25]), "+f"(d[26]), "+f"(d[27]), "+f"(d[28]), "+f"(d[29]), "+f"(d[30]), "+f"(d[31])
        : "r"(da_lo), "r"(db_lo), "r"(scale_d));
}
#define FA_NOFB 0
#define FA_DPIN 16
#define FA_RLO 40
#define FA_RHI 232
#define FA_LIM 0x1p40f
__device__ __forceinline__ void attn_consumer(const uint32_t sb, const int wg, const int w4, const int lane) {
    const uint32_t bar_q = sb + FA_BAR, bar_of = bar_q + 96, bar_oe = bar_q + 112, oslot = bar_q + 144;
    const bool lane0 = lane == 0;
    float o[64], sacc[64];
    uint32_t pa[32];
    float ms0 = 0.f, ms1 = 0.f, lrow0 = 1.f, lrow1 = 1.f;
    const float sc = 0.08838834764831845f * 1.4426950408889634f;
    const uint32_t q_lo = desc_lo(sb + FA_Q + wg * 8192, 16), k_lo = desc_lo(sb + FA_KV, 16), v_lo = desc_lo(sb + FA_KV + 32768, 16384);
    uint32_t qd = q_lo + 2048, kd = k_lo + 4096, vd = v_lo, bs = bar_q + 8, bi = bar_q + 8;
    auto issue_qk = [&](uint32_t a, bool half) {
        const uint32_t b = kd;
#pragma unroll
        for (int kk = 0; kk < 8; kk++) {
            if (half) wgmma_ss_n64_lo(sacc, a + (kk >> 2) * 1024 + (kk & 3) * 2, b + (kk >> 2) * 1024 + (kk & 3) * 2, kk != 0);
            else wgmma_ss_n128_lo<0>(sacc, a + (kk >> 2) * 1024 + (kk & 3) * 2, b + (kk >> 2) * 1024 + (kk & 3) * 2, kk != 0);
        }
        wgmma_commit();
    };
    auto issue_pv = [&](bool acc) {
        const uint32_t b = vd;
#pragma unroll
        for (int kk = 0; kk < 8; kk++) wgmma_rs_n128_tb_lo(o, &pa[kk * 4], b + kk * 128, kk != 0 || acc);
        wgmma_commit();
    };
    auto turn_wait = [&]() { asm volatile("bar.sync %0, 256;" :: "r"(1 + wg) : "memory"); };
    auto turn_pass = [&]() { asm volatile("bar.arrive %0, 256;" :: "r"(2 - wg) : "memory"); };
    int item = -1, it = -1, j = 0, nkv = 1, t = 0;
    auto redo = [&](float& l0, float& l1) {
        const size_t row0 = (size_t)fa_head(t) * SEQ + (lane >> 2);
        const uint32_t* qg = reinterpret_cast<const uint32_t*>(g_QA + (row0 + (nkv - 1) * 128 + wg * 64 + w4 * 16) * HD) + (lane & 3);
        const uint32_t* kg = reinterpret_cast<const uint32_t*>(g_KA + (row0 + (nkv - 1 - j) * 128) * HD) + (lane & 3);
        auto ldg = [](const uint32_t* p) { uint32_t v; asm volatile("ld.relaxed.gpu.global.u32 %0, [%1];" : "=r"(v) : "l"(p) : "memory"); return v; };
        const int r0 = j ? 1 << 20 : wg * 64 + w4 * 16 + (lane >> 2) - (lane & 3) * 2;
        float mx0 = -INFINITY, mx1 = -INFINITY;
        const float m0 = ms0, m1 = ms1;
        uint4 tmp[8];
        l0 = 0.f; l1 = 0.f;
#pragma unroll 1
        for (int ps = 0; ps < 32; ps++) {
            const int nb = ps & 15;
            float c[4] = {0.f, 0.f, 0.f, 0.f};
#pragma unroll 1
            for (int kk = 0; kk < 64; kk += 8)
                mma_16816(c, ldg(qg + kk), ldg(qg + kk + 8 * 64), ldg(qg + kk + 4), ldg(qg + kk + 8 * 64 + 4), ldg(kg + nb * 8 * 64 + kk), ldg(kg + nb * 8 * 64 + kk + 4));
#pragma unroll
            for (int i = 0; i < 4; i++)
                if (nb * 8 + (i & 1) - ((i & 2) ? 8 : 0) > r0) c[i] = -INFINITY;
            mx0 = fmaxf(mx0, fmaxf(c[0], c[1])); mx1 = fmaxf(mx1, fmaxf(c[2], c[3]));
#pragma unroll
            for (int i = 0; i < 4; i++) c[i] = ex2f(fmaf(c[i], sc, (i & 2) ? ms1 : ms0));
            l0 += c[0] + c[1]; l1 += c[2] + c[3];
            reinterpret_cast<uint2*>(tmp)[nb] = make_uint2(pack_bf16(c[0], c[1]), pack_bf16(c[2], c[3]));
            if (ps == 15) {
                mx0 = fmaxf(mx0, __shfl_xor_sync(0xffffffff, mx0, 1)); mx1 = fmaxf(mx1, __shfl_xor_sync(0xffffffff, mx1, 1));
                mx0 = fmaxf(mx0, __shfl_xor_sync(0xffffffff, mx0, 2)); mx1 = fmaxf(mx1, __shfl_xor_sync(0xffffffff, mx1, 2));
                ms0 = fminf(-mx0 * sc, ms0); ms1 = fminf(-mx1 * sc, ms1);
                l0 = 0.f; l1 = 0.f;
            }
        }
        const float a0 = ex2f(ms0 - m0), a1 = ex2f(ms1 - m1);
        lrow0 *= a0; lrow1 *= a1;
#pragma unroll
        for (int i = 0; i < 64; i++) o[i] *= (i & 2) ? a1 : a0;
#pragma unroll
        for (int i = 0; i < 8; i++) { pa[4 * i] = tmp[i].x; pa[4 * i + 1] = tmp[i].y; pa[4 * i + 2] = tmp[i].z; pa[4 * i + 3] = tmp[i].w; }
    };
    auto pin_after = [&](float v) {
        asm volatile("{\n.reg .pred p;\nsetp.eq.f32 p, %1, %2;\n@p st.shared.f32 [%0], %1;\n}" :: "r"(oslot + 16), "f"(v), "f"(ms0) : "memory");
    };
    uint32_t ok = 0, okq = 0;
    int tn = 0;
    auto tests = [&]() {
        ok = mbar_test(bs + 48, (it >> 1) & 1);
        asm volatile("ld.shared.s32 %0, [%1];" : "=r"(tn) : "r"((bi ^ 8) + 128) : "memory");
        ok &= mbar_test((bs ^ 8) + 32, ((it + 1) >> 1) & 1);
        okq = mbar_test(bi ^ 8, ((item + 1) >> 1) & 1);
    };
    auto epilogue = [&](int tag, bool real) {
        float l0 = lrow0, l1 = lrow1;
        l0 += __shfl_xor_sync(0xffffffff, l0, 1); l1 += __shfl_xor_sync(0xffffffff, l1, 1);
        l0 += __shfl_xor_sync(0xffffffff, l0, 2); l1 += __shfl_xor_sync(0xffffffff, l1, 2);
        float i0, i1;
        asm("rcp.approx.ftz.f32 %0, %1;" : "=f"(i0) : "f"(l0));
        asm("rcp.approx.ftz.f32 %0, %1;" : "=f"(i1) : "f"(l1));
        const int row = w4 * 16 + (lane >> 2);
        const uint32_t stg = sb + FA_O + wg * 16384 + row * 128;
#pragma unroll
        for (int i = 0; i < 4; i++) {
            const int ch = i * 4 + (lane & 3);
            const uint32_t a = stg + (ch >> 3) * 8192 + (((ch & 7) ^ (row & 7)) << 4);
            const float* q = &o[i * 16];
            asm volatile("st.shared.v4.b32 [%0], {%1, %2, %3, %4};" :: "r"(a), "r"(pack_bf16(q[0] * i0, q[1] * i0)), "r"(pack_bf16(q[4] * i0, q[5] * i0)),
                         "r"(pack_bf16(q[8] * i0, q[9] * i0)), "r"(pack_bf16(q[12] * i0, q[13] * i0)) : "memory");
            asm volatile("st.shared.v4.b32 [%0], {%1, %2, %3, %4};" :: "r"(a + 1024), "r"(pack_bf16(q[2] * i1, q[3] * i1)), "r"(pack_bf16(q[6] * i1, q[7] * i1)),
                         "r"(pack_bf16(q[10] * i1, q[11] * i1)), "r"(pack_bf16(q[14] * i1, q[15] * i1)) : "memory");
        }
        asm volatile("st.shared.s32 [%0], %1;" :: "r"(oslot + wg * 4), "r"(tag) : "memory");
        __syncwarp();
        mbar_arrive_if(bar_of + 8 * wg, lane0 && real);
    };
    auto transition = [&](auto wgc, float& l0, float& l1) {
        constexpr int WG = decltype(wgc)::value;
        constexpr int NE = WG == 0 ? 32 : 64;
        turn_wait();
        wgmma_fence();
        issue_qk(qd, WG == 0);
        issue_pv(nkv > 1);
        turn_pass();
        const int tc = t;
        t = __shfl_sync(0xffffffff, tn, 0);
        nkv = fa_qt(t) + 1;
        mbar_wait(bar_oe + 8 * wg, (max(item, 0) & 1) ^ 1);
        item++; bi ^= 8;
        wgmma_wait<1>();
        mbar_arrive_if(bs + 64, lane0);
        mbar_arrive_if(bi + 16, lane0 && nkv == 1);
        ms0 = -sc * __shfl_sync(0xffffffff, sacc[0], lane & 28); ms1 = -sc * __shfl_sync(0xffffffff, sacc[2], lane & 28);
        const int r0 = w4 * 16 + (lane >> 2) - (lane & 3) * 2;
#pragma unroll
        for (int i = 0; i < 32; i++)
            if ((i >> 2) * 8 + (i & 1) - ((i & 2) ? 8 : 0) > r0) sacc[WG * 32 + i] = -INFINITY;
        float sum[4];
#pragma unroll
        for (int i = 0; i < FA_DPIN; i++) { sacc[i] = ex2f(fmaf(sacc[i], sc, (i & 2) ? ms1 : ms0)); sum[i & 3] = i < 4 ? sacc[i] : sum[i & 3] + sacc[i]; }
        pin_after((sum[0] + sum[1]) + (sum[2] + sum[3]));
        wgmma_wait<0>();
        mbar_arrive_if((bs ^ 8) + 80, lane0 && item > 0);
        epilogue(tc, item > 0);
#pragma unroll
        for (int i = 0; i < NE; i++) {
            if (i >= FA_DPIN) { sacc[i] = ex2f(fmaf(sacc[i], sc, (i & 2) ? ms1 : ms0)); sum[i & 3] += sacc[i]; }
            if (i & 1) pa[i >> 1] = pack_bf16(sacc[i - 1], sacc[i]);
            if (i == NE - 16) { pin_after(sum[0]); tests(); }
        }
        if (NE == 32)
#pragma unroll
            for (int i = 16; i < 32; i++) asm volatile("mov.u32 %0, 0;" : "=r"(pa[i]));
        l0 = sum[0] + sum[1]; l1 = sum[2] + sum[3];
    };
#pragma unroll
    for (int i = 0; i < 32; i++) pa[i] = 0u;
    if (wg == 1) asm volatile("bar.arrive 1, 256;" ::: "memory");
#pragma unroll 1
    for (;;) {
        float l0, l1;
        it++;
        kd = 2 * k_lo + 4096 - kd; vd = 2 * v_lo + 4096 - vd; bs ^= 8;
        if (++j < nkv) {
            if (__builtin_expect(!ok, 0)) {
                mbar_wait(bs + 32, (it >> 1) & 1);
                mbar_wait((bs ^ 8) + 48, ((it - 1) >> 1) & 1);
            }
            turn_wait();
            wgmma_fence();
            issue_qk(qd, false);
            issue_pv(j > 1);
            turn_pass();
            wgmma_wait<1>();
            mbar_arrive_if(bs + 64, lane0);
            mbar_arrive_if(bi + 16, lane0 && j == nkv - 1);
            float sum[4];
#pragma unroll
            for (int i = 0; i < FA_PIN; i++) { sacc[i] = ex2f(fmaf(sacc[i], sc, (i & 2) ? ms1 : ms0)); sum[i & 3] = i < 4 ? sacc[i] : sum[i & 3] + sacc[i]; }
            pin_after((sum[0] + sum[1]) + (sum[2] + sum[3]));
            wgmma_wait<0>();
            mbar_arrive_if((bs ^ 8) + 80, lane0);
#pragma unroll
            for (int i = 0; i < 64; i++) {
                if (i >= FA_PIN) { sacc[i] = ex2f(fmaf(sacc[i], sc, (i & 2) ? ms1 : ms0)); sum[i & 3] = i < 4 ? sacc[i] : sum[i & 3] + sacc[i]; }
                if (i & 1) pa[i >> 1] = pack_bf16(sacc[i - 1], sacc[i]);
                if (i == FA_TEST) { pin_after(sum[0]); tests(); }
            }
            l0 = sum[0] + sum[1]; l1 = sum[2] + sum[3];
        } else {
            if (__builtin_expect(!(ok & okq), 0)) {
                mbar_wait(bi ^ 8, ((item + 1) >> 1) & 1);
                asm volatile("ld.shared.s32 %0, [%1];" : "=r"(tn) : "r"((bi ^ 8) + 128) : "memory");
                mbar_wait((bs ^ 8) + 48, ((it - 1) >> 1) & 1);
                if (tn < 0) break;
                mbar_wait(bs + 32, (it >> 1) & 1);
            }
            qd = 2 * q_lo + 2048 - qd;
            if (wg == 0) transition(std::integral_constant<int, 0>(), l0, l1); else transition(std::integral_constant<int, 1>(), l0, l1);
            j = 0;
            lrow0 = 0.f; lrow1 = 0.f;
        }
        if (!FA_NOFB && __builtin_expect(__any_sync(0xffffffff, !(l0 + l1 < FA_LIM)), 0)) redo(l0, l1);
        lrow0 += l0; lrow1 += l1;
    }
    wgmma_fence();
    issue_pv(nkv > 1);
    mbar_wait(bar_oe + 8 * wg, (item & 1) ^ 1);
    wgmma_wait<0>();
    epilogue(t | 0x80000000, true);
}

__global__ void __launch_bounds__(384, 1) attn_kernel(const __grid_constant__ AttnParams P) {
    extern __shared__ __align__(1024) uint8_t smem_attn[];
    const uint32_t sb = smem_u32(smem_attn);
    const uint32_t bar_q = sb + FA_BAR, bar_qe = bar_q + 16, bar_kf = bar_q + 32, bar_vf = bar_q + 48, bar_ke = bar_q + 64, bar_ve = bar_q + 80,
                   bar_of = bar_q + 96, bar_oe = bar_q + 112, slot = bar_q + 128, oslot = bar_q + 144;
    const int warp = __shfl_sync(0xffffffff, threadIdx.x >> 5, 0);
    const int lane = threadIdx.x & 31;
    if (threadIdx.x == 0) {
        for (int i = 0; i < 2; i++) {
            mbar_init(bar_q + 8 * i, 1); mbar_init(bar_qe + 8 * i, 8); mbar_init(bar_kf + 8 * i, 1); mbar_init(bar_vf + 8 * i, 1);
            mbar_init(bar_ke + 8 * i, 8); mbar_init(bar_ve + 8 * i, 8); mbar_init(bar_of + 8 * i, 4); mbar_init(bar_oe + 8 * i, 1);
        }
        asm volatile("fence.mbarrier_init.release.cluster;" ::: "memory");
    }
    if (threadIdx.x == 256) wait_ctr(CT_AP + (fa_head(blockIdx.x) >> 1), 192u);
    __syncthreads();
    pdl_launch_dependents();
    if (warp >= 8) {
        asm volatile("setmaxnreg.dec.sync.aligned.u32 %0;" :: "n"(FA_RLO));
        if (warp == 11) {
            const uint4 gv0 = __ldg(reinterpret_cast<const uint4*>(P.gate_w) + lane), gv1 = __ldg(reinterpret_cast<const uint4*>(P.gate_w) + 32 + lane);
            const uint32_t gw[8] = {gv0.x, gv0.y, gv0.z, gv0.w, gv1.x, gv1.y, gv1.z, gv1.w};
#pragma unroll 1
            for (int r = blockIdx.x; r < SEQ; r += gridDim.x) {
                const uint4 x0 = __ldg(reinterpret_cast<const uint4*>(P.x + (size_t)r * DM) + lane), x1 = __ldg(reinterpret_cast<const uint4*>(P.x + (size_t)r * DM) + 32 + lane);
                const uint32_t xw[8] = {x0.x, x0.y, x0.z, x0.w, x1.x, x1.y, x1.z, x1.w};
                float sum = 0.f;
#pragma unroll
                for (int e = 0; e < 8; e++) {
                    const uint32_t pr = pack_bf16(__uint_as_float(xw[e] << 16) * __uint_as_float(gw[e] << 16), __uint_as_float(xw[e] & 0xffff0000u) * __uint_as_float(gw[e] & 0xffff0000u));
                    sum += __uint_as_float(pr << 16) + __uint_as_float(pr & 0xffff0000u);
                }
#pragma unroll
                for (int o = 16; o; o >>= 1) sum += __shfl_xor_sync(0xffffffff, sum, o);
                if (lane == 0) g_gate[r] = bf16r(__fdividef(1.f, 1.f + __expf(-bf16r(sum))));
            }
#pragma unroll 1
            for (int i = blockIdx.x * 32 + lane; i < 0; i += gridDim.x * 32) reinterpret_cast<uint4*>(g_ctxA)[i] = make_uint4(~0u, ~0u, ~0u, ~0u);
            __syncwarp();
            if (lane == 0) signal_ctr_generic(CT_G);
        } else if (warp > 8) {
            if (lane == 0) {
                const int wg = warp - 9;
                const uint32_t stg = sb + FA_O + wg * 16384;
                TS_BEGIN_T(1, 320);
                for (int n = 0;; n++) {
                    mbar_wait(bar_of + 8 * wg, n & 1);
                    int t;
                    asm volatile("ld.shared.s32 %0, [%1];" : "=r"(t) : "r"(oslot + wg * 4) : "memory");
                    asm volatile("fence.proxy.async.shared::cta;" ::: "memory");
                    const bool last = t < 0;
                    t &= 0xffff;
                    const int qt = fa_qt(t), h = fa_head(t);
                    tma_store_2d(&P.mapO, stg, 0, h * SEQ + qt * 128 + wg * 64);
                    tma_store_2d(&P.mapO, stg + 8192, 64, h * SEQ + qt * 128 + wg * 64);
                    asm volatile("cp.async.bulk.commit_group;" ::: "memory");
                    asm volatile("cp.async.bulk.wait_group.read 0;" ::: "memory");
                    mbar_arrive(bar_oe + 8 * wg);
                    asm volatile("cp.async.bulk.wait_group 0;" ::: "memory");
                    signal_ctr(CT_CA + qt * 2 + (h >= O2_HE));
                    if (last) break;
                }
                TS_END_T(1, 320);
            }
        } else if (lane == 0) {
            int it = 0, t = blockIdx.x, hp_ready = 1 << (fa_head(t) >> 1);
            auto load_q = [&](int item, int t) {
                const uint32_t b = bar_q + 8 * (item & 1);
                asm volatile("st.shared.s32 [%0], %1;" :: "r"(slot + (item & 1) * 8), "r"(t) : "memory");
                if (t < 0) { mbar_arrive(b); return; }
                const int row = fa_head(t) * SEQ + fa_qt(t) * 128;
                mbar_expect_tx(b, 32768);
                tma_load_2d(sb + FA_Q + (item & 1) * 32768, &P.mapQ, b, 0, row);
                tma_load_2d(sb + FA_Q + (item & 1) * 32768 + 16384, &P.mapQ, b, 64, row);
            };
            auto load_v = [&](int it, int row) {
                const int s = it & 1;
                const uint32_t sv = sb + FA_KV + s * 65536 + 32768;
                mbar_wait(bar_ve + 8 * s, ((it >> 1) & 1) ^ 1);
                mbar_expect_tx(bar_vf + 8 * s, 32768);
                tma_load_2d(sv, &P.mapV, bar_vf + 8 * s, 0, row);
                tma_load_2d(sv + 16384, &P.mapV, bar_vf + 8 * s, 64, row);
            };
            int vrow = 0;
            load_q(0, t);
            for (int item = 0; t >= 0; item++) {
                const int h = fa_head(t);
                for (int j = fa_qt(t); j >= 0; j--, it++) {
                    const int s = it & 1;
                    const uint32_t ph = ((it >> 1) & 1) ^ 1;
                    const uint32_t sk = sb + FA_KV + s * 65536;
                    if (j == 0) t = (int)(gridDim.x + atomicAdd(&g_ctr[CT_ATTN], 1u));
                    mbar_wait(bar_ke + 8 * s, ph);
                    mbar_expect_tx(bar_kf + 8 * s, 32768);
                    tma_load_2d(sk, &P.mapK, bar_kf + 8 * s, 0, h * SEQ + j * 128);
                    tma_load_2d(sk + 16384, &P.mapK, bar_kf + 8 * s, 64, h * SEQ + j * 128);
                    if (it > 0) load_v(it - 1, vrow);
                    vrow = h * SEQ + j * 128;
                    if (j == 0) {
                        if (t >= FA_ITEMS) t = -1;
                        else {
                            const int hp = fa_head(t) >> 1;
                            if (!((hp_ready >> hp) & 1)) { wait_ctr(CT_AP + hp, 192u); hp_ready |= 1 << hp; }
                        }
                        mbar_wait(bar_qe + 8 * ((item + 1) & 1), (((item + 1) >> 1) & 1) ^ 1);
                        load_q(item + 1, t);
                    }
                }
            }
            load_v(it - 1, vrow);
        }
    } else {
        asm volatile("setmaxnreg.inc.sync.aligned.u32 %0;" :: "n"(FA_RHI));
        attn_consumer(sb, warp >> 2, warp & 3, lane);
    }
}

__device__ __forceinline__ uint32_t cluster_ctarank() {
    uint32_t r; asm volatile("mov.u32 %0, %%cluster_ctarank;" : "=r"(r)); return r;
}
__device__ __forceinline__ uint32_t mapa_u32(uint32_t addr, uint32_t rank) {
    uint32_t r; asm volatile("mapa.shared::cluster.u32 %0, %1, %2;" : "=r"(r) : "r"(addr), "r"(rank)); return r;
}
__device__ __forceinline__ void cluster_sync_all() {
    asm volatile("barrier.cluster.arrive.release.aligned;\nbarrier.cluster.wait.acquire.aligned;" ::: "memory");
}
__device__ __forceinline__ void cluster_sync_relaxed() {
    asm volatile("barrier.cluster.arrive.relaxed.aligned;\nbarrier.cluster.wait.aligned;" ::: "memory");
}
__device__ __forceinline__ void st_async_v4(uint32_t addr, uint32_t a, uint32_t b, uint32_t c, uint32_t d, uint32_t mbar) {
    asm volatile("st.async.weak.shared::cluster.mbarrier::complete_tx::bytes.v4.b32 [%0], {%1, %2, %3, %4}, [%5];"
                 :: "r"(addr), "r"(a), "r"(b), "r"(c), "r"(d), "r"(mbar) : "memory");
}
__device__ __forceinline__ void st_async_v2(uint32_t addr, uint32_t a, uint32_t b, uint32_t mbar) {
    asm volatile("st.async.weak.shared::cluster.mbarrier::complete_tx::bytes.v2.b32 [%0], {%1, %2}, [%3];"
                 :: "r"(addr), "r"(a), "r"(b), "r"(mbar) : "memory");
}
__device__ __forceinline__ void st_async_b32(uint32_t addr, uint32_t a, uint32_t mbar) {
    asm volatile("st.async.weak.shared::cluster.mbarrier::complete_tx::bytes.b32 [%0], %1, [%2];" :: "r"(addr), "r"(a), "r"(mbar) : "memory");
}
__device__ __forceinline__ void pace(int cycles) {
    if (cycles > 0) {
        uint32_t t0, t;
        asm volatile("mov.u32 %0, %%clock;" : "=r"(t0));
        do { asm volatile("mov.u32 %0, %%clock;" : "=r"(t)); } while (t - t0 < (uint32_t)cycles);
    }
}
__device__ __forceinline__ void mbar_wait_cl(uint32_t bar, uint32_t parity) {
    uint32_t done = 0;
    for (int it = 0; it < (1 << 22) && !done; it++) {
        asm volatile(
            "{\n.reg .pred p;\n"
            "mbarrier.try_wait.parity.shared::cta.b64 p, [%1], %2;\n"
            "selp.u32 %0, 1, 0, p;\n}\n" : "=r"(done) : "r"(bar), "r"(parity) : "memory");
    }
}
__device__ __forceinline__ void ldmatrix_x4(uint32_t& r0, uint32_t& r1, uint32_t& r2, uint32_t& r3, uint32_t addr) {
    asm volatile("ldmatrix.sync.aligned.m8n8.x4.shared.b16 {%0,%1,%2,%3}, [%4];"
                 : "=r"(r0), "=r"(r1), "=r"(r2), "=r"(r3) : "r"(addr));
}
__device__ __forceinline__ void cp_async16(uint32_t dst, const void* src) {
    asm volatile("cp.async.cg.shared.global [%0], [%1], 16;" :: "r"(dst), "l"(src) : "memory");
}

#define DBG(i)
#define DBGW(i, w)
#define CYC(i)
#define TM(i)
__device__ __forceinline__ void tma_load_2d_mc(uint32_t dst, const CUtensorMap* map, uint32_t bar, int c0, int c1, uint16_t mask) {
    asm volatile(
        "cp.async.bulk.tensor.2d.shared::cluster.global.mbarrier::complete_tx::bytes.multicast::cluster [%0], [%1, {%3, %4}], [%2], %5;"
        :: "r"(dst), "l"((uint64_t)map), "r"(bar), "r"(c0), "r"(c1), "h"(mask) : "memory");
}
__device__ __forceinline__ void bulk_s2s(uint32_t dst_cl, uint32_t src, uint32_t bytes, uint32_t bar_cl) {
    asm volatile("cp.async.bulk.shared::cluster.shared::cta.mbarrier::complete_tx::bytes [%0], [%1], %2, [%3];"
                 :: "r"(dst_cl), "r"(src), "r"(bytes), "r"(bar_cl) : "memory");
}
__device__ __forceinline__ bool elect_one() {
    uint32_t p;
    asm volatile("{\n.reg .pred p;\nelect.sync _|p, 0xffffffff;\nselp.u32 %0, 1, 0, p;\n}" : "=r"(p));
    return p;
}
__device__ __forceinline__ void fence_async_smem() { asm volatile("fence.proxy.async.shared::cta;" ::: "memory"); }
template <int ID, int N> __device__ __forceinline__ void bar_sync() { asm volatile("bar.sync %0, %1;" :: "n"(ID), "n"(N) : "memory"); }
template <int ID, int N> __device__ __forceinline__ void bar_arrive() { asm volatile("bar.arrive %0, %1;" :: "n"(ID), "n"(N) : "memory"); }
__device__ __forceinline__ void sts32(uint32_t a, uint32_t v) { asm volatile("st.shared.u32 [%0], %1;" :: "r"(a), "r"(v) : "memory"); }
__device__ __forceinline__ void ldsm_x4(uint32_t* r, uint32_t addr) {
    asm volatile("ldmatrix.sync.aligned.m8n8.x4.shared.b16 {%0,%1,%2,%3}, [%4];" : "=r"(r[0]), "=r"(r[1]), "=r"(r[2]), "=r"(r[3]) : "r"(addr) : "memory");
}
__device__ __forceinline__ uint32_t pin(uint32_t v) { asm volatile("" : "+r"(v)); return v; }
constexpr uint32_t DHI128 = 0x40000040u, DHI32 = 0xC0000010u;
#define ACC16(d) "+f"(d[0]), "+f"(d[1]), "+f"(d[2]), "+f"(d[3]), "+f"(d[4]), "+f"(d[5]), "+f"(d[6]), "+f"(d[7]), "+f"(d[8]), "+f"(d[9]), "+f"(d[10]), \
    "+f"(d[11]), "+f"(d[12]), "+f"(d[13]), "+f"(d[14]), "+f"(d[15])
#define ACC20(d) ACC16(d), "+f"(d[16]), "+f"(d[17]), "+f"(d[18]), "+f"(d[19])
__device__ __forceinline__ void wgmma_rs(float (&d)[16], const uint32_t (&a)[4], uint32_t db_lo) {
    asm volatile(
        "{\n.reg .b64 db;\nmov.b64 db, {%20, %21};\n"
        "wgmma.mma_async.sync.aligned.m64n32k16.f32.bf16.bf16 {%0,%1,%2,%3,%4,%5,%6,%7,%8,%9,%10,%11,%12,%13,%14,%15}, {%16,%17,%18,%19}, db, 1, 1, 1, 0;\n}\n"
        : ACC16(d) : "r"(a[0]), "r"(a[1]), "r"(a[2]), "r"(a[3]), "r"(db_lo), "n"(DHI128));
}
__device__ __forceinline__ void wgmma_rs(float (&d)[20], const uint32_t (&a)[4], uint32_t db_lo) {
    asm volatile(
        "{\n.reg .b64 db;\nmov.b64 db, {%24, %25};\n"
        "wgmma.mma_async.sync.aligned.m64n40k16.f32.bf16.bf16 {%0,%1,%2,%3,%4,%5,%6,%7,%8,%9,%10,%11,%12,%13,%14,%15,%16,%17,%18,%19}, {%20,%21,%22,%23}, db, 1, 1, 1, 0;\n}\n"
        : ACC20(d) : "r"(a[0]), "r"(a[1]), "r"(a[2]), "r"(a[3]), "r"(db_lo), "n"(DHI128));
}
template <uint32_t AHI, uint32_t BHI>
__device__ __forceinline__ void wgmma_ss(float (&d)[16], uint32_t da_lo, uint32_t db_lo) {
    asm volatile(
        "{\n.reg .b64 da, db;\nmov.b64 da, {%16, %18};\nmov.b64 db, {%17, %19};\n"
        "wgmma.mma_async.sync.aligned.m64n32k16.f32.bf16.bf16 {%0,%1,%2,%3,%4,%5,%6,%7,%8,%9,%10,%11,%12,%13,%14,%15}, da, db, 1, 1, 1, 0, 0;\n}\n"
        : ACC16(d) : "r"(da_lo), "r"(db_lo), "n"(AHI), "n"(BHI));
}
template <uint32_t AHI, uint32_t BHI>
__device__ __forceinline__ void wgmma_ss(float (&d)[20], uint32_t da_lo, uint32_t db_lo) {
    asm volatile(
        "{\n.reg .b64 da, db;\nmov.b64 da, {%20, %22};\nmov.b64 db, {%21, %23};\n"
        "wgmma.mma_async.sync.aligned.m64n40k16.f32.bf16.bf16 {%0,%1,%2,%3,%4,%5,%6,%7,%8,%9,%10,%11,%12,%13,%14,%15,%16,%17,%18,%19}, da, db, 1, 1, 1, 0, 0;\n}\n"
        : ACC20(d) : "r"(da_lo), "r"(db_lo), "n"(AHI), "n"(BHI));
}
template <uint32_t AHI, uint32_t BHI>
__device__ __forceinline__ void wgmma_ss0(float (&d)[20], uint32_t da_lo, uint32_t db_lo) {
    asm volatile(
        "{\n.reg .b64 da, db;\nmov.b64 da, {%20, %22};\nmov.b64 db, {%21, %23};\n"
        "wgmma.mma_async.sync.aligned.m64n40k16.f32.bf16.bf16 {%0,%1,%2,%3,%4,%5,%6,%7,%8,%9,%10,%11,%12,%13,%14,%15,%16,%17,%18,%19}, da, db, 0, 1, 1, 0, 0;\n}\n"
        : "=f"(d[0]), "=f"(d[1]), "=f"(d[2]), "=f"(d[3]), "=f"(d[4]), "=f"(d[5]), "=f"(d[6]), "=f"(d[7]), "=f"(d[8]), "=f"(d[9]), "=f"(d[10]),
          "=f"(d[11]), "=f"(d[12]), "=f"(d[13]), "=f"(d[14]), "=f"(d[15]), "=f"(d[16]), "=f"(d[17]), "=f"(d[18]), "=f"(d[19])
        : "r"(da_lo), "r"(db_lo), "n"(AHI), "n"(BHI));
}
__device__ __forceinline__ void wgmma_ss_n8(float (&d)[4], uint32_t da_lo, uint32_t db_lo) {
    asm volatile(
        "{\n.reg .b64 da, db;\nmov.b64 da, {%4, %6};\nmov.b64 db, {%5, %7};\n"
        "wgmma.mma_async.sync.aligned.m64n8k16.f32.bf16.bf16 {%0,%1,%2,%3}, da, db, 1, 1, 1, 1, 0;\n}\n"
        : "+f"(d[0]), "+f"(d[1]), "+f"(d[2]), "+f"(d[3]) : "r"(da_lo), "r"(db_lo), "n"(DHI128), "n"(DHI32));
}

__device__ __forceinline__ void wgmma_ss_n32_ta(float (&d)[16], uint32_t da_lo, uint32_t db_lo) {
    asm volatile(
        "{\n.reg .b64 da, db;\nmov.b64 da, {%16, %18};\nmov.b64 db, {%17, %18};\n"
        "wgmma.mma_async.sync.aligned.m64n32k16.f32.bf16.bf16 {%0,%1,%2,%3,%4,%5,%6,%7,%8,%9,%10,%11,%12,%13,%14,%15}, da, db, 1, 1, 1, 1, 0;\n}\n"
        : ACC16(d) : "r"(da_lo), "r"(db_lo), "n"(DHI128));
}

constexpr int C2_NS = 4;
#define LAY         160, 127, 0, 16, 24, 8, 47, 87, 150, 135, 147, 32, 159, 0, 87, 119
constexpr uint32_t c2_lay(int i) { constexpr uint32_t t[16] = {LAY}; return t[i] * 1024; }
constexpr uint32_t C2_WO = c2_lay(0);
constexpr uint32_t C2_WQ = c2_lay(1), C2_WK = c2_lay(2), C2_WV = c2_lay(3);
constexpr uint32_t C2_OB = c2_lay(4);
constexpr uint32_t C2_QM = c2_lay(5);
constexpr uint32_t C2_SC = C2_QM + 1024;
constexpr uint32_t C2_PB = C2_SC + 2560;
constexpr uint32_t C2_XB = c2_lay(6), C2_XS = c2_lay(7) - c2_lay(6);
constexpr uint32_t C2_QX = c2_lay(8);
constexpr uint32_t C2_KX = C2_QX + 4096;
constexpr uint32_t C2_VT = c2_lay(9);
constexpr uint32_t C2_PX = c2_lay(10);
constexpr uint32_t C2_SX = c2_lay(11);
constexpr uint32_t C2_BAR = c2_lay(12), C2_S0 = c2_lay(13), C2_S1 = c2_lay(14), C2_S2 = c2_lay(15);
constexpr uint32_t C2_GT = C2_BAR + 256;
constexpr uint32_t C2_T0 = (C2_XB >> 10) * 0x01010101u + 0x18100800u, C2_T1 = ((C2_XB >> 10) + 32) | C2_OB >> 10 << 8 | C2_QM >> 10 << 16 | C2_WQ >> 10 << 24;
__device__ __forceinline__ uint32_t c2_ts(uint32_t r) { return __byte_perm(C2_T0, C2_T1, r) & 0xff; }
constexpr int C2_SMEM = 232448;
#define CH_SPQ 28
#define CH_SPK 0
#define CH_SPV 0
#define CH_EARLY 1
#define CH_ARM 0
#define CH_MB 1
#define CH_TW 1
#define CH_LD 0
#define CH_PFD 1000
#define CH_PT 1260
#define CH_PT1 CH_PT
#define CH_WOT 1
#define CH_NCH 4
#define CH_NQ1 12
#define CH_POLL_DELAY 600

__device__ __forceinline__ uint32_t c2_stage(int wg, int i) { return (wg == 0 ? C2_S0 : wg == 1 ? C2_S1 : C2_S2) + i * 8192; }
__device__ __forceinline__ void c2_stage_load(const CUtensorMap* map, uint32_t sb, int wg, int rank, int col0, int round) {
    const uint32_t bar = sb + C2_BAR + 176 + (wg * 2 + round) * 8;
    mbar_expect_tx(bar, 32768);
#pragma unroll 1
    for (int i = 0; i < 4; i++) {
        tma_load_2d(sb + c2_stage(wg, i), map, bar, col0, ((rank - round * 4 - i) & 7) * 64);
        if (i < 3) pace(round ? CH_PT1 : CH_PT);
    }
}
__device__ __forceinline__ void c2_load_w(uint32_t (&w)[32][4], const CUtensorMap* map, int wg, int rank, int col0, uint32_t t128, uint32_t ws, uint32_t sb) {
    const uint32_t s0 = pin(sb + c2_stage(wg, 0) + t128), s1 = pin(sb + c2_stage(wg, 0) + (t128 ^ 16) + 128);
#pragma unroll
    for (int r = 0; r < 2; r++) {
        mbar_wait(sb + C2_BAR + 176 + (wg * 2 + r) * 8, 0);
#pragma unroll
        for (int e = 0; e < 16; e++) {
            uint32_t w0, w1, w2, w3;
            asm volatile("ld.shared.b32 %0, [%1];" : "=r"(w0) : "r"(s0 + e * 2048) : "memory");
            asm volatile("ld.shared.b32 %0, [%1];" : "=r"(w1) : "r"(s1 + e * 2048) : "memory");
            asm volatile("ld.shared.b32 %0, [%1];" : "=r"(w2) : "r"(s0 + e * 2048 + 1024) : "memory");
            asm volatile("ld.shared.b32 %0, [%1];" : "=r"(w3) : "r"(s1 + e * 2048 + 1024) : "memory");
            uint32_t* d = w[r * 16 + e];
            d[0] = __byte_perm(w0, w1, 0x5410); d[1] = __byte_perm(w0, w1, 0x7632);
            d[2] = __byte_perm(w2, w3, 0x5410); d[3] = __byte_perm(w2, w3, 0x7632);
        }
        if (r == 0) {
            asm volatile("bar.sync %0, 128;" :: "r"(8 + wg) : "memory");
            if ((threadIdx.x & 127) == 32) c2_stage_load(map, sb, wg, rank, col0, 1);
            mbar_wait(sb + C2_BAR + 168, 0);
#pragma unroll 1
            for (int i = threadIdx.x; i < 2048; i += 384) {
                const int k = i >> 2, b = i & 3;
                const uint32_t a0 = sb + C2_WO + k * 128 + (((2 * b) ^ (k & 7)) << 4), a1 = a0 ^ 16;
                uint4 u, v;
                asm volatile("ld.shared.v4.b32 {%0, %1, %2, %3}, [%4];" : "=r"(u.x), "=r"(u.y), "=r"(u.z), "=r"(u.w) : "r"(a0) : "memory");
                asm volatile("ld.shared.v4.b32 {%0, %1, %2, %3}, [%4];" : "=r"(v.x), "=r"(v.y), "=r"(v.z), "=r"(v.w) : "r"(a1) : "memory");
                asm volatile("st.shared.v4.b32 [%0], {%1, %2, %3, %4};" :: "r"(a0), "r"(__byte_perm(u.x, u.y, 0x5410)),
                             "r"(__byte_perm(u.z, u.w, 0x5410)), "r"(__byte_perm(v.x, v.y, 0x5410)), "r"(__byte_perm(v.z, v.w, 0x5410)) : "memory");
                asm volatile("st.shared.v4.b32 [%0], {%1, %2, %3, %4};" :: "r"(a1), "r"(__byte_perm(u.x, u.y, 0x7632)),
                             "r"(__byte_perm(u.z, u.w, 0x7632)), "r"(__byte_perm(v.x, v.y, 0x7632)), "r"(__byte_perm(v.z, v.w, 0x7632)) : "memory");
            }
        }
    }
    cluster_sync_relaxed();
#pragma unroll
    for (int e = 0; e < C2_NS; e++) stmatrix_x4(ws + e * 2048, w[e][0], w[e][1], w[e][2], w[e][3]);
#pragma unroll 1
    for (int i = threadIdx.x; i < 2 * 512 + 256; i += 384)
        sts32(sb + (i < 1024 ? C2_VT + (i >> 9) * 6144 + 4096 + (i & 511) * 4 : C2_PX + 2048 + (i - 1024) * 4), 0u);
    fence_async_smem();
    asm volatile("bar.sync %0, 128;" :: "r"(8 + wg) : "memory");
}
template <int E0, int E1, int SP, int NA>
__device__ __forceinline__ void c2_xstream(float (&acc)[NA], const uint32_t (&w)[32][4], uint32_t xlo, uint32_t rank, uint32_t wslo) {
    if (E0 == 0)
#pragma unroll
        for (int i = 0; i < NA; i++) acc[i] = 0.f;
    wgmma_fence();
#pragma unroll
    for (int n = E0; n < E1; n++) {
        const int e = n < SP ? n + C2_NS : n < SP + C2_NS ? n - SP : n;
        if (e < C2_NS) wgmma_ss<DHI32, DHI128>(acc, wslo + e * 128, xlo + ((rank - (e >> 2)) & 7) * 320 + (e & 3) * 2);
        else wgmma_rs(acc, w[e], xlo + ((rank - (e >> 2)) & 7) * 320 + (e & 3) * 2);
    }
    wgmma_commit();
}
__device__ __forceinline__ constexpr int c2_grp(int i) { return i < 2 ? i : 1 + (i >> 1); }

struct ChainParams {
    CUtensorMap mapX;
    CUtensorMap mapM;
    CUtensorMap mapW[3];
    CUtensorMap mapWo;
    CUtensorMap mapC;
    bf16* out;
};
__global__ void __cluster_dims__(8, 1, 1) __launch_bounds__(384, 1)
chain_kernel(const __grid_constant__ ChainParams P) {
    const CUtensorMap& mapX = P.mapX;
    extern __shared__ __align__(1024) uint8_t smem_chain[];
    const uint32_t sb = smem_u32(smem_chain);
    const uint32_t dlo = ((sb & 0x3FFFF) >> 4) | (1u << 16);
    const int tid = __shfl_sync(0xffffffff, threadIdx.x, threadIdx.x & 31), lane = tid & 31;
    const int warp = __shfl_sync(0xffffffff, tid >> 5, 0), wg = warp >> 2, w4 = warp & 3;
    const uint32_t rank = cluster_ctarank();
    const int C = blockIdx.x >> 3;
    const int h = C * 4 + (rank >> 1);
    const int g = lane >> 2, qc = lane & 3;
    pdl_launch_dependents();
    TS_BEGIN(2);
    CYC(0);
    const uint32_t bar_m = sb + C2_BAR, bar_o = bar_m + 64, bar_sc = bar_m + 128, bar_x = bar_m + 136, bar_sx = bar_m + 152;
    const uint32_t bar_w = bar_m + 168, bar_h = bar_m + 40;
    const int col0 = h * HD + (rank & 1) * 64;
    if (tid == 0) {
        for (int j = 0; j < 5; j++) { mbar_init(bar_m + 8 * j, j ? 1 : 4); mbar_init(bar_o + 8 * j, j ? 1 : 4); }
        for (int j = 0; j < 12; j++) mbar_init(bar_sc + 8 * j, 1);
        mbar_init(bar_h, 32);
        asm volatile("fence.mbarrier_init.release.cluster;" ::: "memory");
    }
    __syncwarp();
    cluster_sync_relaxed();
    if (tid == 0) {
        mbar_expect_tx(bar_x, 32768 + 8192);
        tma_load_2d_mc(sb + C2_XB + rank * 5120, &mapX, bar_x, rank * 64, 0, (uint16_t)0xff);
#pragma unroll 1
        for (int j = 0; j < 8; j++) tma_load_2d(sb + C2_XB + j * 5120 + 4096, &P.mapM, bar_x, j * 64, 0);
        mbar_expect_tx(bar_w, 65536);
    }
    if ((tid & 127) == 32) {
        pace(CH_PFD);
        c2_stage_load(&P.mapW[wg], sb, wg, rank, col0, 0);
#pragma unroll 1
        for (int j = wg; j < 8; j += 3) {
            pace(CH_PT1);
            tma_load_2d(sb + C2_WO + j * 8192, &P.mapWo, bar_w, rank * 64, C * 512 + ((rank - j) & 7) * 64);
        }
    }
    __syncwarp();

    const uint32_t t32 = w4 * 256 + qc * 64 + (((g >> 2) ^ (qc >> 1)) << 4) + (g & 3) * 4;
    const uint32_t t128 = qc * 256 + (((2 * w4 + (g >> 2)) ^ (2 * qc)) << 4) + (g & 3) * 4;
    const uint32_t a32 = (w4 * 16 + (lane & 15)) * 32 + (((lane >> 4) ^ ((lane >> 2) & 1)) << 4);
    const uint32_t ws = sb + (wg == 0 ? C2_WQ : wg == 1 ? C2_WK : C2_WV) + a32;
    uint32_t w[32][4];
    static_assert(C2_NS == 4, "slot 0");
    auto proj_mem = [&](float (&a)[CH_NCH][4], int s, uint32_t l128) {
        uint32_t b[4][8];
#pragma unroll
        for (int i = 0; i < 4 * CH_NCH; i++) a[i >> 2][i & 3] = 0.f;
        const uint32_t par = (s & 1) ^ 1;
        const uint32_t mb = sb + C2_XB + (s & 1) * C2_XS + 4096;
        auto L = [&](int i) {
            ldsm_x4(b[i & 3], mb + ((rank - i) & 7) * 5120 + l128);
            ldsm_x4(b[i & 3] + 4, mb + ((rank - i) & 7) * 5120 + (l128 ^ 64));
        };
        auto H = [&](int i) {
#pragma unroll
            for (int kk = 0; kk < 4; kk++) {
                const uint32_t* f = i ? w[i * 4 + kk] : &b[2 + (kk >> 1)][(kk & 1) * 4];
                mma_16816(a[(i * 4 + kk) % CH_NCH], f[0], f[1], f[2], f[3], b[i & 3][2 * kk], b[i & 3][2 * kk + 1]);
            }
        };
#pragma unroll
        for (int e = 0; e < 4; e++) ldsm_x4(&b[2 + (e >> 1)][(e & 1) * 4], ws + e * 2048);
        mbar_wait(bar_m, par);
        L(0);
        H(0);
        mbar_wait(bar_m + 8, par);
        DBGW(1 + 16 * wg, 0);
        L(1);
        mbar_wait(bar_m + 16, par);
        uint32_t nxt = mbar_test(bar_m + 24, par);
        L(2); L(3);
        H(1);
        if (__builtin_expect(!nxt, 0)) mbar_wait(bar_m + 24, par);
        nxt = mbar_test(bar_m + 32, par);
        L(4); L(5);
        H(2); H(3);
        if (__builtin_expect(!nxt, 0)) mbar_wait(bar_m + 32, par);
        DBGW(2 + 16 * wg, 0);
        L(6); L(7);
        H(4); H(5); H(6); H(7);
#pragma unroll
        for (int i = 0; i < 4; i++) a[0][i] = CH_NCH == 4 ? (a[0][i] + a[1][i]) + (a[2][i] + a[3 % CH_NCH][i]) : CH_NCH == 3 ? a[0][i] + a[1][i] + a[2 % CH_NCH][i] : a[0][i] + a[1][i];
    };
    auto store_x = [&](const float (&acc)[16], uint32_t base) {
#pragma unroll
        for (int j = 0; j < 4; j++) {
            sts32(base + t128 + j * 1024, pack_bf16(acc[4 * j], acc[4 * j + 2]));
            sts32(base + (t128 ^ 16) + 128 + j * 1024, pack_bf16(acc[4 * j + 1], acc[4 * j + 3]));
        }
    };
    auto fresh_lane = [&]() { uint32_t l; asm volatile("mov.u32 %0, %%laneid;" : "=r"(l)); return l; };
    const float scale = 0.08838834764831845f, l2e = 1.4426950408889634f;
    c2_load_w(w, &P.mapW[wg], wg, rank, col0, t128, ws, sb);
    TS_END(6);
    TS_BEGIN(5);
    CYC(1);

    if (wg == 0) {
#pragma unroll 1
        for (int s = -1;;) {
            float qx[16];
            uint32_t* dst = reinterpret_cast<uint32_t*>(g_xbuf + (((s & 1) * 8 + rank) * 8 + C) * 128) + qc * 64 + w4 * 8 + g;
            asm volatile("" : "+l"(dst));
            mbar_wait(bar_x + 8 * ((s + 1) & 1), ((s + 1) >> 1) & 1);
            if (s >= 0) bar_sync<6, 384>();
            c2_xstream<0, CH_NQ1, CH_SPQ>(qx, w, dlo + ((C2_XB + ((s + 1) & 1) * C2_XS) >> 4), rank, dlo + (C2_WQ >> 4));
            if (s >= 0) {
                float acc[4] = {0.f, 0.f, 0.f, 0.f};
                const uint32_t tag = ((s >> 1) & 1) ^ 1;
                uint32_t nxt = 0;
#pragma unroll
                for (int i = 0; i < 8; i++) {
                    if (i < 2 || !(i & 1)) {
                        if (i < 2 || __builtin_expect(!nxt, 0)) mbar_wait(bar_o + 8 * c2_grp(i), s & 1);
                        if (i == 0) DBGW(7, 0);
                        if (i == 1) DBGW(8, 0);
                        if (i == 6) DBGW(9, 0);
                        wgmma_fence();
                    }
#pragma unroll
                    for (int kk = 0; kk < 4; kk++) {
                        if ((i & 1) && i < 7 && kk == CH_WOT) nxt = mbar_test(bar_o + 8 * c2_grp(i + 1), s & 1);
                        wgmma_ss_n8(acc, dlo + ((C2_WO + i * 8192 + kk * 2048) >> 4), dlo + ((C2_OB + i * 1024 + kk * 256) >> 4));
                    }
                }
                wgmma_commit();
                bar_arrive<11, 256>();
                wgmma_wait<0>();
                asm volatile("st.relaxed.gpu.global.u32 [%0], %1;" :: "l"(dst), "r"((pack_bf16(acc[0], acc[2]) & ~1u) | tag) : "memory");
                asm volatile("st.relaxed.gpu.global.u32 [%0 + 128], %1;" :: "l"(dst), "r"((pack_bf16(acc[1], acc[3]) & ~1u) | tag) : "memory");
                bar_arrive<4, 256>();
                DBGW(10, 0);
            }
            s++;
            c2_xstream<CH_NQ1, 32, CH_SPQ>(qx, w, dlo + ((C2_XB + (s & 1) * C2_XS) >> 4), rank, dlo + (C2_WQ >> 4));
            const uint32_t sca = pin(w4 < 2 ? sb + C2_SC + w4 * 512 + lane * 16 : sb + C2_SC + 1024 + lane * 8);
            const uint32_t krow = w4 * 16 + (lane & 15);
            const uint32_t ka0 = pin(sb + C2_KX + krow * 128 + (((lane >> 4) ^ (krow & 7)) << 4));
            const uint32_t l32 = pin(sb + C2_QM + (lane >> 4) * 256 + (lane & 7) * 32 + ((((lane >> 3) & 1) ^ ((lane >> 2) & 1)) << 4));
            const uint32_t qst = pin(sb + C2_QM + t32);
            const uint32_t l128 = pin((lane & 7) * 128 + (((lane >> 3) ^ (lane & 7)) << 4));
            if (s > 0) bar_sync<5, 256>();
            wgmma_wait<0>();
            store_x(qx, sb + C2_QX);
            DBGW(0, 0);
            if (s == NSEG - 1) break;
            {
                float a[CH_NCH][4];
                proj_mem(a, s, l128);
                sts32(qst, pack_bf16(a[0][0], a[0][2]));
                sts32(qst + 32, pack_bf16(a[0][1], a[0][3]));
            }
            DBGW(3, 0);
            if (w4 < 3) {
                uint32_t ka[4][4], qb[8];
                float c[4] = {0.f, 0.f, 0.f, 0.f}, c2[4] = {0.f, 0.f, 0.f, 0.f};
                const uint32_t sc_peer = pin(mapa_u32(sca + 1280, rank ^ 1)), sc_own = pin(mapa_u32(sca, rank));
                bar_sync<1, 384>();
                ldsm_x4(qb, l32);
                ldsm_x4(ka[0], ka0);
                ldsm_x4(ka[1], ka0 ^ 32);
                ldsm_x4(qb + 4, l32 + 512);
                ldsm_x4(ka[2], ka0 ^ 64);
                ldsm_x4(ka[3], ka0 ^ 96);
                mma_16816(c, ka[0][0], ka[0][1], ka[0][2], ka[0][3], qb[0], qb[1]);
                mma_16816(c2, ka[1][0], ka[1][1], ka[1][2], ka[1][3], qb[2], qb[3]);
                mma_16816(c, ka[2][0], ka[2][1], ka[2][2], ka[2][3], qb[4], qb[5]);
                mma_16816(c2, ka[3][0], ka[3][1], ka[3][2], ka[3][3], qb[6], qb[7]);
                const uint32_t u0 = __float_as_uint(c[0] + c2[0]), u1 = __float_as_uint(c[1] + c2[1]);
                const uint32_t u2 = __float_as_uint(c[2] + c2[2]), u3 = __float_as_uint(c[3] + c2[3]);
                asm volatile(
                    "{\n.reg .pred p;\nsetp.lt.u32 p, %8, 2;\n"
                    "@p st.async.weak.shared::cluster.mbarrier::complete_tx::bytes.v4.b32 [%0], {%4, %5, %6, %7}, [%1];\n"
                    "@!p st.async.weak.shared::cluster.mbarrier::complete_tx::bytes.v2.b32 [%0], {%4, %5}, [%1];\n"
                    "@p st.async.weak.shared::cluster.mbarrier::complete_tx::bytes.v4.b32 [%2], {%4, %5, %6, %7}, [%3];\n"
                    "@!p st.async.weak.shared::cluster.mbarrier::complete_tx::bytes.v2.b32 [%2], {%4, %5}, [%3];\n}"
                    :: "r"(sc_peer), "r"(mapa_u32(bar_sc, rank ^ 1)), "r"(sc_own), "r"(mapa_u32(bar_sc, rank)), "r"(u0), "r"(u1), "r"(u2), "r"(u3), "r"(w4) : "memory");
                bar_arrive<2, 224>();
                fence_async_smem();
                if (s >= 4 * CB_FIRST + 5 && (s & 3) == 1 && tid == 0) signal_ctr(CT_CB + ((s - 5) >> 2));
                __syncwarp();
                DBGW(4, 2);
            } else {
                bar_arrive<1, 384>();
                fence_async_smem();
                const uint32_t a = pin(sb + C2_SC + lane * 16), a2 = pin(sb + C2_SC + 1024 + lane * 8), pa = pin(sb + C2_PB + lane * 4);
                mbar_wait(bar_sc, s & 1);
                DBG(5);
                float v[10];
                {
                    float4 x0, x1, y0, y1; float2 x2, y2;
                    asm volatile("ld.shared.v4.f32 {%0, %1, %2, %3}, [%4];" : "=f"(x0.x), "=f"(x0.y), "=f"(x0.z), "=f"(x0.w) : "r"(a) : "memory");
                    asm volatile("ld.shared.v4.f32 {%0, %1, %2, %3}, [%4];" : "=f"(y0.x), "=f"(y0.y), "=f"(y0.z), "=f"(y0.w) : "r"(a + 1280) : "memory");
                    asm volatile("ld.shared.v4.f32 {%0, %1, %2, %3}, [%4];" : "=f"(x1.x), "=f"(x1.y), "=f"(x1.z), "=f"(x1.w) : "r"(a + 512) : "memory");
                    asm volatile("ld.shared.v4.f32 {%0, %1, %2, %3}, [%4];" : "=f"(y1.x), "=f"(y1.y), "=f"(y1.z), "=f"(y1.w) : "r"(a + 1792) : "memory");
                    asm volatile("ld.shared.v2.f32 {%0, %1}, [%2];" : "=f"(x2.x), "=f"(x2.y) : "r"(a2) : "memory");
                    asm volatile("ld.shared.v2.f32 {%0, %1}, [%2];" : "=f"(y2.x), "=f"(y2.y) : "r"(a2 + 1280) : "memory");
                    v[0] = x0.x + y0.x; v[1] = x0.y + y0.y; v[2] = x0.z + y0.z; v[3] = x0.w + y0.w;
                    v[4] = x1.x + y1.x; v[5] = x1.y + y1.y; v[6] = x1.z + y1.z; v[7] = x1.w + y1.w;
                    v[8] = x2.x + y2.x; v[9] = x2.y + y2.y;
                }
                float m0 = fmaxf(fmaxf(fmaxf(v[0], v[2]), fmaxf(v[4], v[6])), v[8]);
                float m1 = fmaxf(fmaxf(fmaxf(v[1], v[3]), fmaxf(v[5], v[7])), v[9]);
#pragma unroll
                for (int o = 4; o < 32; o <<= 1) {
                    m0 = fmaxf(m0, __shfl_xor_sync(0xffffffff, m0, o));
                    m1 = fmaxf(m1, __shfl_xor_sync(0xffffffff, m1, o));
                }
                const float sl = scale * l2e;
                m0 *= sl; m1 *= sl;
#pragma unroll
                for (int j = 0; j < 5; j++)
                    sts32(pa + j * 128, pack_bf16(ex2f(fmaf(v[2 * j], sl, -m0)), ex2f(fmaf(v[2 * j + 1], sl, -m1))));
                bar_arrive<3, 160>();
                DBG(6);
            }
        }
        bar_arrive<1, 384>();
        fence_async_smem();
        bar_arrive<6, 384>();
        TS_MARK(8, 0);
        CYC(2);
        TM(0);
        const uint32_t lane = fresh_lane();
        pace(CH_LD);
        {
            const uint32_t a = sb + C2_WO + ((lane >> 4) * 8 + (lane & 7)) * 128 + (((2 * w4 + ((lane >> 3) & 1)) ^ (lane & 7)) << 4);
#pragma unroll
            for (int e = C2_NS; e < 32; e++)
                asm volatile("ldmatrix.sync.aligned.m8n8.x4.trans.shared.b16 {%0,%1,%2,%3}, [%4];" : "=r"(w[e][0]), "=r"(w[e][1]), "=r"(w[e][2]), "=r"(w[e][3]) : "r"(a + e * 2048) : "memory");
        }
        fence_async_smem();
        if (lane < 8) asm volatile("mbarrier.arrive.relaxed.cluster.shared::cluster.b64 _, [%0];" :: "r"(mapa_u32(bar_h, lane)) : "memory");
        __syncwarp();
        TM(9);
        if (w4 == 0) {
            bar_sync<12, 160>();
            if (CH_MB) asm volatile("fence.acq_rel.gpu;" ::: "memory");
            asm volatile("fence.proxy.async.global;" ::: "memory");
            mbar_wait(bar_h, 0);
            if (elect_one()) tma_load_2d_mc(sb + c2_ts(rank) * 1024, &P.mapC, bar_x, (rank & 1) * 64, h * SEQ + SEQ - 128, (uint16_t)0xff);
            __syncwarp();
            TM(10);
        }
        if (w4 == 1) {
            wait_ctr(CT_P, 104u);
            float4 v;
            asm volatile("ld.relaxed.gpu.global.v4.f32 {%0, %1, %2, %3}, [%4];" : "=f"(v.x), "=f"(v.y), "=f"(v.z), "=f"(v.w) : "l"(g_gate + SEQ - 128 + lane * 4) : "memory");
            asm volatile("st.shared.v4.f32 [%0], {%1, %2, %3, %4};" :: "r"(sb + C2_GT + lane * 16), "f"(1.f - v.x), "f"(1.f - v.y), "f"(1.f - v.z), "f"(1.f - v.w) : "memory");
            __syncwarp();
            if (lane == 0) mbar_expect_tx(bar_x, 65536);
            finish_launch(lane);
        }
        uint32_t* dst = reinterpret_cast<uint32_t*>(P.out + (SEQ - 128 + 2 * (lane & 3)) * DM + rank * 64 + w4 * 16) + (lane >> 2);
#pragma unroll 1
        for (uint32_t q = 0; q < 4; q++, dst += 16 * DM) {
            float acc[16], gt[8];
#pragma unroll
            for (int i = 0; i < 16; i++) acc[i] = 0.f;
            const uint32_t bar = q < 2 ? bar_x : bar_m - 128 + q * 64, db = dlo + (q & 1) * 256;
#pragma unroll
            for (int i = 0; i < 8; i++) {
                if (i == 0 || (CH_TW && (i == 1 || !(i & 1)))) {
                    if (i == 0 || q > 1) mbar_wait(bar + 8 * c2_grp(i), q >> 1);
                    if (!CH_TW && q > 1)
#pragma unroll 1
                        for (uint32_t j = 8; j < 40; j += 8) mbar_wait(bar + j, 1);
                    if (i == 0) TM(13 + q);
                    wgmma_fence();
                }
                if (i == 6) TM(25 + q);
                const uint32_t d = db + (q < 2 ? c2_ts((rank - i) & 7) * 64 : (i ? C2_WO + i * 8192 : C2_QX) >> 4);
#pragma unroll
                for (int kk = 0; kk < 4; kk++) {
                    if (i == 0) wgmma_ss_n32_ta(acc, dlo + ((C2_WO + kk * 2048) >> 4), d + kk * 2);
                    else wgmma_rs(acc, w[i * 4 + kk], d + kk * 2);
                }
            }
            wgmma_commit();
            if (q == 3) asm volatile("barrier.cluster.arrive.relaxed.aligned;" ::: "memory");
#pragma unroll
            for (int j = 0; j < 4; j++)
                asm volatile("ld.shared.v2.f32 {%0, %1}, [%2];" : "=f"(gt[2 * j]), "=f"(gt[2 * j + 1]) : "r"(sb + C2_GT + q * 128 + (lane & 3) * 8 + j * 32) : "memory");
            wgmma_wait<0>();
#pragma unroll
            for (int j = 0; j < 8; j++)
                asm volatile("red.relaxed.gpu.global.add.noftz.bf16x2 [%0], %1;" :: "l"(dst + ((j >> 1) * 8 + (j & 1)) * (DM / 2)),
                             "r"(pack_bf16(acc[(j >> 1) * 4 + (j & 1)] * gt[j], acc[(j >> 1) * 4 + (j & 1) + 2] * gt[j])) : "memory");
            TS_MARK(9 + q, 0);
            TM(17 + q);
        }
    } else if (wg == 1) {
        bool early = false;
#pragma unroll 1
        for (int s = -1;;) {
            if (s > 0 && (!CH_EARLY || s != NSEG - 1 || early)) {
                mbar_wait(bar_sx + 8 * ((s - 1) & 1), ((s - 1) >> 1) & 1);
                const uint32_t a = sb + C2_SX + w4 * 1280 + lane * 8, ap = a + 10240 - (s & 1) * 5120;
                float v[10];
                const int lim = 8 * w4 + g - 2 * qc;
#pragma unroll
                for (int j = 0; j < 5; j++) {
                    float2 x, y;
                    asm volatile("ld.shared.v2.f32 {%0, %1}, [%2];" : "=f"(x.x), "=f"(x.y) : "r"(a + j * 256) : "memory");
                    asm volatile("ld.shared.v2.f32 {%0, %1}, [%2];" : "=f"(y.x), "=f"(y.y) : "r"(ap + j * 256) : "memory");
                    v[2 * j] = (j < 4 && 8 * j > lim) ? -INFINITY : x.x + y.x;
                    v[2 * j + 1] = (j < 4 && 8 * j + 1 > lim) ? -INFINITY : x.y + y.y;
                }
                float mx = fmaxf(fmaxf(fmaxf(v[0], v[1]), fmaxf(v[2], v[3])), fmaxf(fmaxf(v[4], v[5]), fmaxf(v[6], v[7])));
                mx = fmaxf(mx, fmaxf(v[8], v[9]));
                mx = fmaxf(mx, __shfl_xor_sync(0xffffffff, mx, 1));
                mx = fmaxf(mx, __shfl_xor_sync(0xffffffff, mx, 2));
                const float sl = scale * l2e;
                mx *= sl;
#pragma unroll
                for (int j = 0; j < 10; j++) v[j] = ex2f(fmaf(v[j], sl, -mx));
                float sm = ((v[0] + v[1]) + (v[2] + v[3])) + ((v[4] + v[5]) + (v[6] + v[7])) + (v[8] + v[9]);
                sm += __shfl_xor_sync(0xffffffff, sm, 1);
                sm += __shfl_xor_sync(0xffffffff, sm, 2);
                float inv;
                asm("rcp.approx.ftz.f32 %0, %1;" : "=f"(inv) : "f"(sm));
                const uint32_t pa = sb + C2_PX + w4 * 256 + g * 32 + ((g >> 2) << 4) + qc * 4;
#pragma unroll
                for (int j = 0; j < 5; j++) sts32((pa ^ ((j & 1) << 4)) + (j >> 1) * 1024, pack_bf16(v[2 * j] * inv, v[2 * j + 1] * inv));
            }
            if (!early) {
            if (s >= 0) {
                fence_async_smem();
                if (s < NSEG) bar_sync<6, 384>(); else bar_sync<7, 256>();
                DBGW(20, 0);
                TM(s < NSEG ? 2 : 11);
                uint32_t cp[8];
                {
                    float cx[16];
#pragma unroll
                    for (int i = 0; i < 16; i++) cx[i] = 0.f;
                    wgmma_fence();
#pragma unroll
                    for (int kk = 0; kk < 3; kk++)
                        wgmma_ss<DHI32, DHI32>(cx, dlo + ((C2_VT + ((s - 1) & 1) * 6144 + kk * 2048) >> 4), dlo + ((C2_PX + kk * 1024) >> 4));
                    wgmma_commit();
                    wgmma_wait<0>();
#pragma unroll
                    for (int j = 0; j < 4; j++) { cp[2 * j] = pack_bf16(cx[4 * j], cx[4 * j + 2]); cp[2 * j + 1] = pack_bf16(cx[4 * j + 1], cx[4 * j + 3]); }
                    asm volatile("{\n.reg .pred p;\nsetp.gt.u32 p, %0, 99;\n@p st.shared.v4.b32 [%0], {%1, %2, %3, %4};\n@p st.shared.v4.b32 [%0], {%5, %6, %7, %8};\n}"
                                 :: "r"(rank), "r"(cp[0]), "r"(cp[1]), "r"(cp[2]), "r"(cp[3]), "r"(cp[4]), "r"(cp[5]), "r"(cp[6]), "r"(cp[7]) : "memory");
                }
                if (s < NSEG) {
                    float sx[20];
                    wgmma_fence();
                    wgmma_ss0<DHI128, DHI128>(sx, dlo + (C2_QX >> 4), dlo + (C2_KX >> 4));
#pragma unroll
                    for (int kk = 1; kk < 4; kk++) wgmma_ss<DHI128, DHI128>(sx, dlo + (C2_QX >> 4) + kk * 2, dlo + (C2_KX >> 4) + kk * 2);
                    wgmma_commit();
                    wgmma_wait<0>();
                    if (s < NSEG - 1) bar_arrive<5, 256>();
                    if (s > 0 && s < NSEG - 1) {
                        uint32_t* dst = reinterpret_cast<uint32_t*>(g_ctxB + ((size_t)h * SEQ + (s - 1) * SEGL + 2 * qc) * HD + (rank & 1) * 64 + w4 * 16 + 2 * g);
#pragma unroll
                        for (int j = 0; j < 4; j++) {
                            asm volatile("st.global.u32 [%0], %1;" :: "l"(dst + j * 8 * (HD / 2)), "r"(cp[2 * j]) : "memory");
                            asm volatile("st.global.u32 [%0], %1;" :: "l"(dst + (j * 8 + 1) * (HD / 2)), "r"(cp[2 * j + 1]) : "memory");
                        }
                    }
                    DBGW(22, 0);
                    TM(3);
                    if (s == NSEG - 2) bar_arrive<12, 160>();
                    const uint32_t a = sb + C2_SX + w4 * 2560 + lane * 8;
                    if (w4 < 2) {
#pragma unroll
                        for (int j = 0; j < 5; j++) {
                            asm volatile("st.shared.v2.f32 [%0], {%1, %2};" :: "r"(a + j * 256), "f"(sx[4 * j]), "f"(sx[4 * j + 1]) : "memory");
                            asm volatile("st.shared.v2.f32 [%0], {%1, %2};" :: "r"(a + 1280 + j * 256), "f"(sx[4 * j + 2]), "f"(sx[4 * j + 3]) : "memory");
                        }
                    }
                    if (s < NSEG - 1) mbar_wait(bar_x + 8 * ((s + 1) & 1), ((s + 1) >> 1) & 1);
                    const uint32_t pa = mapa_u32(a + 5120 + (s & 1) * 5120, rank ^ 1), pb = mapa_u32(bar_sx + 8 * (s & 1), rank ^ 1);
                    if (s < NSEG - 1) bar_sync<4, 256>(); else bar_sync<9, 128>();
                    if (w4 < 2) {
#pragma unroll
                        for (int j = 0; j < 5; j++) {
                            st_async_v2(pa + j * 256, __float_as_uint(sx[4 * j]), __float_as_uint(sx[4 * j + 1]), pb);
                            st_async_v2(pa + 1280 + j * 256, __float_as_uint(sx[4 * j + 2]), __float_as_uint(sx[4 * j + 3]), pb);
                        }
                    }
                }
                if (s >= NSEG - 1) {
                    const uint32_t a = sb + C2_QX + 4096 - (s & 1) * 4096;
#pragma unroll
                    for (int j = 0; j < 4; j++) {
                        sts32(a + t128 + j * 1024, cp[2 * j]);
                        sts32(a + (t128 ^ 16) + 128 + j * 1024, cp[2 * j + 1]);
                    }
                    fence_async_smem();
                    asm volatile("bar.arrive %0, 160;" :: "r"(s - NSEG + 14) : "memory");
                    TM(s - NSEG + 6);
                    if (s == NSEG) break;
                }
            } else mbar_wait(bar_x, 0);
            s++;
            if (s < NSEG) {
                float acc[16];
                c2_xstream<0, 32, CH_SPK>(acc, w, dlo + ((C2_XB + (s & 1) * C2_XS) >> 4), rank, dlo + (C2_WK >> 4));
                wgmma_wait<0>();
                store_x(acc, sb + C2_KX);
                DBGW(16, 0);
            }
            if (CH_EARLY && s == NSEG - 1) { early = true; continue; }
            }
            early = false;
            if (s < NSEG) TM(4);
            if (s < NSEG) {
                const uint32_t kst = pin(sb + C2_KX + 4096 + t128);
                const uint32_t l128 = pin((lane & 7) * 128 + (((lane >> 3) ^ (lane & 7)) << 4));
                float a[CH_NCH][4];
                proj_mem(a, s, l128);
                sts32(kst, pack_bf16(a[0][0], a[0][2]));
                sts32((kst ^ 16) + 128, pack_bf16(a[0][1], a[0][3]));
                bar_arrive<1, 384>();
                TM(1);
                DBGW(19, 0);
                if (w4 == 0) {
                    if (CH_ARM && lane == 0) mbar_expect_tx(bar_sc, 2560);
                    if (lane < 16 && (lane & 7) >= 1 && (lane & 7) < 5) mbar_expect_tx(bar_m + 8 * lane, ((lane & 7) == 1 ? 1024 : 2048) << (s < NSEG - 1 ? 0 : 2));
                    if (s < NSEG - 1) {
                        if (!CH_ARM && lane == 0) mbar_expect_tx(bar_sc, 2560);
                        if (lane == 8) {
                            mbar_expect_tx(bar_x + 8 * ((s + 1) & 1), 32768);
                            tma_load_2d_mc(sb + C2_XB + ((s + 1) & 1) * C2_XS + rank * 5120, &mapX, bar_x + 8 * ((s + 1) & 1), rank * 64, (s + 1) * SEGL, (uint16_t)0xff);
                            if (s + 2 < NSEG)
                                asm volatile("cp.async.bulk.prefetch.tensor.2d.L2.global [%0, {%1, %2}];" :: "l"((uint64_t)&mapX), "r"(rank * 64), "r"((s + 2) * SEGL) : "memory");
                        }
                    }
                    if (lane == 16) mbar_expect_tx(bar_sx + 8 * (s & 1), 5120);
                    __syncwarp();
                }
            }
        }
        TS_MARK(12, 128);
        asm volatile("barrier.cluster.arrive.relaxed.aligned;" ::: "memory");
    } else {
        uint32_t va[5][2] = {};
        auto store_vt = [&](int s) {
            const uint32_t a = sb + C2_VT + (s & 1) * 6144 + a32;
            stmatrix_x4(a, va[0][0], va[0][1], va[1][0], va[1][1]);
            stmatrix_x4(a + 2048, va[2][0], va[2][1], va[3][0], va[3][1]);
            asm volatile("stmatrix.sync.aligned.m8n8.x2.shared.b16 [%0], {%1, %2};" :: "r"(a + 4096), "r"(va[4][0]), "r"(va[4][1]) : "memory");
        };
#pragma unroll 1
        for (int s = -1;;) {
            if (s >= 0) {
                const int t = tid - 256;
                const uint2* src = g_xbuf + ((s & 1) * 8 + rank) * 1024 + t;
                asm volatile("" : "+l"(src));
                const uint32_t ma = sb + C2_XB + ((s + 1) & 1) * C2_XS + rank * 5120 + 4096 + (t >> 4) * 128 + ((((t >> 1) & 7) ^ (t >> 4)) << 4) + (t & 1) * 8;
                uint32_t ra[8], rb[8];
#pragma unroll
                for (int i = 1; i < 8; i++) {
                    const uint32_t d = (rank + i) & 7;
                    ra[i] = pin(mapa_u32(ma, d)); rb[i] = pin(mapa_u32(bar_m + 8 * c2_grp(i), d));
                }
                if (s == NSEG - 1) break;
                bar_sync<11, 256>();
                DBGW(29, 0);
                pace(CH_POLL_DELAY);
                const uint32_t tag = ((s >> 1) & 1) ^ 1;
                uint32_t p[8][2], m0, m1;
                auto issue = [&](uint32_t (&x)[8][2]) {
#pragma unroll
                    for (int k = 0; k < 8; k++)
                        asm volatile("ld.relaxed.gpu.global.v2.u32 {%0, %1}, [%2];" : "=r"(x[k][0]), "=r"(x[k][1]) : "l"(src + k * 128) : "memory");
                };
                auto check = [&](const uint32_t (&x)[8][2]) {
                    uint32_t bad = 0, bad2 = 0;
                    float r[4];
#pragma unroll
                    for (int k = 0; k < 8; k++) {
                        asm("lop3.b32 %0, %0, %1, %2, 0xf6;" : "+r"(bad) : "r"(x[k][0]), "r"(tag));
                        asm("lop3.b32 %0, %0, %1, %2, 0xf6;" : "+r"(bad2) : "r"(x[k][1]), "r"(tag));
#pragma unroll
                        for (int e = 0; e < 2; e++) {
                            const float lo = __uint_as_float(x[k][e] << 16), hi = __uint_as_float(x[k][e] & 0xffff0000u);
                            r[2 * e] = k ? r[2 * e] + lo : lo;
                            r[2 * e + 1] = k ? r[2 * e + 1] + hi : hi;
                        }
                    }
                    m0 = pack_bf16(r[0], r[1]); m1 = pack_bf16(r[2], r[3]);
                    asm volatile("" : "+r"(m0), "+r"(m1));
                    return __all_sync(0xffffffff, ((bad | bad2) & 1u) == 0u);
                };
                for (int it = 0; it < (1 << 20); it++) {
                    issue(p);
                    if (check(p)) break;
                }
                DBGW(30, 0);
                st_async_v2(ra[1], m0, m1, rb[1]);
                asm volatile("st.shared.v2.b32 [%0], {%1, %2};" :: "r"(ma), "r"(m0), "r"(m1) : "memory");
                __syncwarp();
                if (lane == 0) mbar_arrive(bar_m);
#pragma unroll
                for (int i = 2; i < 8; i++) st_async_v2(ra[i], m0, m1, rb[i]);
                DBGW(31, 0);
                TM(8);
                store_vt(s);
            }
            s++;
            const uint32_t ost = pin(sb + C2_OB + t32), pla = pin(sb + C2_PB + lane * 16), plb = pin(sb + C2_PB + 512 + (lane & 7) * 16);
            bar_sync<1, 384>();
            fence_async_smem();
            DBGW(24, 0);
            if (s < NSEG - 1) bar_sync<2, 224>();
            else bar_arrive<6, 384>();
            {
                float acc[20];
                c2_xstream<0, 32, CH_SPV>(acc, w, dlo + ((C2_XB + (s & 1) * C2_XS) >> 4), rank, dlo + (C2_WV >> 4));
                wgmma_wait<0>();
#pragma unroll
                for (int j = 0; j < 5; j++) { va[j][0] = pack_bf16(acc[4 * j], acc[4 * j + 1]); va[j][1] = pack_bf16(acc[4 * j + 2], acc[4 * j + 3]); }
            }
            DBGW(26, 0);
            TM(7);
            if (s < NSEG - 1) {
                uint32_t p[5];
                bar_sync<3, 160>();
                DBGW(27, 0);
                ldmatrix_x4_trans(p[0], p[1], p[2], p[3], pla);
                asm volatile("ldmatrix.sync.aligned.m8n8.x1.trans.shared.b16 {%0}, [%1];" : "=r"(p[4]) : "r"(plb) : "memory");
                float oa[4] = {0.f, 0.f, 0.f, 0.f}, ob[4] = {0.f, 0.f, 0.f, 0.f}, sa[4] = {0.f, 0.f, 0.f, 0.f}, sc[4] = {0.f, 0.f, 0.f, 0.f};
                const uint32_t one = 0x3f803f80u;
                mma_16816(sa, one, one, one, one, p[0], p[1]);
                mma_16816(oa, va[0][0], va[0][1], va[1][0], va[1][1], p[0], p[1]);
                mma_16816(sc, one, one, one, one, p[2], p[3]);
                mma_16816(ob, va[2][0], va[2][1], va[3][0], va[3][1], p[2], p[3]);
                mma_16816(sa, one, one, one, one, p[4], 0u);
                mma_16816(oa, va[4][0], va[4][1], 0u, 0u, p[4], 0u);
                bar_arrive<6, 384>();
                float i0, i1;
                asm("rcp.approx.ftz.f32 %0, %1;" : "=f"(i0) : "f"(sa[0] + sc[0]));
                asm("rcp.approx.ftz.f32 %0, %1;" : "=f"(i1) : "f"(sa[1] + sc[1]));
                sts32(ost, pack_bf16((oa[0] + ob[0]) * i0, (oa[2] + ob[2]) * i0));
                sts32(ost + 32, pack_bf16((oa[1] + ob[1]) * i1, (oa[3] + ob[3]) * i1));
                fence_async_smem();
                __syncwarp();
                if (elect_one()) {
#pragma unroll
                    for (int i = 1; i < 8; i++) {
                        const uint32_t d = (rank + i) & 7;
                        bulk_s2s(mapa_u32(sb + C2_OB + i * 1024 + w4 * 256, d), sb + C2_OB + w4 * 256, 256, mapa_u32(bar_o + 8 * c2_grp(i), d));
                        if (i == 1) mbar_arrive(bar_o);
                    }
                }
                __syncwarp();
                DBGW(28, 0);
            }
        }
        store_vt(NSEG - 1);
        fence_async_smem();
        bar_arrive<7, 256>();
        const uint32_t lane = fresh_lane();
        if (w4 == 0) {
            mbar_wait(bar_h, 0);
#pragma unroll 1
            for (uint32_t o = 0; o < 2; o++) {
                asm volatile("bar.sync %0, 160;" :: "r"(13 + o) : "memory");
                if (elect_one()) {
#pragma unroll
                    for (int i = 1; i < 8; i++) {
                        const uint32_t d = (rank + i) & 7;
                        bulk_s2s(mapa_u32(sb + C2_WO + i * 8192 + o * 4096, d), sb + C2_QX + o * 4096, 4096, mapa_u32(bar_m + o * 64 + 8 * c2_grp(i), d));
                    }
                }
                __syncwarp();
                if (lane < 4) mbar_arrive(bar_m + o * 64);
                TM(21 + o);
            }
        }
        __syncwarp();
        asm volatile("barrier.cluster.arrive.relaxed.aligned;" ::: "memory");
        g_xbuf[((8 + rank) * 8 + C) * 128 + w4 * 32 + lane] = make_uint2(0u, 0u);
    }
    asm volatile("barrier.cluster.wait.aligned;" ::: "memory");
    TS_END(2);
    CYC(3);
    if (wg == 0) TM(23);
}

constexpr int P3_LEN = 24;
struct Proj3Params {
    CUtensorMap mapA[2];
    CUtensorMap mapW[3];
    bf16* out[3];
    uint16_t sched[34 * P3_LEN];
};
#define P3_STAGES 14
#define P3_LAG 2
#define P3_PACE 0
#define P3T(i)
constexpr int P3_SMEM = P3_STAGES * 16384 + 256 + 2 * P3_LEN * 8;
__device__ __forceinline__ void mbar_arrive_cl(uint32_t bar_cluster_addr) {
    asm volatile("mbarrier.arrive.shared::cluster.b64 _, [%0];" :: "r"(bar_cluster_addr) : "memory");
}
__global__ void __cluster_dims__(2, 1, 1) __launch_bounds__(384, 1) proj3_kernel(const __grid_constant__ Proj3Params P) {
    extern __shared__ __align__(1024) uint8_t smem_proj[];
    const uint32_t sb = smem_u32(smem_proj);
    const uint32_t full = sb + P3_STAGES * 16384, empty = full + 8 * P3_STAGES, done = full + 256;
    const int warp = __shfl_sync(0xffffffff, threadIdx.x >> 5, 0), lane = threadIdx.x & 31;
    const uint32_t rank = cluster_ctarank();
    const uint16_t* sched = P.sched + (blockIdx.x >> 1) * P3_LEN;
    TS_BEGIN(0);
    if (threadIdx.x == 0) {
#pragma unroll 1
        for (int i = 0; i < P3_STAGES; i++) { mbar_init(full + 8 * i, 1); mbar_init(empty + 8 * i, 4); }
        asm volatile("fence.mbarrier_init.release.cluster;" ::: "memory");
    }
    if ((warp == 9 || warp == 10) && lane == 0)
#pragma unroll 1
        for (int i = 0; i < P3_LEN; i++) mbar_init(done + ((warp - 9) * P3_LEN + i) * 8, 4);
    __syncthreads();
    cluster_sync_relaxed();
    pdl_launch_dependents();
    if (warp >= 8) {
        asm volatile("setmaxnreg.dec.sync.aligned.u32 40;");
        if (warp == 8 && lane == 0) {
            uint32_t so = 0, ph = 1;
#pragma unroll 1
            for (;; sched++) {
                const uint32_t e = *sched, z = (e >> 5) & 3, na = e >> 10;
                if (z == 3) break;
#pragma unroll 1
                for (int i = 1 - na; i < 16; i += 2 - na) {
                    mbar_wait(empty + so, ph);
                    mbar_expect_tx(full + so, 16384);
                    if (i & 1) tma_load_2d_mc(sb + so * 2048 + rank * 8192, &P.mapW[z], full + so, (e & 31) * 128 + rank * 64, (i >> 1) * 64, (uint16_t)3);
                    else tma_load_2d(sb + so * 2048, &P.mapA[z != 0], full + so, (i >> 1) * 64, (((e >> 7) & 7) * 2 + rank) * 128);
                    so += 8;
                    if (so == 8 * P3_STAGES) { so = 0; ph ^= 1; }
                }
            }
        } else if (warp < 11 && lane == 0) {
#pragma unroll 1
            for (uint32_t d = done + (warp - 9) * P3_LEN * 8;; d += 8, sched++) {
                const uint32_t e = *sched;
                if (((e >> 5) & 3) == 3) break;
                mbar_wait(d, 0);
                signal_ctr(CT_AP + ((e & 31) >> 1));
            }
        }
    } else {
        asm volatile("setmaxnreg.inc.sync.aligned.u32 232;");
        const int wg = warp >> 2;
        uint32_t a[32][4];
        float acc[64];
        const uint32_t b_lo = desc_lo(sb, 8192);
        const int r = warp * 16 + (lane & 15);
        const uint32_t la = sb + r * 128 + (((lane >> 4) ^ (r & 7)) << 4);
#pragma unroll
        for (int i = 0; i < 32; i++) ldsm_x4(a[i], la + i * 1024);
        const uint32_t rel = mapa_u32(empty, lane & 1);
        const int tw = threadIdx.x & 127;
        uint32_t so = 0, ph = 0;
        if (wg == 1) asm volatile("bar.arrive 1, 256;" ::: "memory");
#pragma unroll 1
        for (uint32_t d = done + wg * P3_LEN * 8;; d += 8, sched++) {
            const uint32_t e = *sched;
            if (((e >> 5) & 3) == 3) break;
            const bool na = e >> 10;
            const bool sig = tw < (na ? 4 : 2);
            uint32_t old = 0;
            auto release = [&]() { asm volatile("{\n.reg .pred p;\nsetp.ne.u32 p, %1, 0;\n@p mbarrier.arrive.shared::cluster.b64 _, [%0];\n}" :: "r"(rel + old), "r"((uint32_t)sig) : "memory"); };
            P3T(0);
            asm volatile("bar.sync %0, 256;" :: "r"(1 + wg) : "memory");
            P3T(1);
#pragma unroll
            for (int k = 0; k < 8; k++) {
                const uint32_t sa = so;
                if (na) {
                    mbar_wait(full + so, ph);
#pragma unroll
                    for (int kk = 0; kk < 4; kk++) ldsm_x4(a[k * 4 + kk], (la + so * 2048) ^ (kk * 32));
                    so += 8;
                    if (so == 8 * P3_STAGES) { so = 0; ph ^= 1; }
                }
                mbar_wait(full + so, ph);
                wgmma_fence();
#pragma unroll
                for (int kk = 0; kk < 4; kk++) wgmma_rs_n128_tb_lo(acc, a[k * 4 + kk], b_lo + so * 128 + kk * 128, (k | kk) != 0);
                wgmma_commit();
                if (k == P3_LAG) asm volatile("bar.arrive %0, 256;" :: "r"(2 - wg) : "memory");
                if (k > 0) { wgmma_wait<1>(); release(); }
                old = (lane & 2) ? sa : so;
                so += 8;
                if (so == 8 * P3_STAGES) { so = 0; ph ^= 1; }
            }
            bf16* dst = P.out[(e >> 5) & 3] + ((size_t)(e & 31) * SEQ + (((e >> 7) & 7) * 2 + rank) * 128 + warp * 16 + (lane >> 2)) * HD + (lane & 3) * 8;
            wgmma_wait<0>();
            P3T(2);
            release();
#pragma unroll
            for (int i = 0; i < 8; i++) {
                const float* c = &acc[(i >> 1) * 16 + (i & 1) * 2];
                *reinterpret_cast<uint4*>(dst + (i & 1) * 8 * HD + (i >> 1) * 32) =
                    make_uint4(pack_bf16(c[0], c[1]), pack_bf16(c[4], c[5]), pack_bf16(c[8], c[9]), pack_bf16(c[12], c[13]));
                pace(P3_PACE);
            }
            __syncwarp();
            mbar_arrive_if(d, lane == 0);
        }
        TS_END(0);
    }
    __syncwarp();
    cluster_sync_relaxed();
}

struct OutParams {
    CUtensorMap mapCtx[2];
    CUtensorMap mapWo[2];
    CUtensorMap mapOut;
    bf16* out;
    uint32_t sched[34 * 2];
};
#define OT(i)
#define O4_CD 2000
#define O6_LEAD 0
constexpr int O4_GRID = 68;
constexpr uint32_t O6_ST = 196608, O6_BAR = O6_ST + 32768;
constexpr int O2_SMEM = O6_BAR + 64;
__device__ __forceinline__ void tma_load_3d(uint32_t dst, const CUtensorMap* map, uint32_t bar, int c0, int c1, int c2) {
    asm volatile(
        "cp.async.bulk.tensor.3d.shared::cluster.global.mbarrier::complete_tx::bytes [%0], [%1, {%3, %4, %5}], [%2];"
        :: "r"(dst), "l"((uint64_t)map), "r"(bar), "r"(c0), "r"(c1), "r"(c2) : "memory");
}
__global__ void __cluster_dims__(2, 1, 1) __launch_bounds__(384, 1) out4_kernel(const __grid_constant__ OutParams P) {
    extern __shared__ __align__(1024) uint8_t smem_out[];
    const uint32_t sb = smem_u32(smem_out);
    const uint32_t full = sb + O6_BAR, empty = full + 32;
    const int warp = __shfl_sync(0xffffffff, threadIdx.x >> 5, 0), lane = threadIdx.x & 31;
    const uint32_t rank = cluster_ctarank();
    const uint32_t e0 = P.sched[blockIdx.x & ~1u], e1 = P.sched[blockIdx.x | 1u];
    TS_BEGIN(4);
    if (threadIdx.x == 352) {
        asm volatile("prefetch.tensormap [%0];" :: "l"((uint64_t)&P.mapWo[(e0 >> 10 & 127) == 0]) : "memory");
        for (int i = 0; i < 4; i++) { mbar_init(full + 8 * i, 1); mbar_init(empty + 8 * i, 4); }
        asm volatile("fence.mbarrier_init.release.cluster;" ::: "memory");
    }
    if (threadIdx.x == 256) asm volatile("prefetch.tensormap [%0];" :: "l"((uint64_t)&P.mapCtx[(e0 >> 10 & 127) == 0]) : "memory");
    __syncwarp();
    asm volatile("barrier.cluster.arrive.relaxed.aligned;" ::: "memory");
    if (warp != 11) asm volatile("barrier.cluster.wait.aligned;" ::: "memory");
    if (warp == 8 || warp == 11) {
        if (lane == 0) {
            uint32_t so = 0, ph = 1;
#pragma unroll 1
            for (uint32_t e = e0, en = e1; e; e = en, en = 0) {
                const uint32_t mt = e & 15, na = e >> 10 & 127, n = na + (e >> 23);
#pragma unroll 1
                for (uint32_t i = 0; i < n; i++) {
                    const uint32_t b = i >= na, k = b ? (e >> 17 & 63) + i - na : (e >> 4 & 63) + i;
                    if (warp == 8) {
                        const bool late = k >= 2 * O2_HE;
                        if (i == 0 || i == na || k == 2 * O2_HE)
                            wait_ctr(b ? CT_CB + max(mt, CB_FIRST) : CT_CA + mt * 2 + late, b ? 64u : late ? 2u * (NH - O2_HE) : 2u * O2_HE);
                        if (i == n - 1) wait_ctr(CT_P, 104u);
                    }
                    mbar_wait(empty + so, ph);
                    if (warp == 8) {
                        mbar_expect_tx(full + so, 49152);
                        tma_load_2d_mc(sb + so * 6144 + rank * 8192, &P.mapCtx[b], full + so, (k & 1) * 64, (k >> 1) * SEQ + mt * 128 + rank * 64, (uint16_t)3);
                    } else tma_load_3d(sb + so * 6144 + 16384, &P.mapWo[b], full + so, 0, k * 64, rank * 4);
                    so = (so + 8) & 31;
                    if (so == 0) ph ^= 1;
                }
            }
        }
        __syncwarp();
        if (warp == 8) finish_launch(lane);
        else asm volatile("barrier.cluster.wait.aligned;" ::: "memory");
    } else if (warp > 8) {
        if (blockIdx.x < 52) {
            pace(O4_CD);
#pragma unroll 1
            for (int i = (blockIdx.x * 2 + warp - 9) * 32 + lane; i < SEQ * DM / 8; i += 104 * 32) reinterpret_cast<uint4*>(P.out)[i] = make_uint4(0u, 0u, 0u, 0u);
            asm volatile("fence.proxy.async.global;" ::: "memory");
            wait_ctr(CT_G, FA_GRID);
            __syncwarp();
            if (lane == 0) signal_ctr(CT_P);
        }
    } else {
        const int wg = warp >> 2;
        float acc[128];
#pragma unroll
        for (int i = 0; i < 128; i++) asm volatile("" : "=f"(acc[i]));
        const uint32_t a_lo = desc_lo(sb + wg * 8192, 16), b_lo = desc_lo(sb + 16384, 8192);
        const uint32_t rel = mapa_u32(empty, lane & 1), sig = (threadIdx.x & 127) < 2;
        const uint32_t st = sb + O6_ST + warp * 4096, sl = st + (lane & 15) * 128 + (((lane >> 4) ^ (lane & 7)) << 4);
        uint32_t so = 0, ph = 0;
        int left = (e0 >> 10 & 127) + (e0 >> 23) + (e1 >> 10 & 127) + (e1 >> 23) - 4;
        if (lane == 0) asm volatile("prefetch.tensormap [%0];" :: "l"((uint64_t)&P.mapOut) : "memory");
        wait_ctr(CT_G, FA_GRID);
#pragma unroll 1
        for (uint32_t e = e0, en = e1; e; e = en, en = 0) {
            const uint32_t row = (e & 15) * 128 + warp * 16, na = e >> 10 & 127, n = na + (e >> 23);
            float g0, g1;
            asm volatile("ld.relaxed.gpu.global.f32 %0, [%1];" : "=f"(g0) : "l"(g_gate + row + (lane >> 2)) : "memory");
            asm volatile("ld.relaxed.gpu.global.f32 %0, [%1 + 32];" : "=f"(g1) : "l"(g_gate + row + (lane >> 2)) : "memory");
            auto release = [&]() {
                asm volatile("{\n.reg .pred p;\nsetp.gt.s32 p, %1, 0;\n@p mbarrier.arrive.shared::cluster.b64 _, [%0];\n}" :: "r"(rel + ((so - 8) & 31)), "r"(sig ? left : 0) : "memory");
                left--;
            };
#pragma unroll 1
            for (uint32_t i = 0;; i++) {
                if (i == na || i == n) {
                    float r0 = g0, r1 = g1;
                    if (i < n) {
                        g0 = fmaxf(1.f - r0, 0x1p-40f); g1 = fmaxf(1.f - r1, 0x1p-40f);
                        r0 = __fdividef(r0, g0); r1 = __fdividef(r1, g1);
                    }
                    wgmma_wait<0>();
                    if (i == n) release();
                    if (i == n) OT(3); else OT(2);
#pragma unroll
                    for (int c = 0; c < 32; c++) { acc[4 * c] *= r0; acc[4 * c + 1] *= r0; acc[4 * c + 2] *= r1; acc[4 * c + 3] *= r1; }
                    if (i == n) break;
                }
                if (O6_LEAD && wg && i + O6_LEAD == n) bar_sync<1, 256>();
                mbar_wait(full + so, ph);
                if (i == 0) OT(1);
                wgmma_fence();
#pragma unroll
                for (int kk = 0; kk < 4; kk++) wgmma_ss_n256_tb(acc, a_lo + so * 384 + kk * 2, b_lo + so * 384 + kk * 128, i | kk);
                wgmma_commit();
                if (O6_LEAD && !wg && i + 1 == n) bar_arrive<1, 256>();
                if (i > 0) { wgmma_wait<1>(); release(); }
                so = (so + 8) & 31;
                if (so == 0) ph ^= 1;
            }
#pragma unroll
            for (int q = 0; q < 4; q++) {
                if (lane == 0) asm volatile("cp.async.bulk.wait_group.read 1;" ::: "memory");
                __syncwarp();
#pragma unroll
                for (int t = 0; t < 4; t++) {
                    const float* c = &acc[q * 32 + t * 8];
                    stmatrix_x4((sl ^ (t * 32)) + (q & 1) * 2048, pack_bf16(c[0], c[1]), pack_bf16(c[2], c[3]), pack_bf16(c[4], c[5]), pack_bf16(c[6], c[7]));
                }
                fence_async_smem();
                __syncwarp();
                if (lane == 0) {
                    asm volatile("cp.reduce.async.bulk.tensor.2d.global.shared::cta.add.bulk_group [%0, {%2, %3}], [%1];"
                                 :: "l"((uint64_t)&P.mapOut), "r"(st + (q & 1) * 2048), "r"(rank * 256 + q * 64), "r"(row) : "memory");
                    asm volatile("cp.async.bulk.commit_group;" ::: "memory");
                }
            }
            OT(4);
        }
        if (lane == 0) asm volatile("cp.async.bulk.wait_group.read 0;" ::: "memory");
    }
    TS_END(4);
}

typedef CUresult (*PFN_encodeTiled)(CUtensorMap*, CUtensorMapDataType, cuuint32_t, void*, const cuuint64_t*,
                                    const cuuint64_t*, const cuuint32_t*, const cuuint32_t*, CUtensorMapInterleave,
                                    CUtensorMapSwizzle, CUtensorMapL2promotion, CUtensorMapFloatOOBfill);
static PFN_encodeTiled g_encode = nullptr;

static void make_map(CUtensorMap* m, const void* ptr, uint64_t rows, uint64_t cols, uint32_t box_rows, bool sw64 = false) {
    cuuint64_t dims[2] = {cols, rows};
    cuuint64_t strides[1] = {cols * 2};
    cuuint32_t box[2] = {sw64 ? 32u : 64u, box_rows};
    cuuint32_t es[2] = {1, 1};
    g_encode(m, CU_TENSOR_MAP_DATA_TYPE_BFLOAT16, 2, const_cast<void*>(ptr), dims, strides, box, es,
             CU_TENSOR_MAP_INTERLEAVE_NONE, sw64 ? CU_TENSOR_MAP_SWIZZLE_64B : CU_TENSOR_MAP_SWIZZLE_128B, CU_TENSOR_MAP_L2_PROMOTION_L2_256B,
             CU_TENSOR_MAP_FLOAT_OOB_FILL_NONE);
}

static void make_map3(CUtensorMap* m, const void* ptr, uint64_t rows, uint64_t cols, uint32_t box_rows, uint32_t nblk) {
    cuuint64_t dims[3] = {64, rows, cols / 64};
    cuuint64_t strides[2] = {cols * 2, 128};
    cuuint32_t box[3] = {64u, box_rows, nblk};
    cuuint32_t es[3] = {1, 1, 1};
    g_encode(m, CU_TENSOR_MAP_DATA_TYPE_BFLOAT16, 3, const_cast<void*>(ptr), dims, strides, box, es,
             CU_TENSOR_MAP_INTERLEAVE_NONE, CU_TENSOR_MAP_SWIZZLE_128B, CU_TENSOR_MAP_L2_PROMOTION_L2_256B, CU_TENSOR_MAP_FLOAT_OOB_FILL_NONE);
}

template <typename... KArgs, typename... Args>
static void launch_pdl(void (*kernel)(KArgs...), int grid, int block, size_t smem, cudaStream_t st, bool pdl, Args... args) {
    cudaLaunchConfig_t cfg = {};
    cfg.gridDim = dim3(grid); cfg.blockDim = dim3(block); cfg.dynamicSmemBytes = smem; cfg.stream = st;
    cudaLaunchAttribute at[1];
    at[0].id = cudaLaunchAttributeProgrammaticStreamSerialization;
    at[0].val.programmaticStreamSerializationAllowed = 1;
    cfg.attrs = at; cfg.numAttrs = pdl ? 1 : 0;
    cudaLaunchKernelEx(&cfg, kernel, KArgs(args)...);
}

extern "C" void kernel_launch(void* const* d_in, const int* in_sizes, int n_in, void* d_out, int out_size) {
    const bf16* x = (const bf16*)d_in[0];
    const bf16* ckv = (const bf16*)d_in[1];
    const bf16* wq = (const bf16*)d_in[2];
    const bf16* wuk = (const bf16*)d_in[3];
    const bf16* wuv = (const bf16*)d_in[4];
    const bf16* wo = (const bf16*)d_in[5];
    const bf16* mem0 = (const bf16*)d_in[7];
    const bf16* Wq = (const bf16*)d_in[8];
    const bf16* Wk = (const bf16*)d_in[9];
    const bf16* Wv = (const bf16*)d_in[10];
    const bf16* Wo = (const bf16*)d_in[11];
    const bf16* gate_w = (const bf16*)d_in[13];
    bf16* out = (bf16*)d_out;

    static Proj3Params P2;
    static ChainParams CP;
    static AttnParams AP;
    static OutParams OP;
    static bool init = false;
    static const void* last_in[15];
    bool same = init;
    for (int i = 0; i < 14 && same; i++) same = last_in[i] == d_in[i];
    same = same && last_in[14] == d_out;
    if (!init) {
        cudaDriverEntryPointQueryResult qr;
        cudaGetDriverEntryPoint("cuTensorMapEncodeTiled", (void**)&g_encode, cudaEnableDefault, &qr);
        cudaFuncSetAttribute(proj3_kernel, cudaFuncAttributeMaxDynamicSharedMemorySize, P3_SMEM);
        for (int p = 0; p < 34; p++) {
            uint16_t* t = P2.sched + p * P3_LEN;
            int n = 0, rows = -1;
            auto add = [&](int z, int mp, int head) {
                t[n++] = (uint16_t)(head | z << 5 | mp << 7 | (rows != (z ? 8 : 0) + mp) << 10);
                rows = (z ? 8 : 0) + mp;
            };
            const int mp = p & 7, kind = p >> 3;
            if (kind == 0) for (int h = 0; h < 23; h++) add(0, mp, h);
            else if (kind < 4) {
                for (int i = kind - 1; i < 54; i += 3) add(1 + (i & 1), mp, i >> 1);
                if (kind < 3) for (int h = 27; h < 32; h++) add(kind, mp, h);
                else for (int h = 23; h < 27; h++) add(0, mp, h);
            } else for (int i = 0; i < 20; i++) add(0, mp * 4 + i / 5, 27 + i % 5);
            while (n < P3_LEN) t[n++] = 3 << 5;
        }
        cudaFuncSetAttribute(attn_kernel, cudaFuncAttributeMaxDynamicSharedMemorySize, FA_SMEM);
        cudaFuncSetAttribute(chain_kernel, cudaFuncAttributeMaxDynamicSharedMemorySize, C2_SMEM);
        cudaFuncSetAttribute(out4_kernel, cudaFuncAttributeMaxDynamicSharedMemorySize, O2_SMEM);
#define O6_SCHED 0x10000, 0x0, 0x20000000, 0x0, 0x20000001, 0x0, 0x5c01, 0x99a2, 0x1f800002, 0x0, 0x10800003, 0xfe6802, 0xb003, 0x4004, 0x764c104, 0x0, 0x19000004, 0x1001c05, 0x1f040005, 0x0, 0x17a20006, 0x3075, 0x880b146, 0x0, 0x5006, 0x9807, 0x19800007, 0x2780fd8, 0xf408, 0x0, 0x1e000008, 0x0, 0x12386289, 0x0, 0xe000009, 0x200667a, 0x1e08000a, 0x0, 0x95c000b, 0x9c0a, 0x12145e9b, 0x0, 0x500000b, 0x1000380c, 0x6a6c, 0xe480bed, 0xc80840d, 0x0, 0x5b2761d, 0x6680fde, 0xa40b, 0x63e0b7e, 0xa009, 0x516146e, 0x6e66a67, 0x52a168e, 0xb535, 0x2ade, 0xfc252c3, 0xc0e, 0xa571, 0x4d6139e, 0x104060ec, 0x0, 0x667f, 0x74be, 0x9c0f, 0x5800c3e
        const uint32_t sched[68] = {O6_SCHED};
        for (int i = 0; i < 68; i++) OP.sched[i] = sched[i];
        init = true;
    }
    if (!same) {
        for (int i = 0; i < 14; i++) last_in[i] = d_in[i];
        last_in[14] = d_out;
        void *pQA, *pKA, *pVA, *pCA, *pCB;
        cudaGetSymbolAddress(&pQA, g_QA); cudaGetSymbolAddress(&pKA, g_KA); cudaGetSymbolAddress(&pVA, g_VA);
        cudaGetSymbolAddress(&pCA, g_ctxA); cudaGetSymbolAddress(&pCB, g_ctxB);
        make_map(&P2.mapA[0], x, SEQ, DM, 128);
        make_map(&P2.mapA[1], ckv, SEQ, DM, 128);
        const void* ws[3] = {wq, wuk, wuv};
        void* cs[3] = {pQA, pKA, pVA};
        for (int i = 0; i < 3; i++) { make_map(&P2.mapW[i], ws[i], DM, NQ, 64); P2.out[i] = (bf16*)cs[i]; }
        make_map(&CP.mapX, x, SEQ, DM, SEGL);
        make_map(&CP.mapM, mem0, NMEM, DM, NMEM);
        make_map(&CP.mapW[0], Wq, DM, NQ, 64);
        make_map(&CP.mapW[1], Wk, DM, NQ, 64);
        make_map(&CP.mapW[2], Wv, DM, NQ, 64);
        make_map(&CP.mapWo, Wo, NQ, DM, 64);
        make_map(&AP.mapQ, pQA, NH * SEQ, HD, 128);
        make_map(&AP.mapK, pKA, NH * SEQ, HD, 128);
        make_map(&AP.mapV, pVA, NH * SEQ, HD, 128);
        make_map(&AP.mapO, pCA, NH * SEQ, HD, 64);
        make_map(&OP.mapCtx[0], pCA, NH * SEQ, HD, 64);
        make_map(&OP.mapCtx[1], pCB, NH * SEQ, HD, 64);
        make_map3(&OP.mapWo[0], wo, NQ, DM, 64, 4);
        make_map3(&OP.mapWo[1], Wo, NQ, DM, 64, 4);
        make_map(&OP.mapOut, out, SEQ, DM, 16);
        OP.out = out;
        make_map(&CP.mapC, pCB, NH * SEQ, HD, 64);
        CP.out = out;
        AP.x = x; AP.gate_w = gate_w;
    }
    cudaStream_t s1 = cudaStreamPerThread;
    const bool pdl = true;
    launch_pdl(chain_kernel, 64, 384, C2_SMEM, s1, false, CP);
    launch_pdl(proj3_kernel, 68, 384, P3_SMEM, s1, pdl, P2);
    launch_pdl(attn_kernel, FA_GRID, 384, FA_SMEM, s1, pdl, AP);
    launch_pdl(out4_kernel, O4_GRID, 384, O2_SMEM, s1, pdl, OP);
}
```

```cpp
#include <cuda_runtime.h>
#include <cuda_bf16.h>
#include <cuda.h>
#include <stdint.h>
#include <type_traits>

constexpr int SEQ = 2048;
constexpr int DM = 512;
constexpr int NH = 32;
constexpr int HD = 128;
constexpr int NQ = NH * HD;
constexpr int SEGL = 32;
constexpr int NMEM = 8;
constexpr int NSEG = SEQ / SEGL;

typedef __nv_bfloat16 bf16;

__device__ bf16 g_QA[SEQ * NQ];
__device__ bf16 g_KA[SEQ * NQ];
__device__ bf16 g_VA[SEQ * NQ];
__device__ bf16 g_ctxA[SEQ * NQ];
__device__ bf16 g_ctxB[SEQ * NQ];
constexpr int CT_ATTN = 1, CT_FIN = 5;
constexpr int CT_P = 48;
constexpr int CT_AP = 64;
#define O2_HE 24
constexpr int CT_CA = 128;
constexpr int CT_CB = 160;
#define CB_FIRST 11
constexpr int CT_N = 192;
__device__ unsigned int g_ctr[CT_N];
__device__ float g_gate[SEQ];
__device__ uint2 g_xbuf[2 * 8 * 8 * 128];

#define FA_GRID 68

#define P2_MARK 0
#define TS_MARK(id, tid)
#define TS_MARK2(id, tid)
#define TS_BEGIN(id)
#define TS_END(id)
#define TS_BEGIN_T(id, tid)
#define TS_END_T(id, tid)
__device__ __forceinline__ void pdl_launch_dependents() { asm volatile("griddepcontrol.launch_dependents;" ::: "memory"); }
__device__ __forceinline__ void wait_ctr(int idx, unsigned int n) {
    unsigned int v; int it = 0;
    do { asm volatile("ld.acquire.gpu.global.u32 %0, [%1];" : "=r"(v) : "l"(&g_ctr[idx]) : "memory"); } while (v < n && ++it < (1 << 22));
}
__device__ __forceinline__ void signal_ctr(int idx) {
    asm volatile("fence.proxy.async.global;" ::: "memory");
    asm volatile("red.release.gpu.global.add.u32 [%0], 1;" :: "l"(&g_ctr[idx]) : "memory");
}
__device__ __forceinline__ void signal_ctr_generic(int idx) {
    asm volatile("red.release.gpu.global.add.u32 [%0], 1;" :: "l"(&g_ctr[idx]) : "memory");
}
__device__ __forceinline__ void finish_launch(int lane) {
    unsigned int tk = 0;
    if (lane == 0) tk = atomicAdd(&g_ctr[CT_FIN], 1u);
    tk = __shfl_sync(0xffffffff, tk, 0);
    if (tk == 64 + 68 - 1)
#pragma unroll 1
        for (int i = lane; i < CT_N; i += 32) g_ctr[i] = 0u;
}
__device__ __forceinline__ uint4 quad_transpose(uint32_t p0, uint32_t p1, uint32_t p2, uint32_t p3, int lane) {
    const bool o1 = lane & 1, o2 = lane & 2;
    uint32_t s0 = o1 ? p0 : p1, s1 = o1 ? p2 : p3;
    s0 = __shfl_xor_sync(0xffffffff, s0, 1); s1 = __shfl_xor_sync(0xffffffff, s1, 1);
    const uint32_t a_lo = o1 ? s0 : p0, a_hi = o1 ? p1 : s0, b_lo = o1 ? s1 : p2, b_hi = o1 ? p3 : s1;
    uint32_t t0 = o2 ? a_lo : b_lo, t1 = o2 ? a_hi : b_hi;
    t0 = __shfl_xor_sync(0xffffffff, t0, 2); t1 = __shfl_xor_sync(0xffffffff, t1, 2);
    return o2 ? make_uint4(t0, t1, b_lo, b_hi) : make_uint4(a_lo, a_hi, t0, t1);
}
__device__ __forceinline__ uint32_t smem_u32(const void* p) {
    return (uint32_t)__cvta_generic_to_shared(p);
}
__device__ __forceinline__ void mbar_init(uint32_t bar, uint32_t count) {
    asm volatile("mbarrier.init.shared::cta.b64 [%0], %1;" :: "r"(bar), "r"(count));
}
__device__ __forceinline__ void mbar_expect_tx(uint32_t bar, uint32_t bytes) {
    asm volatile("mbarrier.arrive.expect_tx.shared::cta.b64 _, [%0], %1;" :: "r"(bar), "r"(bytes) : "memory");
}
__device__ __forceinline__ void mbar_arrive(uint32_t bar) {
    asm volatile("mbarrier.arrive.shared::cta.b64 _, [%0];" :: "r"(bar) : "memory");
}
__device__ __forceinline__ void mbar_wait(uint32_t bar, uint32_t parity) {
    asm volatile(
        "{\n"
        ".reg .pred p, q;\n"
        ".reg .u32 c;\n"
        "mov.u32 c, 0;\n"
        "WAIT_LOOP:\n"
        "mbarrier.try_wait.parity.shared::cta.b64 p, [%0], %1;\n"
        "@p bra WAIT_DONE;\n"
        "add.u32 c, c, 1;\n"
        "setp.lt.u32 q, c, 4000000;\n"
        "@q bra WAIT_LOOP;\n"
        "WAIT_DONE:\n"
        "}\n" :: "r"(bar), "r"(parity) : "memory");
}
__device__ __forceinline__ void tma_load_2d(uint32_t dst, const CUtensorMap* map, uint32_t bar, int c0, int c1) {
    asm volatile(
        "cp.async.bulk.tensor.2d.shared::cluster.global.mbarrier::complete_tx::bytes [%0], [%1, {%3, %4}], [%2];"
        :: "r"(dst), "l"((uint64_t)map), "r"(bar), "r"(c0), "r"(c1) : "memory");
}
constexpr uint64_t L2_NORMAL = 0x1000000000000000ull, L2_FIRST = 0x12F0000000000000ull;
__device__ __forceinline__ void tma_load_2d(uint32_t dst, const CUtensorMap* map, uint32_t bar, int c0, int c1, uint64_t hint) {
    asm volatile(
        "cp.async.bulk.tensor.2d.shared::cluster.global.mbarrier::complete_tx::bytes.L2::cache_hint [%0], [%1, {%3, %4}], [%2], %5;"
        :: "r"(dst), "l"((uint64_t)map), "r"(bar), "r"(c0), "r"(c1), "l"(hint) : "memory");
}
__device__ __forceinline__ void wgmma_fence() { asm volatile("wgmma.fence.sync.aligned;" ::: "memory"); }
__device__ __forceinline__ void wgmma_commit() { asm volatile("wgmma.commit_group.sync.aligned;" ::: "memory"); }
template <int N> __device__ __forceinline__ void wgmma_wait() {
    asm volatile("wgmma.wait_group.sync.aligned %0;" :: "n"(N) : "memory");
}
__device__ __forceinline__ uint64_t make_desc(uint32_t addr, uint32_t lbo, uint32_t sbo) {
    uint64_t d = 0;
    d |= (uint64_t)((addr & 0x3FFFF) >> 4);
    d |= (uint64_t)((lbo >> 4) & 0x3FFF) << 16;
    d |= (uint64_t)((sbo >> 4) & 0x3FFF) << 32;
    d |= (uint64_t)1 << 62;
    return d;
}

#define ACC64(d) \
    "+f"(d[0]), "+f"(d[1]), "+f"(d[2]), "+f"(d[3]), "+f"(d[4]), "+f"(d[5]), "+f"(d[6]), "+f"(d[7]), \
    "+f"(d[8]), "+f"(d[9]), "+f"(d[10]), "+f"(d[11]), "+f"(d[12]), "+f"(d[13]), "+f"(d[14]), "+f"(d[15]), \
    "+f"(d[16]), "+f"(d[17]), "+f"(d[18]), "+f"(d[19]), "+f"(d[20]), "+f"(d[21]), "+f"(d[22]), "+f"(d[23]), \
    "+f"(d[24]), "+f"(d[25]), "+f"(d[26]), "+f"(d[27]), "+f"(d[28]), "+f"(d[29]), "+f"(d[30]), "+f"(d[31]), \
    "+f"(d[32]), "+f"(d[33]), "+f"(d[34]), "+f"(d[35]), "+f"(d[36]), "+f"(d[37]), "+f"(d[38]), "+f"(d[39]), \
    "+f"(d[40]), "+f"(d[41]), "+f"(d[42]), "+f"(d[43]), "+f"(d[44]), "+f"(d[45]), "+f"(d[46]), "+f"(d[47]), \
    "+f"(d[48]), "+f"(d[49]), "+f"(d[50]), "+f"(d[51]), "+f"(d[52]), "+f"(d[53]), "+f"(d[54]), "+f"(d[55]), \
    "+f"(d[56]), "+f"(d[57]), "+f"(d[58]), "+f"(d[59]), "+f"(d[60]), "+f"(d[61]), "+f"(d[62]), "+f"(d[63])
#define ACC64_STR \
    "{%0, %1, %2, %3, %4, %5, %6, %7, %8, %9, %10, %11, %12, %13, %14, %15, " \
    "%16, %17, %18, %19, %20, %21, %22, %23, %24, %25, %26, %27, %28, %29, %30, %31, " \
    "%32, %33, %34, %35, %36, %37, %38, %39, %40, %41, %42, %43, %44, %45, %46, %47, " \
    "%48, %49, %50, %51, %52, %53, %54, %55, %56, %57, %58, %59, %60, %61, %62, %63}"

template <int TB>
__device__ __forceinline__ void wgmma_ss_n128(float (&d)[64], uint64_t da, uint64_t db, int scale_d) {
    asm volatile(
        "{\n.reg .pred p;\nsetp.ne.b32 p, %66, 0;\n"
        "wgmma.mma_async.sync.aligned.m64n128k16.f32.bf16.bf16 " ACC64_STR ", %64, %65, p, 1, 1, 0, %67;\n}\n"
        : ACC64(d) : "l"(da), "l"(db), "r"(scale_d), "n"(TB));
}
__device__ __forceinline__ uint32_t desc_lo(uint32_t addr, uint32_t lbo) { return ((addr & 0x3FFFF) >> 4) | ((lbo >> 4) << 16); }
template <int TB>
__device__ __forceinline__ void wgmma_ss_n128_lo(float (&d)[64], uint32_t da_lo, uint32_t db_lo, int scale_d) {
    asm volatile(
        "{\n.reg .pred p;\n.reg .b64 da, db;\nsetp.ne.b32 p, %66, 0;\n"
        "mov.b64 da, {%64, 0x40000040};\nmov.b64 db, {%65, 0x40000040};\n"
        "wgmma.mma_async.sync.aligned.m64n128k16.f32.bf16.bf16 " ACC64_STR ", da, db, p, 1, 1, 0, %67;\n}\n"
        : ACC64(d) : "r"(da_lo), "r"(db_lo), "r"(scale_d), "n"(TB));
}
__device__ __forceinline__ void wgmma_rs_n128_tb(float (&d)[64], uint32_t a0, uint32_t a1, uint32_t a2, uint32_t a3,
                                                 uint64_t db, int scale_d) {
    asm volatile(
        "{\n.reg .pred p;\nsetp.ne.b32 p, %69, 0;\n"
        "wgmma.mma_async.sync.aligned.m64n128k16.f32.bf16.bf16 " ACC64_STR ", {%64, %65, %66, %67}, %68, p, 1, 1, 1;\n}\n"
        : ACC64(d) : "r"(a0), "r"(a1), "r"(a2), "r"(a3), "l"(db), "r"(scale_d));
}
__device__ __forceinline__ void wgmma_rs_n80(float (&d)[40], const uint32_t (&a)[4], uint32_t db_lo, int scale_d) {
    asm volatile(
        "{\n.reg .pred p;\n.reg .b64 db;\nsetp.ne.b32 p, %45, 0;\nmov.b64 db, {%44, 0x40000040};\n"
        "wgmma.mma_async.sync.aligned.m64n80k16.f32.bf16.bf16 "
        "{%0, %1, %2, %3, %4, %5, %6, %7, %8, %9, %10, %11, %12, %13, %14, %15, %16, %17, %18, %19, %20, %21, %22, %23, %24, %25, %26, %27, %28, %29, %30, %31, %32, %33, %34, %35, %36, %37, %38, %39}, "
        "{%40, %41, %42, %43}, db, p, 1, 1, 0;\n}\n"
        : "+f"(d[0]), "+f"(d[1]), "+f"(d[2]), "+f"(d[3]), "+f"(d[4]), "+f"(d[5]), "+f"(d[6]), "+f"(d[7]), "+f"(d[8]), "+f"(d[9]), "+f"(d[10]), "+f"(d[11]), "+f"(d[12]), "+f"(d[13]), "+f"(d[14]), "+f"(d[15]), "+f"(d[16]), "+f"(d[17]), "+f"(d[18]), "+f"(d[19]), "+f"(d[20]), "+f"(d[21]), "+f"(d[22]), "+f"(d[23]), "+f"(d[24]), "+f"(d[25]), "+f"(d[26]), "+f"(d[27]), "+f"(d[28]), "+f"(d[29]), "+f"(d[30]), "+f"(d[31]), "+f"(d[32]), "+f"(d[33]), "+f"(d[34]), "+f"(d[35]), "+f"(d[36]), "+f"(d[37]), "+f"(d[38]), "+f"(d[39])
        : "r"(a[0]), "r"(a[1]), "r"(a[2]), "r"(a[3]), "r"(db_lo), "r"(scale_d));
}
__device__ __forceinline__ void wgmma_ss_n256_tb(float (&d)[128], uint32_t da_lo, uint32_t db_lo, int scale_d) {
    asm volatile(
        "{\n.reg .pred p;\n.reg .b64 da, db;\nsetp.ne.b32 p, %130, 0;\nmov.b64 da, {%128, 0x40000040};\nmov.b64 db, {%129, 0x40000040};\n"
        "wgmma.mma_async.sync.aligned.m64n256k16.f32.bf16.bf16 {%0, %1, %2, %3, %4, %5, %6, %7, %8, %9, %10, %11, %12, %13, %14, %15, %16, %17, %18, %19, %20, %21, %22, %23, %24, %25, %26, %27, %28, %29, %30, %31, %32, %33, %34, %35, %36, %37, %38, %39, %40, %41, %42, %43, %44, %45, %46, %47, %48, %49, %50, %51, %52, %53, %54, %55, %56, %57, %58, %59, %60, %61, %62, %63, %64, %65, %66, %67, %68, %69, %70, %71, %72, %73, %74, %75, %76, %77, %78, %79, %80, %81, %82, %83, %84, %85, %86, %87, %88, %89, %90, %91, %92, %93, %94, %95, %96, %97, %98, %99, %100, %101, %102, %103, %104, %105, %106, %107, %108, %109, %110, %111, %112, %113, %114, %115, %116, %117, %118, %119, %120, %121, %122, %123, %124, %125, %126, %127}, da, db, p, 1, 1, 0, 1;\n}\n"
        : "+f"(d[0]), "+f"(d[1]), "+f"(d[2]), "+f"(d[3]), "+f"(d[4]), "+f"(d[5]), "+f"(d[6]), "+f"(d[7]), "+f"(d[8]), "+f"(d[9]), "+f"(d[10]), "+f"(d[11]), "+f"(d[12]), "+f"(d[13]), "+f"(d[14]), "+f"(d[15]), "+f"(d[16]), "+f"(d[17]), "+f"(d[18]), "+f"(d[19]), "+f"(d[20]), "+f"(d[21]), "+f"(d[22]), "+f"(d[23]), "+f"(d[24]), "+f"(d[25]), "+f"(d[26]), "+f"(d[27]), "+f"(d[28]), "+f"(d[29]), "+f"(d[30]), "+f"(d[31]), "+f"(d[32]), "+f"(d[33]), "+f"(d[34]), "+f"(d[35]), "+f"(d[36]), "+f"(d[37]), "+f"(d[38]), "+f"(d[39]), "+f"(d[40]), "+f"(d[41]), "+f"(d[42]), "+f"(d[43]), "+f"(d[44]), "+f"(d[45]), "+f"(d[46]), "+f"(d[47]), "+f"(d[48]), "+f"(d[49]), "+f"(d[50]), "+f"(d[51]), "+f"(d[52]), "+f"(d[53]), "+f"(d[54]), "+f"(d[55]), "+f"(d[56]), "+f"(d[57]), "+f"(d[58]), "+f"(d[59]), "+f"(d[60]), "+f"(d[61]), "+f"(d[62]), "+f"(d[63]), "+f"(d[64]), "+f"(d[65]), "+f"(d[66]), "+f"(d[67]), "+f"(d[68]), "+f"(d[69]), "+f"(d[70]), "+f"(d[71]), "+f"(d[72]), "+f"(d[73]), "+f"(d[74]), "+f"(d[75]), "+f"(d[76]), "+f"(d[77]), "+f"(d[78]), "+f"(d[79]), "+f"(d[80]), "+f"(d[81]), "+f"(d[82]), "+f"(d[83]), "+f"(d[84]), "+f"(d[85]), "+f"(d[86]), "+f"(d[87]), "+f"(d[88]), "+f"(d[89]), "+f"(d[90]), "+f"(d[91]), "+f"(d[92]), "+f"(d[93]), "+f"(d[94]), "+f"(d[95]), "+f"(d[96]), "+f"(d[97]), "+f"(d[98]), "+f"(d[99]), "+f"(d[100]), "+f"(d[101]), "+f"(d[102]), "+f"(d[103]), "+f"(d[104]), "+f"(d[105]), "+f"(d[106]), "+f"(d[107]), "+f"(d[108]), "+f"(d[109]), "+f"(d[110]), "+f"(d[111]), "+f"(d[112]), "+f"(d[113]), "+f"(d[114]), "+f"(d[115]), "+f"(d[116]), "+f"(d[117]), "+f"(d[118]), "+f"(d[119]), "+f"(d[120]), "+f"(d[121]), "+f"(d[122]), "+f"(d[123]), "+f"(d[124]), "+f"(d[125]), "+f"(d[126]), "+f"(d[127])
        : "r"(da_lo), "r"(db_lo), "r"(scale_d));
}
__device__ __forceinline__ void stmatrix_x4(uint32_t addr, uint32_t r0, uint32_t r1, uint32_t r2, uint32_t r3) {
    asm volatile("stmatrix.sync.aligned.m8n8.x4.shared.b16 [%0], {%1, %2, %3, %4};" :: "r"(addr), "r"(r0), "r"(r1), "r"(r2), "r"(r3) : "memory");
}
__device__ __forceinline__ void tma_store_2d(const CUtensorMap* map, uint32_t src, int c0, int c1) {
    asm volatile("cp.async.bulk.tensor.2d.global.shared::cta.bulk_group [%0, {%2, %3}], [%1];"
                 :: "l"((uint64_t)map), "r"(src), "r"(c0), "r"(c1) : "memory");
}
__device__ __forceinline__ float ex2f(float x) { float y; asm("ex2.approx.ftz.f32 %0, %1;" : "=f"(y) : "f"(x)); return y; }
__device__ __forceinline__ uint32_t pack_bf16(float lo, float hi) {
    __nv_bfloat162 v = __floats2bfloat162_rn(lo, hi);
    return *reinterpret_cast<uint32_t*>(&v);
}
__device__ __forceinline__ float bf16r(float x) { return __uint_as_float(pack_bf16(0.f, x) & 0xffff0000u); }
__device__ __forceinline__ void mma_16816(float (&c)[4], uint32_t a0, uint32_t a1, uint32_t a2, uint32_t a3,
                                          uint32_t b0, uint32_t b1) {
    asm volatile(
        "mma.sync.aligned.m16n8k16.row.col.f32.bf16.bf16.f32 {%0,%1,%2,%3}, {%4,%5,%6,%7}, {%8,%9}, {%0,%1,%2,%3};"
        : "+f"(c[0]), "+f"(c[1]), "+f"(c[2]), "+f"(c[3])
        : "r"(a0), "r"(a1), "r"(a2), "r"(a3), "r"(b0), "r"(b1));
}
__device__ __forceinline__ void ldmatrix_x4_trans(uint32_t& r0, uint32_t& r1, uint32_t& r2, uint32_t& r3, uint32_t addr) {
    asm volatile("ldmatrix.sync.aligned.m8n8.x4.trans.shared.b16 {%0,%1,%2,%3}, [%4];"
                 : "=r"(r0), "=r"(r1), "=r"(r2), "=r"(r3) : "r"(addr));
}

constexpr uint32_t FA_Q = 0, FA_KV = 65536, FA_O = 196608, FA_BAR = 229376;
constexpr int FA_ITEMS = 16 * NH;
__device__ __forceinline__ int fa_qt(int t) { return 15 - ((t & 127) >> 3); }
__device__ __forceinline__ int fa_head(int t) { return (t >> 7) * 8 + (t & 7); }
__device__ __forceinline__ uint32_t mbar_test(uint32_t bar, uint32_t parity) {
    uint32_t done;
    asm volatile(
        "{\n.reg .pred p;\n"
        "mbarrier.test_wait.parity.shared::cta.b64 p, [%1], %2;\n"
        "selp.u32 %0, 1, 0, p;\n}\n" : "=r"(done) : "r"(bar), "r"(parity) : "memory");
    return done;
}
__device__ __forceinline__ void mbar_arrive_if(uint32_t bar, bool c) {
    asm volatile("{\n.reg .pred p;\nsetp.ne.u32 p, %1, 0;\n@p mbarrier.arrive.shared::cta.b64 _, [%0];\n}" :: "r"(bar), "r"((uint32_t)c) : "memory");
}
__device__ __forceinline__ void sts128_if(bool c, uint32_t a, uint32_t v0, uint32_t v1, uint32_t v2, uint32_t v3) {
    asm volatile("{\n.reg .pred p;\nsetp.ne.u32 p, %5, 0;\n@p st.shared.v4.b32 [%0], {%1, %2, %3, %4};\n}" :: "r"(a), "r"(v0), "r"(v1), "r"(v2), "r"(v3), "r"((uint32_t)c) : "memory");
}
__device__ __forceinline__ void wgmma_rs_n128_tb_lo(float (&d)[64], const uint32_t* a, uint32_t db_lo, int scale_d) {
    asm volatile(
        "{\n.reg .pred p;\n.reg .b64 db;\nsetp.ne.b32 p, %69, 0;\nmov.b64 db, {%68, 0x40000040};\n"
        "wgmma.mma_async.sync.aligned.m64n128k16.f32.bf16.bf16 " ACC64_STR ", {%64, %65, %66, %67}, db, p, 1, 1, 1;\n}\n"
        : ACC64(d) : "r"(a[0]), "r"(a[1]), "r"(a[2]), "r"(a[3]), "r"(db_lo), "r"(scale_d));
}
#define FA_TEST 48
#define FA_PIN 32

__device__ __forceinline__ void wgmma_ss_n64_lo(float (&d)[64], uint32_t da_lo, uint32_t db_lo, int scale_d) {
    asm volatile(
        "{\n.reg .pred p;\n.reg .b64 da, db;\nsetp.ne.b32 p, %34, 0;\n"
        "mov.b64 da, {%32, 0x40000040};\nmov.b64 db, {%33, 0x40000040};\n"
        "wgmma.mma_async.sync.aligned.m64n64k16.f32.bf16.bf16 {%0, %1, %2, %3, %4, %5, %6, %7, %8, %9, %10, %11, %12, %13, %14, %15, "
        "%16, %17, %18, %19, %20, %21, %22, %23, %24, %25, %26, %27, %28, %29, %30, %31}, da, db, p, 1, 1, 0, 0;\n}\n"
        : "+f"(d[0]), "+f"(d[1]), "+f"(d[2]), "+f"(d[3]), "+f"(d[4]), "+f"(d[5]), "+f"(d[6]), "+f"(d[7]), "+f"(d[8]), "+f"(d[9]), "+f"(d[10]),
          "+f"(d[11]), "+f"(d[12]), "+f"(d[13]), "+f"(d[14]), "+f"(d[15]), "+f"(d[16]), "+f"(d[17]), "+f"(d[18]), "+f"(d[19]), "+f"(d[20]),
          "+f"(d[21]), "+f"(d[22]), "+f"(d[23]), "+f"(d[24]), "+f"(d[25]), "+f"(d[26]), "+f"(d[27]), "+f"(d[28]), "+f"(d[29]), "+f"(d[30]), "+f"(d[31])
        : "r"(da_lo), "r"(db_lo), "r"(scale_d));
}
#define FA_NOFB 0
#define FA_DPIN 16
#define FA_RLO 40
#define FA_RHI 232
#define FA_LIM 0x1p40f
__device__ __forceinline__ uint32_t attn_consumer(const uint32_t sb, const int wg, const int w4, const int lane) {
    const uint32_t bar_q = sb + FA_BAR, bar_of = bar_q + 96, bar_oe = bar_q + 112, oslot = bar_q + 144;
    const bool lane0 = lane == 0;
    float o[64], sacc[64];
    uint32_t pa[32];
    float ms0 = 0.f, ms1 = 0.f, lrow0 = 1.f, lrow1 = 1.f;
    const float sc = 0.08838834764831845f * 1.4426950408889634f;
    const uint32_t q_lo = desc_lo(sb + FA_Q + wg * 8192, 16), k_lo = desc_lo(sb + FA_KV, 16), v_lo = desc_lo(sb + FA_KV + 32768, 16384);
    uint32_t qd = q_lo + 2048, kd = k_lo + 4096, vd = v_lo, bs = bar_q + 8, bi = bar_q + 8;
    auto issue_qk = [&](uint32_t a, bool half) {
        const uint32_t b = kd;
#pragma unroll
        for (int kk = 0; kk < 8; kk++) {
            if (half) wgmma_ss_n64_lo(sacc, a + (kk >> 2) * 1024 + (kk & 3) * 2, b + (kk >> 2) * 1024 + (kk & 3) * 2, kk != 0);
            else wgmma_ss_n128_lo<0>(sacc, a + (kk >> 2) * 1024 + (kk & 3) * 2, b + (kk >> 2) * 1024 + (kk & 3) * 2, kk != 0);
        }
        wgmma_commit();
    };
    auto issue_pv = [&](bool acc) {
        const uint32_t b = vd;
#pragma unroll
        for (int kk = 0; kk < 8; kk++) wgmma_rs_n128_tb_lo(o, &pa[kk * 4], b + kk * 128, kk != 0 || acc);
        wgmma_commit();
    };
    auto turn_wait = [&]() { asm volatile("bar.sync %0, 256;" :: "r"(1 + wg) : "memory"); };
    auto turn_pass = [&]() { asm volatile("bar.arrive %0, 256;" :: "r"(2 - wg) : "memory"); };
    int item = -1, it = -1, j = 0, nkv = 1, t = 0;
    auto redo = [&](float& l0, float& l1) {
        const size_t row0 = (size_t)fa_head(t) * SEQ + (lane >> 2);
        const uint32_t* qg = reinterpret_cast<const uint32_t*>(g_QA + (row0 + (nkv - 1) * 128 + wg * 64 + w4 * 16) * HD) + (lane & 3);
        const uint32_t* kg = reinterpret_cast<const uint32_t*>(g_KA + (row0 + (nkv - 1 - j) * 128) * HD) + (lane & 3);
        auto ldg = [](const uint32_t* p) { uint32_t v; asm volatile("ld.relaxed.gpu.global.u32 %0, [%1];" : "=r"(v) : "l"(p) : "memory"); return v; };
        const int r0 = j ? 1 << 20 : wg * 64 + w4 * 16 + (lane >> 2) - (lane & 3) * 2;
        float mx0 = -INFINITY, mx1 = -INFINITY;
        const float m0 = ms0, m1 = ms1;
        uint4 tmp[8];
        l0 = 0.f; l1 = 0.f;
#pragma unroll 1
        for (int ps = 0; ps < 32; ps++) {
            const int nb = ps & 15;
            float c[4] = {0.f, 0.f, 0.f, 0.f};
#pragma unroll 1
            for (int kk = 0; kk < 64; kk += 8)
                mma_16816(c, ldg(qg + kk), ldg(qg + kk + 8 * 64), ldg(qg + kk + 4), ldg(qg + kk + 8 * 64 + 4), ldg(kg + nb * 8 * 64 + kk), ldg(kg + nb * 8 * 64 + kk + 4));
#pragma unroll
            for (int i = 0; i < 4; i++)
                if (nb * 8 + (i & 1) - ((i & 2) ? 8 : 0) > r0) c[i] = -INFINITY;
            mx0 = fmaxf(mx0, fmaxf(c[0], c[1])); mx1 = fmaxf(mx1, fmaxf(c[2], c[3]));
#pragma unroll
            for (int i = 0; i < 4; i++) c[i] = ex2f(fmaf(c[i], sc, (i & 2) ? ms1 : ms0));
            l0 += c[0] + c[1]; l1 += c[2] + c[3];
            reinterpret_cast<uint2*>(tmp)[nb] = make_uint2(pack_bf16(c[0], c[1]), pack_bf16(c[2], c[3]));
            if (ps == 15) {
                mx0 = fmaxf(mx0, __shfl_xor_sync(0xffffffff, mx0, 1)); mx1 = fmaxf(mx1, __shfl_xor_sync(0xffffffff, mx1, 1));
                mx0 = fmaxf(mx0, __shfl_xor_sync(0xffffffff, mx0, 2)); mx1 = fmaxf(mx1, __shfl_xor_sync(0xffffffff, mx1, 2));
                ms0 = fminf(-mx0 * sc, ms0); ms1 = fminf(-mx1 * sc, ms1);
                l0 = 0.f; l1 = 0.f;
            }
        }
        const float a0 = ex2f(ms0 - m0), a1 = ex2f(ms1 - m1);
        lrow0 *= a0; lrow1 *= a1;
#pragma unroll
        for (int i = 0; i < 64; i++) o[i] *= (i & 2) ? a1 : a0;
#pragma unroll
        for (int i = 0; i < 8; i++) { pa[4 * i] = tmp[i].x; pa[4 * i + 1] = tmp[i].y; pa[4 * i + 2] = tmp[i].z; pa[4 * i + 3] = tmp[i].w; }
    };
    auto pin_after = [&](float v) {
        asm volatile("{\n.reg .pred p;\nsetp.eq.f32 p, %1, %2;\n@p st.shared.f32 [%0], %1;\n}" :: "r"(oslot + 16), "f"(v), "f"(ms0) : "memory");
    };
    auto pack_p = [&](int i) {
        if (i >= FA_PIN) pa[i >> 1] = pack_bf16(sacc[i - 1], sacc[i]);
        else asm volatile("{\n.reg .pred p;\nsetp.ne.b32 p, %3, 0x7fc12345;\n@p cvt.rn.bf16x2.f32 %0, %2, %1;\n}" : "+r"(pa[i >> 1]) : "f"(sacc[i - 1]), "f"(sacc[i]), "r"(__float_as_uint(o[0])));
    };
    uint32_t ok = 0, okq = 0;
    int tn = 0;
    auto tests = [&]() {
        ok = mbar_test(bs + 48, (it >> 1) & 1);
        asm volatile("ld.shared.s32 %0, [%1];" : "=r"(tn) : "r"((bi ^ 8) + 128) : "memory");
        ok &= mbar_test((bs ^ 8) + 32, ((it + 1) >> 1) & 1);
        okq = mbar_test(bi ^ 8, ((item + 1) >> 1) & 1);
    };
    auto epilogue = [&](int tag, bool real) {
        float l0 = lrow0, l1 = lrow1;
        l0 += __shfl_xor_sync(0xffffffff, l0, 1); l1 += __shfl_xor_sync(0xffffffff, l1, 1);
        l0 += __shfl_xor_sync(0xffffffff, l0, 2); l1 += __shfl_xor_sync(0xffffffff, l1, 2);
        float i0, i1;
        asm("rcp.approx.ftz.f32 %0, %1;" : "=f"(i0) : "f"(l0));
        asm("rcp.approx.ftz.f32 %0, %1;" : "=f"(i1) : "f"(l1));
        const int row = w4 * 16 + (lane >> 2);
        const uint32_t stg = sb + FA_O + wg * 16384 + row * 128;
#pragma unroll
        for (int i = 0; i < 4; i++) {
            const int ch = i * 4 + (lane & 3);
            const uint32_t a = stg + (ch >> 3) * 8192 + (((ch & 7) ^ (row & 7)) << 4);
            const float* q = &o[i * 16];
            sts128_if(real, a, pack_bf16(q[0] * i0, q[1] * i0), pack_bf16(q[4] * i0, q[5] * i0), pack_bf16(q[8] * i0, q[9] * i0), pack_bf16(q[12] * i0, q[13] * i0));
            sts128_if(real, a + 1024, pack_bf16(q[2] * i1, q[3] * i1), pack_bf16(q[6] * i1, q[7] * i1), pack_bf16(q[10] * i1, q[11] * i1), pack_bf16(q[14] * i1, q[15] * i1));
        }
        asm volatile("st.shared.s32 [%0], %1;" :: "r"(oslot + wg * 4), "r"(tag) : "memory");
        __syncwarp();
        mbar_arrive_if(bar_of + 8 * wg, lane0 && real);
    };
    auto transition = [&](auto wgc, float& l0, float& l1) {
        constexpr int WG = decltype(wgc)::value;
        constexpr int NE = WG == 0 ? 32 : 64;
        turn_wait();
        wgmma_fence();
        issue_qk(qd, WG == 0);
        issue_pv(nkv > 1);
        turn_pass();
        const int tc = t;
        t = __shfl_sync(0xffffffff, tn, 0);
        nkv = fa_qt(t) + 1;
        mbar_wait(bar_oe + 8 * wg, (max(item, 0) & 1) ^ 1);
        item++; bi ^= 8;
        wgmma_wait<1>();
        mbar_arrive_if(bs + 64, lane0);
        mbar_arrive_if(bi + 16, lane0 && nkv == 1);
        ms0 = -sc * __shfl_sync(0xffffffff, sacc[0], lane & 28); ms1 = -sc * __shfl_sync(0xffffffff, sacc[2], lane & 28);
        const int r0 = w4 * 16 + (lane >> 2) - (lane & 3) * 2;
#pragma unroll
        for (int i = 0; i < 32; i++)
            if ((i >> 2) * 8 + (i & 1) - ((i & 2) ? 8 : 0) > r0) sacc[WG * 32 + i] = -INFINITY;
        float sum[4];
#pragma unroll
        for (int i = 0; i < FA_DPIN; i++) { sacc[i] = ex2f(fmaf(sacc[i], sc, (i & 2) ? ms1 : ms0)); sum[i & 3] = i < 4 ? sacc[i] : sum[i & 3] + sacc[i]; }
        pin_after((sum[0] + sum[1]) + (sum[2] + sum[3]));
        wgmma_wait<0>();
        mbar_arrive_if((bs ^ 8) + 80, lane0 && item > 0);
        epilogue(tc, item > 0);
#pragma unroll
        for (int i = 0; i < NE; i++) {
            if (i >= FA_DPIN) { sacc[i] = ex2f(fmaf(sacc[i], sc, (i & 2) ? ms1 : ms0)); sum[i & 3] += sacc[i]; }
            if (i & 1) pack_p(i);
            if (i == NE - 16) { pin_after(sum[0]); tests(); }
        }
        if (NE == 32)
#pragma unroll
            for (int i = 16; i < 32; i++) asm volatile("mov.u32 %0, 0;" : "=r"(pa[i]));
        l0 = sum[0] + sum[1]; l1 = sum[2] + sum[3];
    };
#pragma unroll
    for (int i = 0; i < 32; i++) pa[i] = 0u;
#pragma unroll 1
    for (;;) {
        float l0, l1;
        it++;
        kd = 2 * k_lo + 4096 - kd; vd = 2 * v_lo + 4096 - vd; bs ^= 8;
        if (++j < nkv) {
            if (__builtin_expect(!ok, 0)) {
                mbar_wait(bs + 32, (it >> 1) & 1);
                mbar_wait((bs ^ 8) + 48, ((it - 1) >> 1) & 1);
            }
            turn_wait();
            wgmma_fence();
            issue_qk(qd, false);
            issue_pv(j > 1);
            turn_pass();
            wgmma_wait<1>();
            mbar_arrive_if(bs + 64, lane0);
            mbar_arrive_if(bi + 16, lane0 && j == nkv - 1);
            float sum[4];
#pragma unroll
            for (int i = 0; i < FA_PIN; i++) { sacc[i] = ex2f(fmaf(sacc[i], sc, (i & 2) ? ms1 : ms0)); sum[i & 3] = i < 4 ? sacc[i] : sum[i & 3] + sacc[i]; }
            pin_after((sum[0] + sum[1]) + (sum[2] + sum[3]));
            wgmma_wait<0>();
            mbar_arrive_if((bs ^ 8) + 80, lane0);
#pragma unroll
            for (int i = 0; i < 64; i++) {
                if (i >= FA_PIN) { sacc[i] = ex2f(fmaf(sacc[i], sc, (i & 2) ? ms1 : ms0)); sum[i & 3] = i < 4 ? sacc[i] : sum[i & 3] + sacc[i]; }
                if (i & 1) pack_p(i);
                if (i == FA_TEST) { pin_after(sum[0]); tests(); }
            }
            l0 = sum[0] + sum[1]; l1 = sum[2] + sum[3];
        } else {
            if (__builtin_expect(!(ok & okq), 0)) {
                mbar_wait(bi ^ 8, ((item + 1) >> 1) & 1);
                asm volatile("ld.shared.s32 %0, [%1];" : "=r"(tn) : "r"((bi ^ 8) + 128) : "memory");
                mbar_wait((bs ^ 8) + 48, ((it - 1) >> 1) & 1);
                if (tn < 0) break;
                mbar_wait(bs + 32, (it >> 1) & 1);
            }
            qd = 2 * q_lo + 2048 - qd;
            if (wg == 0) transition(std::integral_constant<int, 0>(), l0, l1); else transition(std::integral_constant<int, 1>(), l0, l1);
            j = 0;
            lrow0 = 0.f; lrow1 = 0.f;
        }
        if (!FA_NOFB && __builtin_expect(__any_sync(0xffffffff, !(l0 + l1 < FA_LIM)), 0)) redo(l0, l1);
        lrow0 += l0; lrow1 += l1;
    }
    wgmma_fence();
    issue_pv(nkv > 1);
    mbar_wait(bar_oe + 8 * wg, (item & 1) ^ 1);
    wgmma_wait<0>();
    mbar_arrive_if((bs ^ 8) + 80, lane0);
    epilogue(t | 0x80000000, true);
    return __shfl_sync(0xffffffff, ~tn * 2 + (item & 1), 0);
}

__device__ __forceinline__ uint32_t cluster_ctarank() {
    uint32_t r; asm volatile("mov.u32 %0, %%cluster_ctarank;" : "=r"(r)); return r;
}
__device__ __forceinline__ uint32_t mapa_u32(uint32_t addr, uint32_t rank) {
    uint32_t r; asm volatile("mapa.shared::cluster.u32 %0, %1, %2;" : "=r"(r) : "r"(addr), "r"(rank)); return r;
}
__device__ __forceinline__ void cluster_sync_all() {
    asm volatile("barrier.cluster.arrive.release.aligned;\nbarrier.cluster.wait.acquire.aligned;" ::: "memory");
}
__device__ __forceinline__ void cluster_sync_relaxed() {
    asm volatile("barrier.cluster.arrive.relaxed.aligned;\nbarrier.cluster.wait.aligned;" ::: "memory");
}
__device__ __forceinline__ void st_async_v4(uint32_t addr, uint32_t a, uint32_t b, uint32_t c, uint32_t d, uint32_t mbar) {
    asm volatile("st.async.weak.shared::cluster.mbarrier::complete_tx::bytes.v4.b32 [%0], {%1, %2, %3, %4}, [%5];"
                 :: "r"(addr), "r"(a), "r"(b), "r"(c), "r"(d), "r"(mbar) : "memory");
}
__device__ __forceinline__ void st_async_v2(uint32_t addr, uint32_t a, uint32_t b, uint32_t mbar) {
    asm volatile("st.async.weak.shared::cluster.mbarrier::complete_tx::bytes.v2.b32 [%0], {%1, %2}, [%3];"
                 :: "r"(addr), "r"(a), "r"(b), "r"(mbar) : "memory");
}
__device__ __forceinline__ void st_async_b32(uint32_t addr, uint32_t a, uint32_t mbar) {
    asm volatile("st.async.weak.shared::cluster.mbarrier::complete_tx::bytes.b32 [%0], %1, [%2];" :: "r"(addr), "r"(a), "r"(mbar) : "memory");
}
__device__ __forceinline__ void pace(int cycles) {
    if (cycles > 0) {
        uint32_t t0, t;
        asm volatile("mov.u32 %0, %%clock;" : "=r"(t0));
        do { asm volatile("mov.u32 %0, %%clock;" : "=r"(t)); } while (t - t0 < (uint32_t)cycles);
    }
}
__device__ __forceinline__ void mbar_wait_cl(uint32_t bar, uint32_t parity) {
    uint32_t done = 0;
    for (int it = 0; it < (1 << 22) && !done; it++) {
        asm volatile(
            "{\n.reg .pred p;\n"
            "mbarrier.try_wait.parity.shared::cta.b64 p, [%1], %2;\n"
            "selp.u32 %0, 1, 0, p;\n}\n" : "=r"(done) : "r"(bar), "r"(parity) : "memory");
    }
}
__device__ __forceinline__ void ldmatrix_x4(uint32_t& r0, uint32_t& r1, uint32_t& r2, uint32_t& r3, uint32_t addr) {
    asm volatile("ldmatrix.sync.aligned.m8n8.x4.shared.b16 {%0,%1,%2,%3}, [%4];"
                 : "=r"(r0), "=r"(r1), "=r"(r2), "=r"(r3) : "r"(addr));
}
__device__ __forceinline__ void cp_async16(uint32_t dst, const void* src) {
    asm volatile("cp.async.cg.shared.global [%0], [%1], 16;" :: "r"(dst), "l"(src) : "memory");
}

#define DBG(i)
#define DBGW(i, w)
#define CYC(i)
#define TM(i)
__device__ __forceinline__ void tma_load_2d_mc(uint32_t dst, const CUtensorMap* map, uint32_t bar, int c0, int c1, uint16_t mask) {
    asm volatile(
        "cp.async.bulk.tensor.2d.shared::cluster.global.mbarrier::complete_tx::bytes.multicast::cluster [%0], [%1, {%3, %4}], [%2], %5;"
        :: "r"(dst), "l"((uint64_t)map), "r"(bar), "r"(c0), "r"(c1), "h"(mask) : "memory");
}
__device__ __forceinline__ void tma_load_2d_mc(uint32_t dst, const CUtensorMap* map, uint32_t bar, int c0, int c1, uint16_t mask, uint64_t hint) {
    asm volatile(
        "cp.async.bulk.tensor.2d.shared::cluster.global.mbarrier::complete_tx::bytes.multicast::cluster.L2::cache_hint [%0], [%1, {%3, %4}], [%2], %5, %6;"
        :: "r"(dst), "l"((uint64_t)map), "r"(bar), "r"(c0), "r"(c1), "h"(mask), "l"(hint) : "memory");
}
__device__ __forceinline__ void bulk_s2s(uint32_t dst_cl, uint32_t src, uint32_t bytes, uint32_t bar_cl) {
    asm volatile("cp.async.bulk.shared::cluster.shared::cta.mbarrier::complete_tx::bytes [%0], [%1], %2, [%3];"
                 :: "r"(dst_cl), "r"(src), "r"(bytes), "r"(bar_cl) : "memory");
}
__device__ __forceinline__ bool elect_one() {
    uint32_t p;
    asm volatile("{\n.reg .pred p;\nelect.sync _|p, 0xffffffff;\nselp.u32 %0, 1, 0, p;\n}" : "=r"(p));
    return p;
}
__device__ __forceinline__ void fence_async_smem() { asm volatile("fence.proxy.async.shared::cta;" ::: "memory"); }
template <int ID, int N> __device__ __forceinline__ void bar_sync() { asm volatile("bar.sync %0, %1;" :: "n"(ID), "n"(N) : "memory"); }
template <int ID, int N> __device__ __forceinline__ void bar_arrive() { asm volatile("bar.arrive %0, %1;" :: "n"(ID), "n"(N) : "memory"); }
__device__ __forceinline__ void sts32(uint32_t a, uint32_t v) { asm volatile("st.shared.u32 [%0], %1;" :: "r"(a), "r"(v) : "memory"); }
__device__ __forceinline__ void ldsm_x4(uint32_t* r, uint32_t addr) {
    asm volatile("ldmatrix.sync.aligned.m8n8.x4.shared.b16 {%0,%1,%2,%3}, [%4];" : "=r"(r[0]), "=r"(r[1]), "=r"(r[2]), "=r"(r[3]) : "r"(addr) : "memory");
}
__device__ __forceinline__ uint32_t pin(uint32_t v) { asm volatile("" : "+r"(v)); return v; }
constexpr uint32_t DHI128 = 0x40000040u, DHI32 = 0xC0000010u;
#define ACC16(d) "+f"(d[0]), "+f"(d[1]), "+f"(d[2]), "+f"(d[3]), "+f"(d[4]), "+f"(d[5]), "+f"(d[6]), "+f"(d[7]), "+f"(d[8]), "+f"(d[9]), "+f"(d[10]), \
    "+f"(d[11]), "+f"(d[12]), "+f"(d[13]), "+f"(d[14]), "+f"(d[15])
#define ACC20(d) ACC16(d), "+f"(d[16]), "+f"(d[17]), "+f"(d[18]), "+f"(d[19])
__device__ __forceinline__ void wgmma_rs(float (&d)[16], const uint32_t (&a)[4], uint32_t db_lo) {
    asm volatile(
        "{\n.reg .b64 db;\nmov.b64 db, {%20, %21};\n"
        "wgmma.mma_async.sync.aligned.m64n32k16.f32.bf16.bf16 {%0,%1,%2,%3,%4,%5,%6,%7,%8,%9,%10,%11,%12,%13,%14,%15}, {%16,%17,%18,%19}, db, 1, 1, 1, 0;\n}\n"
        : ACC16(d) : "r"(a[0]), "r"(a[1]), "r"(a[2]), "r"(a[3]), "r"(db_lo), "n"(DHI128));
}
__device__ __forceinline__ void wgmma_rs(float (&d)[20], const uint32_t (&a)[4], uint32_t db_lo) {
    asm volatile(
        "{\n.reg .b64 db;\nmov.b64 db, {%24, %25};\n"
        "wgmma.mma_async.sync.aligned.m64n40k16.f32.bf16.bf16 {%0,%1,%2,%3,%4,%5,%6,%7,%8,%9,%10,%11,%12,%13,%14,%15,%16,%17,%18,%19}, {%20,%21,%22,%23}, db, 1, 1, 1, 0;\n}\n"
        : ACC20(d) : "r"(a[0]), "r"(a[1]), "r"(a[2]), "r"(a[3]), "r"(db_lo), "n"(DHI128));
}
template <uint32_t AHI, uint32_t BHI>
__device__ __forceinline__ void wgmma_ss(float (&d)[16], uint32_t da_lo, uint32_t db_lo) {
    asm volatile(
        "{\n.reg .b64 da, db;\nmov.b64 da, {%16, %18};\nmov.b64 db, {%17, %19};\n"
        "wgmma.mma_async.sync.aligned.m64n32k16.f32.bf16.bf16 {%0,%1,%2,%3,%4,%5,%6,%7,%8,%9,%10,%11,%12,%13,%14,%15}, da, db, 1, 1, 1, 0, 0;\n}\n"
        : ACC16(d) : "r"(da_lo), "r"(db_lo), "n"(AHI), "n"(BHI));
}
template <uint32_t AHI, uint32_t BHI>
__device__ __forceinline__ void wgmma_ss(float (&d)[20], uint32_t da_lo, uint32_t db_lo) {
    asm volatile(
        "{\n.reg .b64 da, db;\nmov.b64 da, {%20, %22};\nmov.b64 db, {%21, %23};\n"
        "wgmma.mma_async.sync.aligned.m64n40k16.f32.bf16.bf16 {%0,%1,%2,%3,%4,%5,%6,%7,%8,%9,%10,%11,%12,%13,%14,%15,%16,%17,%18,%19}, da, db, 1, 1, 1, 0, 0;\n}\n"
        : ACC20(d) : "r"(da_lo), "r"(db_lo), "n"(AHI), "n"(BHI));
}
template <uint32_t AHI, uint32_t BHI>
__device__ __forceinline__ void wgmma_ss0(float (&d)[20], uint32_t da_lo, uint32_t db_lo) {
    asm volatile(
        "{\n.reg .b64 da, db;\nmov.b64 da, {%20, %22};\nmov.b64 db, {%21, %23};\n"
        "wgmma.mma_async.sync.aligned.m64n40k16.f32.bf16.bf16 {%0,%1,%2,%3,%4,%5,%6,%7,%8,%9,%10,%11,%12,%13,%14,%15,%16,%17,%18,%19}, da, db, 0, 1, 1, 0, 0;\n}\n"
        : "=f"(d[0]), "=f"(d[1]), "=f"(d[2]), "=f"(d[3]), "=f"(d[4]), "=f"(d[5]), "=f"(d[6]), "=f"(d[7]), "=f"(d[8]), "=f"(d[9]), "=f"(d[10]),
          "=f"(d[11]), "=f"(d[12]), "=f"(d[13]), "=f"(d[14]), "=f"(d[15]), "=f"(d[16]), "=f"(d[17]), "=f"(d[18]), "=f"(d[19])
        : "r"(da_lo), "r"(db_lo), "n"(AHI), "n"(BHI));
}
__device__ __forceinline__ void wgmma_ss_n8(float (&d)[4], uint32_t da_lo, uint32_t db_lo) {
    asm volatile(
        "{\n.reg .b64 da, db;\nmov.b64 da, {%4, %6};\nmov.b64 db, {%5, %7};\n"
        "wgmma.mma_async.sync.aligned.m64n8k16.f32.bf16.bf16 {%0,%1,%2,%3}, da, db, 1, 1, 1, 1, 0;\n}\n"
        : "+f"(d[0]), "+f"(d[1]), "+f"(d[2]), "+f"(d[3]) : "r"(da_lo), "r"(db_lo), "n"(DHI128), "n"(DHI32));
}

__device__ __forceinline__ void wgmma_ss_n32_ta(float (&d)[16], uint32_t da_lo, uint32_t db_lo) {
    asm volatile(
        "{\n.reg .b64 da, db;\nmov.b64 da, {%16, %18};\nmov.b64 db, {%17, %18};\n"
        "wgmma.mma_async.sync.aligned.m64n32k16.f32.bf16.bf16 {%0,%1,%2,%3,%4,%5,%6,%7,%8,%9,%10,%11,%12,%13,%14,%15}, da, db, 1, 1, 1, 1, 0;\n}\n"
        : ACC16(d) : "r"(da_lo), "r"(db_lo), "n"(DHI128));
}

constexpr int C2_NS = 4;
#define LAY         160, 127, 0, 16, 24, 8, 47, 87, 150, 135, 147, 32, 159, 0, 87, 119
constexpr uint32_t c2_lay(int i) { constexpr uint32_t t[16] = {LAY}; return t[i] * 1024; }
constexpr uint32_t C2_WO = c2_lay(0);
constexpr uint32_t C2_WQ = c2_lay(1), C2_WK = c2_lay(2), C2_WV = c2_lay(3);
constexpr uint32_t C2_OB = c2_lay(4);
constexpr uint32_t C2_QM = c2_lay(5);
constexpr uint32_t C2_SC = C2_QM + 1024;
constexpr uint32_t C2_PB = c2_lay(12) + 256;
#define CH_CS (C2_QM + 4096)
constexpr uint32_t C2_CS = CH_CS;
constexpr uint32_t C2_XB = c2_lay(6), C2_XS = c2_lay(7) - c2_lay(6);
constexpr uint32_t C2_QX = c2_lay(8);
constexpr uint32_t C2_KX = C2_QX + 4096;
constexpr uint32_t C2_VT = c2_lay(9);
constexpr uint32_t C2_PX = c2_lay(10);
constexpr uint32_t C2_SX = c2_lay(11);
constexpr uint32_t C2_BAR = c2_lay(12), C2_S0 = c2_lay(13), C2_S1 = c2_lay(14), C2_S2 = c2_lay(15);
constexpr uint32_t C2_GT = C2_BAR + 256;
constexpr uint32_t C2_T0 = (C2_XB >> 10) * 0x01010101u + 0x18100800u, C2_T1 = ((C2_XB >> 10) + 32) | C2_OB >> 10 << 8 | C2_QM >> 10 << 16 | C2_WQ >> 10 << 24;
__device__ __forceinline__ uint32_t c2_ts(uint32_t r) { return __byte_perm(C2_T0, C2_T1, r) & 0xff; }
constexpr int C2_SMEM = 232448;
#define CH_SPQ 28
#define CH_SPK 0
#define CH_SPV 0
#define CH_EARLY 1
#define CH_ARM 0
#define CH_MB 1
#define CH_TW 1
#define CH_LD 0
#define CH_PFD 0
#define CH_PT 0
#define CH_PT1 CH_PT
#define CH_PF2 0
#define CH_EFW 0
#define CH_TS 1
#define CH_WOT 1
#define CH_NCH 4
#define CH_NQ1 12
#define CH_POLL_DELAY 500

__device__ __forceinline__ uint32_t c2_stage(int wg, int i) { return (wg == 0 ? C2_S0 : wg == 1 ? C2_S1 : C2_S2) + i * 8192; }
__device__ __forceinline__ void c2_stage_load(const CUtensorMap* map, uint32_t sb, int wg, int rank, int col0, int round) {
    const uint32_t bar = sb + C2_BAR + 176 + (wg * 2 + round) * 8;
    mbar_expect_tx(bar, 32768);
#pragma unroll 1
    for (int i = 0; i < 4; i++) {
        tma_load_2d(sb + c2_stage(wg, i), map, bar, col0, ((rank - round * 4 - i) & 7) * 64, CH_EFW ? L2_FIRST : L2_NORMAL);
        if (i < 3) pace(round ? CH_PT1 : CH_PT);
    }
}
__device__ __forceinline__ void c2_load_w(uint32_t (&w)[32][4], const CUtensorMap* map, int wg, int rank, int col0, uint32_t t128, uint32_t ws, uint32_t sb) {
    const uint32_t s0 = pin(sb + c2_stage(wg, 0) + t128), s1 = pin(sb + c2_stage(wg, 0) + (t128 ^ 16) + 128);
#pragma unroll
    for (int r = 0; r < 2; r++) {
        mbar_wait(sb + C2_BAR + 176 + (wg * 2 + r) * 8, 0);
#pragma unroll
        for (int e = 0; e < 16; e++) {
            uint32_t w0, w1, w2, w3;
            asm volatile("ld.shared.b32 %0, [%1];" : "=r"(w0) : "r"(s0 + e * 2048) : "memory");
            asm volatile("ld.shared.b32 %0, [%1];" : "=r"(w1) : "r"(s1 + e * 2048) : "memory");
            asm volatile("ld.shared.b32 %0, [%1];" : "=r"(w2) : "r"(s0 + e * 2048 + 1024) : "memory");
            asm volatile("ld.shared.b32 %0, [%1];" : "=r"(w3) : "r"(s1 + e * 2048 + 1024) : "memory");
            uint32_t* d = w[r * 16 + e];
            d[0] = __byte_perm(w0, w1, 0x5410); d[1] = __byte_perm(w0, w1, 0x7632);
            d[2] = __byte_perm(w2, w3, 0x5410); d[3] = __byte_perm(w2, w3, 0x7632);
        }
        if (r == 0) {
            asm volatile("bar.sync %0, 128;" :: "r"(8 + wg) : "memory");
            if ((threadIdx.x & 127) == 32) c2_stage_load(map, sb, wg, rank, col0, 1);
            mbar_wait(sb + C2_BAR + 168, 0);
#pragma unroll 1
            for (int i = threadIdx.x; i < 2048; i += 384) {
                const int k = i >> 2, b = i & 3;
                const uint32_t a0 = sb + C2_WO + k * 128 + (((2 * b) ^ (k & 7)) << 4), a1 = a0 ^ 16;
                uint4 u, v;
                asm volatile("ld.shared.v4.b32 {%0, %1, %2, %3}, [%4];" : "=r"(u.x), "=r"(u.y), "=r"(u.z), "=r"(u.w) : "r"(a0) : "memory");
                asm volatile("ld.shared.v4.b32 {%0, %1, %2, %3}, [%4];" : "=r"(v.x), "=r"(v.y), "=r"(v.z), "=r"(v.w) : "r"(a1) : "memory");
                asm volatile("st.shared.v4.b32 [%0], {%1, %2, %3, %4};" :: "r"(a0), "r"(__byte_perm(u.x, u.y, 0x5410)),
                             "r"(__byte_perm(u.z, u.w, 0x5410)), "r"(__byte_perm(v.x, v.y, 0x5410)), "r"(__byte_perm(v.z, v.w, 0x5410)) : "memory");
                asm volatile("st.shared.v4.b32 [%0], {%1, %2, %3, %4};" :: "r"(a1), "r"(__byte_perm(u.x, u.y, 0x7632)),
                             "r"(__byte_perm(u.z, u.w, 0x7632)), "r"(__byte_perm(v.x, v.y, 0x7632)), "r"(__byte_perm(v.z, v.w, 0x7632)) : "memory");
            }
        }
    }
    cluster_sync_relaxed();
#pragma unroll
    for (int e = 0; e < C2_NS; e++) stmatrix_x4(ws + e * 2048, w[e][0], w[e][1], w[e][2], w[e][3]);
#pragma unroll 1
    for (int i = threadIdx.x; i < 2 * 512 + 256; i += 384)
        sts32(sb + (i < 1024 ? C2_VT + (i >> 9) * 6144 + 4096 + (i & 511) * 4 : C2_PX + 2048 + (i - 1024) * 4), 0u);
    fence_async_smem();
    asm volatile("bar.sync %0, 128;" :: "r"(8 + wg) : "memory");
}
template <int E0, int E1, int SP, int NA>
__device__ __forceinline__ void c2_xstream(float (&acc)[NA], const uint32_t (&w)[32][4], uint32_t xlo, uint32_t rank, uint32_t wslo) {
    if (E0 == 0)
#pragma unroll
        for (int i = 0; i < NA; i++) acc[i] = 0.f;
    wgmma_fence();
#pragma unroll
    for (int n = E0; n < E1; n++) {
        const int e = n < SP ? n + C2_NS : n < SP + C2_NS ? n - SP : n;
        if (e < C2_NS) wgmma_ss<DHI32, DHI128>(acc, wslo + e * 128, xlo + ((rank - (e >> 2)) & 7) * 320 + (e & 3) * 2);
        else wgmma_rs(acc, w[e], xlo + ((rank - (e >> 2)) & 7) * 320 + (e & 3) * 2);
    }
    wgmma_commit();
}
__device__ __forceinline__ constexpr int c2_grp(int i) { return i < 2 ? i : 1 + (i >> 1); }

struct ChainParams {
    CUtensorMap mapX;
    CUtensorMap mapM;
    CUtensorMap mapW[3];
    CUtensorMap mapWo;
    CUtensorMap mapC;
    CUtensorMap mapS;
    bf16* out;
};
__global__ void __cluster_dims__(8, 1, 1) __launch_bounds__(384, 1)
chain_kernel(const __grid_constant__ ChainParams P) {
    const CUtensorMap& mapX = P.mapX;
    extern __shared__ __align__(1024) uint8_t smem_chain[];
    const uint32_t sb = smem_u32(smem_chain);
    const uint32_t dlo = ((sb & 0x3FFFF) >> 4) | (1u << 16);
    const int tid = __shfl_sync(0xffffffff, threadIdx.x, threadIdx.x & 31), lane = tid & 31;
    const int warp = __shfl_sync(0xffffffff, tid >> 5, 0), wg = warp >> 2, w4 = warp & 3;
    const uint32_t rank = cluster_ctarank();
    const int C = blockIdx.x >> 3;
    const int h = C * 4 + (rank >> 1);
    const int g = lane >> 2, qc = lane & 3;
    pdl_launch_dependents();
    TS_BEGIN(2);
    CYC(0);
    const uint32_t bar_m = sb + C2_BAR, bar_o = bar_m + 64, bar_sc = bar_m + 128, bar_x = bar_m + 136, bar_sx = bar_m + 152;
    const uint32_t bar_w = bar_m + 168, bar_h = bar_m + 40;
    const int col0 = h * HD + (rank & 1) * 64;
    if (tid == 0) {
        for (int j = 0; j < 5; j++) { mbar_init(bar_m + 8 * j, j ? 1 : 4); mbar_init(bar_o + 8 * j, j ? 1 : 4); }
        for (int j = 0; j < 12; j++) mbar_init(bar_sc + 8 * j, 1);
        mbar_init(bar_h, 32);
        asm volatile("fence.mbarrier_init.release.cluster;" ::: "memory");
    }
    __syncwarp();
    cluster_sync_relaxed();
    if (tid == 0) {
        mbar_expect_tx(bar_x, 32768 + 8192);
        tma_load_2d_mc(sb + C2_XB + rank * 5120, &mapX, bar_x, rank * 64, 0, (uint16_t)0xff);
#pragma unroll 1
        for (int j = 0; j < 8; j++) tma_load_2d(sb + C2_XB + j * 5120 + 4096, &P.mapM, bar_x, j * 64, 0);
        mbar_expect_tx(bar_w, 65536);
    }
    if ((tid & 127) == 32) {
        pace(CH_PFD);
        c2_stage_load(&P.mapW[wg], sb, wg, rank, col0, 0);
#pragma unroll 1
        for (int j = wg; j < 8; j += 3) {
            pace(CH_PT1);
            tma_load_2d(sb + C2_WO + j * 8192, &P.mapWo, bar_w, rank * 64, C * 512 + ((rank - j) & 7) * 64, CH_EFW ? L2_FIRST : L2_NORMAL);
        }
    }
    __syncwarp();

    const uint32_t t32 = w4 * 256 + qc * 64 + (((g >> 2) ^ (qc >> 1)) << 4) + (g & 3) * 4;
    const uint32_t t128 = qc * 256 + (((2 * w4 + (g >> 2)) ^ (2 * qc)) << 4) + (g & 3) * 4;
    const uint32_t a32 = (w4 * 16 + (lane & 15)) * 32 + (((lane >> 4) ^ ((lane >> 2) & 1)) << 4);
    const uint32_t ws = sb + (wg == 0 ? C2_WQ : wg == 1 ? C2_WK : C2_WV) + a32;
    uint32_t w[32][4];
    static_assert(C2_NS == 4, "slot 0");
    auto proj_mem = [&](float (&a)[CH_NCH][4], int s, uint32_t l128) {
        uint32_t b[4][8];
#pragma unroll
        for (int i = 0; i < 4 * CH_NCH; i++) a[i >> 2][i & 3] = 0.f;
        const uint32_t par = (s & 1) ^ 1;
        const uint32_t mb = sb + C2_XB + (s & 1) * C2_XS + 4096;
        auto L = [&](int i) {
            ldsm_x4(b[i & 3], mb + ((rank - i) & 7) * 5120 + l128);
            ldsm_x4(b[i & 3] + 4, mb + ((rank - i) & 7) * 5120 + (l128 ^ 64));
        };
        auto H = [&](int i) {
#pragma unroll
            for (int kk = 0; kk < 4; kk++) {
                const uint32_t* f = i ? w[i * 4 + kk] : &b[2 + (kk >> 1)][(kk & 1) * 4];
                mma_16816(a[(i * 4 + kk) % CH_NCH], f[0], f[1], f[2], f[3], b[i & 3][2 * kk], b[i & 3][2 * kk + 1]);
            }
        };
#pragma unroll
        for (int e = 0; e < 4; e++) ldsm_x4(&b[2 + (e >> 1)][(e & 1) * 4], ws + e * 2048);
        mbar_wait(bar_m, par);
        L(0);
        H(0);
        mbar_wait(bar_m + 8, par);
        DBGW(1 + 16 * wg, 0);
        L(1);
        mbar_wait(bar_m + 16, par);
        uint32_t nxt = mbar_test(bar_m + 24, par);
        L(2); L(3);
        H(1);
        if (__builtin_expect(!nxt, 0)) mbar_wait(bar_m + 24, par);
        nxt = mbar_test(bar_m + 32, par);
        L(4); L(5);
        H(2); H(3);
        if (__builtin_expect(!nxt, 0)) mbar_wait(bar_m + 32, par);
        DBGW(2 + 16 * wg, 0);
        L(6); L(7);
        H(4); H(5); H(6); H(7);
#pragma unroll
        for (int i = 0; i < 4; i++) a[0][i] = CH_NCH == 4 ? (a[0][i] + a[1][i]) + (a[2][i] + a[3 % CH_NCH][i]) : CH_NCH == 3 ? a[0][i] + a[1][i] + a[2 % CH_NCH][i] : a[0][i] + a[1][i];
    };
    auto store_x = [&](const float (&acc)[16], uint32_t base) {
#pragma unroll
        for (int j = 0; j < 4; j++) {
            sts32(base + t128 + j * 1024, pack_bf16(acc[4 * j], acc[4 * j + 2]));
            sts32(base + (t128 ^ 16) + 128 + j * 1024, pack_bf16(acc[4 * j + 1], acc[4 * j + 3]));
        }
    };
    auto fresh_lane = [&]() { uint32_t l; asm volatile("mov.u32 %0, %%laneid;" : "=r"(l)); return l; };
    const float scale = 0.08838834764831845f, l2e = 1.4426950408889634f;
    c2_load_w(w, &P.mapW[wg], wg, rank, col0, t128, ws, sb);
    TS_END(6);
    TS_BEGIN(5);
    CYC(1);

    if (wg == 0) {
#pragma unroll 1
        for (int s = -1;;) {
            float qx[16];
            uint32_t* dst = reinterpret_cast<uint32_t*>(g_xbuf + (((s & 1) * 8 + rank) * 8 + C) * 128) + qc * 64 + w4 * 8 + g;
            asm volatile("" : "+l"(dst));
            mbar_wait(bar_x + 8 * ((s + 1) & 1), ((s + 1) >> 1) & 1);
            if (s >= 0) bar_sync<6, 384>();
            c2_xstream<0, CH_NQ1, CH_SPQ>(qx, w, dlo + ((C2_XB + ((s + 1) & 1) * C2_XS) >> 4), rank, dlo + (C2_WQ >> 4));
            if (s >= 0) {
                float acc[4] = {0.f, 0.f, 0.f, 0.f};
                const uint32_t tag = ((s >> 1) & 1) ^ 1;
                uint32_t nxt = 0;
#pragma unroll
                for (int i = 0; i < 8; i++) {
                    if (i < 2 || !(i & 1)) {
                        if (i < 2 || __builtin_expect(!nxt, 0)) mbar_wait(bar_o + 8 * c2_grp(i), s & 1);
                        if (i == 0) DBGW(7, 0);
                        if (i == 1) DBGW(8, 0);
                        if (i == 6) DBGW(9, 0);
                        wgmma_fence();
                    }
#pragma unroll
                    for (int kk = 0; kk < 4; kk++) {
                        if ((i & 1) && i < 7 && kk == CH_WOT) nxt = mbar_test(bar_o + 8 * c2_grp(i + 1), s & 1);
                        wgmma_ss_n8(acc, dlo + ((C2_WO + i * 8192 + kk * 2048) >> 4), dlo + ((C2_OB + i * 1024 + kk * 256) >> 4));
                    }
                }
                wgmma_commit();
                bar_arrive<11, 256>();
                wgmma_wait<0>();
                asm volatile("st.relaxed.gpu.global.u32 [%0], %1;" :: "l"(dst), "r"((pack_bf16(acc[0], acc[2]) & ~1u) | tag) : "memory");
                asm volatile("st.relaxed.gpu.global.u32 [%0 + 128], %1;" :: "l"(dst), "r"((pack_bf16(acc[1], acc[3]) & ~1u) | tag) : "memory");
                bar_arrive<4, 256>();
                DBGW(10, 0);
            }
            s++;
            c2_xstream<CH_NQ1, 32, CH_SPQ>(qx, w, dlo + ((C2_XB + (s & 1) * C2_XS) >> 4), rank, dlo + (C2_WQ >> 4));
            const uint32_t sca = pin(w4 < 2 ? sb + C2_SC + w4 * 512 + lane * 16 : sb + C2_SC + 1024 + lane * 8);
            const uint32_t krow = w4 * 16 + (lane & 15);
            const uint32_t ka0 = pin(sb + C2_KX + krow * 128 + (((lane >> 4) ^ (krow & 7)) << 4));
            const uint32_t l32 = pin(sb + C2_QM + (lane >> 4) * 256 + (lane & 7) * 32 + ((((lane >> 3) & 1) ^ ((lane >> 2) & 1)) << 4));
            const uint32_t qst = pin(sb + C2_QM + t32);
            const uint32_t l128 = pin((lane & 7) * 128 + (((lane >> 3) ^ (lane & 7)) << 4));
            if (s > 0) bar_sync<5, 256>();
            wgmma_wait<0>();
            store_x(qx, sb + C2_QX);
            DBGW(0, 0);
            if (s == NSEG - 1) break;
            {
                float a[CH_NCH][4];
                proj_mem(a, s, l128);
                sts32(qst, pack_bf16(a[0][0], a[0][2]));
                sts32(qst + 32, pack_bf16(a[0][1], a[0][3]));
            }
            DBGW(3, 0);
            if (w4 < 3) {
                uint32_t ka[4][4], qb[8];
                float c[4] = {0.f, 0.f, 0.f, 0.f}, c2[4] = {0.f, 0.f, 0.f, 0.f};
                const uint32_t sc_peer = pin(mapa_u32(sca + 1280, rank ^ 1)), sc_own = pin(mapa_u32(sca, rank));
                bar_sync<1, 384>();
                ldsm_x4(qb, l32);
                ldsm_x4(ka[0], ka0);
                ldsm_x4(ka[1], ka0 ^ 32);
                ldsm_x4(qb + 4, l32 + 512);
                ldsm_x4(ka[2], ka0 ^ 64);
                ldsm_x4(ka[3], ka0 ^ 96);
                mma_16816(c, ka[0][0], ka[0][1], ka[0][2], ka[0][3], qb[0], qb[1]);
                mma_16816(c2, ka[1][0], ka[1][1], ka[1][2], ka[1][3], qb[2], qb[3]);
                mma_16816(c, ka[2][0], ka[2][1], ka[2][2], ka[2][3], qb[4], qb[5]);
                mma_16816(c2, ka[3][0], ka[3][1], ka[3][2], ka[3][3], qb[6], qb[7]);
                const uint32_t u0 = __float_as_uint(c[0] + c2[0]), u1 = __float_as_uint(c[1] + c2[1]);
                const uint32_t u2 = __float_as_uint(c[2] + c2[2]), u3 = __float_as_uint(c[3] + c2[3]);
                asm volatile(
                    "{\n.reg .pred p;\nsetp.lt.u32 p, %8, 2;\n"
                    "@p st.async.weak.shared::cluster.mbarrier::complete_tx::bytes.v4.b32 [%0], {%4, %5, %6, %7}, [%1];\n"
                    "@!p st.async.weak.shared::cluster.mbarrier::complete_tx::bytes.v2.b32 [%0], {%4, %5}, [%1];\n"
                    "@p st.async.weak.shared::cluster.mbarrier::complete_tx::bytes.v4.b32 [%2], {%4, %5, %6, %7}, [%3];\n"
                    "@!p st.async.weak.shared::cluster.mbarrier::complete_tx::bytes.v2.b32 [%2], {%4, %5}, [%3];\n}"
                    :: "r"(sc_peer), "r"(mapa_u32(bar_sc, rank ^ 1)), "r"(sc_own), "r"(mapa_u32(bar_sc, rank)), "r"(u0), "r"(u1), "r"(u2), "r"(u3), "r"(w4) : "memory");
                bar_arrive<2, 224>();
                fence_async_smem();
                if (!CH_TS && s >= 4 * CB_FIRST + 5 && (s & 3) == 1 && tid == 0) signal_ctr(CT_CB + ((s - 5) >> 2));
                __syncwarp();
                DBGW(4, 2);
            } else {
                bar_arrive<1, 384>();
                fence_async_smem();
                const uint32_t a = pin(sb + C2_SC + lane * 16), a2 = pin(sb + C2_SC + 1024 + lane * 8), pa = pin(sb + C2_PB + lane * 4);
                mbar_wait(bar_sc, s & 1);
                DBG(5);
                float v[10];
                {
                    float4 x0, x1, y0, y1; float2 x2, y2;
                    asm volatile("ld.shared.v4.f32 {%0, %1, %2, %3}, [%4];" : "=f"(x0.x), "=f"(x0.y), "=f"(x0.z), "=f"(x0.w) : "r"(a) : "memory");
                    asm volatile("ld.shared.v4.f32 {%0, %1, %2, %3}, [%4];" : "=f"(y0.x), "=f"(y0.y), "=f"(y0.z), "=f"(y0.w) : "r"(a + 1280) : "memory");
                    asm volatile("ld.shared.v4.f32 {%0, %1, %2, %3}, [%4];" : "=f"(x1.x), "=f"(x1.y), "=f"(x1.z), "=f"(x1.w) : "r"(a + 512) : "memory");
                    asm volatile("ld.shared.v4.f32 {%0, %1, %2, %3}, [%4];" : "=f"(y1.x), "=f"(y1.y), "=f"(y1.z), "=f"(y1.w) : "r"(a + 1792) : "memory");
                    asm volatile("ld.shared.v2.f32 {%0, %1}, [%2];" : "=f"(x2.x), "=f"(x2.y) : "r"(a2) : "memory");
                    asm volatile("ld.shared.v2.f32 {%0, %1}, [%2];" : "=f"(y2.x), "=f"(y2.y) : "r"(a2 + 1280) : "memory");
                    v[0] = x0.x + y0.x; v[1] = x0.y + y0.y; v[2] = x0.z + y0.z; v[3] = x0.w + y0.w;
                    v[4] = x1.x + y1.x; v[5] = x1.y + y1.y; v[6] = x1.z + y1.z; v[7] = x1.w + y1.w;
                    v[8] = x2.x + y2.x; v[9] = x2.y + y2.y;
                }
                float m0 = fmaxf(fmaxf(fmaxf(v[0], v[2]), fmaxf(v[4], v[6])), v[8]);
                float m1 = fmaxf(fmaxf(fmaxf(v[1], v[3]), fmaxf(v[5], v[7])), v[9]);
#pragma unroll
                for (int o = 4; o < 32; o <<= 1) {
                    m0 = fmaxf(m0, __shfl_xor_sync(0xffffffff, m0, o));
                    m1 = fmaxf(m1, __shfl_xor_sync(0xffffffff, m1, o));
                }
                const float sl = scale * l2e;
                m0 *= sl; m1 *= sl;
#pragma unroll
                for (int j = 0; j < 5; j++)
                    sts32(pa + j * 128, pack_bf16(ex2f(fmaf(v[2 * j], sl, -m0)), ex2f(fmaf(v[2 * j + 1], sl, -m1))));
                bar_arrive<3, 160>();
                DBG(6);
            }
        }
        bar_arrive<1, 384>();
        fence_async_smem();
        bar_arrive<6, 384>();
        TS_MARK(8, 0);
        CYC(2);
        TM(0);
        const uint32_t lane = fresh_lane();
        pace(CH_LD);
        {
            const uint32_t a = sb + C2_WO + ((lane >> 4) * 8 + (lane & 7)) * 128 + (((2 * w4 + ((lane >> 3) & 1)) ^ (lane & 7)) << 4);
#pragma unroll
            for (int e = C2_NS; e < 32; e++)
                asm volatile("ldmatrix.sync.aligned.m8n8.x4.trans.shared.b16 {%0,%1,%2,%3}, [%4];" : "=r"(w[e][0]), "=r"(w[e][1]), "=r"(w[e][2]), "=r"(w[e][3]) : "r"(a + e * 2048) : "memory");
        }
        fence_async_smem();
        if (CH_TS && w4 == 0) bar_sync<12, 160>();
        if (lane < 8) asm volatile("mbarrier.arrive.relaxed.cluster.shared::cluster.b64 _, [%0];" :: "r"(mapa_u32(bar_h, lane)) : "memory");
        __syncwarp();
        TM(9);
        if (w4 == 0) {
            if (!CH_TS) bar_sync<12, 160>();
            if (!CH_TS) asm volatile("fence.acq_rel.gpu;" ::: "memory");
            if (!CH_TS) asm volatile("fence.proxy.async.global;" ::: "memory");
            mbar_wait(bar_h, 0);
            if (elect_one()) tma_load_2d_mc(sb + c2_ts(rank) * 1024, &P.mapC, bar_x, (rank & 1) * 64, h * SEQ + SEQ - 128, (uint16_t)0xff);
            __syncwarp();
            TM(10);
        }
        if (w4 == 1) {
            wait_ctr(CT_P, FA_GRID);
            float4 v;
            asm volatile("ld.relaxed.gpu.global.v4.f32 {%0, %1, %2, %3}, [%4];" : "=f"(v.x), "=f"(v.y), "=f"(v.z), "=f"(v.w) : "l"(g_gate + SEQ - 128 + lane * 4) : "memory");
            asm volatile("st.shared.v4.f32 [%0], {%1, %2, %3, %4};" :: "r"(sb + C2_GT + lane * 16), "f"(1.f - v.x), "f"(1.f - v.y), "f"(1.f - v.z), "f"(1.f - v.w) : "memory");
            __syncwarp();
            if (lane == 0) mbar_expect_tx(bar_x, 65536);
            finish_launch(lane);
        }
        uint32_t* dst = reinterpret_cast<uint32_t*>(P.out + (SEQ - 128 + 2 * (lane & 3)) * DM + rank * 64 + w4 * 16) + (lane >> 2);
#pragma unroll 1
        for (uint32_t q = 0; q < 4; q++, dst += 16 * DM) {
            float acc[16], gt[8];
#pragma unroll
            for (int i = 0; i < 16; i++) acc[i] = 0.f;
            const uint32_t bar = q < 2 ? bar_x : bar_m - 128 + q * 64, db = dlo + (q & 1) * 256;
#pragma unroll
            for (int i = 0; i < 8; i++) {
                if (i == 0 || (CH_TW && (i == 1 || !(i & 1)))) {
                    if (i == 0 || q > 1) mbar_wait(bar + 8 * c2_grp(i), q >> 1);
                    if (!CH_TW && q > 1)
#pragma unroll 1
                        for (uint32_t j = 8; j < 40; j += 8) mbar_wait(bar + j, 1);
                    if (i == 0) TM(13 + q);
                    wgmma_fence();
                }
                if (i == 6) TM(25 + q);
                const uint32_t d = db + (q < 2 ? c2_ts((rank - i) & 7) * 64 : (i ? C2_WO + i * 8192 : C2_QX) >> 4);
#pragma unroll
                for (int kk = 0; kk < 4; kk++) {
                    if (i == 0) wgmma_ss_n32_ta(acc, dlo + ((C2_WO + kk * 2048) >> 4), d + kk * 2);
                    else wgmma_rs(acc, w[i * 4 + kk], d + kk * 2);
                }
            }
            wgmma_commit();
            if (q == 3) asm volatile("barrier.cluster.arrive.relaxed.aligned;" ::: "memory");
#pragma unroll
            for (int j = 0; j < 4; j++)
                asm volatile("ld.shared.v2.f32 {%0, %1}, [%2];" : "=f"(gt[2 * j]), "=f"(gt[2 * j + 1]) : "r"(sb + C2_GT + q * 128 + (lane & 3) * 8 + j * 32) : "memory");
            wgmma_wait<0>();
#pragma unroll
            for (int j = 0; j < 8; j++)
                asm volatile("red.relaxed.gpu.global.add.noftz.bf16x2 [%0], %1;" :: "l"(dst + ((j >> 1) * 8 + (j & 1)) * (DM / 2)),
                             "r"(pack_bf16(acc[(j >> 1) * 4 + (j & 1)] * gt[j], acc[(j >> 1) * 4 + (j & 1) + 2] * gt[j])) : "memory");
            TS_MARK(9 + q, 0);
            TM(17 + q);
        }
    } else if (wg == 1) {
        bool early = false;
#pragma unroll 1
        for (int s = -1;;) {
            if (s > 0 && (!CH_EARLY || s != NSEG - 1 || early)) {
                mbar_wait(bar_sx + 8 * ((s - 1) & 1), ((s - 1) >> 1) & 1);
                const uint32_t a = sb + C2_SX + w4 * 1280 + lane * 8, ap = a + 10240 - (s & 1) * 5120;
                float v[10];
                const int lim = 8 * w4 + g - 2 * qc;
#pragma unroll
                for (int j = 0; j < 5; j++) {
                    float2 x, y;
                    asm volatile("ld.shared.v2.f32 {%0, %1}, [%2];" : "=f"(x.x), "=f"(x.y) : "r"(a + j * 256) : "memory");
                    asm volatile("ld.shared.v2.f32 {%0, %1}, [%2];" : "=f"(y.x), "=f"(y.y) : "r"(ap + j * 256) : "memory");
                    v[2 * j] = (j < 4 && 8 * j > lim) ? -INFINITY : x.x + y.x;
                    v[2 * j + 1] = (j < 4 && 8 * j + 1 > lim) ? -INFINITY : x.y + y.y;
                }
                float mx = fmaxf(fmaxf(fmaxf(v[0], v[1]), fmaxf(v[2], v[3])), fmaxf(fmaxf(v[4], v[5]), fmaxf(v[6], v[7])));
                mx = fmaxf(mx, fmaxf(v[8], v[9]));
                mx = fmaxf(mx, __shfl_xor_sync(0xffffffff, mx, 1));
                mx = fmaxf(mx, __shfl_xor_sync(0xffffffff, mx, 2));
                const float sl = scale * l2e;
                mx *= sl;
#pragma unroll
                for (int j = 0; j < 10; j++) v[j] = ex2f(fmaf(v[j], sl, -mx));
                float sm = ((v[0] + v[1]) + (v[2] + v[3])) + ((v[4] + v[5]) + (v[6] + v[7])) + (v[8] + v[9]);
                sm += __shfl_xor_sync(0xffffffff, sm, 1);
                sm += __shfl_xor_sync(0xffffffff, sm, 2);
                float inv;
                asm("rcp.approx.ftz.f32 %0, %1;" : "=f"(inv) : "f"(sm));
                const uint32_t pa = sb + C2_PX + w4 * 256 + g * 32 + ((g >> 2) << 4) + qc * 4;
#pragma unroll
                for (int j = 0; j < 5; j++) sts32((pa ^ ((j & 1) << 4)) + (j >> 1) * 1024, pack_bf16(v[2 * j] * inv, v[2 * j + 1] * inv));
            }
            if (!early) {
            if (s >= 0) {
                fence_async_smem();
                if (s < NSEG) bar_sync<6, 384>(); else bar_sync<7, 256>();
                DBGW(20, 0);
                TM(s < NSEG ? 2 : 11);
                uint32_t cp[8];
                {
                    float cx[16];
#pragma unroll
                    for (int i = 0; i < 16; i++) cx[i] = 0.f;
                    wgmma_fence();
#pragma unroll
                    for (int kk = 0; kk < 3; kk++)
                        wgmma_ss<DHI32, DHI32>(cx, dlo + ((C2_VT + ((s - 1) & 1) * 6144 + kk * 2048) >> 4), dlo + ((C2_PX + kk * 1024) >> 4));
                    wgmma_commit();
                    wgmma_wait<0>();
#pragma unroll
                    for (int j = 0; j < 4; j++) { cp[2 * j] = pack_bf16(cx[4 * j], cx[4 * j + 2]); cp[2 * j + 1] = pack_bf16(cx[4 * j + 1], cx[4 * j + 3]); }
                    asm volatile("{\n.reg .pred p;\nsetp.gt.u32 p, %0, 99;\n@p st.shared.v4.b32 [%0], {%1, %2, %3, %4};\n@p st.shared.v4.b32 [%0], {%5, %6, %7, %8};\n}"
                                 :: "r"(rank), "r"(cp[0]), "r"(cp[1]), "r"(cp[2]), "r"(cp[3]), "r"(cp[4]), "r"(cp[5]), "r"(cp[6]), "r"(cp[7]) : "memory");
                }
                if (s < NSEG) {
                    float sx[20];
                    wgmma_fence();
                    wgmma_ss0<DHI128, DHI128>(sx, dlo + (C2_QX >> 4), dlo + (C2_KX >> 4));
#pragma unroll
                    for (int kk = 1; kk < 4; kk++) wgmma_ss<DHI128, DHI128>(sx, dlo + (C2_QX >> 4) + kk * 2, dlo + (C2_KX >> 4) + kk * 2);
                    wgmma_commit();
                    wgmma_wait<0>();
                    if (s < NSEG - 1) bar_arrive<5, 256>();
                    if (CH_TS && s > 0 && s < NSEG - 1) {
                        const uint32_t a = sb + C2_CS + w4 * 1024;
#pragma unroll
                        for (int j = 0; j < 8; j++) sts32(a + qc * 64 + g * 4 + (j >> 1) * 256 + (j & 1) * 32, cp[j]);
                        fence_async_smem();
                        __syncwarp();
                        if (elect_one()) tma_store_2d(&P.mapS, a, (rank & 1) * 64 + w4 * 16, h * SEQ + (s - 1) * SEGL);
                        asm volatile("cp.async.bulk.commit_group;" ::: "memory");
                    }
                    if (!CH_TS && s > 0 && s < NSEG - 1) {
                        uint32_t* dst = reinterpret_cast<uint32_t*>(g_ctxB + ((size_t)h * SEQ + (s - 1) * SEGL + 2 * qc) * HD + (rank & 1) * 64 + w4 * 16 + 2 * g);
#pragma unroll
                        for (int j = 0; j < 4; j++) {
                            asm volatile("st.global.u32 [%0], %1;" :: "l"(dst + j * 8 * (HD / 2)), "r"(cp[2 * j]) : "memory");
                            asm volatile("st.global.u32 [%0], %1;" :: "l"(dst + (j * 8 + 1) * (HD / 2)), "r"(cp[2 * j + 1]) : "memory");
                        }
                    }
                    DBGW(22, 0);
                    TM(3);
                    if (!CH_TS && s == NSEG - 2) bar_arrive<12, 160>();
                    const uint32_t a = sb + C2_SX + w4 * 2560 + lane * 8;
                    if (w4 < 2) {
#pragma unroll
                        for (int j = 0; j < 5; j++) {
                            asm volatile("st.shared.v2.f32 [%0], {%1, %2};" :: "r"(a + j * 256), "f"(sx[4 * j]), "f"(sx[4 * j + 1]) : "memory");
                            asm volatile("st.shared.v2.f32 [%0], {%1, %2};" :: "r"(a + 1280 + j * 256), "f"(sx[4 * j + 2]), "f"(sx[4 * j + 3]) : "memory");
                        }
                    }
                    if (s < NSEG - 1) mbar_wait(bar_x + 8 * ((s + 1) & 1), ((s + 1) >> 1) & 1);
                    const uint32_t pa = mapa_u32(a + 5120 + (s & 1) * 5120, rank ^ 1), pb = mapa_u32(bar_sx + 8 * (s & 1), rank ^ 1);
                    if (s < NSEG - 1) bar_sync<4, 256>(); else bar_sync<9, 128>();
                    if (w4 < 2) {
#pragma unroll
                        for (int j = 0; j < 5; j++) {
                            st_async_v2(pa + j * 256, __float_as_uint(sx[4 * j]), __float_as_uint(sx[4 * j + 1]), pb);
                            st_async_v2(pa + 1280 + j * 256, __float_as_uint(sx[4 * j + 2]), __float_as_uint(sx[4 * j + 3]), pb);
                        }
                    }
                }
                if (s >= NSEG - 1) {
                    const uint32_t a = sb + C2_QX + 4096 - (s & 1) * 4096;
#pragma unroll
                    for (int j = 0; j < 4; j++) {
                        sts32(a + t128 + j * 1024, cp[2 * j]);
                        sts32(a + (t128 ^ 16) + 128 + j * 1024, cp[2 * j + 1]);
                    }
                    fence_async_smem();
                    asm volatile("bar.arrive %0, 160;" :: "r"(s - NSEG + 14) : "memory");
                    TM(s - NSEG + 6);
                    if (s == NSEG) break;
                }
            } else mbar_wait(bar_x, 0);
            s++;
            if (s < NSEG) {
                float acc[16];
                c2_xstream<0, 32, CH_SPK>(acc, w, dlo + ((C2_XB + (s & 1) * C2_XS) >> 4), rank, dlo + (C2_WK >> 4));
                wgmma_wait<0>();
                store_x(acc, sb + C2_KX);
                DBGW(16, 0);
            }
            if (CH_EARLY && s == NSEG - 1) {
                if (CH_TS) {
                    asm volatile("cp.async.bulk.wait_group 0;" ::: "memory");
                    bar_arrive<12, 160>();
                }
                early = true;
                continue;
            }
            }
            early = false;
            if (s < NSEG) TM(4);
            if (s < NSEG) {
                const uint32_t kst = pin(sb + C2_KX + 4096 + t128);
                const uint32_t l128 = pin((lane & 7) * 128 + (((lane >> 3) ^ (lane & 7)) << 4));
                float a[CH_NCH][4];
                proj_mem(a, s, l128);
                sts32(kst, pack_bf16(a[0][0], a[0][2]));
                sts32((kst ^ 16) + 128, pack_bf16(a[0][1], a[0][3]));
                bar_arrive<1, 384>();
                TM(1);
                DBGW(19, 0);
                if (CH_TS) {
                    asm volatile("cp.async.bulk.wait_group 0;" ::: "memory");
                    __syncwarp();
                    if (s >= 4 * CB_FIRST + 5 && (s & 3) == 1 && lane == 0) asm volatile("red.relaxed.gpu.global.add.u32 [%0], 1;" :: "l"(&g_ctr[CT_CB + ((s - 5) >> 2)]) : "memory");
                }
                if (w4 == 0) {
                    if (CH_ARM && lane == 0) mbar_expect_tx(bar_sc, 2560);
                    if (lane < 16 && (lane & 7) >= 1 && (lane & 7) < 5) mbar_expect_tx(bar_m + 8 * lane, ((lane & 7) == 1 ? 1024 : 2048) << (s < NSEG - 1 ? 0 : 2));
                    if (s < NSEG - 1) {
                        if (!CH_ARM && lane == 0) mbar_expect_tx(bar_sc, 2560);
                        if (lane == 8) {
                            mbar_expect_tx(bar_x + 8 * ((s + 1) & 1), 32768);
                            tma_load_2d_mc(sb + C2_XB + ((s + 1) & 1) * C2_XS + rank * 5120, &mapX, bar_x + 8 * ((s + 1) & 1), rank * 64, (s + 1) * SEGL, (uint16_t)0xff);
                            if (s + 2 < NSEG)
                                asm volatile("cp.async.bulk.prefetch.tensor.2d.L2.global [%0, {%1, %2}];" :: "l"((uint64_t)&mapX), "r"(rank * 64), "r"((s + 2) * SEGL) : "memory");
                        }
                    }
                    if (lane == 16) mbar_expect_tx(bar_sx + 8 * (s & 1), 5120);
                    __syncwarp();
                }
            }
        }
        TS_MARK(12, 128);
        asm volatile("barrier.cluster.arrive.relaxed.aligned;" ::: "memory");
    } else {
        uint32_t va[5][2] = {};
        auto store_vt = [&](int s) {
            const uint32_t a = sb + C2_VT + (s & 1) * 6144 + a32;
            stmatrix_x4(a, va[0][0], va[0][1], va[1][0], va[1][1]);
            stmatrix_x4(a + 2048, va[2][0], va[2][1], va[3][0], va[3][1]);
            asm volatile("stmatrix.sync.aligned.m8n8.x2.shared.b16 [%0], {%1, %2};" :: "r"(a + 4096), "r"(va[4][0]), "r"(va[4][1]) : "memory");
        };
#pragma unroll 1
        for (int s = -1;;) {
            if (s >= 0) {
                const int t = tid - 256;
                const uint2* src = g_xbuf + ((s & 1) * 8 + rank) * 1024 + t;
                asm volatile("" : "+l"(src));
                const uint32_t ma = sb + C2_XB + ((s + 1) & 1) * C2_XS + rank * 5120 + 4096 + (t >> 4) * 128 + ((((t >> 1) & 7) ^ (t >> 4)) << 4) + (t & 1) * 8;
                uint32_t ra[8], rb[8];
#pragma unroll
                for (int i = 1; i < 8; i++) {
                    const uint32_t d = (rank + i) & 7;
                    ra[i] = pin(mapa_u32(ma, d)); rb[i] = pin(mapa_u32(bar_m + 8 * c2_grp(i), d));
                }
                if (s == NSEG - 1) break;
                bar_sync<11, 256>();
                DBGW(29, 0);
                pace(CH_POLL_DELAY);
                const uint32_t tag = ((s >> 1) & 1) ^ 1;
                uint32_t p[8][2], m0, m1;
                auto issue = [&](uint32_t (&x)[8][2]) {
#pragma unroll
                    for (int k = 0; k < 8; k++)
                        asm volatile("ld.relaxed.gpu.global.v2.u32 {%0, %1}, [%2];" : "=r"(x[k][0]), "=r"(x[k][1]) : "l"(src + k * 128) : "memory");
                };
                auto check = [&](const uint32_t (&x)[8][2]) {
                    uint32_t bad = 0, bad2 = 0;
                    float r[4];
#pragma unroll
                    for (int k = 0; k < 8; k++) {
                        asm("lop3.b32 %0, %0, %1, %2, 0xf6;" : "+r"(bad) : "r"(x[k][0]), "r"(tag));
                        asm("lop3.b32 %0, %0, %1, %2, 0xf6;" : "+r"(bad2) : "r"(x[k][1]), "r"(tag));
#pragma unroll
                        for (int e = 0; e < 2; e++) {
                            const float lo = __uint_as_float(x[k][e] << 16), hi = __uint_as_float(x[k][e] & 0xffff0000u);
                            r[2 * e] = k ? r[2 * e] + lo : lo;
                            r[2 * e + 1] = k ? r[2 * e + 1] + hi : hi;
                        }
                    }
                    m0 = pack_bf16(r[0], r[1]); m1 = pack_bf16(r[2], r[3]);
                    asm volatile("" : "+r"(m0), "+r"(m1));
                    return __all_sync(0xffffffff, ((bad | bad2) & 1u) == 0u);
                };
                for (int it = 0; it < (1 << 20); it++) {
                    issue(p);
                    if (check(p)) break;
                }
                DBGW(30, 0);
                st_async_v2(ra[1], m0, m1, rb[1]);
                asm volatile("st.shared.v2.b32 [%0], {%1, %2};" :: "r"(ma), "r"(m0), "r"(m1) : "memory");
                __syncwarp();
                if (lane == 0) mbar_arrive(bar_m);
#pragma unroll
                for (int i = 2; i < 8; i++) st_async_v2(ra[i], m0, m1, rb[i]);
                DBGW(31, 0);
                TM(8);
                store_vt(s);
            }
            s++;
            const uint32_t ost = pin(sb + C2_OB + t32), pla = pin(sb + C2_PB + lane * 16), plb = pin(sb + C2_PB + 512 + (lane & 7) * 16);
            bar_sync<1, 384>();
            fence_async_smem();
            DBGW(24, 0);
            if (s < NSEG - 1) bar_sync<2, 224>();
            else bar_arrive<6, 384>();
            {
                float acc[20];
                c2_xstream<0, 32, CH_SPV>(acc, w, dlo + ((C2_XB + (s & 1) * C2_XS) >> 4), rank, dlo + (C2_WV >> 4));
                wgmma_wait<0>();
#pragma unroll
                for (int j = 0; j < 5; j++) { va[j][0] = pack_bf16(acc[4 * j], acc[4 * j + 1]); va[j][1] = pack_bf16(acc[4 * j + 2], acc[4 * j + 3]); }
            }
            DBGW(26, 0);
            TM(7);
            if (s < NSEG - 1) {
                uint32_t p[5];
                bar_sync<3, 160>();
                DBGW(27, 0);
                ldmatrix_x4_trans(p[0], p[1], p[2], p[3], pla);
                asm volatile("ldmatrix.sync.aligned.m8n8.x1.trans.shared.b16 {%0}, [%1];" : "=r"(p[4]) : "r"(plb) : "memory");
                float oa[4] = {0.f, 0.f, 0.f, 0.f}, ob[4] = {0.f, 0.f, 0.f, 0.f}, sa[4] = {0.f, 0.f, 0.f, 0.f}, sc[4] = {0.f, 0.f, 0.f, 0.f};
                const uint32_t one = 0x3f803f80u;
                mma_16816(sa, one, one, one, one, p[0], p[1]);
                mma_16816(oa, va[0][0], va[0][1], va[1][0], va[1][1], p[0], p[1]);
                mma_16816(sc, one, one, one, one, p[2], p[3]);
                mma_16816(ob, va[2][0], va[2][1], va[3][0], va[3][1], p[2], p[3]);
                mma_16816(sa, one, one, one, one, p[4], 0u);
                mma_16816(oa, va[4][0], va[4][1], 0u, 0u, p[4], 0u);
                bar_arrive<6, 384>();
                float i0, i1;
                asm("rcp.approx.ftz.f32 %0, %1;" : "=f"(i0) : "f"(sa[0] + sc[0]));
                asm("rcp.approx.ftz.f32 %0, %1;" : "=f"(i1) : "f"(sa[1] + sc[1]));
                sts32(ost, pack_bf16((oa[0] + ob[0]) * i0, (oa[2] + ob[2]) * i0));
                sts32(ost + 32, pack_bf16((oa[1] + ob[1]) * i1, (oa[3] + ob[3]) * i1));
                fence_async_smem();
                __syncwarp();
                if (elect_one()) {
#pragma unroll
                    for (int i = 1; i < 8; i++) {
                        const uint32_t d = (rank + i) & 7;
                        bulk_s2s(mapa_u32(sb + C2_OB + i * 1024 + w4 * 256, d), sb + C2_OB + w4 * 256, 256, mapa_u32(bar_o + 8 * c2_grp(i), d));
                        if (i == 1) mbar_arrive(bar_o);
                    }
                }
                __syncwarp();
                DBGW(28, 0);
            }
        }
        store_vt(NSEG - 1);
        fence_async_smem();
        bar_arrive<7, 256>();
        const uint32_t lane = fresh_lane();
        if (w4 == 0) {
            mbar_wait(bar_h, 0);
#pragma unroll 1
            for (uint32_t o = 0; o < 2; o++) {
                asm volatile("bar.sync %0, 160;" :: "r"(13 + o) : "memory");
                if (elect_one()) {
#pragma unroll
                    for (int i = 1; i < 8; i++) {
                        const uint32_t d = (rank + i) & 7;
                        bulk_s2s(mapa_u32(sb + C2_WO + i * 8192 + o * 4096, d), sb + C2_QX + o * 4096, 4096, mapa_u32(bar_m + o * 64 + 8 * c2_grp(i), d));
                    }
                }
                __syncwarp();
                if (lane < 4) mbar_arrive(bar_m + o * 64);
                TM(21 + o);
            }
        }
        __syncwarp();
        asm volatile("barrier.cluster.arrive.relaxed.aligned;" ::: "memory");
        g_xbuf[((8 + rank) * 8 + C) * 128 + w4 * 32 + lane] = make_uint2(0u, 0u);
    }
    asm volatile("barrier.cluster.wait.aligned;" ::: "memory");
    TS_END(2);
    CYC(3);
    if (wg == 0) TM(23);
}

constexpr int P3_LEN = 24;
struct SideParams {
    CUtensorMap mapA[2];
    CUtensorMap mapW[3];
    CUtensorMap mapQ, mapK, mapV;
    CUtensorMap mapO;
    CUtensorMap mapCtx[2];
    CUtensorMap mapWo[2];
    CUtensorMap mapOut;
    bf16* qkv[3];
    const bf16 *x, *gate_w;
    bf16* out;
    uint32_t jobs[34 * 2];
    uint16_t sched[34 * P3_LEN];
    uint8_t first[34];
};
constexpr int P3_STAGES = 14;
#define P3_LAG 2
#define SD_GD 12000
#define SD_D0 4000
#define SD_EFW 0
#define SD_EFA 0
#define SD_EFS 0
#define SD_EFK 0
#define SD_ALIAS 1
#define SD_GW 2
#define SD_NS 1
#define SD_CT 384
#define PT(i)
#define OT(i)
constexpr uint32_t SD_PF = FA_BAR + 256, SD_PE = SD_PF + 8 * P3_STAGES, SD_OF = SD_PE + 8 * P3_STAGES, SD_OE = SD_OF + 32, SD_CL = SD_OE + 32, SD_DONE = FA_BAR + 576;
constexpr int SD_SMEM = SD_DONE + 2 * P3_LEN * 8;
__device__ __forceinline__ void tma_load_3d(uint32_t dst, const CUtensorMap* map, uint32_t bar, int c0, int c1, int c2) {
    asm volatile(
        "cp.async.bulk.tensor.3d.shared::cluster.global.mbarrier::complete_tx::bytes [%0], [%1, {%3, %4, %5}], [%2];"
        :: "r"(dst), "l"((uint64_t)map), "r"(bar), "r"(c0), "r"(c1), "r"(c2) : "memory");
}
__global__ void __cluster_dims__(2, 1, 1) __launch_bounds__(384, 1) side_kernel(const __grid_constant__ SideParams P) {
    extern __shared__ __align__(1024) uint8_t smem_side[];
    const uint32_t sb = smem_u32(smem_side);
    const uint32_t full = sb + SD_PF, empty = sb + SD_PE, done = sb + SD_DONE;
    const uint32_t bar_q = sb + FA_BAR, bar_qe = bar_q + 16, bar_kf = bar_q + 32, bar_vf = bar_q + 48, bar_ke = bar_q + 64, bar_ve = bar_q + 80,
                   bar_of = bar_q + 96, bar_oe = bar_q + 112, oslot = bar_q + 144;
    const int warp = __shfl_sync(0xffffffff, threadIdx.x >> 5, 0), lane = threadIdx.x & 31;
    const uint32_t rank = cluster_ctarank();
    const uint16_t* sched = P.sched + (blockIdx.x >> 1) * P3_LEN;
    const uint32_t so0 = P.first[blockIdx.x >> 1] * 8;
    TS_BEGIN_T(0, 320);
    if (warp == 0 && lane < P3_STAGES) {
        mbar_init(full + 8 * lane, 1); mbar_init(empty + 8 * lane, 4);
        if (8 * lane < so0) {
            mbar_arrive(full + 8 * lane);
            asm volatile("mbarrier.arrive.shared::cta.b64 _, [%0], 4;" :: "r"(empty + 8 * lane) : "memory");
        }
    }
    if (warp == 1 && lane < 16) mbar_init(bar_q + 8 * lane, (0x14881181u >> (lane >> 1) * 4) & 15);
    if (warp == 2 && lane < 9) mbar_init(sb + SD_OF + 8 * lane, (lane >> 2 & 1) + 1);
    if (warp == 3 || (warp == 4 && lane < 2 * P3_LEN - 32)) mbar_init(done + (threadIdx.x - 96) * 8, 4);
    if (warp < 5) asm volatile("fence.mbarrier_init.release.cluster;" ::: "memory");
    __syncthreads();
    cluster_sync_relaxed();
    if (warp >= 8) {
        asm volatile("setmaxnreg.dec.sync.aligned.u32 %0;" :: "n"(FA_RLO));
        if (warp == 8) {
            uint32_t so = so0, ph = 1;
            pace(SD_D0);
#pragma unroll 1
            for (;; sched++) {
                const uint32_t e = *sched, z = (e >> 5) & 3, na = e >> 10;
                if (z == 3) break;
#pragma unroll 1
                for (int i = 1 - na; i < 16; i += 2 - na) {
                    mbar_wait(empty + so, ph);
                    if (elect_one()) {
                        mbar_expect_tx(full + so, 16384);
                        if (i & 1) tma_load_2d_mc(sb + so * 2048 + rank * 8192, &P.mapW[z], full + so, (e & 31) * 128 + rank * 64, (i >> 1) * 64, (uint16_t)3, SD_EFW ? L2_FIRST : L2_NORMAL);
                        else tma_load_2d(sb + so * 2048, &P.mapA[z != 0], full + so, (i >> 1) * 64, (((e >> 7) & 7) * 2 + rank) * 128, SD_EFA && z ? L2_FIRST : L2_NORMAL);
                    }
                    so += 8;
                    if (so == 8 * P3_STAGES) { so = 0; ph ^= 1; }
                }
            }
            TS_MARK(13, 256);
            PT(0);
            int it = 0, t = blockIdx.x, hp_ready = 0;
            auto load = [&](uint32_t dst, const CUtensorMap* map, uint32_t bar, int row) {
                if (elect_one()) {
                    mbar_expect_tx(bar, 32768);
                    tma_load_2d(dst, map, bar, 0, row, SD_EFK && map != &P.mapQ ? L2_FIRST : L2_NORMAL);
                    tma_load_2d(dst + 16384, map, bar, 64, row, SD_EFK && map != &P.mapQ ? L2_FIRST : L2_NORMAL);
                }
            };
            auto load_q = [&](int item) {
                const uint32_t b = bar_q + 8 * (item & 1);
                sts32(b + 128, t);
                if (t < 0) { mbar_arrive_if(b, lane == 0); return; }
                const int hp = fa_head(t) >> 1;
                if (!((hp_ready >> hp) & 1)) { wait_ctr(CT_AP + hp, 192u); hp_ready |= 1 << hp; }
                load(sb + FA_Q + (item & 1) * 32768, &P.mapQ, b, fa_head(t) * SEQ + fa_qt(t) * 128);
            };
            auto load_v = [&](int it, int row) {
                const int s = it & 1;
                if (it < 2) mbar_wait(empty + 56 + 32 * s, ph);
                mbar_wait(bar_ve + 8 * s, ((it >> 1) & 1) ^ 1);
                load(sb + FA_KV + s * 65536 + 32768, &P.mapV, bar_vf + 8 * s, row);
            };
            int vrow = 0;
            mbar_wait(empty + 8, ph);
            PT(1);
            load_q(0);
            PT(2);
#pragma unroll 1
            for (int item = 0; t >= 0; item++) {
                const int h = fa_head(t);
                if (item == 1 && blockIdx.x < 8) TS_MARK(14, 256);
#pragma unroll 1
                for (int j = fa_qt(t); j >= 0; j--, it++) {
                    const int s = it & 1;
                    uint32_t tn = 0;
                    asm volatile("{\n.reg .pred p;\nsetp.eq.u32 p, %2, 0;\n@p atom.relaxed.gpu.global.add.u32 %0, [%1], 1;\n}" : "+r"(tn) : "l"(&g_ctr[CT_ATTN] + lane), "r"(j | lane) : "memory");
                    if (it < 2) mbar_wait(empty + 40 + 32 * s, ph);
                    mbar_wait(bar_ke + 8 * s, ((it >> 1) & 1) ^ 1);
                    PT(4 + it);
                    load(sb + FA_KV + s * 65536, &P.mapK, bar_kf + 8 * s, h * SEQ + j * 128);
                    if (it > 0) load_v(it - 1, vrow);
                    vrow = h * SEQ + j * 128;
                    if (j == 0) {
                        const int tp = t;
                        t = FA_GRID + __shfl_sync(0xffffffff, tn, 0);
                        mbar_arrive_if(sb + SD_CL, tp < SD_CT && t >= SD_CT && lane == 0);
                        if (t >= FA_ITEMS) t = FA_ITEMS - 1 - t;
                        mbar_wait(bar_qe + 8 * ((item + 1) & 1), (((item + 1) >> 1) & 1) ^ 1);
                        load_q(item + 1);
                    }
                }
            }
            load_v(it - 1, vrow);
            TS_MARK(15, 256);
            const uint32_t tk = ~t;
            so = 0; ph = 1;
            TS_BEGIN_T(4, 256);
            wait_ctr(CT_P, FA_GRID);
#pragma unroll 1
            for (uint32_t e = P.jobs[tk & ~1u], en = P.jobs[tk | 1u]; e; e = en, en = 0) {
                const uint32_t mt = e & 15, na = e >> 10 & 127, n = na + (e >> 23);
#pragma unroll 1
                for (uint32_t i = 0; i < n; i++) {
                    const uint32_t b = i >= na, k = b ? (e >> 17 & 63) + i - na : (e >> 4 & 63) + i;
                    mbar_wait(so < 16 ? bar_ke + 8 * (~it & 1) : bar_ve - 16 + so, ((it - 1 - (so == 24)) >> 1) & 1);
                    mbar_wait(sb + SD_OE + so, ph);
                    if (elect_one()) {
                        mbar_expect_tx(sb + SD_OF + so, 49152);
                        tma_load_3d(sb + so * 6144 + 16384, &P.mapWo[b], sb + SD_OF + so, 0, k * 64, (tk & 1) * 4);
                    }
                    const bool late = k >= 2 * O2_HE;
                    if (i == 0 || i == na || k == 2 * O2_HE)
                        wait_ctr(b ? CT_CB + max(mt, CB_FIRST) : CT_CA + mt * 2 + late, b ? (CH_TS ? 256u : 64u) : late ? 2u * (NH - O2_HE) : 2u * O2_HE);
                    if (elect_one()) tma_load_2d(sb + so * 6144, &P.mapCtx[b], sb + SD_OF + so, (k & 1) * 64, (k >> 1) * SEQ + mt * 128);
                    so = (so + 8) & 31;
                    if (so == 0) ph ^= 1;
                }
            }
            TS_END_T(4, 256);
            finish_launch(lane);
        } else if (warp == 11) {
#pragma unroll 1
            for (int i = 0; i < 4000 && !mbar_test(done + 8 * SD_GW, 0); i++) __nanosleep(500);
            const uint4 gv0 = __ldg(reinterpret_cast<const uint4*>(P.gate_w) + lane), gv1 = __ldg(reinterpret_cast<const uint4*>(P.gate_w) + 32 + lane);
            const uint32_t gw[8] = {gv0.x, gv0.y, gv0.z, gv0.w, gv1.x, gv1.y, gv1.z, gv1.w};
#pragma unroll 1
            for (int r = blockIdx.x; r < SEQ; r += gridDim.x) {
                const uint4 x0 = __ldg(reinterpret_cast<const uint4*>(P.x + (size_t)r * DM) + lane), x1 = __ldg(reinterpret_cast<const uint4*>(P.x + (size_t)r * DM) + 32 + lane);
                const uint32_t xw[8] = {x0.x, x0.y, x0.z, x0.w, x1.x, x1.y, x1.z, x1.w};
                float sum = 0.f;
#pragma unroll
                for (int e = 0; e < 8; e++) {
                    const uint32_t pr = pack_bf16(__uint_as_float(xw[e] << 16) * __uint_as_float(gw[e] << 16), __uint_as_float(xw[e] & 0xffff0000u) * __uint_as_float(gw[e] & 0xffff0000u));
                    sum += __uint_as_float(pr << 16) + __uint_as_float(pr & 0xffff0000u);
                }
#pragma unroll
                for (int o = 16; o; o >>= 1) sum += __shfl_xor_sync(0xffffffff, sum, o);
                if (lane == 0) g_gate[r] = bf16r(__fdividef(1.f, 1.f + __expf(-bf16r(sum))));
            }
#pragma unroll 1
            for (int i = 0; i < 4000 && !mbar_test(sb + SD_CL, 0); i++) __nanosleep(500);
#pragma unroll 1
            for (int i = blockIdx.x * 32 + lane; i < SEQ * DM / 8; i += gridDim.x * 32) reinterpret_cast<uint4*>(P.out)[i] = make_uint4(0u, 0u, 0u, 0u);
            asm volatile("fence.proxy.async.global;" ::: "memory");
            __syncwarp();
            if (lane == 0) signal_ctr(CT_P);
        } else if (lane == 0) {
            const int wg = warp - 9;
#pragma unroll 1
            for (uint32_t d = done + wg * P3_LEN * 8;; d += 8, sched++) {
                const uint32_t e = *sched;
                if (((e >> 5) & 3) == 3) break;
                mbar_wait(d, 0);
                signal_ctr(CT_AP + ((e & 31) >> 1));
            }
            const uint32_t stg = sb + FA_O + wg * 16384;
            TS_END_T(0, 320);
            TS_BEGIN_T(1, 320);
#pragma unroll 1
            for (int n = 0;; n++) {
                mbar_wait(bar_of + 8 * wg, n & 1);
                int t;
                asm volatile("ld.shared.s32 %0, [%1];" : "=r"(t) : "r"(oslot + wg * 4) : "memory");
                asm volatile("fence.proxy.async.shared::cta;" ::: "memory");
                const bool last = t < 0;
                t &= 0xffff;
                const int qt = fa_qt(t), h = fa_head(t);
                tma_store_2d(&P.mapO, stg, 0, h * SEQ + qt * 128 + wg * 64);
                tma_store_2d(&P.mapO, stg + 8192, 64, h * SEQ + qt * 128 + wg * 64);
                asm volatile("cp.async.bulk.commit_group;" ::: "memory");
                asm volatile("cp.async.bulk.wait_group.read 0;" ::: "memory");
                mbar_arrive(bar_oe + 8 * wg);
                asm volatile("cp.async.bulk.wait_group 0;" ::: "memory");
                signal_ctr(CT_CA + qt * 2 + (h >= O2_HE));
                if (last) break;
            }
            TS_END_T(1, 320);
        }
    } else {
        asm volatile("setmaxnreg.inc.sync.aligned.u32 %0;" :: "n"(FA_RHI));
        const int wg = warp >> 2;
        {
            uint32_t a[32][4];
            float acc[64];
            const uint32_t b_lo = desc_lo(sb, 8192);
            const int r = warp * 16 + (lane & 15);
            const uint32_t la = sb + r * 128 + (((lane >> 4) ^ (r & 7)) << 4);
#pragma unroll
            for (int i = 0; i < 32; i++) ldsm_x4(a[i], la + i * 1024);
            const uint32_t rel = mapa_u32(empty, lane & 1);
            const int tw = threadIdx.x & 127;
            uint32_t so = so0, ph = 0;
            if (wg == 1) asm volatile("bar.arrive 1, 256;" ::: "memory");
#pragma unroll 1
            for (uint32_t d = done + wg * P3_LEN * 8;; d += 8, sched++) {
                const uint32_t e = *sched;
                if (((e >> 5) & 3) == 3) break;
                const bool na = e >> 10;
                const bool sig = tw < (na ? 4 : 2);
                uint32_t old = 0;
                auto release = [&]() { asm volatile("{\n.reg .pred p;\nsetp.ne.u32 p, %1, 0;\n@p mbarrier.arrive.shared::cluster.b64 _, [%0];\n}" :: "r"(rel + old), "r"((uint32_t)sig) : "memory"); };
                asm volatile("bar.sync %0, 256;" :: "r"(1 + wg) : "memory");
#pragma unroll
                for (int k = 0; k < 8; k++) {
                    const uint32_t sa = so;
                    if (na) {
                        mbar_wait(full + so, ph);
#pragma unroll
                        for (int kk = 0; kk < 4; kk++) ldsm_x4(a[k * 4 + kk], (la + so * 2048) ^ (kk * 32));
                        so += 8;
                        if (so == 8 * P3_STAGES) { so = 0; ph ^= 1; }
                    }
                    mbar_wait(full + so, ph);
                    wgmma_fence();
#pragma unroll
                    for (int kk = 0; kk < 4; kk++) wgmma_rs_n128_tb_lo(acc, a[k * 4 + kk], b_lo + so * 128 + kk * 128, (k | kk) != 0);
                    wgmma_commit();
                    if (k == P3_LAG) asm volatile("bar.arrive %0, 256;" :: "r"(2 - wg) : "memory");
                    if (k > 0) { wgmma_wait<1>(); release(); }
                    old = (lane & 2) ? sa : so;
                    so += 8;
                    if (so == 8 * P3_STAGES) { so = 0; ph ^= 1; }
                }
                bf16* dst = P.qkv[(e >> 5) & 3] + ((size_t)(e & 31) * SEQ + (((e >> 7) & 7) * 2 + rank) * 128 + warp * 16 + (lane >> 2)) * HD + (lane & 3) * 8;
                wgmma_wait<0>();
                release();
#pragma unroll
                for (int i = 0; i < 8; i++) {
                    const float* c = &acc[(i >> 1) * 16 + (i & 1) * 2];
                    *reinterpret_cast<uint4*>(dst + (i & 1) * 8 * HD + (i >> 1) * 32) =
                        make_uint4(pack_bf16(c[0], c[1]), pack_bf16(c[4], c[5]), pack_bf16(c[8], c[9]), pack_bf16(c[12], c[13]));
                }
                __syncwarp();
                mbar_arrive_if(d, lane == 0);
            }
        }
        const uint32_t tk = attn_consumer(sb, wg, warp & 3, lane);
        float acc[128];
#pragma unroll
        for (int i = 0; i < 128; i++) asm volatile("" : "=f"(acc[i]));
        const uint32_t a_lo = desc_lo(sb + wg * 8192, 16), b_lo = desc_lo(sb + 16384, 8192);
        const uint32_t st = sb + FA_O + warp * 4096, sl = st + (lane & 15) * 128 + (((lane >> 4) ^ (lane & 7)) << 4);
        const bool sig = (threadIdx.x & 127) == 0;
        uint32_t so = 0, ph = 0;
#pragma unroll 1
        for (uint32_t e = P.jobs[(tk >> 1) & ~1u], en = P.jobs[(tk >> 1) | 1u]; e; e = en, en = 0) {
            const uint32_t row = (e & 15) * 128 + warp * 16, na = e >> 10 & 127, n = na + (e >> 23);
            float g0, g1;
#pragma unroll 1
            for (uint32_t i = 0;; i++) {
                if (i == n || (i == na && i)) {
                    const float w0 = fmaxf(1.f - g0, 0x1p-40f), w1 = fmaxf(1.f - g1, 0x1p-40f);
                    const float r0 = i < n ? __fdividef(g0, w0) : na < n ? w0 : g0, r1 = i < n ? __fdividef(g1, w1) : na < n ? w1 : g1;
                    wgmma_wait<0>();
                    mbar_arrive_if(sb + SD_OE + ((so - 8) & 31), sig && i == n);
                    if (i == n) OT(3); else OT(2);
#pragma unroll
                    for (int c = 0; c < 32; c++) { acc[4 * c] *= r0; acc[4 * c + 1] *= r0; acc[4 * c + 2] *= r1; acc[4 * c + 3] *= r1; }
                    if (i == n) break;
                }
                mbar_wait(sb + SD_OF + so, ph);
                if (i == 0) OT(1);
                wgmma_fence();
#pragma unroll
                for (int kk = 0; kk < 4; kk++) wgmma_ss_n256_tb(acc, a_lo + so * 384 + kk * 2, b_lo + so * 384 + kk * 128, i | kk);
                wgmma_commit();
                if (i > 0) { wgmma_wait<1>(); mbar_arrive_if(sb + SD_OE + ((so - 8) & 31), sig); }
                else {
                    asm volatile("ld.relaxed.gpu.global.f32 %0, [%1];" : "=f"(g0) : "l"(g_gate + row + (lane >> 2)) : "memory");
                    asm volatile("ld.relaxed.gpu.global.f32 %0, [%1 + 32];" : "=f"(g1) : "l"(g_gate + row + (lane >> 2)) : "memory");
                }
                so = (so + 8) & 31;
                if (so == 0) ph ^= 1;
            }
            mbar_wait(bar_oe + 8 * wg, tk & 1);
#pragma unroll
            for (int q = 0; q < 4; q++) {
                if (lane == 0) asm volatile("cp.async.bulk.wait_group.read 1;" ::: "memory");
                __syncwarp();
#pragma unroll
                for (int t = 0; t < 4; t++) {
                    const float* c = &acc[q * 32 + t * 8];
                    stmatrix_x4((sl ^ (t * 32)) + (q & 1) * 2048, pack_bf16(c[0], c[1]), pack_bf16(c[2], c[3]), pack_bf16(c[4], c[5]), pack_bf16(c[6], c[7]));
                }
                fence_async_smem();
                __syncwarp();
                if (lane == 0) {
                    asm volatile("cp.reduce.async.bulk.tensor.2d.global.shared::cta.add.bulk_group [%0, {%2, %3}], [%1];"
                                 :: "l"((uint64_t)&P.mapOut), "r"(st + (q & 1) * 2048), "r"((tk & 2) * 128 + q * 64), "r"(row) : "memory");
                    asm volatile("cp.async.bulk.commit_group;" ::: "memory");
                }
            }
            OT(4);
        }
        if (lane == 0) asm volatile("cp.async.bulk.wait_group.read 0;" ::: "memory");
    }
}

typedef CUresult (*PFN_encodeTiled)(CUtensorMap*, CUtensorMapDataType, cuuint32_t, void*, const cuuint64_t*,
                                    const cuuint64_t*, const cuuint32_t*, const cuuint32_t*, CUtensorMapInterleave,
                                    CUtensorMapSwizzle, CUtensorMapL2promotion, CUtensorMapFloatOOBfill);
static PFN_encodeTiled g_encode = nullptr;

static void make_map(CUtensorMap* m, const void* ptr, uint64_t rows, uint64_t cols, uint32_t box_rows, bool narrow = false) {
    cuuint64_t dims[2] = {cols, rows};
    cuuint64_t strides[1] = {cols * 2};
    cuuint32_t box[2] = {narrow ? 16u : 64u, box_rows};
    cuuint32_t es[2] = {1, 1};
    g_encode(m, CU_TENSOR_MAP_DATA_TYPE_BFLOAT16, 2, const_cast<void*>(ptr), dims, strides, box, es,
             CU_TENSOR_MAP_INTERLEAVE_NONE, narrow ? CU_TENSOR_MAP_SWIZZLE_NONE : CU_TENSOR_MAP_SWIZZLE_128B, CU_TENSOR_MAP_L2_PROMOTION_L2_256B,
             CU_TENSOR_MAP_FLOAT_OOB_FILL_NONE);
}

static void make_map3(CUtensorMap* m, const void* ptr, uint64_t rows, uint64_t cols, uint32_t box_rows, uint32_t nblk) {
    cuuint64_t dims[3] = {64, rows, cols / 64};
    cuuint64_t strides[2] = {cols * 2, 128};
    cuuint32_t box[3] = {64u, box_rows, nblk};
    cuuint32_t es[3] = {1, 1, 1};
    g_encode(m, CU_TENSOR_MAP_DATA_TYPE_BFLOAT16, 3, const_cast<void*>(ptr), dims, strides, box, es,
             CU_TENSOR_MAP_INTERLEAVE_NONE, CU_TENSOR_MAP_SWIZZLE_128B, CU_TENSOR_MAP_L2_PROMOTION_L2_256B, CU_TENSOR_MAP_FLOAT_OOB_FILL_NONE);
}

template <typename... KArgs, typename... Args>
static void launch_pdl(void (*kernel)(KArgs...), int grid, int block, size_t smem, cudaStream_t st, bool pdl, Args... args) {
    cudaLaunchConfig_t cfg = {};
    cfg.gridDim = dim3(grid); cfg.blockDim = dim3(block); cfg.dynamicSmemBytes = smem; cfg.stream = st;
    cudaLaunchAttribute at[1];
    at[0].id = cudaLaunchAttributeProgrammaticStreamSerialization;
    at[0].val.programmaticStreamSerializationAllowed = 1;
    cfg.attrs = at; cfg.numAttrs = pdl ? 1 : 0;
    cudaLaunchKernelEx(&cfg, kernel, KArgs(args)...);
}

extern "C" void kernel_launch(void* const* d_in, const int* in_sizes, int n_in, void* d_out, int out_size) {
    const bf16* x = (const bf16*)d_in[0];
    const bf16* ckv = (const bf16*)d_in[1];
    const bf16* wq = (const bf16*)d_in[2];
    const bf16* wuk = (const bf16*)d_in[3];
    const bf16* wuv = (const bf16*)d_in[4];
    const bf16* wo = (const bf16*)d_in[5];
    const bf16* mem0 = (const bf16*)d_in[7];
    const bf16* Wq = (const bf16*)d_in[8];
    const bf16* Wk = (const bf16*)d_in[9];
    const bf16* Wv = (const bf16*)d_in[10];
    const bf16* Wo = (const bf16*)d_in[11];
    const bf16* gate_w = (const bf16*)d_in[13];
    bf16* out = (bf16*)d_out;

    static SideParams SP;
    static ChainParams CP;
    static bool init = false;
    static const void* last_in[15];
    bool same = init;
    for (int i = 0; i < 14 && same; i++) same = last_in[i] == d_in[i];
    same = same && last_in[14] == d_out;
    if (!init) {
        cudaDriverEntryPointQueryResult qr;
        cudaGetDriverEntryPoint("cuTensorMapEncodeTiled", (void**)&g_encode, cudaEnableDefault, &qr);
        cudaFuncSetAttribute(side_kernel, cudaFuncAttributeMaxDynamicSharedMemorySize, SD_SMEM);
        for (int p = 0; p < 34; p++) {
            uint16_t* t = SP.sched + p * P3_LEN;
            int n = 0, rows = -1;
            auto add = [&](int z, int mp, int head) {
#define P3_RQ 10
#define P3_RK 19
                head = (head + 32 - (z ? P3_RK : P3_RQ)) & 31;
                t[n++] = (uint16_t)(head | z << 5 | mp << 7 | (rows != (z ? 8 : 0) + mp) << 10);
                rows = (z ? 8 : 0) + mp;
            };
            const int mp = p & 7, kind = p >> 3;
            if (kind == 0) for (int h = 0; h < 23; h++) add(0, mp, h);
            else if (kind < 4) {
                for (int i = kind - 1; i < 54; i += 3) add(1 + (i & 1), mp, i >> 1);
                if (kind < 3) for (int h = 27; h < 32; h++) add(kind, mp, h);
                else for (int h = 23; h < 27; h++) add(0, mp, h);
            } else for (int i = 0; i < 20; i++) add(0, mp * 4 + i / 5, 27 + i % 5);
            int stages = 0;
            for (int i = 0; i < n; i++) stages += 8 << (t[i] >> 10);
            SP.first[p] = (uint8_t)((P3_STAGES - stages % P3_STAGES) % P3_STAGES);
            while (n < P3_LEN) t[n++] = 3 << 5;
        }
        cudaFuncSetAttribute(chain_kernel, cudaFuncAttributeMaxDynamicSharedMemorySize, C2_SMEM);
#define O6_SCHED 0x10000, 0x0, 0x20000000, 0x0, 0x20000001, 0x0, 0x5c01, 0x99a2, 0x1f800002, 0x0, 0x10800003, 0xfe6802, 0xb003, 0x4004, 0x764c104, 0x0, 0x19000004, 0x1001c05, 0x1f040005, 0x0, 0x17a20006, 0x3075, 0x880b146, 0x0, 0x5006, 0x9807, 0x19800007, 0x2780fd8, 0xf408, 0x0, 0x1e000008, 0x0, 0x12386289, 0x0, 0xe000009, 0x200667a, 0x1e08000a, 0x0, 0x95c000b, 0x9c0a, 0x12145e9b, 0x0, 0x500000b, 0x1000380c, 0x6a6c, 0xe480bed, 0xc80840d, 0x0, 0x5b2761d, 0x6680fde, 0xa40b, 0x63e0b7e, 0xa009, 0x516146e, 0x6e66a67, 0x52a168e, 0xb535, 0x2ade, 0xfc252c3, 0xc0e, 0xa571, 0x4d6139e, 0x104060ec, 0x0, 0x667f, 0x74be, 0x9c0f, 0x5800c3e
        const uint32_t sched[68] = {O6_SCHED};
        for (int i = 0; i < 68; i++) SP.jobs[i] = sched[i];
        init = true;
    }
    if (!same) {
        for (int i = 0; i < 14; i++) last_in[i] = d_in[i];
        last_in[14] = d_out;
        void *pQA, *pKA, *pVA, *pCA, *pCB;
        cudaGetSymbolAddress(&pQA, g_QA); cudaGetSymbolAddress(&pKA, g_KA); cudaGetSymbolAddress(&pVA, g_VA);
        cudaGetSymbolAddress(&pCA, g_ctxA); cudaGetSymbolAddress(&pCB, g_ctxB);
        pCA = pQA;
        make_map(&SP.mapA[0], x, SEQ, DM, 128);
        make_map(&SP.mapA[1], ckv, SEQ, DM, 128);
        const void* ws[3] = {wq, wuk, wuv};
        void* cs[3] = {pQA, pKA, pVA};
        for (int i = 0; i < 3; i++) { make_map(&SP.mapW[i], ws[i], DM, NQ, 64); SP.qkv[i] = (bf16*)cs[i]; }
        make_map(&CP.mapX, x, SEQ, DM, SEGL);
        make_map(&CP.mapM, mem0, NMEM, DM, NMEM);
        make_map(&CP.mapW[0], Wq, DM, NQ, 64);
        make_map(&CP.mapW[1], Wk, DM, NQ, 64);
        make_map(&CP.mapW[2], Wv, DM, NQ, 64);
        make_map(&CP.mapWo, Wo, NQ, DM, 64);
        make_map(&SP.mapQ, pQA, NH * SEQ, HD, 128);
        make_map(&SP.mapK, pKA, NH * SEQ, HD, 128);
        make_map(&SP.mapV, pVA, NH * SEQ, HD, 128);
        make_map(&SP.mapO, pCA, NH * SEQ, HD, 64);
        make_map(&SP.mapCtx[0], pCA, NH * SEQ, HD, 128);
        make_map(&SP.mapCtx[1], pCB, NH * SEQ, HD, 128);
        make_map3(&SP.mapWo[0], wo, NQ, DM, 64, 4);
        make_map3(&SP.mapWo[1], Wo, NQ, DM, 64, 4);
        make_map(&SP.mapOut, out, SEQ, DM, 16);
        SP.out = out;
        make_map(&CP.mapC, pCB, NH * SEQ, HD, 64);
        make_map(&CP.mapS, pCB, NH * SEQ, HD, 32, true);
        CP.out = out;
        SP.x = x; SP.gate_w = gate_w;
    }
    cudaStream_t s1 = cudaStreamPerThread;
    const bool pdl = true;
    launch_pdl(chain_kernel, 64, 384, C2_SMEM, s1, false, CP);
    launch_pdl(side_kernel, FA_GRID, 384, SD_SMEM, s1, pdl, SP);
}
```

```cpp
#include <cuda_runtime.h>
#include <cuda_bf16.h>
#include <cuda.h>
#include <stdint.h>
#include <type_traits>

constexpr int SEQ = 2048;
constexpr int DM = 512;
constexpr int NH = 32;
constexpr int HD = 128;
constexpr int NQ = NH * HD;
constexpr int SEGL = 32;
constexpr int NMEM = 8;
constexpr int NSEG = SEQ / SEGL;

typedef __nv_bfloat16 bf16;

__device__ bf16 g_QA[SEQ * NQ];
__device__ bf16 g_KA[SEQ * NQ];
__device__ bf16 g_VA[SEQ * NQ];
__device__ bf16 g_ctxA[SEQ * NQ];
__device__ bf16 g_ctxB[SEQ * NQ];
constexpr int CT_ATTN = 1, CT_FIN = 5;
constexpr int CT_P = 48;
constexpr int CT_AP = 64;
#define O2_HE 24
constexpr int CT_CA = 128;
constexpr int CT_CB = 160;
#define CB_FIRST 11
constexpr int CT_N = 192;
__device__ unsigned int g_ctr[CT_N];
__device__ float g_gate[SEQ];
__device__ uint2 g_xbuf[2 * 8 * 8 * 128];

#define FA_GRID 68

#define P2_MARK 0
#define TS_MARK(id, tid)
#define TS_MARK2(id, tid)
#define TS_BEGIN(id)
#define TS_END(id)
#define TS_BEGIN_T(id, tid)
#define TS_END_T(id, tid)
__device__ __forceinline__ void pdl_launch_dependents() { asm volatile("griddepcontrol.launch_dependents;" ::: "memory"); }
__device__ __forceinline__ void wait_ctr(int idx, unsigned int n) {
    unsigned int v; int it = 0;
    do { asm volatile("ld.acquire.gpu.global.u32 %0, [%1];" : "=r"(v) : "l"(&g_ctr[idx]) : "memory"); } while (v < n && ++it < (1 << 22));
}
__device__ __forceinline__ void signal_ctr(int idx) {
    asm volatile("fence.proxy.async.global;" ::: "memory");
    asm volatile("red.release.gpu.global.add.u32 [%0], 1;" :: "l"(&g_ctr[idx]) : "memory");
}
__device__ __forceinline__ void signal_ctr_generic(int idx) {
    asm volatile("red.release.gpu.global.add.u32 [%0], 1;" :: "l"(&g_ctr[idx]) : "memory");
}
__device__ __forceinline__ void finish_launch(int lane) {
    unsigned int tk = 0;
    if (lane == 0) tk = atomicAdd(&g_ctr[CT_FIN], 1u);
    tk = __shfl_sync(0xffffffff, tk, 0);
    if (tk == 64 + 68 - 1)
#pragma unroll 1
        for (int i = lane; i < CT_N; i += 32) g_ctr[i] = 0u;
}
__device__ __forceinline__ uint4 quad_transpose(uint32_t p0, uint32_t p1, uint32_t p2, uint32_t p3, int lane) {
    const bool o1 = lane & 1, o2 = lane & 2;
    uint32_t s0 = o1 ? p0 : p1, s1 = o1 ? p2 : p3;
    s0 = __shfl_xor_sync(0xffffffff, s0, 1); s1 = __shfl_xor_sync(0xffffffff, s1, 1);
    const uint32_t a_lo = o1 ? s0 : p0, a_hi = o1 ? p1 : s0, b_lo = o1 ? s1 : p2, b_hi = o1 ? p3 : s1;
    uint32_t t0 = o2 ? a_lo : b_lo, t1 = o2 ? a_hi : b_hi;
    t0 = __shfl_xor_sync(0xffffffff, t0, 2); t1 = __shfl_xor_sync(0xffffffff, t1, 2);
    return o2 ? make_uint4(t0, t1, b_lo, b_hi) : make_uint4(a_lo, a_hi, t0, t1);
}
__device__ __forceinline__ uint32_t smem_u32(const void* p) {
    return (uint32_t)__cvta_generic_to_shared(p);
}
__device__ __forceinline__ void mbar_init(uint32_t bar, uint32_t count) {
    asm volatile("mbarrier.init.shared::cta.b64 [%0], %1;" :: "r"(bar), "r"(count));
}
__device__ __forceinline__ void mbar_expect_tx(uint32_t bar, uint32_t bytes) {
    asm volatile("mbarrier.arrive.expect_tx.shared::cta.b64 _, [%0], %1;" :: "r"(bar), "r"(bytes) : "memory");
}
__device__ __forceinline__ void mbar_arrive(uint32_t bar) {
    asm volatile("mbarrier.arrive.shared::cta.b64 _, [%0];" :: "r"(bar) : "memory");
}
__device__ __forceinline__ void mbar_wait(uint32_t bar, uint32_t parity) {
    asm volatile(
        "{\n"
        ".reg .pred p, q;\n"
        ".reg .u32 c;\n"
        "mov.u32 c, 0;\n"
        "WAIT_LOOP:\n"
        "mbarrier.try_wait.parity.shared::cta.b64 p, [%0], %1;\n"
        "@p bra WAIT_DONE;\n"
        "add.u32 c, c, 1;\n"
        "setp.lt.u32 q, c, 4000000;\n"
        "@q bra WAIT_LOOP;\n"
        "WAIT_DONE:\n"
        "}\n" :: "r"(bar), "r"(parity) : "memory");
}
__device__ __forceinline__ void tma_load_2d(uint32_t dst, const CUtensorMap* map, uint32_t bar, int c0, int c1) {
    asm volatile(
        "cp.async.bulk.tensor.2d.shared::cluster.global.mbarrier::complete_tx::bytes [%0], [%1, {%3, %4}], [%2];"
        :: "r"(dst), "l"((uint64_t)map), "r"(bar), "r"(c0), "r"(c1) : "memory");
}
constexpr uint64_t L2_NORMAL = 0x1000000000000000ull, L2_FIRST = 0x12F0000000000000ull;
__device__ __forceinline__ void tma_load_2d(uint32_t dst, const CUtensorMap* map, uint32_t bar, int c0, int c1, uint64_t hint) {
    asm volatile(
        "cp.async.bulk.tensor.2d.shared::cluster.global.mbarrier::complete_tx::bytes.L2::cache_hint [%0], [%1, {%3, %4}], [%2], %5;"
        :: "r"(dst), "l"((uint64_t)map), "r"(bar), "r"(c0), "r"(c1), "l"(hint) : "memory");
}
__device__ __forceinline__ void wgmma_fence() { asm volatile("wgmma.fence.sync.aligned;" ::: "memory"); }
__device__ __forceinline__ void wgmma_commit() { asm volatile("wgmma.commit_group.sync.aligned;" ::: "memory"); }
template <int N> __device__ __forceinline__ void wgmma_wait() {
    asm volatile("wgmma.wait_group.sync.aligned %0;" :: "n"(N) : "memory");
}
__device__ __forceinline__ uint64_t make_desc(uint32_t addr, uint32_t lbo, uint32_t sbo) {
    uint64_t d = 0;
    d |= (uint64_t)((addr & 0x3FFFF) >> 4);
    d |= (uint64_t)((lbo >> 4) & 0x3FFF) << 16;
    d |= (uint64_t)((sbo >> 4) & 0x3FFF) << 32;
    d |= (uint64_t)1 << 62;
    return d;
}

#define ACC64(d) \
    "+f"(d[0]), "+f"(d[1]), "+f"(d[2]), "+f"(d[3]), "+f"(d[4]), "+f"(d[5]), "+f"(d[6]), "+f"(d[7]), \
    "+f"(d[8]), "+f"(d[9]), "+f"(d[10]), "+f"(d[11]), "+f"(d[12]), "+f"(d[13]), "+f"(d[14]), "+f"(d[15]), \
    "+f"(d[16]), "+f"(d[17]), "+f"(d[18]), "+f"(d[19]), "+f"(d[20]), "+f"(d[21]), "+f"(d[22]), "+f"(d[23]), \
    "+f"(d[24]), "+f"(d[25]), "+f"(d[26]), "+f"(d[27]), "+f"(d[28]), "+f"(d[29]), "+f"(d[30]), "+f"(d[31]), \
    "+f"(d[32]), "+f"(d[33]), "+f"(d[34]), "+f"(d[35]), "+f"(d[36]), "+f"(d[37]), "+f"(d[38]), "+f"(d[39]), \
    "+f"(d[40]), "+f"(d[41]), "+f"(d[42]), "+f"(d[43]), "+f"(d[44]), "+f"(d[45]), "+f"(d[46]), "+f"(d[47]), \
    "+f"(d[48]), "+f"(d[49]), "+f"(d[50]), "+f"(d[51]), "+f"(d[52]), "+f"(d[53]), "+f"(d[54]), "+f"(d[55]), \
    "+f"(d[56]), "+f"(d[57]), "+f"(d[58]), "+f"(d[59]), "+f"(d[60]), "+f"(d[61]), "+f"(d[62]), "+f"(d[63])
#define ACC64_STR \
    "{%0, %1, %2, %3, %4, %5, %6, %7, %8, %9, %10, %11, %12, %13, %14, %15, " \
    "%16, %17, %18, %19, %20, %21, %22, %23, %24, %25, %26, %27, %28, %29, %30, %31, " \
    "%32, %33, %34, %35, %36, %37, %38, %39, %40, %41, %42, %43, %44, %45, %46, %47, " \
    "%48, %49, %50, %51, %52, %53, %54, %55, %56, %57, %58, %59, %60, %61, %62, %63}"

template <int TB>
__device__ __forceinline__ void wgmma_ss_n128(float (&d)[64], uint64_t da, uint64_t db, int scale_d) {
    asm volatile(
        "{\n.reg .pred p;\nsetp.ne.b32 p, %66, 0;\n"
        "wgmma.mma_async.sync.aligned.m64n128k16.f32.bf16.bf16 " ACC64_STR ", %64, %65, p, 1, 1, 0, %67;\n}\n"
        : ACC64(d) : "l"(da), "l"(db), "r"(scale_d), "n"(TB));
}
__device__ __forceinline__ uint32_t desc_lo(uint32_t addr, uint32_t lbo) { return ((addr & 0x3FFFF) >> 4) | ((lbo >> 4) << 16); }
template <int TB>
__device__ __forceinline__ void wgmma_ss_n128_lo(float (&d)[64], uint32_t da_lo, uint32_t db_lo, int scale_d) {
    asm volatile(
        "{\n.reg .pred p;\n.reg .b64 da, db;\nsetp.ne.b32 p, %66, 0;\n"
        "mov.b64 da, {%64, 0x40000040};\nmov.b64 db, {%65, 0x40000040};\n"
        "wgmma.mma_async.sync.aligned.m64n128k16.f32.bf16.bf16 " ACC64_STR ", da, db, p, 1, 1, 0, %67;\n}\n"
        : ACC64(d) : "r"(da_lo), "r"(db_lo), "r"(scale_d), "n"(TB));
}
__device__ __forceinline__ void wgmma_rs_n128_tb(float (&d)[64], uint32_t a0, uint32_t a1, uint32_t a2, uint32_t a3,
                                                 uint64_t db, int scale_d) {
    asm volatile(
        "{\n.reg .pred p;\nsetp.ne.b32 p, %69, 0;\n"
        "wgmma.mma_async.sync.aligned.m64n128k16.f32.bf16.bf16 " ACC64_STR ", {%64, %65, %66, %67}, %68, p, 1, 1, 1;\n}\n"
        : ACC64(d) : "r"(a0), "r"(a1), "r"(a2), "r"(a3), "l"(db), "r"(scale_d));
}
__device__ __forceinline__ void wgmma_rs_n80(float (&d)[40], const uint32_t (&a)[4], uint32_t db_lo, int scale_d) {
    asm volatile(
        "{\n.reg .pred p;\n.reg .b64 db;\nsetp.ne.b32 p, %45, 0;\nmov.b64 db, {%44, 0x40000040};\n"
        "wgmma.mma_async.sync.aligned.m64n80k16.f32.bf16.bf16 "
        "{%0, %1, %2, %3, %4, %5, %6, %7, %8, %9, %10, %11, %12, %13, %14, %15, %16, %17, %18, %19, %20, %21, %22, %23, %24, %25, %26, %27, %28, %29, %30, %31, %32, %33, %34, %35, %36, %37, %38, %39}, "
        "{%40, %41, %42, %43}, db, p, 1, 1, 0;\n}\n"
        : "+f"(d[0]), "+f"(d[1]), "+f"(d[2]), "+f"(d[3]), "+f"(d[4]), "+f"(d[5]), "+f"(d[6]), "+f"(d[7]), "+f"(d[8]), "+f"(d[9]), "+f"(d[10]), "+f"(d[11]), "+f"(d[12]), "+f"(d[13]), "+f"(d[14]), "+f"(d[15]), "+f"(d[16]), "+f"(d[17]), "+f"(d[18]), "+f"(d[19]), "+f"(d[20]), "+f"(d[21]), "+f"(d[22]), "+f"(d[23]), "+f"(d[24]), "+f"(d[25]), "+f"(d[26]), "+f"(d[27]), "+f"(d[28]), "+f"(d[29]), "+f"(d[30]), "+f"(d[31]), "+f"(d[32]), "+f"(d[33]), "+f"(d[34]), "+f"(d[35]), "+f"(d[36]), "+f"(d[37]), "+f"(d[38]), "+f"(d[39])
        : "r"(a[0]), "r"(a[1]), "r"(a[2]), "r"(a[3]), "r"(db_lo), "r"(scale_d));
}
__device__ __forceinline__ void wgmma_ss_n256_tb(float (&d)[128], uint32_t da_lo, uint32_t db_lo, int scale_d) {
    asm volatile(
        "{\n.reg .pred p;\n.reg .b64 da, db;\nsetp.ne.b32 p, %130, 0;\nmov.b64 da, {%128, 0x40000040};\nmov.b64 db, {%129, 0x40000040};\n"
        "wgmma.mma_async.sync.aligned.m64n256k16.f32.bf16.bf16 {%0, %1, %2, %3, %4, %5, %6, %7, %8, %9, %10, %11, %12, %13, %14, %15, %16, %17, %18, %19, %20, %21, %22, %23, %24, %25, %26, %27, %28, %29, %30, %31, %32, %33, %34, %35, %36, %37, %38, %39, %40, %41, %42, %43, %44, %45, %46, %47, %48, %49, %50, %51, %52, %53, %54, %55, %56, %57, %58, %59, %60, %61, %62, %63, %64, %65, %66, %67, %68, %69, %70, %71, %72, %73, %74, %75, %76, %77, %78, %79, %80, %81, %82, %83, %84, %85, %86, %87, %88, %89, %90, %91, %92, %93, %94, %95, %96, %97, %98, %99, %100, %101, %102, %103, %104, %105, %106, %107, %108, %109, %110, %111, %112, %113, %114, %115, %116, %117, %118, %119, %120, %121, %122, %123, %124, %125, %126, %127}, da, db, p, 1, 1, 0, 1;\n}\n"
        : "+f"(d[0]), "+f"(d[1]), "+f"(d[2]), "+f"(d[3]), "+f"(d[4]), "+f"(d[5]), "+f"(d[6]), "+f"(d[7]), "+f"(d[8]), "+f"(d[9]), "+f"(d[10]), "+f"(d[11]), "+f"(d[12]), "+f"(d[13]), "+f"(d[14]), "+f"(d[15]), "+f"(d[16]), "+f"(d[17]), "+f"(d[18]), "+f"(d[19]), "+f"(d[20]), "+f"(d[21]), "+f"(d[22]), "+f"(d[23]), "+f"(d[24]), "+f"(d[25]), "+f"(d[26]), "+f"(d[27]), "+f"(d[28]), "+f"(d[29]), "+f"(d[30]), "+f"(d[31]), "+f"(d[32]), "+f"(d[33]), "+f"(d[34]), "+f"(d[35]), "+f"(d[36]), "+f"(d[37]), "+f"(d[38]), "+f"(d[39]), "+f"(d[40]), "+f"(d[41]), "+f"(d[42]), "+f"(d[43]), "+f"(d[44]), "+f"(d[45]), "+f"(d[46]), "+f"(d[47]), "+f"(d[48]), "+f"(d[49]), "+f"(d[50]), "+f"(d[51]), "+f"(d[52]), "+f"(d[53]), "+f"(d[54]), "+f"(d[55]), "+f"(d[56]), "+f"(d[57]), "+f"(d[58]), "+f"(d[59]), "+f"(d[60]), "+f"(d[61]), "+f"(d[62]), "+f"(d[63]), "+f"(d[64]), "+f"(d[65]), "+f"(d[66]), "+f"(d[67]), "+f"(d[68]), "+f"(d[69]), "+f"(d[70]), "+f"(d[71]), "+f"(d[72]), "+f"(d[73]), "+f"(d[74]), "+f"(d[75]), "+f"(d[76]), "+f"(d[77]), "+f"(d[78]), "+f"(d[79]), "+f"(d[80]), "+f"(d[81]), "+f"(d[82]), "+f"(d[83]), "+f"(d[84]), "+f"(d[85]), "+f"(d[86]), "+f"(d[87]), "+f"(d[88]), "+f"(d[89]), "+f"(d[90]), "+f"(d[91]), "+f"(d[92]), "+f"(d[93]), "+f"(d[94]), "+f"(d[95]), "+f"(d[96]), "+f"(d[97]), "+f"(d[98]), "+f"(d[99]), "+f"(d[100]), "+f"(d[101]), "+f"(d[102]), "+f"(d[103]), "+f"(d[104]), "+f"(d[105]), "+f"(d[106]), "+f"(d[107]), "+f"(d[108]), "+f"(d[109]), "+f"(d[110]), "+f"(d[111]), "+f"(d[112]), "+f"(d[113]), "+f"(d[114]), "+f"(d[115]), "+f"(d[116]), "+f"(d[117]), "+f"(d[118]), "+f"(d[119]), "+f"(d[120]), "+f"(d[121]), "+f"(d[122]), "+f"(d[123]), "+f"(d[124]), "+f"(d[125]), "+f"(d[126]), "+f"(d[127])
        : "r"(da_lo), "r"(db_lo), "r"(scale_d));
}
__device__ __forceinline__ void stmatrix_x4(uint32_t addr, uint32_t r0, uint32_t r1, uint32_t r2, uint32_t r3) {
    asm volatile("stmatrix.sync.aligned.m8n8.x4.shared.b16 [%0], {%1, %2, %3, %4};" :: "r"(addr), "r"(r0), "r"(r1), "r"(r2), "r"(r3) : "memory");
}
__device__ __forceinline__ void tma_store_2d(const CUtensorMap* map, uint32_t src, int c0, int c1) {
    asm volatile("cp.async.bulk.tensor.2d.global.shared::cta.bulk_group [%0, {%2, %3}], [%1];"
                 :: "l"((uint64_t)map), "r"(src), "r"(c0), "r"(c1) : "memory");
}
__device__ __forceinline__ float ex2f(float x) { float y; asm("ex2.approx.ftz.f32 %0, %1;" : "=f"(y) : "f"(x)); return y; }
__device__ __forceinline__ uint32_t pack_bf16(float lo, float hi) {
    __nv_bfloat162 v = __floats2bfloat162_rn(lo, hi);
    return *reinterpret_cast<uint32_t*>(&v);
}
__device__ __forceinline__ float bf16r(float x) { return __uint_as_float(pack_bf16(0.f, x) & 0xffff0000u); }
__device__ __forceinline__ void mma_16816(float (&c)[4], uint32_t a0, uint32_t a1, uint32_t a2, uint32_t a3,
                                          uint32_t b0, uint32_t b1) {
    asm volatile(
        "mma.sync.aligned.m16n8k16.row.col.f32.bf16.bf16.f32 {%0,%1,%2,%3}, {%4,%5,%6,%7}, {%8,%9}, {%0,%1,%2,%3};"
        : "+f"(c[0]), "+f"(c[1]), "+f"(c[2]), "+f"(c[3])
        : "r"(a0), "r"(a1), "r"(a2), "r"(a3), "r"(b0), "r"(b1));
}
__device__ __forceinline__ void ldmatrix_x4_trans(uint32_t& r0, uint32_t& r1, uint32_t& r2, uint32_t& r3, uint32_t addr) {
    asm volatile("ldmatrix.sync.aligned.m8n8.x4.trans.shared.b16 {%0,%1,%2,%3}, [%4];"
                 : "=r"(r0), "=r"(r1), "=r"(r2), "=r"(r3) : "r"(addr));
}

constexpr uint32_t FA_Q = 0, FA_KV = 65536, FA_O = 196608, FA_BAR = 229376;
constexpr int FA_ITEMS = 16 * NH;
__device__ __forceinline__ int fa_qt(int t) { return 15 - ((t & 127) >> 3); }
__device__ __forceinline__ int fa_head(int t) { return (t >> 7) * 8 + (t & 7); }
__device__ __forceinline__ uint32_t mbar_test(uint32_t bar, uint32_t parity) {
    uint32_t done;
    asm volatile(
        "{\n.reg .pred p;\n"
        "mbarrier.test_wait.parity.shared::cta.b64 p, [%1], %2;\n"
        "selp.u32 %0, 1, 0, p;\n}\n" : "=r"(done) : "r"(bar), "r"(parity) : "memory");
    return done;
}
__device__ __forceinline__ void mbar_arrive_if(uint32_t bar, bool c) {
    asm volatile("{\n.reg .pred p;\nsetp.ne.u32 p, %1, 0;\n@p mbarrier.arrive.shared::cta.b64 _, [%0];\n}" :: "r"(bar), "r"((uint32_t)c) : "memory");
}
__device__ __forceinline__ uint32_t pin(uint32_t v) { asm volatile("" : "+r"(v)); return v; }
__device__ __forceinline__ void sts128_if(bool c, uint32_t a, uint32_t v0, uint32_t v1, uint32_t v2, uint32_t v3) {
    asm volatile("{\n.reg .pred p;\nsetp.ne.u32 p, %5, 0;\n@p st.shared.v4.b32 [%0], {%1, %2, %3, %4};\n}" :: "r"(a), "r"(v0), "r"(v1), "r"(v2), "r"(v3), "r"((uint32_t)c) : "memory");
}
__device__ __forceinline__ void wgmma_rs_n128_tb_lo(float (&d)[64], const uint32_t* a, uint32_t db_lo, int scale_d) {
    asm volatile(
        "{\n.reg .pred p;\n.reg .b64 db;\nsetp.ne.b32 p, %69, 0;\nmov.b64 db, {%68, 0x40000040};\n"
        "wgmma.mma_async.sync.aligned.m64n128k16.f32.bf16.bf16 " ACC64_STR ", {%64, %65, %66, %67}, db, p, 1, 1, 1;\n}\n"
        : ACC64(d) : "r"(a[0]), "r"(a[1]), "r"(a[2]), "r"(a[3]), "r"(db_lo), "r"(scale_d));
}
#define FA_TEST 48
#define FA_PIN 32

__device__ __forceinline__ void wgmma_ss_n64_lo(float (&d)[64], uint32_t da_lo, uint32_t db_lo, int scale_d) {
    asm volatile(
        "{\n.reg .pred p;\n.reg .b64 da, db;\nsetp.ne.b32 p, %34, 0;\n"
        "mov.b64 da, {%32, 0x40000040};\nmov.b64 db, {%33, 0x40000040};\n"
        "wgmma.mma_async.sync.aligned.m64n64k16.f32.bf16.bf16 {%0, %1, %2, %3, %4, %5, %6, %7, %8, %9, %10, %11, %12, %13, %14, %15, "
        "%16, %17, %18, %19, %20, %21, %22, %23, %24, %25, %26, %27, %28, %29, %30, %31}, da, db, p, 1, 1, 0, 0;\n}\n"
        : "+f"(d[0]), "+f"(d[1]), "+f"(d[2]), "+f"(d[3]), "+f"(d[4]), "+f"(d[5]), "+f"(d[6]), "+f"(d[7]), "+f"(d[8]), "+f"(d[9]), "+f"(d[10]),
          "+f"(d[11]), "+f"(d[12]), "+f"(d[13]), "+f"(d[14]), "+f"(d[15]), "+f"(d[16]), "+f"(d[17]), "+f"(d[18]), "+f"(d[19]), "+f"(d[20]),
          "+f"(d[21]), "+f"(d[22]), "+f"(d[23]), "+f"(d[24]), "+f"(d[25]), "+f"(d[26]), "+f"(d[27]), "+f"(d[28]), "+f"(d[29]), "+f"(d[30]), "+f"(d[31])
        : "r"(da_lo), "r"(db_lo), "r"(scale_d));
}
#define FA_UD 1
#define FA_PP 0
#define FA_NOFB 0
#define FA_DPIN 16
#define FA_RLO 40
#define FA_RHI 232
#define FA_LIM 0x1p40f
__device__ __forceinline__ uint32_t attn_consumer(const uint32_t sb, const int wg, const int w4, const int lane) {
    const uint32_t bar_q = sb + FA_BAR, bar_of = bar_q + 96, bar_oe = bar_q + 112, oslot = bar_q + 144;
    const bool lane0 = lane == 0;
    float o[64], sacc[64];
    uint32_t pa[32];
    float ms0 = 0.f, ms1 = 0.f, lrow0 = 1.f, lrow1 = 1.f;
    const float sc = 0.08838834764831845f * 1.4426950408889634f;
    const uint32_t q_lo = desc_lo(sb + FA_Q + wg * 8192, 16), k_lo = desc_lo(sb + FA_KV, 16), v_lo = desc_lo(sb + FA_KV + 32768, 16384);
    uint32_t qd = q_lo + 2048, kd = k_lo + 4096, vd = v_lo, bs = bar_q + 8, bi = bar_q + 8;
    auto issue_qk = [&](uint32_t a, bool half) {
        const uint32_t b = kd;
#pragma unroll
        for (int i = 0; i < 64; i++) asm volatile("" : "=f"(sacc[i]));
#pragma unroll
        for (int kk = 0; kk < 8; kk++) {
            if (half) wgmma_ss_n64_lo(sacc, a + (kk >> 2) * 1024 + (kk & 3) * 2, b + (kk >> 2) * 1024 + (kk & 3) * 2, kk != 0);
            else wgmma_ss_n128_lo<0>(sacc, a + (kk >> 2) * 1024 + (kk & 3) * 2, b + (kk >> 2) * 1024 + (kk & 3) * 2, kk != 0);
        }
        wgmma_commit();
    };
    auto issue_pv = [&](bool acc) {
        const uint32_t b = vd;
#pragma unroll
        for (int kk = 0; kk < 8; kk++) wgmma_rs_n128_tb_lo(o, &pa[kk * 4], b + kk * 128, kk != 0 || acc);
        wgmma_commit();
    };
    auto turn_wait = [&]() { asm volatile("bar.sync %0, 256;" :: "r"(1 + wg) : "memory"); };
    auto turn_pass = [&]() { asm volatile("bar.arrive %0, 256;" :: "r"(2 - wg) : "memory"); };
    int item = -1, it = -1, j = 0, nkv = 1, t = 0;
    auto redo = [&](float& l0, float& l1) {
        const size_t row0 = (size_t)fa_head(t) * SEQ + (lane >> 2);
        const uint32_t* qg = reinterpret_cast<const uint32_t*>(g_QA + (row0 + (nkv - 1) * 128 + wg * 64 + w4 * 16) * HD) + (lane & 3);
        const uint32_t* kg = reinterpret_cast<const uint32_t*>(g_KA + (row0 + (nkv - 1 - j) * 128) * HD) + (lane & 3);
        auto ldg = [](const uint32_t* p) { uint32_t v; asm volatile("ld.relaxed.gpu.global.u32 %0, [%1];" : "=r"(v) : "l"(p) : "memory"); return v; };
        const int r0 = j ? 1 << 20 : wg * 64 + w4 * 16 + (lane >> 2) - (lane & 3) * 2;
        float mx0 = -INFINITY, mx1 = -INFINITY;
        const float m0 = ms0, m1 = ms1;
        uint4 tmp[8];
        l0 = 0.f; l1 = 0.f;
#pragma unroll 1
        for (int ps = 0; ps < 32; ps++) {
            const int nb = ps & 15;
            float c[4] = {0.f, 0.f, 0.f, 0.f};
#pragma unroll 1
            for (int kk = 0; kk < 64; kk += 8)
                mma_16816(c, ldg(qg + kk), ldg(qg + kk + 8 * 64), ldg(qg + kk + 4), ldg(qg + kk + 8 * 64 + 4), ldg(kg + nb * 8 * 64 + kk), ldg(kg + nb * 8 * 64 + kk + 4));
#pragma unroll
            for (int i = 0; i < 4; i++)
                if (nb * 8 + (i & 1) - ((i & 2) ? 8 : 0) > r0) c[i] = -INFINITY;
            mx0 = fmaxf(mx0, fmaxf(c[0], c[1])); mx1 = fmaxf(mx1, fmaxf(c[2], c[3]));
#pragma unroll
            for (int i = 0; i < 4; i++) c[i] = ex2f(fmaf(c[i], sc, (i & 2) ? ms1 : ms0));
            l0 += c[0] + c[1]; l1 += c[2] + c[3];
            reinterpret_cast<uint2*>(tmp)[nb] = make_uint2(pack_bf16(c[0], c[1]), pack_bf16(c[2], c[3]));
            if (ps == 15) {
                mx0 = fmaxf(mx0, __shfl_xor_sync(0xffffffff, mx0, 1)); mx1 = fmaxf(mx1, __shfl_xor_sync(0xffffffff, mx1, 1));
                mx0 = fmaxf(mx0, __shfl_xor_sync(0xffffffff, mx0, 2)); mx1 = fmaxf(mx1, __shfl_xor_sync(0xffffffff, mx1, 2));
                ms0 = fminf(-mx0 * sc, ms0); ms1 = fminf(-mx1 * sc, ms1);
                l0 = 0.f; l1 = 0.f;
            }
        }
        const float a0 = ex2f(ms0 - m0), a1 = ex2f(ms1 - m1);
        lrow0 *= a0; lrow1 *= a1;
#pragma unroll
        for (int i = 0; i < 64; i++) o[i] *= (i & 2) ? a1 : a0;
#pragma unroll
        for (int i = 0; i < 8; i++) { pa[4 * i] = tmp[i].x; pa[4 * i + 1] = tmp[i].y; pa[4 * i + 2] = tmp[i].z; pa[4 * i + 3] = tmp[i].w; }
    };
    auto pin_after = [&](float v) {
        asm volatile("{\n.reg .pred p;\nsetp.eq.f32 p, %1, %2;\n@p st.shared.f32 [%0], %1;\n}" :: "r"(oslot + 16), "f"(v), "f"(ms0) : "memory");
    };
    auto pack_p = [&](int i) {
        if (i >= FA_PP) pa[i >> 1] = pack_bf16(sacc[i - 1], sacc[i]);
        else asm volatile("{\n.reg .pred p;\nsetp.ne.b32 p, %3, 0x7fc12345;\n@p cvt.rn.bf16x2.f32 %0, %2, %1;\n}" : "+r"(pa[i >> 1]) : "f"(sacc[i - 1]), "f"(sacc[i]), "r"(__float_as_uint(o[0])));
    };
    uint32_t ok = 0, okq = 0;
    int tn = 0;
    auto tests = [&]() {
        ok = mbar_test(bs + 48, (it >> 1) & 1);
        asm volatile("ld.shared.s32 %0, [%1];" : "=r"(tn) : "r"((bi ^ 8) + 128) : "memory");
        ok &= mbar_test((bs ^ 8) + 32, ((it + 1) >> 1) & 1);
        okq = mbar_test(bi ^ 8, ((item + 1) >> 1) & 1);
    };
    auto epilogue = [&](int tag, bool real) {
        float l0 = lrow0, l1 = lrow1;
        l0 += __shfl_xor_sync(0xffffffff, l0, 1); l1 += __shfl_xor_sync(0xffffffff, l1, 1);
        l0 += __shfl_xor_sync(0xffffffff, l0, 2); l1 += __shfl_xor_sync(0xffffffff, l1, 2);
        float i0, i1;
        asm("rcp.approx.ftz.f32 %0, %1;" : "=f"(i0) : "f"(l0));
        asm("rcp.approx.ftz.f32 %0, %1;" : "=f"(i1) : "f"(l1));
        const int row = w4 * 16 + (lane >> 2);
        const uint32_t stg = sb + FA_O + wg * 16384 + row * 128;
#pragma unroll
        for (int i = 0; i < 4; i++) {
            const int ch = i * 4 + (lane & 3);
            const uint32_t a = stg + (ch >> 3) * 8192 + (((ch & 7) ^ (row & 7)) << 4);
            const float* q = &o[i * 16];
            sts128_if(real, a, pack_bf16(q[0] * i0, q[1] * i0), pack_bf16(q[4] * i0, q[5] * i0), pack_bf16(q[8] * i0, q[9] * i0), pack_bf16(q[12] * i0, q[13] * i0));
            sts128_if(real, a + 1024, pack_bf16(q[2] * i1, q[3] * i1), pack_bf16(q[6] * i1, q[7] * i1), pack_bf16(q[10] * i1, q[11] * i1), pack_bf16(q[14] * i1, q[15] * i1));
        }
        asm volatile("st.shared.s32 [%0], %1;" :: "r"(oslot + wg * 4), "r"(tag) : "memory");
        __syncwarp();
        mbar_arrive_if(bar_of + 8 * wg, lane0 && real);
    };
    auto transition = [&](auto wgc, float& l0, float& l1) {
        constexpr int WG = decltype(wgc)::value;
        constexpr int NE = WG == 0 ? 32 : 64;
        turn_wait();
        wgmma_fence();
        issue_qk(qd, WG == 0);
        issue_pv(nkv > 1);
        turn_pass();
        const int tc = t;
        t = __shfl_sync(0xffffffff, tn, 0);
        nkv = fa_qt(t) + 1;
        mbar_wait(bar_oe + 8 * wg, (max(item, 0) & 1) ^ 1);
        item++; bi ^= 8;
        wgmma_wait<1>();
        mbar_arrive_if(bs + 64, lane0);
        mbar_arrive_if(bi + 16, lane0 && nkv == 1);
        ms0 = -sc * __shfl_sync(0xffffffff, sacc[0], lane & 28); ms1 = -sc * __shfl_sync(0xffffffff, sacc[2], lane & 28);
        const int r0 = w4 * 16 + (lane >> 2) - (lane & 3) * 2;
#pragma unroll
        for (int i = 0; i < 32; i++)
            if ((i >> 2) * 8 + (i & 1) - ((i & 2) ? 8 : 0) > r0) sacc[WG * 32 + i] = -INFINITY;
        float sum[4];
#pragma unroll
        for (int i = 0; i < FA_DPIN; i++) { sacc[i] = ex2f(fmaf(sacc[i], sc, (i & 2) ? ms1 : ms0)); sum[i & 3] = i < 4 ? sacc[i] : sum[i & 3] + sacc[i]; }
        pin_after((sum[0] + sum[1]) + (sum[2] + sum[3]));
        wgmma_wait<0>();
        mbar_arrive_if((bs ^ 8) + 80, lane0 && item > 0);
        epilogue(tc, item > 0);
#pragma unroll
        for (int i = 0; i < NE; i++) {
            if (i >= FA_DPIN) { sacc[i] = ex2f(fmaf(sacc[i], sc, (i & 2) ? ms1 : ms0)); sum[i & 3] += sacc[i]; }
            if (i & 1) pack_p(i);
            if (i == NE - 16) { pin_after(sum[0]); tests(); }
        }
        if (NE == 32)
#pragma unroll
            for (int i = 16; i < 32; i++) asm volatile("mov.u32 %0, 0;" : "=r"(pa[i]));
        l0 = sum[0] + sum[1]; l1 = sum[2] + sum[3];
    };
#pragma unroll
    for (int i = 0; i < 32; i++) pa[i] = 0u;
#pragma unroll 1
    for (;;) {
        float l0, l1;
        it++;
        kd = 2 * k_lo + 4096 - kd; vd = 2 * v_lo + 4096 - vd; bs ^= 8;
        if (++j < nkv) {
            if (__builtin_expect(!ok, 0)) {
                mbar_wait(bs + 32, (it >> 1) & 1);
                mbar_wait((bs ^ 8) + 48, ((it - 1) >> 1) & 1);
            }
            turn_wait();
            wgmma_fence();
            issue_qk(qd, false);
            issue_pv(j > 1);
            turn_pass();
            wgmma_wait<1>();
            mbar_arrive_if(bs + 64, lane0);
            mbar_arrive_if(bi + 16, lane0 && j == nkv - 1);
            float sum[4];
#pragma unroll
            for (int i = 0; i < FA_PIN; i++) { sacc[i] = ex2f(fmaf(sacc[i], sc, (i & 2) ? ms1 : ms0)); sum[i & 3] = i < 4 ? sacc[i] : sum[i & 3] + sacc[i]; }
            pin_after((sum[0] + sum[1]) + (sum[2] + sum[3]));
            wgmma_wait<0>();
            mbar_arrive_if((bs ^ 8) + 80, lane0);
#pragma unroll
            for (int i = 0; i < 64; i++) {
                if (i >= FA_PIN) { sacc[i] = ex2f(fmaf(sacc[i], sc, (i & 2) ? ms1 : ms0)); sum[i & 3] = i < 4 ? sacc[i] : sum[i & 3] + sacc[i]; }
                if (i & 1) pack_p(i);
                if (i == FA_TEST) { pin_after(sum[0]); tests(); }
            }
            l0 = sum[0] + sum[1]; l1 = sum[2] + sum[3];
        } else {
            if (__builtin_expect(!(ok & okq), 0)) {
                mbar_wait(bi ^ 8, ((item + 1) >> 1) & 1);
                asm volatile("ld.shared.s32 %0, [%1];" : "=r"(tn) : "r"((bi ^ 8) + 128) : "memory");
                mbar_wait((bs ^ 8) + 48, ((it - 1) >> 1) & 1);
                if (tn < 0) break;
                mbar_wait(bs + 32, (it >> 1) & 1);
            }
            qd = 2 * q_lo + 2048 - qd;
            if (wg == 0) transition(std::integral_constant<int, 0>(), l0, l1); else transition(std::integral_constant<int, 1>(), l0, l1);
            j = 0;
            lrow0 = 0.f; lrow1 = 0.f;
        }
        if (!FA_NOFB && __builtin_expect(__any_sync(0xffffffff, !(l0 + l1 < FA_LIM)), 0)) redo(l0, l1);
        lrow0 += l0; lrow1 += l1;
    }
    wgmma_fence();
    issue_pv(nkv > 1);
    mbar_wait(bar_oe + 8 * wg, (item & 1) ^ 1);
    wgmma_wait<0>();
    mbar_arrive_if((bs ^ 8) + 80, lane0);
    epilogue(t | 0x80000000, true);
    return __shfl_sync(0xffffffff, ~tn * 2 + (item & 1), 0);
}

__device__ __forceinline__ uint32_t cluster_ctarank() {
    uint32_t r; asm volatile("mov.u32 %0, %%cluster_ctarank;" : "=r"(r)); return r;
}
__device__ __forceinline__ uint32_t mapa_u32(uint32_t addr, uint32_t rank) {
    uint32_t r; asm volatile("mapa.shared::cluster.u32 %0, %1, %2;" : "=r"(r) : "r"(addr), "r"(rank)); return r;
}
__device__ __forceinline__ void cluster_sync_all() {
    asm volatile("barrier.cluster.arrive.release.aligned;\nbarrier.cluster.wait.acquire.aligned;" ::: "memory");
}
__device__ __forceinline__ void cluster_sync_relaxed() {
    asm volatile("barrier.cluster.arrive.relaxed.aligned;\nbarrier.cluster.wait.aligned;" ::: "memory");
}
__device__ __forceinline__ void st_async_v4(uint32_t addr, uint32_t a, uint32_t b, uint32_t c, uint32_t d, uint32_t mbar) {
    asm volatile("st.async.weak.shared::cluster.mbarrier::complete_tx::bytes.v4.b32 [%0], {%1, %2, %3, %4}, [%5];"
                 :: "r"(addr), "r"(a), "r"(b), "r"(c), "r"(d), "r"(mbar) : "memory");
}
__device__ __forceinline__ void st_async_v2(uint32_t addr, uint32_t a, uint32_t b, uint32_t mbar) {
    asm volatile("st.async.weak.shared::cluster.mbarrier::complete_tx::bytes.v2.b32 [%0], {%1, %2}, [%3];"
                 :: "r"(addr), "r"(a), "r"(b), "r"(mbar) : "memory");
}
__device__ __forceinline__ void st_async_b32(uint32_t addr, uint32_t a, uint32_t mbar) {
    asm volatile("st.async.weak.shared::cluster.mbarrier::complete_tx::bytes.b32 [%0], %1, [%2];" :: "r"(addr), "r"(a), "r"(mbar) : "memory");
}
__device__ __forceinline__ void pace(int cycles) {
    if (cycles > 0) {
        uint32_t t0, t;
        asm volatile("mov.u32 %0, %%clock;" : "=r"(t0));
        do { asm volatile("mov.u32 %0, %%clock;" : "=r"(t)); } while (t - t0 < (uint32_t)cycles);
    }
}
__device__ __forceinline__ void mbar_wait_cl(uint32_t bar, uint32_t parity) {
    uint32_t done = 0;
    for (int it = 0; it < (1 << 22) && !done; it++) {
        asm volatile(
            "{\n.reg .pred p;\n"
            "mbarrier.try_wait.parity.shared::cta.b64 p, [%1], %2;\n"
            "selp.u32 %0, 1, 0, p;\n}\n" : "=r"(done) : "r"(bar), "r"(parity) : "memory");
    }
}
__device__ __forceinline__ void ldmatrix_x4(uint32_t& r0, uint32_t& r1, uint32_t& r2, uint32_t& r3, uint32_t addr) {
    asm volatile("ldmatrix.sync.aligned.m8n8.x4.shared.b16 {%0,%1,%2,%3}, [%4];"
                 : "=r"(r0), "=r"(r1), "=r"(r2), "=r"(r3) : "r"(addr));
}
__device__ __forceinline__ void cp_async16(uint32_t dst, const void* src) {
    asm volatile("cp.async.cg.shared.global [%0], [%1], 16;" :: "r"(dst), "l"(src) : "memory");
}

#define DBG(i)
#define DBGW(i, w)
#define CYC(i)
#define PM(i)
#define TM(i)
__device__ __forceinline__ void tma_load_2d_mc(uint32_t dst, const CUtensorMap* map, uint32_t bar, int c0, int c1, uint16_t mask) {
    asm volatile(
        "cp.async.bulk.tensor.2d.shared::cluster.global.mbarrier::complete_tx::bytes.multicast::cluster [%0], [%1, {%3, %4}], [%2], %5;"
        :: "r"(dst), "l"((uint64_t)map), "r"(bar), "r"(c0), "r"(c1), "h"(mask) : "memory");
}
__device__ __forceinline__ void tma_load_2d_mc(uint32_t dst, const CUtensorMap* map, uint32_t bar, int c0, int c1, uint16_t mask, uint64_t hint) {
    asm volatile(
        "cp.async.bulk.tensor.2d.shared::cluster.global.mbarrier::complete_tx::bytes.multicast::cluster.L2::cache_hint [%0], [%1, {%3, %4}], [%2], %5, %6;"
        :: "r"(dst), "l"((uint64_t)map), "r"(bar), "r"(c0), "r"(c1), "h"(mask), "l"(hint) : "memory");
}
__device__ __forceinline__ void bulk_s2s(uint32_t dst_cl, uint32_t src, uint32_t bytes, uint32_t bar_cl) {
    asm volatile("cp.async.bulk.shared::cluster.shared::cta.mbarrier::complete_tx::bytes [%0], [%1], %2, [%3];"
                 :: "r"(dst_cl), "r"(src), "r"(bytes), "r"(bar_cl) : "memory");
}
__device__ __forceinline__ bool elect_one() {
    uint32_t p;
    asm volatile("{\n.reg .pred p;\nelect.sync _|p, 0xffffffff;\nselp.u32 %0, 1, 0, p;\n}" : "=r"(p));
    return p;
}
__device__ __forceinline__ void fence_async_smem() { asm volatile("fence.proxy.async.shared::cta;" ::: "memory"); }
template <int ID, int N> __device__ __forceinline__ void bar_sync() { asm volatile("bar.sync %0, %1;" :: "n"(ID), "n"(N) : "memory"); }
template <int ID, int N> __device__ __forceinline__ void bar_arrive() { asm volatile("bar.arrive %0, %1;" :: "n"(ID), "n"(N) : "memory"); }
__device__ __forceinline__ void sts32(uint32_t a, uint32_t v) { asm volatile("st.shared.u32 [%0], %1;" :: "r"(a), "r"(v) : "memory"); }
__device__ __forceinline__ void ldsm_x4(uint32_t* r, uint32_t addr) {
    asm volatile("ldmatrix.sync.aligned.m8n8.x4.shared.b16 {%0,%1,%2,%3}, [%4];" : "=r"(r[0]), "=r"(r[1]), "=r"(r[2]), "=r"(r[3]) : "r"(addr) : "memory");
}
constexpr uint32_t DHI128 = 0x40000040u, DHI32 = 0xC0000010u;
#define ACC16(d) "+f"(d[0]), "+f"(d[1]), "+f"(d[2]), "+f"(d[3]), "+f"(d[4]), "+f"(d[5]), "+f"(d[6]), "+f"(d[7]), "+f"(d[8]), "+f"(d[9]), "+f"(d[10]), \
    "+f"(d[11]), "+f"(d[12]), "+f"(d[13]), "+f"(d[14]), "+f"(d[15])
#define ACC20(d) ACC16(d), "+f"(d[16]), "+f"(d[17]), "+f"(d[18]), "+f"(d[19])
__device__ __forceinline__ void wgmma_rs(float (&d)[16], const uint32_t (&a)[4], uint32_t db_lo) {
    asm volatile(
        "{\n.reg .b64 db;\nmov.b64 db, {%20, %21};\n"
        "wgmma.mma_async.sync.aligned.m64n32k16.f32.bf16.bf16 {%0,%1,%2,%3,%4,%5,%6,%7,%8,%9,%10,%11,%12,%13,%14,%15}, {%16,%17,%18,%19}, db, 1, 1, 1, 0;\n}\n"
        : ACC16(d) : "r"(a[0]), "r"(a[1]), "r"(a[2]), "r"(a[3]), "r"(db_lo), "n"(DHI128));
}
__device__ __forceinline__ void wgmma_rs(float (&d)[20], const uint32_t (&a)[4], uint32_t db_lo) {
    asm volatile(
        "{\n.reg .b64 db;\nmov.b64 db, {%24, %25};\n"
        "wgmma.mma_async.sync.aligned.m64n40k16.f32.bf16.bf16 {%0,%1,%2,%3,%4,%5,%6,%7,%8,%9,%10,%11,%12,%13,%14,%15,%16,%17,%18,%19}, {%20,%21,%22,%23}, db, 1, 1, 1, 0;\n}\n"
        : ACC20(d) : "r"(a[0]), "r"(a[1]), "r"(a[2]), "r"(a[3]), "r"(db_lo), "n"(DHI128));
}
template <uint32_t AHI, uint32_t BHI>
__device__ __forceinline__ void wgmma_ss(float (&d)[16], uint32_t da_lo, uint32_t db_lo) {
    asm volatile(
        "{\n.reg .b64 da, db;\nmov.b64 da, {%16, %18};\nmov.b64 db, {%17, %19};\n"
        "wgmma.mma_async.sync.aligned.m64n32k16.f32.bf16.bf16 {%0,%1,%2,%3,%4,%5,%6,%7,%8,%9,%10,%11,%12,%13,%14,%15}, da, db, 1, 1, 1, 0, 0;\n}\n"
        : ACC16(d) : "r"(da_lo), "r"(db_lo), "n"(AHI), "n"(BHI));
}
template <uint32_t AHI, uint32_t BHI>
__device__ __forceinline__ void wgmma_ss(float (&d)[20], uint32_t da_lo, uint32_t db_lo) {
    asm volatile(
        "{\n.reg .b64 da, db;\nmov.b64 da, {%20, %22};\nmov.b64 db, {%21, %23};\n"
        "wgmma.mma_async.sync.aligned.m64n40k16.f32.bf16.bf16 {%0,%1,%2,%3,%4,%5,%6,%7,%8,%9,%10,%11,%12,%13,%14,%15,%16,%17,%18,%19}, da, db, 1, 1, 1, 0, 0;\n}\n"
        : ACC20(d) : "r"(da_lo), "r"(db_lo), "n"(AHI), "n"(BHI));
}
template <uint32_t AHI, uint32_t BHI>
__device__ __forceinline__ void wgmma_ss0(float (&d)[20], uint32_t da_lo, uint32_t db_lo) {
    asm volatile(
        "{\n.reg .b64 da, db;\nmov.b64 da, {%20, %22};\nmov.b64 db, {%21, %23};\n"
        "wgmma.mma_async.sync.aligned.m64n40k16.f32.bf16.bf16 {%0,%1,%2,%3,%4,%5,%6,%7,%8,%9,%10,%11,%12,%13,%14,%15,%16,%17,%18,%19}, da, db, 0, 1, 1, 0, 0;\n}\n"
        : "=f"(d[0]), "=f"(d[1]), "=f"(d[2]), "=f"(d[3]), "=f"(d[4]), "=f"(d[5]), "=f"(d[6]), "=f"(d[7]), "=f"(d[8]), "=f"(d[9]), "=f"(d[10]),
          "=f"(d[11]), "=f"(d[12]), "=f"(d[13]), "=f"(d[14]), "=f"(d[15]), "=f"(d[16]), "=f"(d[17]), "=f"(d[18]), "=f"(d[19])
        : "r"(da_lo), "r"(db_lo), "n"(AHI), "n"(BHI));
}
__device__ __forceinline__ void wgmma_ss_n8(float (&d)[4], uint32_t da_lo, uint32_t db_lo) {
    asm volatile(
        "{\n.reg .b64 da, db;\nmov.b64 da, {%4, %6};\nmov.b64 db, {%5, %7};\n"
        "wgmma.mma_async.sync.aligned.m64n8k16.f32.bf16.bf16 {%0,%1,%2,%3}, da, db, 1, 1, 1, 1, 0;\n}\n"
        : "+f"(d[0]), "+f"(d[1]), "+f"(d[2]), "+f"(d[3]) : "r"(da_lo), "r"(db_lo), "n"(DHI128), "n"(DHI32));
}

__device__ __forceinline__ void wgmma_ss_n32_ta(float (&d)[16], uint32_t da_lo, uint32_t db_lo) {
    asm volatile(
        "{\n.reg .b64 da, db;\nmov.b64 da, {%16, %18};\nmov.b64 db, {%17, %18};\n"
        "wgmma.mma_async.sync.aligned.m64n32k16.f32.bf16.bf16 {%0,%1,%2,%3,%4,%5,%6,%7,%8,%9,%10,%11,%12,%13,%14,%15}, da, db, 1, 1, 1, 1, 0;\n}\n"
        : ACC16(d) : "r"(da_lo), "r"(db_lo), "n"(DHI128));
}

constexpr int C2_NS = 4;
#define LAY         160, 127, 0, 16, 24, 8, 47, 87, 150, 135, 147, 32, 159, 0, 87, 119
constexpr uint32_t c2_lay(int i) { constexpr uint32_t t[16] = {LAY}; return t[i] * 1024; }
constexpr uint32_t C2_WO = c2_lay(0);
constexpr uint32_t C2_WQ = c2_lay(1), C2_WK = c2_lay(2), C2_WV = c2_lay(3);
constexpr uint32_t C2_OB = c2_lay(4);
constexpr uint32_t C2_QM = c2_lay(5);
constexpr uint32_t C2_SC = C2_QM + 1024;
constexpr uint32_t C2_PB = c2_lay(12) + 320;
#define CH_CS (C2_QM + 4096)
constexpr uint32_t C2_CS = CH_CS;
constexpr uint32_t C2_XB = c2_lay(6), C2_XS = c2_lay(7) - c2_lay(6);
constexpr uint32_t C2_QX = c2_lay(8);
constexpr uint32_t C2_KX = C2_QX + 4096;
constexpr uint32_t C2_VT = c2_lay(9);
constexpr uint32_t C2_PX = c2_lay(10);
constexpr uint32_t C2_SX = c2_lay(11);
constexpr uint32_t C2_BAR = c2_lay(12), C2_S0 = c2_lay(13), C2_S1 = c2_lay(14), C2_S2 = c2_lay(15);
constexpr uint32_t C2_GT = C2_BAR + 320;
constexpr uint32_t C2_T0 = (C2_XB >> 10) * 0x01010101u + 0x18100800u, C2_T1 = ((C2_XB >> 10) + 32) | C2_OB >> 10 << 8 | C2_QM >> 10 << 16 | C2_WQ >> 10 << 24;
__device__ __forceinline__ uint32_t c2_ts(uint32_t r) { return __byte_perm(C2_T0, C2_T1, r) & 0xff; }
constexpr int C2_SMEM = 232448;
#define CH_SPQ 28
#define CH_SPK 0
#define CH_SPV 0
#define CH_EARLY 1
#define CH_ARM 0
#define CH_MB 1
#define CH_TW 1
#define CH_LD 0
#define CH_PFD 300
#define CH_PT 300
#define CH_PT1 CH_PT
#define CH_PF2 0
#define CH_EFW 0
#define CH_TS 1
#define CH_WL 2
#define CH_WU 2
#define CH_PT2 CH_PT
#define CH_PS 0
#define CH_PSZ 16384
#define CH_PSI 0
#define CH_PL 0
#define CH_PX 0
#define CH_P0 0
#define CH_PO 0
#define CH_WR 4
#define CH_WOT 1
#define CH_NCH 4
#define CH_NQ1 12
#define CH_POLL_DELAY 500

__device__ __forceinline__ uint32_t c2_stage(int wg, int i) { return (wg == 0 ? C2_S0 : wg == 1 ? C2_S1 : C2_S2) + i * 8192; }
__device__ __forceinline__ void c2_stage_load(const CUtensorMap* map, uint32_t sb, int wg, int rank, int col0, int i) {
    const uint32_t bar = sb + C2_BAR + 176 + (wg * 4 + (i & 3)) * 8;
    mbar_expect_tx(bar, 8192);
    tma_load_2d(sb + c2_stage(wg, i & 3), map, bar, col0, ((rank - i) & 7) * 64);
}
__device__ __forceinline__ void c2_wo(uint32_t sb, int t, int n) {
    mbar_wait(sb + C2_BAR + 168, 0);
    constexpr int U = CH_WU;
#pragma unroll U
    for (int i = t; i < 2048; i += n) {
        const int k = i >> 2, b = i & 3;
        const uint32_t a0 = sb + C2_WO + k * 128 + (((2 * b) ^ (k & 7)) << 4), a1 = a0 ^ 16;
        uint4 u, v;
        asm volatile("ld.shared.v4.b32 {%0, %1, %2, %3}, [%4];" : "=r"(u.x), "=r"(u.y), "=r"(u.z), "=r"(u.w) : "r"(a0) : "memory");
        asm volatile("ld.shared.v4.b32 {%0, %1, %2, %3}, [%4];" : "=r"(v.x), "=r"(v.y), "=r"(v.z), "=r"(v.w) : "r"(a1) : "memory");
        asm volatile("st.shared.v4.b32 [%0], {%1, %2, %3, %4};" :: "r"(a0), "r"(__byte_perm(u.x, u.y, 0x5410)),
                     "r"(__byte_perm(u.z, u.w, 0x5410)), "r"(__byte_perm(v.x, v.y, 0x5410)), "r"(__byte_perm(v.z, v.w, 0x5410)) : "memory");
        asm volatile("st.shared.v4.b32 [%0], {%1, %2, %3, %4};" :: "r"(a1), "r"(__byte_perm(u.x, u.y, 0x7632)),
                     "r"(__byte_perm(u.z, u.w, 0x7632)), "r"(__byte_perm(v.x, v.y, 0x7632)), "r"(__byte_perm(v.z, v.w, 0x7632)) : "memory");
    }
}
__device__ __forceinline__ void c2_load_w(uint32_t (&w)[32][4], const CUtensorMap* map, const CUtensorMap* mapWo, int wg, int rank, int col0, uint32_t t128, uint32_t ws, uint32_t sb) {
    const uint32_t s0 = pin(sb + c2_stage(wg, 0) + t128), s1 = pin(sb + c2_stage(wg, 0) + (t128 ^ 16) + 128);
#pragma unroll
    for (int r = 0; r < 8; r++) {
        mbar_wait(sb + C2_BAR + 176 + (wg * 4 + (r & 3)) * 8, r >> 2);
        if (r == 0) PM(2);
        if (r == 3) PM(3);
        if (r == 7) PM(4);
#pragma unroll
        for (int e = (r & 3) * 4; e < (r & 3) * 4 + 4; e++) {
            uint32_t w0, w1, w2, w3;
            asm volatile("ld.shared.b32 %0, [%1];" : "=r"(w0) : "r"(s0 + e * 2048) : "memory");
            asm volatile("ld.shared.b32 %0, [%1];" : "=r"(w1) : "r"(s1 + e * 2048) : "memory");
            asm volatile("ld.shared.b32 %0, [%1];" : "=r"(w2) : "r"(s0 + e * 2048 + 1024) : "memory");
            asm volatile("ld.shared.b32 %0, [%1];" : "=r"(w3) : "r"(s1 + e * 2048 + 1024) : "memory");
            uint32_t* d = w[(r >> 2) * 16 + e];
            d[0] = __byte_perm(w0, w1, 0x5410); d[1] = __byte_perm(w0, w1, 0x7632);
            d[2] = __byte_perm(w2, w3, 0x5410); d[3] = __byte_perm(w2, w3, 0x7632);
        }
        if (r < 4) asm volatile("bar.sync %0, 128;" :: "r"(8 + wg) : "memory");
        if ((threadIdx.x & 96) == 32 && elect_one()) {
            if (r < 4) c2_stage_load(map, sb, wg, rank, col0, r + 4);
            const int j = wg + (r - CH_WR) * 3;
            if (r >= CH_WR && j < 8) tma_load_2d(sb + C2_WO + j * 8192, mapWo, sb + C2_BAR + 168, rank * 64, (blockIdx.x >> 3) * 512 + ((rank - j) & 7) * 64);
        }
    }
    PM(5);
    cluster_sync_relaxed();
    PM(6);
#pragma unroll
    for (int e = 0; e < C2_NS; e++) stmatrix_x4(ws + e * 2048, w[e][0], w[e][1], w[e][2], w[e][3]);
#pragma unroll 1
    for (int i = threadIdx.x; i < 2 * 512 + 256; i += 384)
        sts32(sb + (i < 1024 ? C2_VT + (i >> 9) * 6144 + 4096 + (i & 511) * 4 : C2_PX + 2048 + (i - 1024) * 4), 0u);
    fence_async_smem();
    asm volatile("bar.sync %0, 128;" :: "r"(8 + wg) : "memory");
}
template <int E0, int E1, int SP, int NA>
__device__ __forceinline__ void c2_xstream(float (&acc)[NA], const uint32_t (&w)[32][4], uint32_t xlo, uint32_t rank, uint32_t wslo) {
    if (E0 == 0)
#pragma unroll
        for (int i = 0; i < NA; i++) acc[i] = 0.f;
    wgmma_fence();
#pragma unroll
    for (int n = E0; n < E1; n++) {
        const int e = n < SP ? n + C2_NS : n < SP + C2_NS ? n - SP : n;
        if (e < C2_NS) wgmma_ss<DHI32, DHI128>(acc, wslo + e * 128, xlo + ((rank - (e >> 2)) & 7) * 320 + (e & 3) * 2);
        else wgmma_rs(acc, w[e], xlo + ((rank - (e >> 2)) & 7) * 320 + (e & 3) * 2);
    }
    wgmma_commit();
}
__device__ __forceinline__ constexpr int c2_grp(int i) { return i < 2 ? i : 1 + (i >> 1); }

struct ChainParams {
    CUtensorMap mapX;
    CUtensorMap mapM;
    CUtensorMap mapW[3];
    CUtensorMap mapWo;
    CUtensorMap mapC;
    CUtensorMap mapS;
    bf16* out;
    const char* pf[6];
};
__global__ void __cluster_dims__(8, 1, 1) __launch_bounds__(384, 1)
chain_kernel(const __grid_constant__ ChainParams P) {
    const CUtensorMap& mapX = P.mapX;
    extern __shared__ __align__(1024) uint8_t smem_chain[];
    const uint32_t sb = smem_u32(smem_chain);
    const uint32_t dlo = ((sb & 0x3FFFF) >> 4) | (1u << 16);
    const int tid = __shfl_sync(0xffffffff, threadIdx.x, threadIdx.x & 31), lane = tid & 31;
    const int warp = __shfl_sync(0xffffffff, tid >> 5, 0), wg = warp >> 2, w4 = warp & 3;
    const uint32_t rank = cluster_ctarank();
    const int C = blockIdx.x >> 3;
    const int h = C * 4 + (rank >> 1);
    const int g = lane >> 2, qc = lane & 3;
    pdl_launch_dependents();
    TS_BEGIN(2);
    CYC(0);
    PM(0);
    const uint32_t bar_m = sb + C2_BAR, bar_o = bar_m + 64, bar_sc = bar_m + 128, bar_x = bar_m + 136, bar_sx = bar_m + 152;
    const uint32_t bar_w = bar_m + 168, bar_h = bar_m + 40;
    const int col0 = h * HD + (rank & 1) * 64;
    if (tid == 0) {
        for (int j = 0; j < 5; j++) { mbar_init(bar_m + 8 * j, j ? 1 : 4); mbar_init(bar_o + 8 * j, j ? 1 : 4); }
        for (int j = 0; j < 18; j++) mbar_init(bar_sc + 8 * j, 1);
        mbar_init(bar_h, 32);
        asm volatile("fence.mbarrier_init.release.cluster;" ::: "memory");
    }
    __syncwarp();
    cluster_sync_relaxed();
    PM(1);
    if (tid == 0) {
        mbar_expect_tx(bar_x, 32768 + 8192);
        tma_load_2d_mc(sb + C2_XB + rank * 5120, &mapX, bar_x, rank * 64, 0, (uint16_t)0xff);
#pragma unroll 1
        for (int j = 0; j < 8; j++) tma_load_2d(sb + C2_XB + j * 5120 + 4096, &P.mapM, bar_x, j * 64, 0);
        mbar_expect_tx(bar_w, 65536);
    }
    if ((tid & 127) == 32) {
        pace(CH_PFD);
#pragma unroll 1
        for (int i = 0; i < 4; i++) {
            c2_stage_load(&P.mapW[wg], sb, wg, rank, col0, i);
            if (i < 3) pace(CH_PT);
        }
    }
    __syncwarp();

    const uint32_t t32 = w4 * 256 + qc * 64 + (((g >> 2) ^ (qc >> 1)) << 4) + (g & 3) * 4;
    const uint32_t t128 = qc * 256 + (((2 * w4 + (g >> 2)) ^ (2 * qc)) << 4) + (g & 3) * 4;
    const uint32_t a32 = (w4 * 16 + (lane & 15)) * 32 + (((lane >> 4) ^ ((lane >> 2) & 1)) << 4);
    const uint32_t ws = sb + (wg == 0 ? C2_WQ : wg == 1 ? C2_WK : C2_WV) + a32;
    uint32_t w[32][4];
    static_assert(C2_NS == 4, "slot 0");
    auto proj_mem = [&](float (&a)[CH_NCH][4], int s, uint32_t l128) {
        uint32_t b[4][8];
#pragma unroll
        for (int i = 0; i < 4 * CH_NCH; i++) a[i >> 2][i & 3] = 0.f;
        const uint32_t par = (s & 1) ^ 1;
        const uint32_t mb = sb + C2_XB + (s & 1) * C2_XS + 4096;
        auto L = [&](int i) {
            ldsm_x4(b[i & 3], mb + ((rank - i) & 7) * 5120 + l128);
            ldsm_x4(b[i & 3] + 4, mb + ((rank - i) & 7) * 5120 + (l128 ^ 64));
        };
        auto H = [&](int i) {
#pragma unroll
            for (int kk = 0; kk < 4; kk++) {
                const uint32_t* f = i ? w[i * 4 + kk] : &b[2 + (kk >> 1)][(kk & 1) * 4];
                mma_16816(a[(i * 4 + kk) % CH_NCH], f[0], f[1], f[2], f[3], b[i & 3][2 * kk], b[i & 3][2 * kk + 1]);
            }
        };
#pragma unroll
        for (int e = 0; e < 4; e++) ldsm_x4(&b[2 + (e >> 1)][(e & 1) * 4], ws + e * 2048);
        mbar_wait(bar_m, par);
        L(0);
        H(0);
        mbar_wait(bar_m + 8, par);
        DBGW(1 + 16 * wg, 0);
        L(1);
        mbar_wait(bar_m + 16, par);
        uint32_t nxt = mbar_test(bar_m + 24, par);
        L(2); L(3);
        H(1);
        if (__builtin_expect(!nxt, 0)) mbar_wait(bar_m + 24, par);
        nxt = mbar_test(bar_m + 32, par);
        L(4); L(5);
        H(2); H(3);
        if (__builtin_expect(!nxt, 0)) mbar_wait(bar_m + 32, par);
        DBGW(2 + 16 * wg, 0);
        L(6); L(7);
        H(4); H(5); H(6); H(7);
#pragma unroll
        for (int i = 0; i < 4; i++) a[0][i] = CH_NCH == 4 ? (a[0][i] + a[1][i]) + (a[2][i] + a[3 % CH_NCH][i]) : CH_NCH == 3 ? a[0][i] + a[1][i] + a[2 % CH_NCH][i] : a[0][i] + a[1][i];
    };
    auto store_x = [&](const float (&acc)[16], uint32_t base) {
#pragma unroll
        for (int j = 0; j < 4; j++) {
            sts32(base + t128 + j * 1024, pack_bf16(acc[4 * j], acc[4 * j + 2]));
            sts32(base + (t128 ^ 16) + 128 + j * 1024, pack_bf16(acc[4 * j + 1], acc[4 * j + 3]));
        }
    };
    auto fresh_lane = [&]() { uint32_t l; asm volatile("mov.u32 %0, %%laneid;" : "=r"(l)); return l; };
    const float scale = 0.08838834764831845f, l2e = 1.4426950408889634f;
    c2_load_w(w, &P.mapW[wg], &P.mapWo, wg, rank, col0, t128, ws, sb);
    TS_END(6);
    TS_BEGIN(5);
    CYC(1);
    PM(7);

    if (wg == 0) {
#pragma unroll 1
        for (int s = -1;;) {
            float qx[16];
            uint32_t* dst = reinterpret_cast<uint32_t*>(g_xbuf + (((s & 1) * 8 + rank) * 8 + C) * 128) + qc * 64 + w4 * 8 + g;
            asm volatile("" : "+l"(dst));
            mbar_wait(bar_x + 8 * ((s + 1) & 1), ((s + 1) >> 1) & 1);
            if (s >= 0) bar_sync<6, 384>();
            c2_xstream<0, CH_NQ1, CH_SPQ>(qx, w, dlo + ((C2_XB + ((s + 1) & 1) * C2_XS) >> 4), rank, dlo + (C2_WQ >> 4));
            if (s >= 0) {
                float acc[4] = {0.f, 0.f, 0.f, 0.f};
                const uint32_t tag = ((s >> 1) & 1) ^ 1;
                uint32_t nxt = 0;
#pragma unroll
                for (int i = 0; i < 8; i++) {
                    if (i < 2 || !(i & 1)) {
                        if (i < 2 || __builtin_expect(!nxt, 0)) mbar_wait(bar_o + 8 * c2_grp(i), s & 1);
                        if (i == 0) DBGW(7, 0);
                        if (i == 1) DBGW(8, 0);
                        if (i == 6) DBGW(9, 0);
                        wgmma_fence();
                    }
#pragma unroll
                    for (int kk = 0; kk < 4; kk++) {
                        if ((i & 1) && i < 7 && kk == CH_WOT) nxt = mbar_test(bar_o + 8 * c2_grp(i + 1), s & 1);
                        wgmma_ss_n8(acc, dlo + ((C2_WO + i * 8192 + kk * 2048) >> 4), dlo + ((C2_OB + i * 1024 + kk * 256) >> 4));
                    }
                }
                wgmma_commit();
                bar_arrive<11, 256>();
                wgmma_wait<0>();
                asm volatile("st.relaxed.gpu.global.u32 [%0], %1;" :: "l"(dst), "r"((pack_bf16(acc[0], acc[2]) & ~1u) | tag) : "memory");
                asm volatile("st.relaxed.gpu.global.u32 [%0 + 128], %1;" :: "l"(dst), "r"((pack_bf16(acc[1], acc[3]) & ~1u) | tag) : "memory");
                bar_arrive<4, 256>();
                DBGW(10, 0);
            }
            s++;
            c2_xstream<CH_NQ1, 32, CH_SPQ>(qx, w, dlo + ((C2_XB + (s & 1) * C2_XS) >> 4), rank, dlo + (C2_WQ >> 4));
            const uint32_t sca = pin(w4 < 2 ? sb + C2_SC + w4 * 512 + lane * 16 : sb + C2_SC + 1024 + lane * 8);
            const uint32_t krow = w4 * 16 + (lane & 15);
            const uint32_t ka0 = pin(sb + C2_KX + krow * 128 + (((lane >> 4) ^ (krow & 7)) << 4));
            const uint32_t l32 = pin(sb + C2_QM + (lane >> 4) * 256 + (lane & 7) * 32 + ((((lane >> 3) & 1) ^ ((lane >> 2) & 1)) << 4));
            const uint32_t qst = pin(sb + C2_QM + t32);
            const uint32_t l128 = pin((lane & 7) * 128 + (((lane >> 3) ^ (lane & 7)) << 4));
            if (s > 0) bar_sync<5, 256>();
            wgmma_wait<0>();
            store_x(qx, sb + C2_QX);
            DBGW(0, 0);
            if (s == NSEG - 1) break;
            {
                float a[CH_NCH][4];
                proj_mem(a, s, l128);
                sts32(qst, pack_bf16(a[0][0], a[0][2]));
                sts32(qst + 32, pack_bf16(a[0][1], a[0][3]));
            }
            DBGW(3, 0);
            if (w4 < 3) {
                uint32_t ka[4][4], qb[8];
                float c[4] = {0.f, 0.f, 0.f, 0.f}, c2[4] = {0.f, 0.f, 0.f, 0.f};
                const uint32_t sc_peer = pin(mapa_u32(sca + 1280, rank ^ 1)), sc_own = pin(mapa_u32(sca, rank));
                bar_sync<1, 384>();
                ldsm_x4(qb, l32);
                ldsm_x4(ka[0], ka0);
                ldsm_x4(ka[1], ka0 ^ 32);
                ldsm_x4(qb + 4, l32 + 512);
                ldsm_x4(ka[2], ka0 ^ 64);
                ldsm_x4(ka[3], ka0 ^ 96);
                mma_16816(c, ka[0][0], ka[0][1], ka[0][2], ka[0][3], qb[0], qb[1]);
                mma_16816(c2, ka[1][0], ka[1][1], ka[1][2], ka[1][3], qb[2], qb[3]);
                mma_16816(c, ka[2][0], ka[2][1], ka[2][2], ka[2][3], qb[4], qb[5]);
                mma_16816(c2, ka[3][0], ka[3][1], ka[3][2], ka[3][3], qb[6], qb[7]);
                const uint32_t u0 = __float_as_uint(c[0] + c2[0]), u1 = __float_as_uint(c[1] + c2[1]);
                const uint32_t u2 = __float_as_uint(c[2] + c2[2]), u3 = __float_as_uint(c[3] + c2[3]);
                asm volatile(
                    "{\n.reg .pred p;\nsetp.lt.u32 p, %8, 2;\n"
                    "@p st.async.weak.shared::cluster.mbarrier::complete_tx::bytes.v4.b32 [%0], {%4, %5, %6, %7}, [%1];\n"
                    "@!p st.async.weak.shared::cluster.mbarrier::complete_tx::bytes.v2.b32 [%0], {%4, %5}, [%1];\n"
                    "@p st.async.weak.shared::cluster.mbarrier::complete_tx::bytes.v4.b32 [%2], {%4, %5, %6, %7}, [%3];\n"
                    "@!p st.async.weak.shared::cluster.mbarrier::complete_tx::bytes.v2.b32 [%2], {%4, %5}, [%3];\n}"
                    :: "r"(sc_peer), "r"(mapa_u32(bar_sc, rank ^ 1)), "r"(sc_own), "r"(mapa_u32(bar_sc, rank)), "r"(u0), "r"(u1), "r"(u2), "r"(u3), "r"(w4) : "memory");
                bar_arrive<2, 224>();
                fence_async_smem();
                if (!CH_TS && s >= 4 * CB_FIRST + 5 && (s & 3) == 1 && tid == 0) signal_ctr(CT_CB + ((s - 5) >> 2));
                __syncwarp();
                DBGW(4, 2);
            } else {
                bar_arrive<1, 384>();
                fence_async_smem();
                const uint32_t a = pin(sb + C2_SC + lane * 16), a2 = pin(sb + C2_SC + 1024 + lane * 8), pa = pin(sb + C2_PB + lane * 4);
                mbar_wait(bar_sc, s & 1);
                DBG(5);
                float v[10];
                {
                    float4 x0, x1, y0, y1; float2 x2, y2;
                    asm volatile("ld.shared.v4.f32 {%0, %1, %2, %3}, [%4];" : "=f"(x0.x), "=f"(x0.y), "=f"(x0.z), "=f"(x0.w) : "r"(a) : "memory");
                    asm volatile("ld.shared.v4.f32 {%0, %1, %2, %3}, [%4];" : "=f"(y0.x), "=f"(y0.y), "=f"(y0.z), "=f"(y0.w) : "r"(a + 1280) : "memory");
                    asm volatile("ld.shared.v4.f32 {%0, %1, %2, %3}, [%4];" : "=f"(x1.x), "=f"(x1.y), "=f"(x1.z), "=f"(x1.w) : "r"(a + 512) : "memory");
                    asm volatile("ld.shared.v4.f32 {%0, %1, %2, %3}, [%4];" : "=f"(y1.x), "=f"(y1.y), "=f"(y1.z), "=f"(y1.w) : "r"(a + 1792) : "memory");
                    asm volatile("ld.shared.v2.f32 {%0, %1}, [%2];" : "=f"(x2.x), "=f"(x2.y) : "r"(a2) : "memory");
                    asm volatile("ld.shared.v2.f32 {%0, %1}, [%2];" : "=f"(y2.x), "=f"(y2.y) : "r"(a2 + 1280) : "memory");
                    v[0] = x0.x + y0.x; v[1] = x0.y + y0.y; v[2] = x0.z + y0.z; v[3] = x0.w + y0.w;
                    v[4] = x1.x + y1.x; v[5] = x1.y + y1.y; v[6] = x1.z + y1.z; v[7] = x1.w + y1.w;
                    v[8] = x2.x + y2.x; v[9] = x2.y + y2.y;
                }
                float m0 = fmaxf(fmaxf(fmaxf(v[0], v[2]), fmaxf(v[4], v[6])), v[8]);
                float m1 = fmaxf(fmaxf(fmaxf(v[1], v[3]), fmaxf(v[5], v[7])), v[9]);
#pragma unroll
                for (int o = 4; o < 32; o <<= 1) {
                    m0 = fmaxf(m0, __shfl_xor_sync(0xffffffff, m0, o));
                    m1 = fmaxf(m1, __shfl_xor_sync(0xffffffff, m1, o));
                }
                const float sl = scale * l2e;
                m0 *= sl; m1 *= sl;
#pragma unroll
                for (int j = 0; j < 5; j++)
                    sts32(pa + j * 128, pack_bf16(ex2f(fmaf(v[2 * j], sl, -m0)), ex2f(fmaf(v[2 * j + 1], sl, -m1))));
                bar_arrive<3, 160>();
                DBG(6);
            }
        }
        bar_arrive<1, 384>();
        fence_async_smem();
        bar_arrive<6, 384>();
        TS_MARK(8, 0);
        CYC(2);
        TM(0);
        const uint32_t lane = fresh_lane();
        pace(CH_LD);
        {
            const uint32_t a = sb + C2_WO + ((lane >> 4) * 8 + (lane & 7)) * 128 + (((2 * w4 + ((lane >> 3) & 1)) ^ (lane & 7)) << 4);
#pragma unroll
            for (int e = C2_NS; e < 32; e++)
                asm volatile("ldmatrix.sync.aligned.m8n8.x4.trans.shared.b16 {%0,%1,%2,%3}, [%4];" : "=r"(w[e][0]), "=r"(w[e][1]), "=r"(w[e][2]), "=r"(w[e][3]) : "r"(a + e * 2048) : "memory");
        }
        fence_async_smem();
        if (CH_TS && w4 == 0) bar_sync<12, 160>();
        if (lane < 8) asm volatile("mbarrier.arrive.relaxed.cluster.shared::cluster.b64 _, [%0];" :: "r"(mapa_u32(bar_h, lane)) : "memory");
        __syncwarp();
        TM(9);
        if (w4 == 0) {
            if (!CH_TS) bar_sync<12, 160>();
            if (!CH_TS) asm volatile("fence.acq_rel.gpu;" ::: "memory");
            if (!CH_TS) asm volatile("fence.proxy.async.global;" ::: "memory");
            mbar_wait(bar_h, 0);
            if (elect_one()) tma_load_2d_mc(sb + c2_ts(rank) * 1024, &P.mapC, bar_x, (rank & 1) * 64, h * SEQ + SEQ - 128, (uint16_t)0xff);
            __syncwarp();
            TM(10);
        }
        if (w4 == 1) {
            wait_ctr(CT_P, FA_GRID);
            float4 v;
            asm volatile("ld.relaxed.gpu.global.v4.f32 {%0, %1, %2, %3}, [%4];" : "=f"(v.x), "=f"(v.y), "=f"(v.z), "=f"(v.w) : "l"(g_gate + SEQ - 128 + lane * 4) : "memory");
            asm volatile("st.shared.v4.f32 [%0], {%1, %2, %3, %4};" :: "r"(sb + C2_GT + lane * 16), "f"(1.f - v.x), "f"(1.f - v.y), "f"(1.f - v.z), "f"(1.f - v.w) : "memory");
            __syncwarp();
            if (lane == 0) mbar_expect_tx(bar_x, 65536);
            finish_launch(lane);
        }
        uint32_t* dst = reinterpret_cast<uint32_t*>(P.out + (SEQ - 128 + 2 * (lane & 3)) * DM + rank * 64 + w4 * 16) + (lane >> 2);
#pragma unroll 1
        for (uint32_t q = 0; q < 4; q++, dst += 16 * DM) {
            float acc[16], gt[8];
#pragma unroll
            for (int i = 0; i < 16; i++) acc[i] = 0.f;
            const uint32_t bar = q < 2 ? bar_x : bar_m - 128 + q * 64, db = dlo + (q & 1) * 256;
#pragma unroll
            for (int i = 0; i < 8; i++) {
                if (i == 0 || (CH_TW && (i == 1 || !(i & 1)))) {
                    if (i == 0 || q > 1) mbar_wait(bar + 8 * c2_grp(i), q >> 1);
                    if (!CH_TW && q > 1)
#pragma unroll 1
                        for (uint32_t j = 8; j < 40; j += 8) mbar_wait(bar + j, 1);
                    if (i == 0) TM(13 + q);
                    wgmma_fence();
                }
                if (i == 6) TM(25 + q);
                const uint32_t d = db + (q < 2 ? c2_ts((rank - i) & 7) * 64 : (i ? C2_WO + i * 8192 : C2_QX) >> 4);
#pragma unroll
                for (int kk = 0; kk < 4; kk++) {
                    if (i == 0) wgmma_ss_n32_ta(acc, dlo + ((C2_WO + kk * 2048) >> 4), d + kk * 2);
                    else wgmma_rs(acc, w[i * 4 + kk], d + kk * 2);
                }
            }
            wgmma_commit();
            if (q == 3) asm volatile("barrier.cluster.arrive.relaxed.aligned;" ::: "memory");
#pragma unroll
            for (int j = 0; j < 4; j++)
                asm volatile("ld.shared.v2.f32 {%0, %1}, [%2];" : "=f"(gt[2 * j]), "=f"(gt[2 * j + 1]) : "r"(sb + C2_GT + q * 128 + (lane & 3) * 8 + j * 32) : "memory");
            wgmma_wait<0>();
#pragma unroll
            for (int j = 0; j < 8; j++)
                asm volatile("red.relaxed.gpu.global.add.noftz.bf16x2 [%0], %1;" :: "l"(dst + ((j >> 1) * 8 + (j & 1)) * (DM / 2)),
                             "r"(pack_bf16(acc[(j >> 1) * 4 + (j & 1)] * gt[j], acc[(j >> 1) * 4 + (j & 1) + 2] * gt[j])) : "memory");
            TS_MARK(9 + q, 0);
            TM(17 + q);
        }
    } else if (wg == 1) {
        bool early = false;
#pragma unroll 1
        for (int s = -1;;) {
            if (s > 0 && (!CH_EARLY || s != NSEG - 1 || early)) {
                mbar_wait(bar_sx + 8 * ((s - 1) & 1), ((s - 1) >> 1) & 1);
                const uint32_t a = sb + C2_SX + w4 * 1280 + lane * 8, ap = a + 10240 - (s & 1) * 5120;
                float v[10];
                const int lim = 8 * w4 + g - 2 * qc;
#pragma unroll
                for (int j = 0; j < 5; j++) {
                    float2 x, y;
                    asm volatile("ld.shared.v2.f32 {%0, %1}, [%2];" : "=f"(x.x), "=f"(x.y) : "r"(a + j * 256) : "memory");
                    asm volatile("ld.shared.v2.f32 {%0, %1}, [%2];" : "=f"(y.x), "=f"(y.y) : "r"(ap + j * 256) : "memory");
                    v[2 * j] = (j < 4 && 8 * j > lim) ? -INFINITY : x.x + y.x;
                    v[2 * j + 1] = (j < 4 && 8 * j + 1 > lim) ? -INFINITY : x.y + y.y;
                }
                float mx = fmaxf(fmaxf(fmaxf(v[0], v[1]), fmaxf(v[2], v[3])), fmaxf(fmaxf(v[4], v[5]), fmaxf(v[6], v[7])));
                mx = fmaxf(mx, fmaxf(v[8], v[9]));
                mx = fmaxf(mx, __shfl_xor_sync(0xffffffff, mx, 1));
                mx = fmaxf(mx, __shfl_xor_sync(0xffffffff, mx, 2));
                const float sl = scale * l2e;
                mx *= sl;
#pragma unroll
                for (int j = 0; j < 10; j++) v[j] = ex2f(fmaf(v[j], sl, -mx));
                float sm = ((v[0] + v[1]) + (v[2] + v[3])) + ((v[4] + v[5]) + (v[6] + v[7])) + (v[8] + v[9]);
                sm += __shfl_xor_sync(0xffffffff, sm, 1);
                sm += __shfl_xor_sync(0xffffffff, sm, 2);
                float inv;
                asm("rcp.approx.ftz.f32 %0, %1;" : "=f"(inv) : "f"(sm));
                const uint32_t pa = sb + C2_PX + w4 * 256 + g * 32 + ((g >> 2) << 4) + qc * 4;
#pragma unroll
                for (int j = 0; j < 5; j++) sts32((pa ^ ((j & 1) << 4)) + (j >> 1) * 1024, pack_bf16(v[2 * j] * inv, v[2 * j + 1] * inv));
            }
            if (!early) {
            if (s >= 0) {
                fence_async_smem();
                if (s < NSEG) bar_sync<6, 384>(); else bar_sync<7, 256>();
                DBGW(20, 0);
                TM(s < NSEG ? 2 : 11);
                uint32_t cp[8];
                {
                    float cx[16];
#pragma unroll
                    for (int i = 0; i < 16; i++) cx[i] = 0.f;
                    wgmma_fence();
#pragma unroll
                    for (int kk = 0; kk < 3; kk++)
                        wgmma_ss<DHI32, DHI32>(cx, dlo + ((C2_VT + ((s - 1) & 1) * 6144 + kk * 2048) >> 4), dlo + ((C2_PX + kk * 1024) >> 4));
                    wgmma_commit();
                    wgmma_wait<0>();
#pragma unroll
                    for (int j = 0; j < 4; j++) { cp[2 * j] = pack_bf16(cx[4 * j], cx[4 * j + 2]); cp[2 * j + 1] = pack_bf16(cx[4 * j + 1], cx[4 * j + 3]); }
                    asm volatile("{\n.reg .pred p;\nsetp.gt.u32 p, %0, 99;\n@p st.shared.v4.b32 [%0], {%1, %2, %3, %4};\n@p st.shared.v4.b32 [%0], {%5, %6, %7, %8};\n}"
                                 :: "r"(rank), "r"(cp[0]), "r"(cp[1]), "r"(cp[2]), "r"(cp[3]), "r"(cp[4]), "r"(cp[5]), "r"(cp[6]), "r"(cp[7]) : "memory");
                }
                if (s < NSEG) {
                    float sx[20];
                    wgmma_fence();
                    wgmma_ss0<DHI128, DHI128>(sx, dlo + (C2_QX >> 4), dlo + (C2_KX >> 4));
#pragma unroll
                    for (int kk = 1; kk < 4; kk++) wgmma_ss<DHI128, DHI128>(sx, dlo + (C2_QX >> 4) + kk * 2, dlo + (C2_KX >> 4) + kk * 2);
                    wgmma_commit();
                    wgmma_wait<0>();
                    if (s < NSEG - 1) bar_arrive<5, 256>();
                    if (CH_TS && s > 0 && s < NSEG - 1) {
                        const uint32_t a = sb + C2_CS + w4 * 1024;
#pragma unroll
                        for (int j = 0; j < 8; j++) sts32(a + qc * 64 + g * 4 + (j >> 1) * 256 + (j & 1) * 32, cp[j]);
                        fence_async_smem();
                        __syncwarp();
                        if (elect_one()) tma_store_2d(&P.mapS, a, (rank & 1) * 64 + w4 * 16, h * SEQ + (s - 1) * SEGL);
                        asm volatile("cp.async.bulk.commit_group;" ::: "memory");
                    }
                    if (!CH_TS && s > 0 && s < NSEG - 1) {
                        uint32_t* dst = reinterpret_cast<uint32_t*>(g_ctxB + ((size_t)h * SEQ + (s - 1) * SEGL + 2 * qc) * HD + (rank & 1) * 64 + w4 * 16 + 2 * g);
#pragma unroll
                        for (int j = 0; j < 4; j++) {
                            asm volatile("st.global.u32 [%0], %1;" :: "l"(dst + j * 8 * (HD / 2)), "r"(cp[2 * j]) : "memory");
                            asm volatile("st.global.u32 [%0], %1;" :: "l"(dst + (j * 8 + 1) * (HD / 2)), "r"(cp[2 * j + 1]) : "memory");
                        }
                    }
                    DBGW(22, 0);
                    TM(3);
                    if (!CH_TS && s == NSEG - 2) bar_arrive<12, 160>();
                    const uint32_t a = sb + C2_SX + w4 * 2560 + lane * 8;
                    if (w4 < 2) {
#pragma unroll
                        for (int j = 0; j < 5; j++) {
                            asm volatile("st.shared.v2.f32 [%0], {%1, %2};" :: "r"(a + j * 256), "f"(sx[4 * j]), "f"(sx[4 * j + 1]) : "memory");
                            asm volatile("st.shared.v2.f32 [%0], {%1, %2};" :: "r"(a + 1280 + j * 256), "f"(sx[4 * j + 2]), "f"(sx[4 * j + 3]) : "memory");
                        }
                    }
                    if (s < NSEG - 1) mbar_wait(bar_x + 8 * ((s + 1) & 1), ((s + 1) >> 1) & 1);
                    const uint32_t pa = mapa_u32(a + 5120 + (s & 1) * 5120, rank ^ 1), pb = mapa_u32(bar_sx + 8 * (s & 1), rank ^ 1);
                    if (s < NSEG - 1) bar_sync<4, 256>(); else bar_sync<9, 128>();
                    if (w4 < 2) {
#pragma unroll
                        for (int j = 0; j < 5; j++) {
                            st_async_v2(pa + j * 256, __float_as_uint(sx[4 * j]), __float_as_uint(sx[4 * j + 1]), pb);
                            st_async_v2(pa + 1280 + j * 256, __float_as_uint(sx[4 * j + 2]), __float_as_uint(sx[4 * j + 3]), pb);
                        }
                    }
                }
                if (s >= NSEG - 1) {
                    const uint32_t a = sb + C2_QX + 4096 - (s & 1) * 4096;
#pragma unroll
                    for (int j = 0; j < 4; j++) {
                        sts32(a + t128 + j * 1024, cp[2 * j]);
                        sts32(a + (t128 ^ 16) + 128 + j * 1024, cp[2 * j + 1]);
                    }
                    fence_async_smem();
                    asm volatile("bar.arrive %0, 160;" :: "r"(s - NSEG + 14) : "memory");
                    TM(s - NSEG + 6);
                    if (s == NSEG) break;
                }
            } else mbar_wait(bar_x, 0);
            s++;
            if (s < NSEG) {
                float acc[16];
                c2_xstream<0, 32, CH_SPK>(acc, w, dlo + ((C2_XB + (s & 1) * C2_XS) >> 4), rank, dlo + (C2_WK >> 4));
                wgmma_wait<0>();
                store_x(acc, sb + C2_KX);
                DBGW(16, 0);
            }
            if (CH_EARLY && s == NSEG - 1) {
                if (CH_TS) {
                    asm volatile("cp.async.bulk.wait_group 0;" ::: "memory");
                    bar_arrive<12, 160>();
                }
                early = true;
                continue;
            }
            }
            early = false;
            if (s < NSEG) TM(4);
            if (s < NSEG) {
                const uint32_t kst = pin(sb + C2_KX + 4096 + t128);
                const uint32_t l128 = pin((lane & 7) * 128 + (((lane >> 3) ^ (lane & 7)) << 4));
                float a[CH_NCH][4];
                proj_mem(a, s, l128);
                sts32(kst, pack_bf16(a[0][0], a[0][2]));
                sts32((kst ^ 16) + 128, pack_bf16(a[0][1], a[0][3]));
                bar_arrive<1, 384>();
                TM(1);
                DBGW(19, 0);
                if (CH_TS) {
                    asm volatile("cp.async.bulk.wait_group 0;" ::: "memory");
                    __syncwarp();
                    if (s >= 4 * CB_FIRST + 5 && (s & 3) == 1 && lane == 0) asm volatile("red.relaxed.gpu.global.add.u32 [%0], 1;" :: "l"(&g_ctr[CT_CB + ((s - 5) >> 2)]) : "memory");
                }
                if (w4 == 0) {
                    if (CH_ARM && lane == 0) mbar_expect_tx(bar_sc, 2560);
                    if (lane < 16 && (lane & 7) >= 1 && (lane & 7) < 5) mbar_expect_tx(bar_m + 8 * lane, ((lane & 7) == 1 ? 1024 : 2048) << (s < NSEG - 1 ? 0 : 2));
                    if (s < NSEG - 1) {
                        if (!CH_ARM && lane == 0) mbar_expect_tx(bar_sc, 2560);
                        if (lane == 8) {
                            mbar_expect_tx(bar_x + 8 * ((s + 1) & 1), 32768);
                            tma_load_2d_mc(sb + C2_XB + ((s + 1) & 1) * C2_XS + rank * 5120, &mapX, bar_x + 8 * ((s + 1) & 1), rank * 64, (s + 1) * SEGL, (uint16_t)0xff);
                            if (s + 2 < NSEG)
                                asm volatile("cp.async.bulk.prefetch.tensor.2d.L2.global [%0, {%1, %2}];" :: "l"((uint64_t)&mapX), "r"(rank * 64), "r"((s + 2) * SEGL) : "memory");
                        }
                    }
                    if (lane == 16) mbar_expect_tx(bar_sx + 8 * (s & 1), 5120);
                    __syncwarp();
                }
            }
        }
        TS_MARK(12, 128);
        asm volatile("barrier.cluster.arrive.relaxed.aligned;" ::: "memory");
    } else {
        c2_wo(sb, tid - 256, 128);
        uint32_t va[5][2] = {};
        auto store_vt = [&](int s) {
            const uint32_t a = sb + C2_VT + (s & 1) * 6144 + a32;
            stmatrix_x4(a, va[0][0], va[0][1], va[1][0], va[1][1]);
            stmatrix_x4(a + 2048, va[2][0], va[2][1], va[3][0], va[3][1]);
            asm volatile("stmatrix.sync.aligned.m8n8.x2.shared.b16 [%0], {%1, %2};" :: "r"(a + 4096), "r"(va[4][0]), "r"(va[4][1]) : "memory");
        };
#pragma unroll 1
        for (int s = -1;;) {
            if (s >= 0) {
                const int t = tid - 256;
                const uint2* src = g_xbuf + ((s & 1) * 8 + rank) * 1024 + t;
                asm volatile("" : "+l"(src));
                const uint32_t ma = sb + C2_XB + ((s + 1) & 1) * C2_XS + rank * 5120 + 4096 + (t >> 4) * 128 + ((((t >> 1) & 7) ^ (t >> 4)) << 4) + (t & 1) * 8;
                uint32_t ra[8], rb[8];
#pragma unroll
                for (int i = 1; i < 8; i++) {
                    const uint32_t d = (rank + i) & 7;
                    ra[i] = pin(mapa_u32(ma, d)); rb[i] = pin(mapa_u32(bar_m + 8 * c2_grp(i), d));
                }
                if (s == NSEG - 1) break;
                bar_sync<11, 256>();
                DBGW(29, 0);
                pace(CH_POLL_DELAY);
                const uint32_t tag = ((s >> 1) & 1) ^ 1;
                uint32_t p[8][2], m0, m1;
                auto issue = [&](uint32_t (&x)[8][2]) {
#pragma unroll
                    for (int k = 0; k < 8; k++)
                        asm volatile("ld.relaxed.gpu.global.v2.u32 {%0, %1}, [%2];" : "=r"(x[k][0]), "=r"(x[k][1]) : "l"(src + k * 128) : "memory");
                };
                auto check = [&](const uint32_t (&x)[8][2]) {
                    uint32_t bad = 0, bad2 = 0;
                    float r[4];
#pragma unroll
                    for (int k = 0; k < 8; k++) {
                        asm("lop3.b32 %0, %0, %1, %2, 0xf6;" : "+r"(bad) : "r"(x[k][0]), "r"(tag));
                        asm("lop3.b32 %0, %0, %1, %2, 0xf6;" : "+r"(bad2) : "r"(x[k][1]), "r"(tag));
#pragma unroll
                        for (int e = 0; e < 2; e++) {
                            const float lo = __uint_as_float(x[k][e] << 16), hi = __uint_as_float(x[k][e] & 0xffff0000u);
                            r[2 * e] = k ? r[2 * e] + lo : lo;
                            r[2 * e + 1] = k ? r[2 * e + 1] + hi : hi;
                        }
                    }
                    m0 = pack_bf16(r[0], r[1]); m1 = pack_bf16(r[2], r[3]);
                    asm volatile("" : "+r"(m0), "+r"(m1));
                    return __all_sync(0xffffffff, ((bad | bad2) & 1u) == 0u);
                };
                for (int it = 0; it < (1 << 20); it++) {
                    issue(p);
                    if (check(p)) break;
                }
                DBGW(30, 0);
                st_async_v2(ra[1], m0, m1, rb[1]);
                asm volatile("st.shared.v2.b32 [%0], {%1, %2};" :: "r"(ma), "r"(m0), "r"(m1) : "memory");
                __syncwarp();
                if (lane == 0) mbar_arrive(bar_m);
#pragma unroll
                for (int i = 2; i < 8; i++) st_async_v2(ra[i], m0, m1, rb[i]);
                DBGW(31, 0);
                TM(8);
                store_vt(s);
            }
            s++;
            const uint32_t ost = pin(sb + C2_OB + t32), pla = pin(sb + C2_PB + lane * 16), plb = pin(sb + C2_PB + 512 + (lane & 7) * 16);
            bar_sync<1, 384>();
            fence_async_smem();
            DBGW(24, 0);
            if (s < NSEG - 1) bar_sync<2, 224>();
            else bar_arrive<6, 384>();
            {
                float acc[20];
                c2_xstream<0, 32, CH_SPV>(acc, w, dlo + ((C2_XB + (s & 1) * C2_XS) >> 4), rank, dlo + (C2_WV >> 4));
                wgmma_wait<0>();
#pragma unroll
                for (int j = 0; j < 5; j++) { va[j][0] = pack_bf16(acc[4 * j], acc[4 * j + 1]); va[j][1] = pack_bf16(acc[4 * j + 2], acc[4 * j + 3]); }
            }
            DBGW(26, 0);
            TM(7);
            if (s < NSEG - 1) {
                uint32_t p[5];
                bar_sync<3, 160>();
                DBGW(27, 0);
                ldmatrix_x4_trans(p[0], p[1], p[2], p[3], pla);
                asm volatile("ldmatrix.sync.aligned.m8n8.x1.trans.shared.b16 {%0}, [%1];" : "=r"(p[4]) : "r"(plb) : "memory");
                float oa[4] = {0.f, 0.f, 0.f, 0.f}, ob[4] = {0.f, 0.f, 0.f, 0.f}, sa[4] = {0.f, 0.f, 0.f, 0.f}, sc[4] = {0.f, 0.f, 0.f, 0.f};
                const uint32_t one = 0x3f803f80u;
                mma_16816(sa, one, one, one, one, p[0], p[1]);
                mma_16816(oa, va[0][0], va[0][1], va[1][0], va[1][1], p[0], p[1]);
                mma_16816(sc, one, one, one, one, p[2], p[3]);
                mma_16816(ob, va[2][0], va[2][1], va[3][0], va[3][1], p[2], p[3]);
                mma_16816(sa, one, one, one, one, p[4], 0u);
                mma_16816(oa, va[4][0], va[4][1], 0u, 0u, p[4], 0u);
                bar_arrive<6, 384>();
                float i0, i1;
                asm("rcp.approx.ftz.f32 %0, %1;" : "=f"(i0) : "f"(sa[0] + sc[0]));
                asm("rcp.approx.ftz.f32 %0, %1;" : "=f"(i1) : "f"(sa[1] + sc[1]));
                sts32(ost, pack_bf16((oa[0] + ob[0]) * i0, (oa[2] + ob[2]) * i0));
                sts32(ost + 32, pack_bf16((oa[1] + ob[1]) * i1, (oa[3] + ob[3]) * i1));
                fence_async_smem();
                __syncwarp();
                if (elect_one()) {
#pragma unroll
                    for (int i = 1; i < 8; i++) {
                        const uint32_t d = (rank + i) & 7;
                        bulk_s2s(mapa_u32(sb + C2_OB + i * 1024 + w4 * 256, d), sb + C2_OB + w4 * 256, 256, mapa_u32(bar_o + 8 * c2_grp(i), d));
                        if (i == 1) mbar_arrive(bar_o);
                    }
                }
                __syncwarp();
                DBGW(28, 0);
            }
        }
        store_vt(NSEG - 1);
        fence_async_smem();
        bar_arrive<7, 256>();
        const uint32_t lane = fresh_lane();
        if (w4 == 0) {
            mbar_wait(bar_h, 0);
#pragma unroll 1
            for (uint32_t o = 0; o < 2; o++) {
                asm volatile("bar.sync %0, 160;" :: "r"(13 + o) : "memory");
                if (elect_one()) {
#pragma unroll
                    for (int i = 1; i < 8; i++) {
                        const uint32_t d = (rank + i) & 7;
                        bulk_s2s(mapa_u32(sb + C2_WO + i * 8192 + o * 4096, d), sb + C2_QX + o * 4096, 4096, mapa_u32(bar_m + o * 64 + 8 * c2_grp(i), d));
                    }
                }
                __syncwarp();
                if (lane < 4) mbar_arrive(bar_m + o * 64);
                TM(21 + o);
            }
        }
        __syncwarp();
        asm volatile("barrier.cluster.arrive.relaxed.aligned;" ::: "memory");
        g_xbuf[((8 + rank) * 8 + C) * 128 + w4 * 32 + lane] = make_uint2(0u, 0u);
    }
    asm volatile("barrier.cluster.wait.aligned;" ::: "memory");
    TS_END(2);
    CYC(3);
    if (wg == 0) TM(23);
}

constexpr int P3_LEN = 24;
struct SideParams {
    CUtensorMap mapA[2];
    CUtensorMap mapW[3];
    CUtensorMap mapQ, mapK, mapV;
    CUtensorMap mapO;
    CUtensorMap mapCtx[2];
    CUtensorMap mapWo[2];
    CUtensorMap mapOut;
    bf16* qkv[3];
    const bf16 *x, *gate_w;
    bf16* out;
    uint32_t jobs[34 * 2];
    uint16_t sched[34 * P3_LEN];
    uint8_t first[34];
};
constexpr int P3_STAGES = 14;
#define P3_LAG 2
#define SD_GD 12000
#define SD_D0 0
#define SD_EFW 0
#define SD_EFA 0
#define SD_EFS 0
#define SD_EFK 0
#define SD_ALIAS 1
#define SD_JN 1
#define SD_PB 0
#define SD_GW 2
#define SD_NS 1
#define SD_CT 384
#define PT(i)
#define SC(i)
#define OT(i)
constexpr uint32_t SD_PF = FA_BAR + 256, SD_PE = SD_PF + 8 * P3_STAGES, SD_OF = SD_PE + 8 * P3_STAGES, SD_OE = SD_OF + 32, SD_CL = SD_OE + 32, SD_DONE = FA_BAR + 576;
constexpr int SD_SMEM = SD_DONE + 2 * P3_LEN * 8;
__device__ __forceinline__ void tma_load_3d(uint32_t dst, const CUtensorMap* map, uint32_t bar, int c0, int c1, int c2) {
    asm volatile(
        "cp.async.bulk.tensor.3d.shared::cluster.global.mbarrier::complete_tx::bytes [%0], [%1, {%3, %4, %5}], [%2];"
        :: "r"(dst), "l"((uint64_t)map), "r"(bar), "r"(c0), "r"(c1), "r"(c2) : "memory");
}
__global__ void __cluster_dims__(2, 1, 1) __launch_bounds__(384, 1) side_kernel(const __grid_constant__ SideParams P) {
    extern __shared__ __align__(1024) uint8_t smem_side[];
    const uint32_t sb = smem_u32(smem_side);
    const uint32_t full = sb + SD_PF, empty = sb + SD_PE, done = sb + SD_DONE;
    const uint32_t bar_q = sb + FA_BAR, bar_qe = bar_q + 16, bar_kf = bar_q + 32, bar_vf = bar_q + 48, bar_ke = bar_q + 64, bar_ve = bar_q + 80,
                   bar_of = bar_q + 96, bar_oe = bar_q + 112, oslot = bar_q + 144;
    const int warp = __shfl_sync(0xffffffff, threadIdx.x >> 5, 0), lane = threadIdx.x & 31;
    const uint32_t rank = cluster_ctarank();
    const uint16_t* sched = P.sched + (blockIdx.x >> 1) * P3_LEN;
    const uint32_t so0 = P.first[blockIdx.x >> 1] * 8;
    TS_BEGIN_T(0, 320);
    if (warp == 0 && lane < P3_STAGES) {
        mbar_init(full + 8 * lane, 1); mbar_init(empty + 8 * lane, 4);
        if (8 * lane < so0) {
            mbar_arrive(full + 8 * lane);
            asm volatile("mbarrier.arrive.shared::cta.b64 _, [%0], 4;" :: "r"(empty + 8 * lane) : "memory");
        }
    }
    if (warp == 1 && lane < 16) mbar_init(bar_q + 8 * lane, (0x14881181u >> (lane >> 1) * 4) & 15);
    if (warp == 2 && lane < 9) mbar_init(sb + SD_OF + 8 * lane, (lane >> 2 & 1) + 1);
    if (warp == 3 || (warp == 4 && lane < 2 * P3_LEN - 32)) mbar_init(done + (threadIdx.x - 96) * 8, 4);
    if (warp < 5) asm volatile("fence.mbarrier_init.release.cluster;" ::: "memory");
    __syncthreads();
    cluster_sync_relaxed();
    if (warp >= 8) {
        asm volatile("setmaxnreg.dec.sync.aligned.u32 %0;" :: "n"(FA_RLO));
        if (warp == 8) {
            uint32_t so = so0, ph = 1;
            pace(SD_D0);
#pragma unroll 1
            for (;; sched++) {
                const uint32_t e = *sched, z = (e >> 5) & 3, na = e >> 10;
                if (z == 3) break;
#pragma unroll 1
                for (int i = 1 - na; i < 16; i += 2 - na) {
                    mbar_wait(empty + so, ph);
                    if (elect_one()) {
                        mbar_expect_tx(full + so, 16384);
                        if (i & 1) tma_load_2d_mc(sb + so * 2048 + rank * 8192, &P.mapW[z], full + so, (e & 31) * 128 + rank * 64, (i >> 1) * 64, (uint16_t)3, SD_EFW ? L2_FIRST : L2_NORMAL);
                        else tma_load_2d(sb + so * 2048, &P.mapA[z != 0], full + so, (i >> 1) * 64, (((e >> 7) & 7) * 2 + rank) * 128, SD_EFA && z ? L2_FIRST : L2_NORMAL);
                    }
                    so += 8;
                    if (so == 8 * P3_STAGES) { so = 0; ph ^= 1; }
                }
            }
            TS_MARK(13, 256);
            PT(0);
            int it = 0, t = blockIdx.x, hp_ready = 0;
            auto load = [&](uint32_t dst, const CUtensorMap* map, uint32_t bar, int row) {
                if (elect_one()) {
                    mbar_expect_tx(bar, 32768);
                    tma_load_2d(dst, map, bar, 0, row, SD_EFK && map != &P.mapQ ? L2_FIRST : L2_NORMAL);
                    tma_load_2d(dst + 16384, map, bar, 64, row, SD_EFK && map != &P.mapQ ? L2_FIRST : L2_NORMAL);
                }
            };
            auto load_q = [&](int item) {
                const uint32_t b = bar_q + 8 * (item & 1);
                sts32(b + 128, t);
                if (t < 0) { mbar_arrive_if(b, lane == 0); return; }
                const int hp = fa_head(t) >> 1;
                if (!((hp_ready >> hp) & 1)) { wait_ctr(CT_AP + hp, 192u); hp_ready |= 1 << hp; }
                load(sb + FA_Q + (item & 1) * 32768, &P.mapQ, b, fa_head(t) * SEQ + fa_qt(t) * 128);
            };
            auto load_v = [&](int it, int row) {
                const int s = it & 1;
                if (it < 2) mbar_wait(empty + 56 + 32 * s, ph);
                mbar_wait(bar_ve + 8 * s, ((it >> 1) & 1) ^ 1);
                load(sb + FA_KV + s * 65536 + 32768, &P.mapV, bar_vf + 8 * s, row);
            };
            int vrow = 0;
            mbar_wait(empty + 8, ph);
            PT(1);
            load_q(0);
            PT(2);
#pragma unroll 1
            for (int item = 0; t >= 0; item++) {
                const int h = fa_head(t), jn = min(fa_qt(t), SD_JN);
                if (item == 1 && blockIdx.x < 8) TS_MARK(14, 256);
#pragma unroll 1
                for (int j = fa_qt(t); j >= 0; j--, it++) {
                    const int s = it & 1;
                    uint32_t tn = 0;
                    asm volatile("{\n.reg .pred p;\nsetp.eq.u32 p, %2, 0;\n@p atom.relaxed.gpu.global.add.u32 %0, [%1], 1;\n}" : "+r"(tn) : "l"(&g_ctr[CT_ATTN] + lane), "r"((j ^ jn) | lane) : "memory");
                    if (it < 2) mbar_wait(empty + 40 + 32 * s, ph);
                    mbar_wait(bar_ke + 8 * s, ((it >> 1) & 1) ^ 1);
                    PT(4 + it);
                    load(sb + FA_KV + s * 65536, &P.mapK, bar_kf + 8 * s, h * SEQ + j * 128);
                    if (it > 0) load_v(it - 1, vrow);
                    vrow = h * SEQ + j * 128;
                    if (j == jn) {
                        const int tp = t;
                        t = FA_GRID + __shfl_sync(0xffffffff, tn, 0);
                        mbar_arrive_if(sb + SD_CL, tp < SD_CT && t >= SD_CT && lane == 0);
                        if (t >= FA_ITEMS) t = FA_ITEMS - 1 - t;
                        mbar_wait(bar_qe + 8 * ((item + 1) & 1), (((item + 1) >> 1) & 1) ^ 1);
                        load_q(item + 1);
                    }
                }
            }
            load_v(it - 1, vrow);
            TS_MARK(15, 256);
            const uint32_t tk = ~t;
            so = 0; ph = 1;
            TS_BEGIN_T(4, 256);
            wait_ctr(CT_P, FA_GRID);
#pragma unroll 1
            for (uint32_t e = P.jobs[tk & ~1u], en = P.jobs[tk | 1u]; e; e = en, en = 0) {
                const uint32_t mt = e & 15, na = e >> 10 & 127, n = na + (e >> 23);
#pragma unroll 1
                for (uint32_t i = 0; i < n; i++) {
                    const uint32_t b = i >= na, k = b ? (e >> 17 & 63) + i - na : (e >> 4 & 63) + i;
                    mbar_wait(so < 16 ? bar_ke + 8 * (~it & 1) : bar_ve - 16 + so, ((it - 1 - (so == 24)) >> 1) & 1);
                    mbar_wait(sb + SD_OE + so, ph);
                    if (elect_one()) {
                        mbar_expect_tx(sb + SD_OF + so, 49152);
                        tma_load_3d(sb + so * 6144 + 16384, &P.mapWo[b], sb + SD_OF + so, 0, k * 64, (tk & 1) * 4);
                    }
                    const bool late = k >= 2 * O2_HE;
                    if (i == 0 || i == na || k == 2 * O2_HE)
                        wait_ctr(b ? CT_CB + max(mt, CB_FIRST) : CT_CA + mt * 2 + late, b ? (CH_TS ? 256u : 64u) : late ? 2u * (NH - O2_HE) : 2u * O2_HE);
                    if (elect_one()) tma_load_2d(sb + so * 6144, &P.mapCtx[b], sb + SD_OF + so, (k & 1) * 64, (k >> 1) * SEQ + mt * 128);
                    so = (so + 8) & 31;
                    if (so == 0) ph ^= 1;
                }
            }
            TS_END_T(4, 256);
            finish_launch(lane);
        } else if (warp == 11) {
#pragma unroll 1
            for (int i = 0; i < 4000 && !mbar_test(done + 8 * SD_GW, 0); i++) __nanosleep(500);
            const uint4 gv0 = __ldg(reinterpret_cast<const uint4*>(P.gate_w) + lane), gv1 = __ldg(reinterpret_cast<const uint4*>(P.gate_w) + 32 + lane);
            const uint32_t gw[8] = {gv0.x, gv0.y, gv0.z, gv0.w, gv1.x, gv1.y, gv1.z, gv1.w};
#pragma unroll 1
            for (int r = blockIdx.x; r < SEQ; r += gridDim.x) {
                const uint4 x0 = __ldg(reinterpret_cast<const uint4*>(P.x + (size_t)r * DM) + lane), x1 = __ldg(reinterpret_cast<const uint4*>(P.x + (size_t)r * DM) + 32 + lane);
                const uint32_t xw[8] = {x0.x, x0.y, x0.z, x0.w, x1.x, x1.y, x1.z, x1.w};
                float sum = 0.f;
#pragma unroll
                for (int e = 0; e < 8; e++) {
                    const uint32_t pr = pack_bf16(__uint_as_float(xw[e] << 16) * __uint_as_float(gw[e] << 16), __uint_as_float(xw[e] & 0xffff0000u) * __uint_as_float(gw[e] & 0xffff0000u));
                    sum += __uint_as_float(pr << 16) + __uint_as_float(pr & 0xffff0000u);
                }
#pragma unroll
                for (int o = 16; o; o >>= 1) sum += __shfl_xor_sync(0xffffffff, sum, o);
                if (lane == 0) g_gate[r] = bf16r(__fdividef(1.f, 1.f + __expf(-bf16r(sum))));
            }
#pragma unroll 1
            for (int i = 0; i < 4000 && !mbar_test(sb + SD_CL, 0); i++) __nanosleep(500);
#pragma unroll 1
            for (int i = blockIdx.x * 32 + lane; i < SEQ * DM / 8; i += gridDim.x * 32) reinterpret_cast<uint4*>(P.out)[i] = make_uint4(0u, 0u, 0u, 0u);
            asm volatile("fence.proxy.async.global;" ::: "memory");
            __syncwarp();
            if (lane == 0) signal_ctr(CT_P);
        } else if (lane == 0) {
            const int wg = warp - 9;
            SC(0);
#pragma unroll 1
            for (uint32_t d = done + wg * P3_LEN * 8;; d += 8, sched++) {
                const uint32_t e = *sched;
                if (((e >> 5) & 3) == 3) break;
                mbar_wait(d, 0);
                signal_ctr(CT_AP + ((e & 31) >> 1));
            }
            const uint32_t stg = sb + FA_O + wg * 16384;
            TS_END_T(0, 320);
            SC(1);
            TS_BEGIN_T(1, 320);
#pragma unroll 1
            for (int n = 0;; n++) {
                mbar_wait(bar_of + 8 * wg, n & 1);
                int t;
                asm volatile("ld.shared.s32 %0, [%1];" : "=r"(t) : "r"(oslot + wg * 4) : "memory");
                asm volatile("fence.proxy.async.shared::cta;" ::: "memory");
                const bool last = t < 0;
                t &= 0xffff;
                const int qt = fa_qt(t), h = fa_head(t);
                tma_store_2d(&P.mapO, stg, 0, h * SEQ + qt * 128 + wg * 64);
                tma_store_2d(&P.mapO, stg + 8192, 64, h * SEQ + qt * 128 + wg * 64);
                asm volatile("cp.async.bulk.commit_group;" ::: "memory");
                asm volatile("cp.async.bulk.wait_group.read 0;" ::: "memory");
                mbar_arrive(bar_oe + 8 * wg);
                asm volatile("cp.async.bulk.wait_group 0;" ::: "memory");
                signal_ctr(CT_CA + qt * 2 + (h >= O2_HE));
                if (last) break;
            }
            TS_END_T(1, 320);
            SC(2);
        }
    } else {
        asm volatile("setmaxnreg.inc.sync.aligned.u32 %0;" :: "n"(FA_RHI));
        const int wg = warp >> 2;
        {
            uint32_t a[32][4];
            float acc[64];
            const uint32_t b_lo = desc_lo(sb, 8192);
            const int r = warp * 16 + (lane & 15);
            const uint32_t la = sb + r * 128 + (((lane >> 4) ^ (r & 7)) << 4);
#pragma unroll
            for (int i = 0; i < 32; i++) ldsm_x4(a[i], la + i * 1024);
            const uint32_t rel = mapa_u32(empty, lane & 1);
            const int tw = threadIdx.x & 127;
            uint32_t so = so0, ph = 0;
            const uint32_t b1 = SD_PB ? pin(1 + wg) : 1 + wg;
            if (wg == 1) asm volatile("bar.arrive 1, 256;" ::: "memory");
#pragma unroll 1
            for (uint32_t d = done + wg * P3_LEN * 8;; d += 8, sched++) {
                const uint32_t e = *sched;
                if (((e >> 5) & 3) == 3) break;
                const bool na = e >> 10;
                const bool sig = tw < (na ? 4 : 2);
                uint32_t old = 0;
                auto release = [&]() { asm volatile("{\n.reg .pred p;\nsetp.ne.u32 p, %1, 0;\n@p mbarrier.arrive.shared::cluster.b64 _, [%0];\n}" :: "r"(rel + old), "r"((uint32_t)sig) : "memory"); };
                asm volatile("bar.sync %0, 256;" :: "r"(b1) : "memory");
#pragma unroll
                for (int k = 0; k < 8; k++) {
                    const uint32_t sa = so;
                    if (na) {
                        mbar_wait(full + so, ph);
#pragma unroll
                        for (int kk = 0; kk < 4; kk++) ldsm_x4(a[k * 4 + kk], (la + so * 2048) ^ (kk * 32));
                        so += 8;
                        if (so == 8 * P3_STAGES) { so = 0; ph ^= 1; }
                    }
                    mbar_wait(full + so, ph);
                    wgmma_fence();
#pragma unroll
                    for (int kk = 0; kk < 4; kk++) wgmma_rs_n128_tb_lo(acc, a[k * 4 + kk], b_lo + so * 128 + kk * 128, (k | kk) != 0);
                    wgmma_commit();
                    if (k == P3_LAG) asm volatile("bar.arrive %0, 256;" :: "r"(2 - wg) : "memory");
                    if (k > 0) { wgmma_wait<1>(); release(); }
                    old = (lane & 2) ? sa : so;
                    so += 8;
                    if (so == 8 * P3_STAGES) { so = 0; ph ^= 1; }
                }
                bf16* dst = P.qkv[(e >> 5) & 3] + ((size_t)(e & 31) * SEQ + (((e >> 7) & 7) * 2 + rank) * 128 + warp * 16 + (lane >> 2)) * HD + (lane & 3) * 8;
                wgmma_wait<0>();
                release();
#pragma unroll
                for (int i = 0; i < 8; i++) {
                    const float* c = &acc[(i >> 1) * 16 + (i & 1) * 2];
                    *reinterpret_cast<uint4*>(dst + (i & 1) * 8 * HD + (i >> 1) * 32) =
                        make_uint4(pack_bf16(c[0], c[1]), pack_bf16(c[4], c[5]), pack_bf16(c[8], c[9]), pack_bf16(c[12], c[13]));
                }
                __syncwarp();
                mbar_arrive_if(d, lane == 0);
            }
        }
        const uint32_t tk = attn_consumer(sb, wg, warp & 3, lane);
        float acc[128];
#pragma unroll
        for (int i = 0; i < 128; i++) asm volatile("" : "=f"(acc[i]));
        const uint32_t a_lo = desc_lo(sb + wg * 8192, 16), b_lo = desc_lo(sb + 16384, 8192);
        const uint32_t st = sb + FA_O + warp * 4096, sl = st + (lane & 15) * 128 + (((lane >> 4) ^ (lane & 7)) << 4);
        const bool sig = (threadIdx.x & 127) == 0;
        uint32_t so = 0, ph = 0;
        uint32_t pk[64], part = 4, row0 = 0;
#pragma unroll
        for (int i = 0; i < 64; i++) asm volatile("" : "=r"(pk[i]));
        auto drain = [&](const uint32_t* c, uint32_t q) {
            asm volatile("cp.async.bulk.wait_group.read 1;" ::: "memory");
            __syncwarp();
#pragma unroll
            for (int t = 0; t < 4; t++) stmatrix_x4((sl ^ (t * 32)) + (q & 1) * 2048, c[4 * t], c[4 * t + 1], c[4 * t + 2], c[4 * t + 3]);
            fence_async_smem();
            __syncwarp();
            if (elect_one())
                asm volatile("cp.reduce.async.bulk.tensor.2d.global.shared::cta.add.bulk_group [%0, {%2, %3}], [%1];"
                             :: "l"((uint64_t)&P.mapOut), "r"(st + (q & 1) * 2048), "r"((tk & 2) * 128 + q * 64), "r"(row0) : "memory");
            asm volatile("cp.async.bulk.commit_group;" ::: "memory");
        };
#pragma unroll 1
        for (uint32_t e = P.jobs[(tk >> 1) & ~1u], en = P.jobs[(tk >> 1) | 1u]; e; e = en, en = 0) {
            const uint32_t row = (e & 15) * 128 + warp * 16, na = e >> 10 & 127, n = na + (e >> 23);
            float g0, g1;
#pragma unroll 1
            for (uint32_t i = 0;; i++) {
                if (i == n || (i == na && i)) {
                    const float w0 = fmaxf(1.f - g0, 0x1p-40f), w1 = fmaxf(1.f - g1, 0x1p-40f);
                    const float r0 = i < n ? __fdividef(g0, w0) : na < n ? w0 : g0, r1 = i < n ? __fdividef(g1, w1) : na < n ? w1 : g1;
                    wgmma_wait<0>();
                    mbar_arrive_if(sb + SD_OE + ((so - 8) & 31), sig && i == n);
                    if (i == n) OT(3); else OT(2);
#pragma unroll
                    for (int c = 0; c < 32; c++) { acc[4 * c] *= r0; acc[4 * c + 1] *= r0; acc[4 * c + 2] *= r1; acc[4 * c + 3] *= r1; }
                    if (i == n) break;
                }
                mbar_wait(sb + SD_OF + so, ph);
                if (i == 0) OT(1);
                wgmma_fence();
#pragma unroll
                for (int kk = 0; kk < 4; kk++) wgmma_ss_n256_tb(acc, a_lo + so * 384 + kk * 2, b_lo + so * 384 + kk * 128, i | kk);
                wgmma_commit();
                if (i > 0) { wgmma_wait<1>(); mbar_arrive_if(sb + SD_OE + ((so - 8) & 31), sig); }
                else {
                    asm volatile("ld.relaxed.gpu.global.f32 %0, [%1];" : "=f"(g0) : "l"(g_gate + row + (lane >> 2)) : "memory");
                    asm volatile("ld.relaxed.gpu.global.f32 %0, [%1 + 32];" : "=f"(g1) : "l"(g_gate + row + (lane >> 2)) : "memory");
                }
                if (part < 4) {
                    drain(pk, part++);
#pragma unroll
                    for (int c = 0; c < 48; c++) pk[c] = pk[c + 16];
                }
                so = (so + 8) & 31;
                if (so == 0) ph ^= 1;
            }
#pragma unroll
            for (int c = 0; c < 64; c++) pk[c] = pack_bf16(acc[2 * c], acc[2 * c + 1]);
            part = 0; row0 = row;
            mbar_wait(bar_oe + 8 * wg, tk & 1);
            OT(4);
        }
#pragma unroll
        for (int q = 0; q < 4; q++) drain(pk + 16 * q, q);
        asm volatile("cp.async.bulk.wait_group.read 0;" ::: "memory");
    }
}

typedef CUresult (*PFN_encodeTiled)(CUtensorMap*, CUtensorMapDataType, cuuint32_t, void*, const cuuint64_t*,
                                    const cuuint64_t*, const cuuint32_t*, const cuuint32_t*, CUtensorMapInterleave,
                                    CUtensorMapSwizzle, CUtensorMapL2promotion, CUtensorMapFloatOOBfill);
static PFN_encodeTiled g_encode = nullptr;

static void make_map(CUtensorMap* m, const void* ptr, uint64_t rows, uint64_t cols, uint32_t box_rows, bool narrow = false) {
    cuuint64_t dims[2] = {cols, rows};
    cuuint64_t strides[1] = {cols * 2};
    cuuint32_t box[2] = {narrow ? 16u : 64u, box_rows};
    cuuint32_t es[2] = {1, 1};
    g_encode(m, CU_TENSOR_MAP_DATA_TYPE_BFLOAT16, 2, const_cast<void*>(ptr), dims, strides, box, es,
             CU_TENSOR_MAP_INTERLEAVE_NONE, narrow ? CU_TENSOR_MAP_SWIZZLE_NONE : CU_TENSOR_MAP_SWIZZLE_128B, CU_TENSOR_MAP_L2_PROMOTION_L2_256B,
             CU_TENSOR_MAP_FLOAT_OOB_FILL_NONE);
}

static void make_map3(CUtensorMap* m, const void* ptr, uint64_t rows, uint64_t cols, uint32_t box_rows, uint32_t nblk) {
    cuuint64_t dims[3] = {64, rows, cols / 64};
    cuuint64_t strides[2] = {cols * 2, 128};
    cuuint32_t box[3] = {64u, box_rows, nblk};
    cuuint32_t es[3] = {1, 1, 1};
    g_encode(m, CU_TENSOR_MAP_DATA_TYPE_BFLOAT16, 3, const_cast<void*>(ptr), dims, strides, box, es,
             CU_TENSOR_MAP_INTERLEAVE_NONE, CU_TENSOR_MAP_SWIZZLE_128B, CU_TENSOR_MAP_L2_PROMOTION_L2_256B, CU_TENSOR_MAP_FLOAT_OOB_FILL_NONE);
}

template <typename... KArgs, typename... Args>
static void launch_pdl(void (*kernel)(KArgs...), int grid, int block, size_t smem, cudaStream_t st, bool pdl, Args... args) {
    cudaLaunchConfig_t cfg = {};
    cfg.gridDim = dim3(grid); cfg.blockDim = dim3(block); cfg.dynamicSmemBytes = smem; cfg.stream = st;
    cudaLaunchAttribute at[1];
    at[0].id = cudaLaunchAttributeProgrammaticStreamSerialization;
    at[0].val.programmaticStreamSerializationAllowed = 1;
    cfg.attrs = at; cfg.numAttrs = pdl ? 1 : 0;
    cudaLaunchKernelEx(&cfg, kernel, KArgs(args)...);
}

extern "C" void kernel_launch(void* const* d_in, const int* in_sizes, int n_in, void* d_out, int out_size) {
    const bf16* x = (const bf16*)d_in[0];
    const bf16* ckv = (const bf16*)d_in[1];
    const bf16* wq = (const bf16*)d_in[2];
    const bf16* wuk = (const bf16*)d_in[3];
    const bf16* wuv = (const bf16*)d_in[4];
    const bf16* wo = (const bf16*)d_in[5];
    const bf16* mem0 = (const bf16*)d_in[7];
    const bf16* Wq = (const bf16*)d_in[8];
    const bf16* Wk = (const bf16*)d_in[9];
    const bf16* Wv = (const bf16*)d_in[10];
    const bf16* Wo = (const bf16*)d_in[11];
    const bf16* gate_w = (const bf16*)d_in[13];
    bf16* out = (bf16*)d_out;

    static SideParams SP;
    static ChainParams CP;
    static bool init = false;
    static const void* last_in[15];
    bool same = init;
    for (int i = 0; i < 14 && same; i++) same = last_in[i] == d_in[i];
    same = same && last_in[14] == d_out;
    if (!init) {
        cudaDriverEntryPointQueryResult qr;
        cudaGetDriverEntryPoint("cuTensorMapEncodeTiled", (void**)&g_encode, cudaEnableDefault, &qr);
        cudaFuncSetAttribute(side_kernel, cudaFuncAttributeMaxDynamicSharedMemorySize, SD_SMEM);
        for (int p = 0; p < 34; p++) {
            uint16_t* t = SP.sched + p * P3_LEN;
            int n = 0, rows = -1;
            auto add = [&](int z, int mp, int head) {
#define P3_RQ 12
#define P3_RK 22
                head = (head + 32 - (z ? P3_RK : P3_RQ)) & 31;
                t[n++] = (uint16_t)(head | z << 5 | mp << 7 | (rows != (z ? 8 : 0) + mp) << 10);
                rows = (z ? 8 : 0) + mp;
            };
            const int mp = p & 7, kind = p >> 3;
            if (kind == 0) for (int h = 0; h < 23; h++) add(0, mp, h);
            else if (kind < 4) {
                for (int i = kind - 1; i < 54; i += 3) add(1 + (i & 1), mp, i >> 1);
                if (kind < 3) for (int h = 27; h < 32; h++) add(kind, mp, h);
                else for (int h = 23; h < 27; h++) add(0, mp, h);
            } else for (int i = 0; i < 20; i++) add(0, mp * 4 + i / 5, 27 + i % 5);
            int stages = 0;
            for (int i = 0; i < n; i++) stages += 8 << (t[i] >> 10);
            SP.first[p] = (uint8_t)((P3_STAGES - stages % P3_STAGES) % P3_STAGES);
            while (n < P3_LEN) t[n++] = 3 << 5;
        }
        cudaFuncSetAttribute(chain_kernel, cudaFuncAttributeMaxDynamicSharedMemorySize, C2_SMEM);
#define O6_SCHED 0xfc10, 0x0, 0x1e860400, 0x0, 0x1800000, 0xec51, 0x1c001401, 0x0, 0x4700001, 0x1a180002, 0xf432, 0x0, 0x6000c02, 0xc005003, 0xb143, 0x2782c04, 0x1e000004, 0x0, 0xd4b4, 0x2780ac5, 0x1e000005, 0x0, 0x12b61006, 0x4ae5, 0xf046, 0x0, 0xd800006, 0x8007, 0x2001008, 0x19800007, 0x1e080008, 0x0, 0xf048, 0x0, 0xd4c85f9, 0x0, 0x13000009, 0x7e217ba, 0xec0a, 0x0, 0x1880000a, 0x240b, 0x1d00000b, 0x0, 0x374389b, 0x1280000c, 0xdca7e1c, 0x0, 0x840c, 0xc34000d, 0xd007c0d, 0x0, 0x76485fd, 0x492000e, 0xa57b, 0x4ee1bae, 0x7c09, 0x5363cee, 0x6e68207, 0x480040e, 0xb005, 0x4dc0b8e, 0x3e9e, 0x14300003, 0x840f, 0x4ca31de, 0x7e1f, 0x4a4341e
        const uint32_t sched[68] = {O6_SCHED};
        for (int i = 0; i < 68; i++) SP.jobs[i] = sched[i];
        init = true;
    }
    if (!same) {
        for (int i = 0; i < 14; i++) last_in[i] = d_in[i];
        last_in[14] = d_out;
        void *pQA, *pKA, *pVA, *pCA, *pCB;
        cudaGetSymbolAddress(&pQA, g_QA); cudaGetSymbolAddress(&pKA, g_KA); cudaGetSymbolAddress(&pVA, g_VA);
        cudaGetSymbolAddress(&pCA, g_ctxA); cudaGetSymbolAddress(&pCB, g_ctxB);
        pCA = pQA;
        make_map(&SP.mapA[0], x, SEQ, DM, 128);
        make_map(&SP.mapA[1], ckv, SEQ, DM, 128);
        const void* ws[3] = {wq, wuk, wuv};
        void* cs[3] = {pQA, pKA, pVA};
        for (int i = 0; i < 3; i++) { make_map(&SP.mapW[i], ws[i], DM, NQ, 64); SP.qkv[i] = (bf16*)cs[i]; }
        make_map(&CP.mapX, x, SEQ, DM, SEGL);
        make_map(&CP.mapM, mem0, NMEM, DM, NMEM);
        make_map(&CP.mapW[0], Wq, DM, NQ, 64);
        make_map(&CP.mapW[1], Wk, DM, NQ, 64);
        make_map(&CP.mapW[2], Wv, DM, NQ, 64);
        make_map(&CP.mapWo, Wo, NQ, DM, 64);
        make_map(&SP.mapQ, pQA, NH * SEQ, HD, 128);
        make_map(&SP.mapK, pKA, NH * SEQ, HD, 128);
        make_map(&SP.mapV, pVA, NH * SEQ, HD, 128);
        make_map(&SP.mapO, pCA, NH * SEQ, HD, 64);
        make_map(&SP.mapCtx[0], pCA, NH * SEQ, HD, 128);
        make_map(&SP.mapCtx[1], pCB, NH * SEQ, HD, 128);
        make_map3(&SP.mapWo[0], wo, NQ, DM, 64, 4);
        make_map3(&SP.mapWo[1], Wo, NQ, DM, 64, 4);
        make_map(&SP.mapOut, out, SEQ, DM, 16);
        SP.out = out;
        make_map(&CP.mapC, pCB, NH * SEQ, HD, 64);
        make_map(&CP.mapS, pCB, NH * SEQ, HD, 32, true);
        CP.out = out;
        const void* pf[6] = {x, ckv, Wq, Wk, Wv, Wo};
        for (int i = 0; i < 6; i++) CP.pf[i] = (const char*)pf[i];
        SP.x = x; SP.gate_w = gate_w;
    }
    cudaStream_t s1 = cudaStreamPerThread;
    const bool pdl = true;
    launch_pdl(chain_kernel, 64, 384, C2_SMEM, s1, false, CP);
    launch_pdl(side_kernel, FA_GRID, 384, SD_SMEM, s1, pdl, SP);
}
```

```cpp
#include <cuda_runtime.h>
#include <cuda_bf16.h>
#include <cuda.h>
#include <stdint.h>
#include <type_traits>

constexpr int SEQ = 2048;
constexpr int DM = 512;
constexpr int NH = 32;
constexpr int HD = 128;
constexpr int NQ = NH * HD;
constexpr int SEGL = 32;
constexpr int NMEM = 8;
constexpr int NSEG = SEQ / SEGL;

typedef __nv_bfloat16 bf16;

#define BIG_AL 4096
__device__ __align__(BIG_AL) bf16 g_QA[SEQ * NQ];
__device__ __align__(BIG_AL) bf16 g_KA[SEQ * NQ];
__device__ __align__(BIG_AL) bf16 g_VA[SEQ * NQ];
__device__ __align__(BIG_AL) bf16 g_ctxA[SEQ * NQ];
__device__ __align__(BIG_AL) bf16 g_ctxB[SEQ * NQ];
constexpr int CT_ATTN = 1, CT_FIN = 5;
constexpr int CT_P = 48;
constexpr int CT_AP = 64;
#define O2_HE 24
constexpr int CT_CA = 128;
constexpr int CT_CB = 160;
#define CB_ST 32
#define CB_FIRST 11
constexpr int CT_N = CT_CB + 32 * (CB_ST ? CB_ST : 1);
__device__ __align__(128) unsigned int g_ctr[CT_N];
__device__ float g_gate[SEQ];
__device__ __align__(4096) char g_xbuf[9 * 65536];

#define FA_GRID 68

#define P2_MARK 0
#define TS_MARK(id, tid)
#define TS_MARK2(id, tid)
#define TS_BEGIN(id)
#define TS_END(id)
#define TS_BEGIN_T(id, tid)
#define TS_END_T(id, tid)
__device__ __forceinline__ void pdl_launch_dependents() { asm volatile("griddepcontrol.launch_dependents;" ::: "memory"); }
__device__ __forceinline__ void wait_ctr(int idx, unsigned int n) {
    unsigned int v; int it = 0;
    do { asm volatile("ld.acquire.gpu.global.u32 %0, [%1];" : "=r"(v) : "l"(&g_ctr[idx]) : "memory"); } while (v < n && ++it < (1 << 22));
}
__device__ __forceinline__ void signal_ctr(int idx) {
    asm volatile("fence.proxy.async.global;" ::: "memory");
    asm volatile("red.release.gpu.global.add.u32 [%0], 1;" :: "l"(&g_ctr[idx]) : "memory");
}
__device__ __forceinline__ void signal_ctr_generic(int idx) {
    asm volatile("red.release.gpu.global.add.u32 [%0], 1;" :: "l"(&g_ctr[idx]) : "memory");
}
__device__ __forceinline__ void finish_launch(int lane) {
    unsigned int tk = 0;
    if (lane == 0) tk = atomicAdd(&g_ctr[CT_FIN], 1u);
    tk = __shfl_sync(0xffffffff, tk, 0);
    if (tk == 64 + 68 - 1) {
#pragma unroll 1
        for (int i = lane; i < CT_CB; i += 32) g_ctr[i] = 0u;
        *reinterpret_cast<uint4*>(&g_ctr[CT_CB + lane * CB_ST]) = make_uint4(0u, 0u, 0u, 0u);
    }
}
__device__ __forceinline__ uint4 quad_transpose(uint32_t p0, uint32_t p1, uint32_t p2, uint32_t p3, int lane) {
    const bool o1 = lane & 1, o2 = lane & 2;
    uint32_t s0 = o1 ? p0 : p1, s1 = o1 ? p2 : p3;
    s0 = __shfl_xor_sync(0xffffffff, s0, 1); s1 = __shfl_xor_sync(0xffffffff, s1, 1);
    const uint32_t a_lo = o1 ? s0 : p0, a_hi = o1 ? p1 : s0, b_lo = o1 ? s1 : p2, b_hi = o1 ? p3 : s1;
    uint32_t t0 = o2 ? a_lo : b_lo, t1 = o2 ? a_hi : b_hi;
    t0 = __shfl_xor_sync(0xffffffff, t0, 2); t1 = __shfl_xor_sync(0xffffffff, t1, 2);
    return o2 ? make_uint4(t0, t1, b_lo, b_hi) : make_uint4(a_lo, a_hi, t0, t1);
}
__device__ __forceinline__ uint32_t smem_u32(const void* p) {
    return (uint32_t)__cvta_generic_to_shared(p);
}
__device__ __forceinline__ void mbar_init(uint32_t bar, uint32_t count) {
    asm volatile("mbarrier.init.shared::cta.b64 [%0], %1;" :: "r"(bar), "r"(count));
}
__device__ __forceinline__ void mbar_expect_tx(uint32_t bar, uint32_t bytes) {
    asm volatile("mbarrier.arrive.expect_tx.shared::cta.b64 _, [%0], %1;" :: "r"(bar), "r"(bytes) : "memory");
}
__device__ __forceinline__ void mbar_arrive(uint32_t bar) {
    asm volatile("mbarrier.arrive.shared::cta.b64 _, [%0];" :: "r"(bar) : "memory");
}
__device__ __forceinline__ void mbar_wait(uint32_t bar, uint32_t parity) {
    asm volatile(
        "{\n"
        ".reg .pred p, q;\n"
        ".reg .u32 c;\n"
        "mov.u32 c, 0;\n"
        "WAIT_LOOP:\n"
        "mbarrier.try_wait.parity.shared::cta.b64 p, [%0], %1;\n"
        "@p bra WAIT_DONE;\n"
        "add.u32 c, c, 1;\n"
        "setp.lt.u32 q, c, 4000000;\n"
        "@q bra WAIT_LOOP;\n"
        "WAIT_DONE:\n"
        "}\n" :: "r"(bar), "r"(parity) : "memory");
}
__device__ __forceinline__ void tma_load_2d(uint32_t dst, const CUtensorMap* map, uint32_t bar, int c0, int c1) {
    asm volatile(
        "cp.async.bulk.tensor.2d.shared::cluster.global.mbarrier::complete_tx::bytes [%0], [%1, {%3, %4}], [%2];"
        :: "r"(dst), "l"((uint64_t)map), "r"(bar), "r"(c0), "r"(c1) : "memory");
}
constexpr uint64_t L2_NORMAL = 0x1000000000000000ull, L2_FIRST = 0x12F0000000000000ull;
__device__ __forceinline__ void tma_load_2d(uint32_t dst, const CUtensorMap* map, uint32_t bar, int c0, int c1, uint64_t hint) {
    asm volatile(
        "cp.async.bulk.tensor.2d.shared::cluster.global.mbarrier::complete_tx::bytes.L2::cache_hint [%0], [%1, {%3, %4}], [%2], %5;"
        :: "r"(dst), "l"((uint64_t)map), "r"(bar), "r"(c0), "r"(c1), "l"(hint) : "memory");
}
__device__ __forceinline__ void wgmma_fence() { asm volatile("wgmma.fence.sync.aligned;" ::: "memory"); }
__device__ __forceinline__ void wgmma_commit() { asm volatile("wgmma.commit_group.sync.aligned;" ::: "memory"); }
template <int N> __device__ __forceinline__ void wgmma_wait() {
    asm volatile("wgmma.wait_group.sync.aligned %0;" :: "n"(N) : "memory");
}
__device__ __forceinline__ uint64_t make_desc(uint32_t addr, uint32_t lbo, uint32_t sbo) {
    uint64_t d = 0;
    d |= (uint64_t)((addr & 0x3FFFF) >> 4);
    d |= (uint64_t)((lbo >> 4) & 0x3FFF) << 16;
    d |= (uint64_t)((sbo >> 4) & 0x3FFF) << 32;
    d |= (uint64_t)1 << 62;
    return d;
}

#define ACC64(d) \
    "+f"(d[0]), "+f"(d[1]), "+f"(d[2]), "+f"(d[3]), "+f"(d[4]), "+f"(d[5]), "+f"(d[6]), "+f"(d[7]), \
    "+f"(d[8]), "+f"(d[9]), "+f"(d[10]), "+f"(d[11]), "+f"(d[12]), "+f"(d[13]), "+f"(d[14]), "+f"(d[15]), \
    "+f"(d[16]), "+f"(d[17]), "+f"(d[18]), "+f"(d[19]), "+f"(d[20]), "+f"(d[21]), "+f"(d[22]), "+f"(d[23]), \
    "+f"(d[24]), "+f"(d[25]), "+f"(d[26]), "+f"(d[27]), "+f"(d[28]), "+f"(d[29]), "+f"(d[30]), "+f"(d[31]), \
    "+f"(d[32]), "+f"(d[33]), "+f"(d[34]), "+f"(d[35]), "+f"(d[36]), "+f"(d[37]), "+f"(d[38]), "+f"(d[39]), \
    "+f"(d[40]), "+f"(d[41]), "+f"(d[42]), "+f"(d[43]), "+f"(d[44]), "+f"(d[45]), "+f"(d[46]), "+f"(d[47]), \
    "+f"(d[48]), "+f"(d[49]), "+f"(d[50]), "+f"(d[51]), "+f"(d[52]), "+f"(d[53]), "+f"(d[54]), "+f"(d[55]), \
    "+f"(d[56]), "+f"(d[57]), "+f"(d[58]), "+f"(d[59]), "+f"(d[60]), "+f"(d[61]), "+f"(d[62]), "+f"(d[63])
#define ACC64_STR \
    "{%0, %1, %2, %3, %4, %5, %6, %7, %8, %9, %10, %11, %12, %13, %14, %15, " \
    "%16, %17, %18, %19, %20, %21, %22, %23, %24, %25, %26, %27, %28, %29, %30, %31, " \
    "%32, %33, %34, %35, %36, %37, %38, %39, %40, %41, %42, %43, %44, %45, %46, %47, " \
    "%48, %49, %50, %51, %52, %53, %54, %55, %56, %57, %58, %59, %60, %61, %62, %63}"

template <int TB>
__device__ __forceinline__ void wgmma_ss_n128(float (&d)[64], uint64_t da, uint64_t db, int scale_d) {
    asm volatile(
        "{\n.reg .pred p;\nsetp.ne.b32 p, %66, 0;\n"
        "wgmma.mma_async.sync.aligned.m64n128k16.f32.bf16.bf16 " ACC64_STR ", %64, %65, p, 1, 1, 0, %67;\n}\n"
        : ACC64(d) : "l"(da), "l"(db), "r"(scale_d), "n"(TB));
}
__device__ __forceinline__ uint32_t desc_lo(uint32_t addr, uint32_t lbo) { return ((addr & 0x3FFFF) >> 4) | ((lbo >> 4) << 16); }
template <int TB>
__device__ __forceinline__ void wgmma_ss_n128_lo(float (&d)[64], uint32_t da_lo, uint32_t db_lo, int scale_d) {
    asm volatile(
        "{\n.reg .pred p;\n.reg .b64 da, db;\nsetp.ne.b32 p, %66, 0;\n"
        "mov.b64 da, {%64, 0x40000040};\nmov.b64 db, {%65, 0x40000040};\n"
        "wgmma.mma_async.sync.aligned.m64n128k16.f32.bf16.bf16 " ACC64_STR ", da, db, p, 1, 1, 0, %67;\n}\n"
        : ACC64(d) : "r"(da_lo), "r"(db_lo), "r"(scale_d), "n"(TB));
}
__device__ __forceinline__ void wgmma_rs_n128_tb(float (&d)[64], uint32_t a0, uint32_t a1, uint32_t a2, uint32_t a3,
                                                 uint64_t db, int scale_d) {
    asm volatile(
        "{\n.reg .pred p;\nsetp.ne.b32 p, %69, 0;\n"
        "wgmma.mma_async.sync.aligned.m64n128k16.f32.bf16.bf16 " ACC64_STR ", {%64, %65, %66, %67}, %68, p, 1, 1, 1;\n}\n"
        : ACC64(d) : "r"(a0), "r"(a1), "r"(a2), "r"(a3), "l"(db), "r"(scale_d));
}
__device__ __forceinline__ void wgmma_rs_n80(float (&d)[40], const uint32_t (&a)[4], uint32_t db_lo, int scale_d) {
    asm volatile(
        "{\n.reg .pred p;\n.reg .b64 db;\nsetp.ne.b32 p, %45, 0;\nmov.b64 db, {%44, 0x40000040};\n"
        "wgmma.mma_async.sync.aligned.m64n80k16.f32.bf16.bf16 "
        "{%0, %1, %2, %3, %4, %5, %6, %7, %8, %9, %10, %11, %12, %13, %14, %15, %16, %17, %18, %19, %20, %21, %22, %23, %24, %25, %26, %27, %28, %29, %30, %31, %32, %33, %34, %35, %36, %37, %38, %39}, "
        "{%40, %41, %42, %43}, db, p, 1, 1, 0;\n}\n"
        : "+f"(d[0]), "+f"(d[1]), "+f"(d[2]), "+f"(d[3]), "+f"(d[4]), "+f"(d[5]), "+f"(d[6]), "+f"(d[7]), "+f"(d[8]), "+f"(d[9]), "+f"(d[10]), "+f"(d[11]), "+f"(d[12]), "+f"(d[13]), "+f"(d[14]), "+f"(d[15]), "+f"(d[16]), "+f"(d[17]), "+f"(d[18]), "+f"(d[19]), "+f"(d[20]), "+f"(d[21]), "+f"(d[22]), "+f"(d[23]), "+f"(d[24]), "+f"(d[25]), "+f"(d[26]), "+f"(d[27]), "+f"(d[28]), "+f"(d[29]), "+f"(d[30]), "+f"(d[31]), "+f"(d[32]), "+f"(d[33]), "+f"(d[34]), "+f"(d[35]), "+f"(d[36]), "+f"(d[37]), "+f"(d[38]), "+f"(d[39])
        : "r"(a[0]), "r"(a[1]), "r"(a[2]), "r"(a[3]), "r"(db_lo), "r"(scale_d));
}
__device__ __forceinline__ void wgmma_ss_n256_tb(float (&d)[128], uint32_t da_lo, uint32_t db_lo, int scale_d) {
    asm volatile(
        "{\n.reg .pred p;\n.reg .b64 da, db;\nsetp.ne.b32 p, %130, 0;\nmov.b64 da, {%128, 0x40000040};\nmov.b64 db, {%129, 0x40000040};\n"
        "wgmma.mma_async.sync.aligned.m64n256k16.f32.bf16.bf16 {%0, %1, %2, %3, %4, %5, %6, %7, %8, %9, %10, %11, %12, %13, %14, %15, %16, %17, %18, %19, %20, %21, %22, %23, %24, %25, %26, %27, %28, %29, %30, %31, %32, %33, %34, %35, %36, %37, %38, %39, %40, %41, %42, %43, %44, %45, %46, %47, %48, %49, %50, %51, %52, %53, %54, %55, %56, %57, %58, %59, %60, %61, %62, %63, %64, %65, %66, %67, %68, %69, %70, %71, %72, %73, %74, %75, %76, %77, %78, %79, %80, %81, %82, %83, %84, %85, %86, %87, %88, %89, %90, %91, %92, %93, %94, %95, %96, %97, %98, %99, %100, %101, %102, %103, %104, %105, %106, %107, %108, %109, %110, %111, %112, %113, %114, %115, %116, %117, %118, %119, %120, %121, %122, %123, %124, %125, %126, %127}, da, db, p, 1, 1, 0, 1;\n}\n"
        : "+f"(d[0]), "+f"(d[1]), "+f"(d[2]), "+f"(d[3]), "+f"(d[4]), "+f"(d[5]), "+f"(d[6]), "+f"(d[7]), "+f"(d[8]), "+f"(d[9]), "+f"(d[10]), "+f"(d[11]), "+f"(d[12]), "+f"(d[13]), "+f"(d[14]), "+f"(d[15]), "+f"(d[16]), "+f"(d[17]), "+f"(d[18]), "+f"(d[19]), "+f"(d[20]), "+f"(d[21]), "+f"(d[22]), "+f"(d[23]), "+f"(d[24]), "+f"(d[25]), "+f"(d[26]), "+f"(d[27]), "+f"(d[28]), "+f"(d[29]), "+f"(d[30]), "+f"(d[31]), "+f"(d[32]), "+f"(d[33]), "+f"(d[34]), "+f"(d[35]), "+f"(d[36]), "+f"(d[37]), "+f"(d[38]), "+f"(d[39]), "+f"(d[40]), "+f"(d[41]), "+f"(d[42]), "+f"(d[43]), "+f"(d[44]), "+f"(d[45]), "+f"(d[46]), "+f"(d[47]), "+f"(d[48]), "+f"(d[49]), "+f"(d[50]), "+f"(d[51]), "+f"(d[52]), "+f"(d[53]), "+f"(d[54]), "+f"(d[55]), "+f"(d[56]), "+f"(d[57]), "+f"(d[58]), "+f"(d[59]), "+f"(d[60]), "+f"(d[61]), "+f"(d[62]), "+f"(d[63]), "+f"(d[64]), "+f"(d[65]), "+f"(d[66]), "+f"(d[67]), "+f"(d[68]), "+f"(d[69]), "+f"(d[70]), "+f"(d[71]), "+f"(d[72]), "+f"(d[73]), "+f"(d[74]), "+f"(d[75]), "+f"(d[76]), "+f"(d[77]), "+f"(d[78]), "+f"(d[79]), "+f"(d[80]), "+f"(d[81]), "+f"(d[82]), "+f"(d[83]), "+f"(d[84]), "+f"(d[85]), "+f"(d[86]), "+f"(d[87]), "+f"(d[88]), "+f"(d[89]), "+f"(d[90]), "+f"(d[91]), "+f"(d[92]), "+f"(d[93]), "+f"(d[94]), "+f"(d[95]), "+f"(d[96]), "+f"(d[97]), "+f"(d[98]), "+f"(d[99]), "+f"(d[100]), "+f"(d[101]), "+f"(d[102]), "+f"(d[103]), "+f"(d[104]), "+f"(d[105]), "+f"(d[106]), "+f"(d[107]), "+f"(d[108]), "+f"(d[109]), "+f"(d[110]), "+f"(d[111]), "+f"(d[112]), "+f"(d[113]), "+f"(d[114]), "+f"(d[115]), "+f"(d[116]), "+f"(d[117]), "+f"(d[118]), "+f"(d[119]), "+f"(d[120]), "+f"(d[121]), "+f"(d[122]), "+f"(d[123]), "+f"(d[124]), "+f"(d[125]), "+f"(d[126]), "+f"(d[127])
        : "r"(da_lo), "r"(db_lo), "r"(scale_d));
}
__device__ __forceinline__ void stmatrix_x4(uint32_t addr, uint32_t r0, uint32_t r1, uint32_t r2, uint32_t r3) {
    asm volatile("stmatrix.sync.aligned.m8n8.x4.shared.b16 [%0], {%1, %2, %3, %4};" :: "r"(addr), "r"(r0), "r"(r1), "r"(r2), "r"(r3) : "memory");
}
__device__ __forceinline__ void tma_store_2d(const CUtensorMap* map, uint32_t src, int c0, int c1) {
    asm volatile("cp.async.bulk.tensor.2d.global.shared::cta.bulk_group [%0, {%2, %3}], [%1];"
                 :: "l"((uint64_t)map), "r"(src), "r"(c0), "r"(c1) : "memory");
}
__device__ __forceinline__ float ex2f(float x) { float y; asm("ex2.approx.ftz.f32 %0, %1;" : "=f"(y) : "f"(x)); return y; }
__device__ __forceinline__ uint32_t pack_bf16(float lo, float hi) {
    __nv_bfloat162 v = __floats2bfloat162_rn(lo, hi);
    return *reinterpret_cast<uint32_t*>(&v);
}
__device__ __forceinline__ float bf16r(float x) { return __uint_as_float(pack_bf16(0.f, x) & 0xffff0000u); }
__device__ __forceinline__ void mma_16816(float (&c)[4], uint32_t a0, uint32_t a1, uint32_t a2, uint32_t a3,
                                          uint32_t b0, uint32_t b1) {
    asm volatile(
        "mma.sync.aligned.m16n8k16.row.col.f32.bf16.bf16.f32 {%0,%1,%2,%3}, {%4,%5,%6,%7}, {%8,%9}, {%0,%1,%2,%3};"
        : "+f"(c[0]), "+f"(c[1]), "+f"(c[2]), "+f"(c[3])
        : "r"(a0), "r"(a1), "r"(a2), "r"(a3), "r"(b0), "r"(b1));
}
__device__ __forceinline__ void ldmatrix_x4_trans(uint32_t& r0, uint32_t& r1, uint32_t& r2, uint32_t& r3, uint32_t addr) {
    asm volatile("ldmatrix.sync.aligned.m8n8.x4.trans.shared.b16 {%0,%1,%2,%3}, [%4];"
                 : "=r"(r0), "=r"(r1), "=r"(r2), "=r"(r3) : "r"(addr));
}

constexpr uint32_t FA_Q = 0, FA_KV = 65536, FA_O = 196608, FA_BAR = 229376;
constexpr int FA_ITEMS = 16 * NH;
__device__ __forceinline__ int fa_qt(int t) { return 15 - ((t & 127) >> 3); }
__device__ __forceinline__ int fa_head(int t) { return (t >> 7) * 8 + (t & 7); }
__device__ __forceinline__ uint32_t mbar_test(uint32_t bar, uint32_t parity) {
    uint32_t done;
    asm volatile(
        "{\n.reg .pred p;\n"
        "mbarrier.test_wait.parity.shared::cta.b64 p, [%1], %2;\n"
        "selp.u32 %0, 1, 0, p;\n}\n" : "=r"(done) : "r"(bar), "r"(parity) : "memory");
    return done;
}
__device__ __forceinline__ void mbar_arrive_if(uint32_t bar, bool c) {
    asm volatile("{\n.reg .pred p;\nsetp.ne.u32 p, %1, 0;\n@p mbarrier.arrive.shared::cta.b64 _, [%0];\n}" :: "r"(bar), "r"((uint32_t)c) : "memory");
}
__device__ __forceinline__ uint32_t pin(uint32_t v) { asm volatile("" : "+r"(v)); return v; }
__device__ __forceinline__ void sts128_if(bool c, uint32_t a, uint32_t v0, uint32_t v1, uint32_t v2, uint32_t v3) {
    asm volatile("{\n.reg .pred p;\nsetp.ne.u32 p, %5, 0;\n@p st.shared.v4.b32 [%0], {%1, %2, %3, %4};\n}" :: "r"(a), "r"(v0), "r"(v1), "r"(v2), "r"(v3), "r"((uint32_t)c) : "memory");
}
__device__ __forceinline__ void wgmma_rs_n128_tb_lo(float (&d)[64], const uint32_t* a, uint32_t db_lo, int scale_d) {
    asm volatile(
        "{\n.reg .pred p;\n.reg .b64 db;\nsetp.ne.b32 p, %69, 0;\nmov.b64 db, {%68, 0x40000040};\n"
        "wgmma.mma_async.sync.aligned.m64n128k16.f32.bf16.bf16 " ACC64_STR ", {%64, %65, %66, %67}, db, p, 1, 1, 1;\n}\n"
        : ACC64(d) : "r"(a[0]), "r"(a[1]), "r"(a[2]), "r"(a[3]), "r"(db_lo), "r"(scale_d));
}
#define FA_TEST 48
#define FA_PIN 32

__device__ __forceinline__ void wgmma_ss_n64_lo(float (&d)[64], uint32_t da_lo, uint32_t db_lo, int scale_d) {
    asm volatile(
        "{\n.reg .pred p;\n.reg .b64 da, db;\nsetp.ne.b32 p, %34, 0;\n"
        "mov.b64 da, {%32, 0x40000040};\nmov.b64 db, {%33, 0x40000040};\n"
        "wgmma.mma_async.sync.aligned.m64n64k16.f32.bf16.bf16 {%0, %1, %2, %3, %4, %5, %6, %7, %8, %9, %10, %11, %12, %13, %14, %15, "
        "%16, %17, %18, %19, %20, %21, %22, %23, %24, %25, %26, %27, %28, %29, %30, %31}, da, db, p, 1, 1, 0, 0;\n}\n"
        : "+f"(d[0]), "+f"(d[1]), "+f"(d[2]), "+f"(d[3]), "+f"(d[4]), "+f"(d[5]), "+f"(d[6]), "+f"(d[7]), "+f"(d[8]), "+f"(d[9]), "+f"(d[10]),
          "+f"(d[11]), "+f"(d[12]), "+f"(d[13]), "+f"(d[14]), "+f"(d[15]), "+f"(d[16]), "+f"(d[17]), "+f"(d[18]), "+f"(d[19]), "+f"(d[20]),
          "+f"(d[21]), "+f"(d[22]), "+f"(d[23]), "+f"(d[24]), "+f"(d[25]), "+f"(d[26]), "+f"(d[27]), "+f"(d[28]), "+f"(d[29]), "+f"(d[30]), "+f"(d[31])
        : "r"(da_lo), "r"(db_lo), "r"(scale_d));
}
#define FA_UD 1
#define FA_PP 0
#define FA_NOFB 0
#define FA_DPIN 16
#define FA_RLO 40
#define FA_RHI 232
#define FA_LIM 0x1p40f
__device__ __forceinline__ uint32_t attn_consumer(const uint32_t sb, const int wg, const int w4, const int lane) {
    const uint32_t bar_q = sb + FA_BAR, bar_of = bar_q + 96, bar_oe = bar_q + 112, oslot = bar_q + 144;
    const bool lane0 = lane == 0;
    float o[64], sacc[64];
    uint32_t pa[32];
    float ms0 = 0.f, ms1 = 0.f, lrow0 = 1.f, lrow1 = 1.f;
    const float sc = 0.08838834764831845f * 1.4426950408889634f;
    const uint32_t q_lo = desc_lo(sb + FA_Q + wg * 8192, 16), k_lo = desc_lo(sb + FA_KV, 16), v_lo = desc_lo(sb + FA_KV + 32768, 16384);
    uint32_t qd = q_lo + 2048, kd = k_lo + 4096, vd = v_lo, bs = bar_q + 8, bi = bar_q + 8;
    auto issue_qk = [&](uint32_t a, bool half) {
        const uint32_t b = kd;
#pragma unroll
        for (int i = 0; i < 64; i++) asm volatile("" : "=f"(sacc[i]));
#pragma unroll
        for (int kk = 0; kk < 8; kk++) {
            if (half) wgmma_ss_n64_lo(sacc, a + (kk >> 2) * 1024 + (kk & 3) * 2, b + (kk >> 2) * 1024 + (kk & 3) * 2, kk != 0);
            else wgmma_ss_n128_lo<0>(sacc, a + (kk >> 2) * 1024 + (kk & 3) * 2, b + (kk >> 2) * 1024 + (kk & 3) * 2, kk != 0);
        }
        wgmma_commit();
    };
    auto issue_pv = [&](bool acc) {
        const uint32_t b = vd;
#pragma unroll
        for (int kk = 0; kk < 8; kk++) wgmma_rs_n128_tb_lo(o, &pa[kk * 4], b + kk * 128, kk != 0 || acc);
        wgmma_commit();
    };
    auto turn_wait = [&]() { asm volatile("bar.sync %0, 256;" :: "r"(1 + wg) : "memory"); };
    auto turn_pass = [&]() { asm volatile("bar.arrive %0, 256;" :: "r"(2 - wg) : "memory"); };
    int item = -1, it = -1, j = 0, nkv = 1, t = 0;
    auto redo = [&](float& l0, float& l1) {
        const size_t row0 = (size_t)fa_head(t) * SEQ + (lane >> 2);
        const uint32_t* qg = reinterpret_cast<const uint32_t*>(g_QA + (row0 + (nkv - 1) * 128 + wg * 64 + w4 * 16) * HD) + (lane & 3);
        const uint32_t* kg = reinterpret_cast<const uint32_t*>(g_KA + (row0 + (nkv - 1 - j) * 128) * HD) + (lane & 3);
        auto ldg = [](const uint32_t* p) { uint32_t v; asm volatile("ld.relaxed.gpu.global.u32 %0, [%1];" : "=r"(v) : "l"(p) : "memory"); return v; };
        const int r0 = j ? 1 << 20 : wg * 64 + w4 * 16 + (lane >> 2) - (lane & 3) * 2;
        float mx0 = -INFINITY, mx1 = -INFINITY;
        const float m0 = ms0, m1 = ms1;
        uint4 tmp[8];
        l0 = 0.f; l1 = 0.f;
#pragma unroll 1
        for (int ps = 0; ps < 32; ps++) {
            const int nb = ps & 15;
            float c[4] = {0.f, 0.f, 0.f, 0.f};
#pragma unroll 1
            for (int kk = 0; kk < 64; kk += 8)
                mma_16816(c, ldg(qg + kk), ldg(qg + kk + 8 * 64), ldg(qg + kk + 4), ldg(qg + kk + 8 * 64 + 4), ldg(kg + nb * 8 * 64 + kk), ldg(kg + nb * 8 * 64 + kk + 4));
#pragma unroll
            for (int i = 0; i < 4; i++)
                if (nb * 8 + (i & 1) - ((i & 2) ? 8 : 0) > r0) c[i] = -INFINITY;
            mx0 = fmaxf(mx0, fmaxf(c[0], c[1])); mx1 = fmaxf(mx1, fmaxf(c[2], c[3]));
#pragma unroll
            for (int i = 0; i < 4; i++) c[i] = ex2f(fmaf(c[i], sc, (i & 2) ? ms1 : ms0));
            l0 += c[0] + c[1]; l1 += c[2] + c[3];
            reinterpret_cast<uint2*>(tmp)[nb] = make_uint2(pack_bf16(c[0], c[1]), pack_bf16(c[2], c[3]));
            if (ps == 15) {
                mx0 = fmaxf(mx0, __shfl_xor_sync(0xffffffff, mx0, 1)); mx1 = fmaxf(mx1, __shfl_xor_sync(0xffffffff, mx1, 1));
                mx0 = fmaxf(mx0, __shfl_xor_sync(0xffffffff, mx0, 2)); mx1 = fmaxf(mx1, __shfl_xor_sync(0xffffffff, mx1, 2));
                ms0 = fminf(-mx0 * sc, ms0); ms1 = fminf(-mx1 * sc, ms1);
                l0 = 0.f; l1 = 0.f;
            }
        }
        const float a0 = ex2f(ms0 - m0), a1 = ex2f(ms1 - m1);
        lrow0 *= a0; lrow1 *= a1;
#pragma unroll
        for (int i = 0; i < 64; i++) o[i] *= (i & 2) ? a1 : a0;
#pragma unroll
        for (int i = 0; i < 8; i++) { pa[4 * i] = tmp[i].x; pa[4 * i + 1] = tmp[i].y; pa[4 * i + 2] = tmp[i].z; pa[4 * i + 3] = tmp[i].w; }
    };
    auto pin_after = [&](float v) {
        asm volatile("{\n.reg .pred p;\nsetp.eq.f32 p, %1, %2;\n@p st.shared.f32 [%0], %1;\n}" :: "r"(oslot + 16), "f"(v), "f"(ms0) : "memory");
    };
    auto pack_p = [&](int i) {
        if (i >= FA_PP) pa[i >> 1] = pack_bf16(sacc[i - 1], sacc[i]);
        else asm volatile("{\n.reg .pred p;\nsetp.ne.b32 p, %3, 0x7fc12345;\n@p cvt.rn.bf16x2.f32 %0, %2, %1;\n}" : "+r"(pa[i >> 1]) : "f"(sacc[i - 1]), "f"(sacc[i]), "r"(__float_as_uint(o[0])));
    };
    uint32_t ok = 0, okq = 0;
    int tn = 0;
    auto tests = [&]() {
        ok = mbar_test(bs + 48, (it >> 1) & 1);
        asm volatile("ld.shared.s32 %0, [%1];" : "=r"(tn) : "r"((bi ^ 8) + 128) : "memory");
        ok &= mbar_test((bs ^ 8) + 32, ((it + 1) >> 1) & 1);
        okq = mbar_test(bi ^ 8, ((item + 1) >> 1) & 1);
    };
    auto epilogue = [&](int tag, bool real) {
        float l0 = lrow0, l1 = lrow1;
        l0 += __shfl_xor_sync(0xffffffff, l0, 1); l1 += __shfl_xor_sync(0xffffffff, l1, 1);
        l0 += __shfl_xor_sync(0xffffffff, l0, 2); l1 += __shfl_xor_sync(0xffffffff, l1, 2);
        float i0, i1;
        asm("rcp.approx.ftz.f32 %0, %1;" : "=f"(i0) : "f"(l0));
        asm("rcp.approx.ftz.f32 %0, %1;" : "=f"(i1) : "f"(l1));
        const int row = w4 * 16 + (lane >> 2);
        const uint32_t stg = sb + FA_O + wg * 16384 + row * 128;
#pragma unroll
        for (int i = 0; i < 4; i++) {
            const int ch = i * 4 + (lane & 3);
            const uint32_t a = stg + (ch >> 3) * 8192 + (((ch & 7) ^ (row & 7)) << 4);
            const float* q = &o[i * 16];
            sts128_if(real, a, pack_bf16(q[0] * i0, q[1] * i0), pack_bf16(q[4] * i0, q[5] * i0), pack_bf16(q[8] * i0, q[9] * i0), pack_bf16(q[12] * i0, q[13] * i0));
            sts128_if(real, a + 1024, pack_bf16(q[2] * i1, q[3] * i1), pack_bf16(q[6] * i1, q[7] * i1), pack_bf16(q[10] * i1, q[11] * i1), pack_bf16(q[14] * i1, q[15] * i1));
        }
        asm volatile("st.shared.s32 [%0], %1;" :: "r"(oslot + wg * 4), "r"(tag) : "memory");
        __syncwarp();
        mbar_arrive_if(bar_of + 8 * wg, lane0 && real);
    };
    auto transition = [&](auto wgc, float& l0, float& l1) {
        constexpr int WG = decltype(wgc)::value;
        constexpr int NE = WG == 0 ? 32 : 64;
        turn_wait();
        wgmma_fence();
        issue_qk(qd, WG == 0);
        issue_pv(nkv > 1);
        turn_pass();
        const int tc = t;
        t = __shfl_sync(0xffffffff, tn, 0);
        nkv = fa_qt(t) + 1;
        mbar_wait(bar_oe + 8 * wg, (max(item, 0) & 1) ^ 1);
        item++; bi ^= 8;
        wgmma_wait<1>();
        mbar_arrive_if(bs + 64, lane0);
        mbar_arrive_if(bi + 16, lane0 && nkv == 1);
        ms0 = -sc * __shfl_sync(0xffffffff, sacc[0], lane & 28); ms1 = -sc * __shfl_sync(0xffffffff, sacc[2], lane & 28);
        const int r0 = w4 * 16 + (lane >> 2) - (lane & 3) * 2;
#pragma unroll
        for (int i = 0; i < 32; i++)
            if ((i >> 2) * 8 + (i & 1) - ((i & 2) ? 8 : 0) > r0) sacc[WG * 32 + i] = -INFINITY;
        float sum[4];
#pragma unroll
        for (int i = 0; i < FA_DPIN; i++) { sacc[i] = ex2f(fmaf(sacc[i], sc, (i & 2) ? ms1 : ms0)); sum[i & 3] = i < 4 ? sacc[i] : sum[i & 3] + sacc[i]; }
        pin_after((sum[0] + sum[1]) + (sum[2] + sum[3]));
        wgmma_wait<0>();
        mbar_arrive_if((bs ^ 8) + 80, lane0 && item > 0);
        epilogue(tc, item > 0);
#pragma unroll
        for (int i = 0; i < NE; i++) {
            if (i >= FA_DPIN) { sacc[i] = ex2f(fmaf(sacc[i], sc, (i & 2) ? ms1 : ms0)); sum[i & 3] += sacc[i]; }
            if (i & 1) pack_p(i);
            if (i == NE - 16) { pin_after(sum[0]); tests(); }
        }
        if (NE == 32)
#pragma unroll
            for (int i = 16; i < 32; i++) asm volatile("mov.u32 %0, 0;" : "=r"(pa[i]));
        l0 = sum[0] + sum[1]; l1 = sum[2] + sum[3];
    };
#pragma unroll
    for (int i = 0; i < 32; i++) pa[i] = 0u;
#pragma unroll 1
    for (;;) {
        float l0, l1;
        it++;
        kd = 2 * k_lo + 4096 - kd; vd = 2 * v_lo + 4096 - vd; bs ^= 8;
        if (++j < nkv) {
            if (__builtin_expect(!ok, 0)) {
                mbar_wait(bs + 32, (it >> 1) & 1);
                mbar_wait((bs ^ 8) + 48, ((it - 1) >> 1) & 1);
            }
            turn_wait();
            wgmma_fence();
            issue_qk(qd, false);
            issue_pv(j > 1);
            turn_pass();
            wgmma_wait<1>();
            mbar_arrive_if(bs + 64, lane0);
            mbar_arrive_if(bi + 16, lane0 && j == nkv - 1);
            float sum[4];
#pragma unroll
            for (int i = 0; i < FA_PIN; i++) { sacc[i] = ex2f(fmaf(sacc[i], sc, (i & 2) ? ms1 : ms0)); sum[i & 3] = i < 4 ? sacc[i] : sum[i & 3] + sacc[i]; }
            pin_after((sum[0] + sum[1]) + (sum[2] + sum[3]));
            wgmma_wait<0>();
            mbar_arrive_if((bs ^ 8) + 80, lane0);
#pragma unroll
            for (int i = 0; i < 64; i++) {
                if (i >= FA_PIN) { sacc[i] = ex2f(fmaf(sacc[i], sc, (i & 2) ? ms1 : ms0)); sum[i & 3] = i < 4 ? sacc[i] : sum[i & 3] + sacc[i]; }
                if (i & 1) pack_p(i);
                if (i == FA_TEST) { pin_after(sum[0]); tests(); }
            }
            l0 = sum[0] + sum[1]; l1 = sum[2] + sum[3];
        } else {
            if (__builtin_expect(!(ok & okq), 0)) {
                mbar_wait(bi ^ 8, ((item + 1) >> 1) & 1);
                asm volatile("ld.shared.s32 %0, [%1];" : "=r"(tn) : "r"((bi ^ 8) + 128) : "memory");
                mbar_wait((bs ^ 8) + 48, ((it - 1) >> 1) & 1);
                if (tn < 0) break;
                mbar_wait(bs + 32, (it >> 1) & 1);
            }
            qd = 2 * q_lo + 2048 - qd;
            if (wg == 0) transition(std::integral_constant<int, 0>(), l0, l1); else transition(std::integral_constant<int, 1>(), l0, l1);
            j = 0;
            lrow0 = 0.f; lrow1 = 0.f;
        }
        if (!FA_NOFB && __builtin_expect(__any_sync(0xffffffff, !(l0 + l1 < FA_LIM)), 0)) redo(l0, l1);
        lrow0 += l0; lrow1 += l1;
    }
    wgmma_fence();
    issue_pv(nkv > 1);
    mbar_wait(bar_oe + 8 * wg, (item & 1) ^ 1);
    wgmma_wait<0>();
    mbar_arrive_if((bs ^ 8) + 80, lane0);
    epilogue(t | 0x80000000, true);
    return __shfl_sync(0xffffffff, ~tn * 2 + (item & 1), 0);
}

__device__ __forceinline__ uint32_t cluster_ctarank() {
    uint32_t r; asm volatile("mov.u32 %0, %%cluster_ctarank;" : "=r"(r)); return r;
}
__device__ __forceinline__ uint32_t mapa_u32(uint32_t addr, uint32_t rank) {
    uint32_t r; asm volatile("mapa.shared::cluster.u32 %0, %1, %2;" : "=r"(r) : "r"(addr), "r"(rank)); return r;
}
__device__ __forceinline__ void cluster_sync_all() {
    asm volatile("barrier.cluster.arrive.release.aligned;\nbarrier.cluster.wait.acquire.aligned;" ::: "memory");
}
__device__ __forceinline__ void cluster_sync_relaxed() {
    asm volatile("barrier.cluster.arrive.relaxed.aligned;\nbarrier.cluster.wait.aligned;" ::: "memory");
}
__device__ __forceinline__ void st_async_v4(uint32_t addr, uint32_t a, uint32_t b, uint32_t c, uint32_t d, uint32_t mbar) {
    asm volatile("st.async.weak.shared::cluster.mbarrier::complete_tx::bytes.v4.b32 [%0], {%1, %2, %3, %4}, [%5];"
                 :: "r"(addr), "r"(a), "r"(b), "r"(c), "r"(d), "r"(mbar) : "memory");
}
__device__ __forceinline__ void st_async_v2(uint32_t addr, uint32_t a, uint32_t b, uint32_t mbar) {
    asm volatile("st.async.weak.shared::cluster.mbarrier::complete_tx::bytes.v2.b32 [%0], {%1, %2}, [%3];"
                 :: "r"(addr), "r"(a), "r"(b), "r"(mbar) : "memory");
}
__device__ __forceinline__ void st_async_b32(uint32_t addr, uint32_t a, uint32_t mbar) {
    asm volatile("st.async.weak.shared::cluster.mbarrier::complete_tx::bytes.b32 [%0], %1, [%2];" :: "r"(addr), "r"(a), "r"(mbar) : "memory");
}
__device__ __forceinline__ void pace(int cycles) {
    if (cycles > 0) {
        uint32_t t0, t;
        asm volatile("mov.u32 %0, %%clock;" : "=r"(t0));
        do { asm volatile("mov.u32 %0, %%clock;" : "=r"(t)); } while (t - t0 < (uint32_t)cycles);
    }
}
__device__ __forceinline__ void mbar_wait_cl(uint32_t bar, uint32_t parity) {
    uint32_t done = 0;
    for (int it = 0; it < (1 << 22) && !done; it++) {
        asm volatile(
            "{\n.reg .pred p;\n"
            "mbarrier.try_wait.parity.shared::cta.b64 p, [%1], %2;\n"
            "selp.u32 %0, 1, 0, p;\n}\n" : "=r"(done) : "r"(bar), "r"(parity) : "memory");
    }
}
__device__ __forceinline__ void ldmatrix_x4(uint32_t& r0, uint32_t& r1, uint32_t& r2, uint32_t& r3, uint32_t addr) {
    asm volatile("ldmatrix.sync.aligned.m8n8.x4.shared.b16 {%0,%1,%2,%3}, [%4];"
                 : "=r"(r0), "=r"(r1), "=r"(r2), "=r"(r3) : "r"(addr));
}
__device__ __forceinline__ void cp_async16(uint32_t dst, const void* src) {
    asm volatile("cp.async.cg.shared.global [%0], [%1], 16;" :: "r"(dst), "l"(src) : "memory");
}

#define DBG(i)
#define DBGW(i, w)
#define CYC(i)
#define PM(i)
#define TM(i)
__device__ __forceinline__ void tma_load_2d_mc(uint32_t dst, const CUtensorMap* map, uint32_t bar, int c0, int c1, uint16_t mask) {
    asm volatile(
        "cp.async.bulk.tensor.2d.shared::cluster.global.mbarrier::complete_tx::bytes.multicast::cluster [%0], [%1, {%3, %4}], [%2], %5;"
        :: "r"(dst), "l"((uint64_t)map), "r"(bar), "r"(c0), "r"(c1), "h"(mask) : "memory");
}
__device__ __forceinline__ void tma_load_2d_mc(uint32_t dst, const CUtensorMap* map, uint32_t bar, int c0, int c1, uint16_t mask, uint64_t hint) {
    asm volatile(
        "cp.async.bulk.tensor.2d.shared::cluster.global.mbarrier::complete_tx::bytes.multicast::cluster.L2::cache_hint [%0], [%1, {%3, %4}], [%2], %5, %6;"
        :: "r"(dst), "l"((uint64_t)map), "r"(bar), "r"(c0), "r"(c1), "h"(mask), "l"(hint) : "memory");
}
__device__ __forceinline__ void bulk_s2s(uint32_t dst_cl, uint32_t src, uint32_t bytes, uint32_t bar_cl) {
    asm volatile("cp.async.bulk.shared::cluster.shared::cta.mbarrier::complete_tx::bytes [%0], [%1], %2, [%3];"
                 :: "r"(dst_cl), "r"(src), "r"(bytes), "r"(bar_cl) : "memory");
}
__device__ __forceinline__ bool elect_one() {
    uint32_t p;
    asm volatile("{\n.reg .pred p;\nelect.sync _|p, 0xffffffff;\nselp.u32 %0, 1, 0, p;\n}" : "=r"(p));
    return p;
}
__device__ __forceinline__ void fence_async_smem() { asm volatile("fence.proxy.async.shared::cta;" ::: "memory"); }
template <int ID, int N> __device__ __forceinline__ void bar_sync() { asm volatile("bar.sync %0, %1;" :: "n"(ID), "n"(N) : "memory"); }
template <int ID, int N> __device__ __forceinline__ void bar_arrive() { asm volatile("bar.arrive %0, %1;" :: "n"(ID), "n"(N) : "memory"); }
__device__ __forceinline__ void sts32(uint32_t a, uint32_t v) { asm volatile("st.shared.u32 [%0], %1;" :: "r"(a), "r"(v) : "memory"); }
__device__ __forceinline__ void ldsm_x4(uint32_t* r, uint32_t addr) {
    asm volatile("ldmatrix.sync.aligned.m8n8.x4.shared.b16 {%0,%1,%2,%3}, [%4];" : "=r"(r[0]), "=r"(r[1]), "=r"(r[2]), "=r"(r[3]) : "r"(addr) : "memory");
}
constexpr uint32_t DHI128 = 0x40000040u, DHI32 = 0xC0000010u;
#define ACC16(d) "+f"(d[0]), "+f"(d[1]), "+f"(d[2]), "+f"(d[3]), "+f"(d[4]), "+f"(d[5]), "+f"(d[6]), "+f"(d[7]), "+f"(d[8]), "+f"(d[9]), "+f"(d[10]), \
    "+f"(d[11]), "+f"(d[12]), "+f"(d[13]), "+f"(d[14]), "+f"(d[15])
#define ACC20(d) ACC16(d), "+f"(d[16]), "+f"(d[17]), "+f"(d[18]), "+f"(d[19])
__device__ __forceinline__ void wgmma_rs(float (&d)[16], const uint32_t (&a)[4], uint32_t db_lo) {
    asm volatile(
        "{\n.reg .b64 db;\nmov.b64 db, {%20, %21};\n"
        "wgmma.mma_async.sync.aligned.m64n32k16.f32.bf16.bf16 {%0,%1,%2,%3,%4,%5,%6,%7,%8,%9,%10,%11,%12,%13,%14,%15}, {%16,%17,%18,%19}, db, 1, 1, 1, 0;\n}\n"
        : ACC16(d) : "r"(a[0]), "r"(a[1]), "r"(a[2]), "r"(a[3]), "r"(db_lo), "n"(DHI128));
}
__device__ __forceinline__ void wgmma_rs(float (&d)[20], const uint32_t (&a)[4], uint32_t db_lo) {
    asm volatile(
        "{\n.reg .b64 db;\nmov.b64 db, {%24, %25};\n"
        "wgmma.mma_async.sync.aligned.m64n40k16.f32.bf16.bf16 {%0,%1,%2,%3,%4,%5,%6,%7,%8,%9,%10,%11,%12,%13,%14,%15,%16,%17,%18,%19}, {%20,%21,%22,%23}, db, 1, 1, 1, 0;\n}\n"
        : ACC20(d) : "r"(a[0]), "r"(a[1]), "r"(a[2]), "r"(a[3]), "r"(db_lo), "n"(DHI128));
}
template <uint32_t AHI, uint32_t BHI>
__device__ __forceinline__ void wgmma_ss(float (&d)[16], uint32_t da_lo, uint32_t db_lo) {
    asm volatile(
        "{\n.reg .b64 da, db;\nmov.b64 da, {%16, %18};\nmov.b64 db, {%17, %19};\n"
        "wgmma.mma_async.sync.aligned.m64n32k16.f32.bf16.bf16 {%0,%1,%2,%3,%4,%5,%6,%7,%8,%9,%10,%11,%12,%13,%14,%15}, da, db, 1, 1, 1, 0, 0;\n}\n"
        : ACC16(d) : "r"(da_lo), "r"(db_lo), "n"(AHI), "n"(BHI));
}
template <uint32_t AHI, uint32_t BHI>
__device__ __forceinline__ void wgmma_ss(float (&d)[20], uint32_t da_lo, uint32_t db_lo) {
    asm volatile(
        "{\n.reg .b64 da, db;\nmov.b64 da, {%20, %22};\nmov.b64 db, {%21, %23};\n"
        "wgmma.mma_async.sync.aligned.m64n40k16.f32.bf16.bf16 {%0,%1,%2,%3,%4,%5,%6,%7,%8,%9,%10,%11,%12,%13,%14,%15,%16,%17,%18,%19}, da, db, 1, 1, 1, 0, 0;\n}\n"
        : ACC20(d) : "r"(da_lo), "r"(db_lo), "n"(AHI), "n"(BHI));
}
template <uint32_t AHI, uint32_t BHI>
__device__ __forceinline__ void wgmma_ss0(float (&d)[20], uint32_t da_lo, uint32_t db_lo) {
    asm volatile(
        "{\n.reg .b64 da, db;\nmov.b64 da, {%20, %22};\nmov.b64 db, {%21, %23};\n"
        "wgmma.mma_async.sync.aligned.m64n40k16.f32.bf16.bf16 {%0,%1,%2,%3,%4,%5,%6,%7,%8,%9,%10,%11,%12,%13,%14,%15,%16,%17,%18,%19}, da, db, 0, 1, 1, 0, 0;\n}\n"
        : "=f"(d[0]), "=f"(d[1]), "=f"(d[2]), "=f"(d[3]), "=f"(d[4]), "=f"(d[5]), "=f"(d[6]), "=f"(d[7]), "=f"(d[8]), "=f"(d[9]), "=f"(d[10]),
          "=f"(d[11]), "=f"(d[12]), "=f"(d[13]), "=f"(d[14]), "=f"(d[15]), "=f"(d[16]), "=f"(d[17]), "=f"(d[18]), "=f"(d[19])
        : "r"(da_lo), "r"(db_lo), "n"(AHI), "n"(BHI));
}
__device__ __forceinline__ void wgmma_ss_n8(float (&d)[4], uint32_t da_lo, uint32_t db_lo) {
    asm volatile(
        "{\n.reg .b64 da, db;\nmov.b64 da, {%4, %6};\nmov.b64 db, {%5, %7};\n"
        "wgmma.mma_async.sync.aligned.m64n8k16.f32.bf16.bf16 {%0,%1,%2,%3}, da, db, 1, 1, 1, 1, 0;\n}\n"
        : "+f"(d[0]), "+f"(d[1]), "+f"(d[2]), "+f"(d[3]) : "r"(da_lo), "r"(db_lo), "n"(DHI128), "n"(DHI32));
}

__device__ __forceinline__ void wgmma_ss_n32_ta(float (&d)[16], uint32_t da_lo, uint32_t db_lo) {
    asm volatile(
        "{\n.reg .b64 da, db;\nmov.b64 da, {%16, %18};\nmov.b64 db, {%17, %18};\n"
        "wgmma.mma_async.sync.aligned.m64n32k16.f32.bf16.bf16 {%0,%1,%2,%3,%4,%5,%6,%7,%8,%9,%10,%11,%12,%13,%14,%15}, da, db, 1, 1, 1, 1, 0;\n}\n"
        : ACC16(d) : "r"(da_lo), "r"(db_lo), "n"(DHI128));
}

constexpr int C2_NS = 4;
#define LAY         160, 127, 0, 16, 24, 8, 47, 87, 150, 135, 147, 32, 159, 0, 87, 119
constexpr uint32_t c2_lay(int i) { constexpr uint32_t t[16] = {LAY}; return t[i] * 1024; }
constexpr uint32_t C2_WO = c2_lay(0);
constexpr uint32_t C2_WQ = c2_lay(1), C2_WK = c2_lay(2), C2_WV = c2_lay(3);
constexpr uint32_t C2_OB = c2_lay(4);
constexpr uint32_t C2_QM = c2_lay(5);
constexpr uint32_t C2_SC = C2_QM + 1024;
constexpr uint32_t C2_PB = c2_lay(12) + 320;
#define CH_CS (C2_QM + 4096)
constexpr uint32_t C2_CS = CH_CS;
constexpr uint32_t C2_XB = c2_lay(6), C2_XS = c2_lay(7) - c2_lay(6);
constexpr uint32_t C2_QX = c2_lay(8);
constexpr uint32_t C2_KX = C2_QX + 4096;
constexpr uint32_t C2_VT = c2_lay(9);
constexpr uint32_t C2_PX = c2_lay(10);
constexpr uint32_t C2_SX = c2_lay(11);
constexpr uint32_t C2_BAR = c2_lay(12), C2_S0 = c2_lay(13), C2_S1 = c2_lay(14), C2_S2 = c2_lay(15);
constexpr uint32_t C2_GT = C2_BAR + 320;
constexpr uint32_t C2_T0 = (C2_XB >> 10) * 0x01010101u + 0x18100800u, C2_T1 = ((C2_XB >> 10) + 32) | C2_OB >> 10 << 8 | C2_QM >> 10 << 16 | C2_WQ >> 10 << 24;
__device__ __forceinline__ uint32_t c2_ts(uint32_t r) { return __byte_perm(C2_T0, C2_T1, r) & 0xff; }
constexpr int C2_SMEM = 232448;
#define CH_SPQ 28
#define CH_SPK 0
#define CH_SPV 0
#define CH_EARLY 1
#define CH_ARM 0
#define CH_MB 1
#define CH_TW 1
#define CH_LD 0
#define CH_PT 6000
#define CH_PI 3
#define CH_PF2 0
#define CH_EFW 0
#define CH_TS 1
#define CH_WL 2
#define CH_WU 2
#define CH_PS 0
#define CH_PSZ 16384
#define CH_PSI 0
#define CH_WR 5
#define CH_WOT 1
#define CH_NCH 4
#define CH_NQ1 12
#define CH_WS 2
#define CH_PRN 4
#define CH_PRM 0
#define CH_POLL_DELAY 500

__device__ __forceinline__ uint32_t c2_stage(int wg, int i) { return (wg == 0 ? C2_S0 : wg == 1 ? C2_S1 : C2_S2) + i * 8192; }
__device__ __forceinline__ void c2_stage_load(const CUtensorMap* map, uint32_t sb, int wg, int rank, int col0, int i) {
    const uint32_t bar = sb + C2_BAR + 176 + (wg * 4 + (i & 3)) * 8;
    mbar_expect_tx(bar, 8192);
    tma_load_2d(sb + c2_stage(wg, i & 3), map, bar, col0, ((rank - i) & 7) * 64);
}
__device__ __forceinline__ uint32_t lds32(uint32_t a) { uint32_t v; asm volatile("ld.shared.b32 %0, [%1];" : "=r"(v) : "r"(a) : "memory"); return v; }
__device__ __forceinline__ void c2_wo(uint32_t sb, int t, int n) {
    mbar_wait(sb + C2_BAR + 168, 0);
    constexpr int U = CH_WU;
#pragma unroll U
    for (int i = t; i < 2048; i += n) {
        const int k = i >> 2, b = i & 3;
        const uint32_t a0 = sb + C2_WO + k * 128 + (((2 * b) ^ (k & 7)) << 4), a1 = a0 ^ 16;
        uint4 u, v;
        asm volatile("ld.shared.v4.b32 {%0, %1, %2, %3}, [%4];" : "=r"(u.x), "=r"(u.y), "=r"(u.z), "=r"(u.w) : "r"(a0) : "memory");
        asm volatile("ld.shared.v4.b32 {%0, %1, %2, %3}, [%4];" : "=r"(v.x), "=r"(v.y), "=r"(v.z), "=r"(v.w) : "r"(a1) : "memory");
        asm volatile("st.shared.v4.b32 [%0], {%1, %2, %3, %4};" :: "r"(a0), "r"(__byte_perm(u.x, u.y, 0x5410)),
                     "r"(__byte_perm(u.z, u.w, 0x5410)), "r"(__byte_perm(v.x, v.y, 0x5410)), "r"(__byte_perm(v.z, v.w, 0x5410)) : "memory");
        asm volatile("st.shared.v4.b32 [%0], {%1, %2, %3, %4};" :: "r"(a1), "r"(__byte_perm(u.x, u.y, 0x7632)),
                     "r"(__byte_perm(u.z, u.w, 0x7632)), "r"(__byte_perm(v.x, v.y, 0x7632)), "r"(__byte_perm(v.z, v.w, 0x7632)) : "memory");
    }
}
__device__ __forceinline__ void c2_load_w(uint32_t (&w)[32][4], const CUtensorMap* map, const CUtensorMap* mapWo, int wg, int rank, int col0, uint32_t t128, uint32_t ws, uint32_t sb) {
    const uint32_t s0 = pin(sb + c2_stage(wg, 0) + t128), s1 = pin(sb + c2_stage(wg, 0) + (t128 ^ 16) + 128);
#pragma unroll
    for (int r = 0; r < 8; r++) {
        mbar_wait(sb + C2_BAR + 176 + (wg * 4 + (r & 3)) * 8, r >> 2);
        if (r == 0) PM(2);
        if (r == 3) PM(3);
        if (r == 7) PM(4);
#pragma unroll
        for (int e = (r & 3) * 4; e < (r & 3) * 4 + 4; e++) {
            uint32_t w0, w1, w2, w3;
            asm volatile("ld.shared.b32 %0, [%1];" : "=r"(w0) : "r"(s0 + e * 2048) : "memory");
            asm volatile("ld.shared.b32 %0, [%1];" : "=r"(w1) : "r"(s1 + e * 2048) : "memory");
            asm volatile("ld.shared.b32 %0, [%1];" : "=r"(w2) : "r"(s0 + e * 2048 + 1024) : "memory");
            asm volatile("ld.shared.b32 %0, [%1];" : "=r"(w3) : "r"(s1 + e * 2048 + 1024) : "memory");
            uint32_t* d = w[(r >> 2) * 16 + e];
            d[0] = __byte_perm(w0, w1, 0x5410); d[1] = __byte_perm(w0, w1, 0x7632);
            d[2] = __byte_perm(w2, w3, 0x5410); d[3] = __byte_perm(w2, w3, 0x7632);
        }
        if (r < 4) asm volatile("bar.sync %0, 128;" :: "r"(8 + wg) : "memory");
        if ((threadIdx.x & 96) == 32 && elect_one()) {
            if (r < 4) c2_stage_load(map, sb, wg, rank, col0, r + 4);
            const int j = wg + (r - CH_WR) * 3;
            if (r >= CH_WR && j < 8) tma_load_2d(sb + C2_WO + j * 8192, mapWo, sb + C2_BAR + 168, rank * 64, (blockIdx.x >> 3) * 512 + ((rank - j) & 7) * 64);
        }
    }
    PM(5);
    cluster_sync_relaxed();
    PM(6);
#pragma unroll
    for (int e = 0; e < C2_NS; e++) stmatrix_x4(ws + e * 2048, w[e][0], w[e][1], w[e][2], w[e][3]);
#pragma unroll 1
    for (int i = threadIdx.x; i < 2 * 512 + 256; i += 384)
        sts32(sb + (i < 1024 ? C2_VT + (i >> 9) * 6144 + 4096 + (i & 511) * 4 : C2_PX + 2048 + (i - 1024) * 4), 0u);
    fence_async_smem();
    asm volatile("bar.sync %0, 128;" :: "r"(8 + wg) : "memory");
}
template <int E0, int E1, int SP, int NA>
__device__ __forceinline__ void c2_xstream(float (&acc)[NA], const uint32_t (&w)[32][4], uint32_t xlo, uint32_t rank, uint32_t wslo) {
    if (E0 == 0)
#pragma unroll
        for (int i = 0; i < NA; i++) acc[i] = 0.f;
    wgmma_fence();
#pragma unroll
    for (int n = E0; n < E1; n++) {
        const int e = n < SP ? n + C2_NS : n < SP + C2_NS ? n - SP : n;
        if (e < C2_NS) wgmma_ss<DHI32, DHI128>(acc, wslo + e * 128, xlo + ((rank - (e >> 2)) & 7) * 320 + (e & 3) * 2);
        else wgmma_rs(acc, w[e], xlo + ((rank - (e >> 2)) & 7) * 320 + (e & 3) * 2);
    }
    wgmma_commit();
}
__device__ __forceinline__ constexpr int c2_grp(int i) { return i < 2 ? i : 1 + (i >> 1); }

struct ChainParams {
    CUtensorMap mapX;
    CUtensorMap mapM;
    CUtensorMap mapW[3];
    CUtensorMap mapWo;
    CUtensorMap mapC;
    CUtensorMap mapS;
    bf16* out;
    char* xb;
};
__global__ void __cluster_dims__(8, 1, 1) __launch_bounds__(384, 1)
chain_kernel(const __grid_constant__ ChainParams P) {
    const CUtensorMap& mapX = P.mapX;
    extern __shared__ __align__(1024) uint8_t smem_chain[];
    const uint32_t sb = smem_u32(smem_chain);
    const uint32_t dlo = ((sb & 0x3FFFF) >> 4) | (1u << 16);
    const int tid = __shfl_sync(0xffffffff, threadIdx.x, threadIdx.x & 31), lane = tid & 31;
    const int warp = __shfl_sync(0xffffffff, tid >> 5, 0), wg = warp >> 2, w4 = warp & 3;
    const uint32_t rank = cluster_ctarank();
    const int C = blockIdx.x >> 3;
    const int h = C * 4 + (rank >> 1);
    const int g = lane >> 2, qc = lane & 3;
    pdl_launch_dependents();
    TS_BEGIN(2);
    CYC(0);
    PM(0);
    const uint32_t bar_m = sb + C2_BAR, bar_o = bar_m + 64, bar_sc = bar_m + 128, bar_x = bar_m + 136, bar_sx = bar_m + 152;
    const uint32_t bar_w = bar_m + 168, bar_h = bar_m + 40;
    const int col0 = h * HD + (rank & 1) * 64;
    if (lane < 3) {
        const uint32_t n = lane * 12 + warp;
        if (n < 34) mbar_init(bar_m + 8 * n, n == 5 ? 32 : (n & ~8) == 0 ? 4 : 1);
        else sts32(bar_m + 280 + (n & 1) * 4, ~0u);
        asm volatile("fence.mbarrier_init.release.cluster;" ::: "memory");
    }
    __syncwarp();
    cluster_sync_relaxed();
    PM(1);
    if (tid == 0) {
        mbar_expect_tx(bar_x, 32768 + 8192);
        tma_load_2d_mc(sb + C2_XB + rank * 5120, &mapX, bar_x, rank * 64, 0, (uint16_t)0xff);
#pragma unroll 1
        for (int j = 0; j < 8; j++) tma_load_2d(sb + C2_XB + j * 5120 + 4096, &P.mapM, bar_x, j * 64, 0);
        mbar_expect_tx(bar_w, 65536);
    }
    if ((tid & 127) == 32) {
#pragma unroll 1
        for (int i = 0; i < 4; i++) {
            c2_stage_load(&P.mapW[wg], sb, wg, rank, col0, i);
            if (i == CH_PI) pace(CH_PT);
        }
    }
    __syncwarp();

    const uint32_t t32 = w4 * 256 + qc * 64 + (((g >> 2) ^ (qc >> 1)) << 4) + (g & 3) * 4;
    const uint32_t t128 = qc * 256 + (((2 * w4 + (g >> 2)) ^ (2 * qc)) << 4) + (g & 3) * 4;
    const uint32_t a32 = (w4 * 16 + (lane & 15)) * 32 + (((lane >> 4) ^ ((lane >> 2) & 1)) << 4);
    const uint32_t ws = sb + (wg == 0 ? C2_WQ : wg == 1 ? C2_WK : C2_WV) + a32;
    uint32_t w[32][4];
    static_assert(C2_NS == 4, "slot 0");
    auto proj_mem = [&](float (&a)[CH_NCH][4], int s, uint32_t l128) {
        uint32_t b[4][8];
#pragma unroll
        for (int i = 0; i < 4 * CH_NCH; i++) a[i >> 2][i & 3] = 0.f;
        const uint32_t par = (s & 1) ^ 1;
        const uint32_t mb = sb + C2_XB + (s & 1) * C2_XS + 4096;
        auto L = [&](int i) {
            ldsm_x4(b[i & 3], mb + ((rank - i) & 7) * 5120 + l128);
            ldsm_x4(b[i & 3] + 4, mb + ((rank - i) & 7) * 5120 + (l128 ^ 64));
        };
        auto H = [&](int i) {
#pragma unroll
            for (int kk = 0; kk < 4; kk++) {
                const uint32_t* f = i ? w[i * 4 + kk] : &b[2 + (kk >> 1)][(kk & 1) * 4];
                mma_16816(a[(i * 4 + kk) % CH_NCH], f[0], f[1], f[2], f[3], b[i & 3][2 * kk], b[i & 3][2 * kk + 1]);
            }
        };
#pragma unroll
        for (int e = 0; e < 4; e++) ldsm_x4(&b[2 + (e >> 1)][(e & 1) * 4], ws + e * 2048);
        mbar_wait(bar_m, par);
        L(0);
        H(0);
        mbar_wait(bar_m + 8, par);
        DBGW(1 + 16 * wg, 0);
        L(1);
        mbar_wait(bar_m + 16, par);
        uint32_t nxt = mbar_test(bar_m + 24, par);
        L(2); L(3);
        H(1);
        if (__builtin_expect(!nxt, 0)) mbar_wait(bar_m + 24, par);
        nxt = mbar_test(bar_m + 32, par);
        L(4); L(5);
        H(2); H(3);
        if (__builtin_expect(!nxt, 0)) mbar_wait(bar_m + 32, par);
        DBGW(2 + 16 * wg, 0);
        L(6); L(7);
        H(4); H(5); H(6); H(7);
#pragma unroll
        for (int i = 0; i < 4; i++) a[0][i] = CH_NCH == 4 ? (a[0][i] + a[1][i]) + (a[2][i] + a[3 % CH_NCH][i]) : CH_NCH == 3 ? a[0][i] + a[1][i] + a[2 % CH_NCH][i] : a[0][i] + a[1][i];
    };
    auto store_x = [&](const float (&acc)[16], uint32_t base) {
#pragma unroll
        for (int j = 0; j < 4; j++) {
            sts32(base + t128 + j * 1024, pack_bf16(acc[4 * j], acc[4 * j + 2]));
            sts32(base + (t128 ^ 16) + 128 + j * 1024, pack_bf16(acc[4 * j + 1], acc[4 * j + 3]));
        }
    };
    auto fresh_lane = [&]() { uint32_t l; asm volatile("mov.u32 %0, %%laneid;" : "=r"(l)); return l; };
    const float scale = 0.08838834764831845f, l2e = 1.4426950408889634f;
    if (CH_WS == 2 && wg == 2) *reinterpret_cast<uint32_t*>(P.xb + (rank * 65536 + (C * 4 + w4) * 128 + (w4 & 1) * 20480 + lane * 4)) = 0u;
    c2_load_w(w, &P.mapW[wg], &P.mapWo, wg, rank, col0, t128, ws, sb);
    TS_END(6);
    TS_BEGIN(5);
    CYC(1);
    PM(7);

    if (wg == 0) {
#pragma unroll 1
        for (int s = -1;;) {
            float qx[16];
            uint32_t* dst = reinterpret_cast<uint32_t*>(P.xb + ((s & 1) * 32768 + rank * 65536 + 4096 + C * 1024 + (qc * 64 + w4 * 8 + g) * 4));
            asm volatile("" : "+l"(dst));
            mbar_wait(bar_x + 8 * ((s + 1) & 1), ((s + 1) >> 1) & 1);
            if (s >= 0) bar_sync<6, 384>();
            c2_xstream<0, CH_NQ1, CH_SPQ>(qx, w, dlo + ((C2_XB + ((s + 1) & 1) * C2_XS) >> 4), rank, dlo + (C2_WQ >> 4));
            if (s >= 0) {
                float acc[4] = {0.f, 0.f, 0.f, 0.f};
                const uint32_t tag = ((s >> 1) & 1) ^ 1;
                uint32_t nxt = 0;
#pragma unroll
                for (int i = 0; i < 8; i++) {
                    if (i < 2 || !(i & 1)) {
                        if (i < 2 || __builtin_expect(!nxt, 0)) mbar_wait(bar_o + 8 * c2_grp(i), s & 1);
                        if (i == 0) DBGW(7, 0);
                        if (i == 1) DBGW(8, 0);
                        if (i == 6) DBGW(9, 0);
                        wgmma_fence();
                    }
#pragma unroll
                    for (int kk = 0; kk < 4; kk++) {
                        if ((i & 1) && i < 7 && kk == CH_WOT) nxt = mbar_test(bar_o + 8 * c2_grp(i + 1), s & 1);
                        wgmma_ss_n8(acc, dlo + ((C2_WO + i * 8192 + kk * 2048) >> 4), dlo + ((C2_OB + i * 1024 + kk * 256) >> 4));
                    }
                }
                wgmma_commit();
                bar_arrive<11, 256>();
                wgmma_wait<0>();
                asm volatile("st.relaxed.gpu.global.u32 [%0], %1;" :: "l"(dst), "r"((pack_bf16(acc[0], acc[2]) & ~1u) | tag) : "memory");
                asm volatile("st.relaxed.gpu.global.u32 [%0 + 128], %1;" :: "l"(dst), "r"((pack_bf16(acc[1], acc[3]) & ~1u) | tag) : "memory");
                asm volatile("st.relaxed.gpu.global.u32 [%0 + 8192], %1;" :: "l"(dst), "r"((pack_bf16(acc[0], acc[2]) & ~1u) | tag) : "memory");
                asm volatile("st.relaxed.gpu.global.u32 [%0 + 8320], %1;" :: "l"(dst), "r"((pack_bf16(acc[1], acc[3]) & ~1u) | tag) : "memory");
                bar_arrive<4, 256>();
                DBGW(10, 0);
            }
            s++;
            c2_xstream<CH_NQ1, 32, CH_SPQ>(qx, w, dlo + ((C2_XB + (s & 1) * C2_XS) >> 4), rank, dlo + (C2_WQ >> 4));
            const uint32_t sca = pin(w4 < 2 ? sb + C2_SC + w4 * 512 + lane * 16 : sb + C2_SC + 1024 + lane * 8);
            const uint32_t krow = w4 * 16 + (lane & 15);
            const uint32_t ka0 = pin(sb + C2_KX + krow * 128 + (((lane >> 4) ^ (krow & 7)) << 4));
            const uint32_t l32 = pin(sb + C2_QM + (lane >> 4) * 256 + (lane & 7) * 32 + ((((lane >> 3) & 1) ^ ((lane >> 2) & 1)) << 4));
            const uint32_t qst = pin(sb + C2_QM + t32);
            const uint32_t l128 = pin((lane & 7) * 128 + (((lane >> 3) ^ (lane & 7)) << 4));
            if (s > 0) bar_sync<5, 256>();
            wgmma_wait<0>();
            store_x(qx, sb + C2_QX);
            DBGW(0, 0);
            if (s == NSEG - 1) break;
            {
                float a[CH_NCH][4];
                proj_mem(a, s, l128);
                sts32(qst, pack_bf16(a[0][0], a[0][2]));
                sts32(qst + 32, pack_bf16(a[0][1], a[0][3]));
            }
            DBGW(3, 0);
            if (w4 < 3) {
                uint32_t ka[4][4], qb[8];
                float c[4] = {0.f, 0.f, 0.f, 0.f}, c2[4] = {0.f, 0.f, 0.f, 0.f};
                const uint32_t sc_peer = pin(mapa_u32(sca + 1280, rank ^ 1)), sc_own = pin(mapa_u32(sca, rank));
                bar_sync<1, 384>();
                ldsm_x4(qb, l32);
                ldsm_x4(ka[0], ka0);
                ldsm_x4(ka[1], ka0 ^ 32);
                ldsm_x4(qb + 4, l32 + 512);
                ldsm_x4(ka[2], ka0 ^ 64);
                ldsm_x4(ka[3], ka0 ^ 96);
                mma_16816(c, ka[0][0], ka[0][1], ka[0][2], ka[0][3], qb[0], qb[1]);
                mma_16816(c2, ka[1][0], ka[1][1], ka[1][2], ka[1][3], qb[2], qb[3]);
                mma_16816(c, ka[2][0], ka[2][1], ka[2][2], ka[2][3], qb[4], qb[5]);
                mma_16816(c2, ka[3][0], ka[3][1], ka[3][2], ka[3][3], qb[6], qb[7]);
                const uint32_t u0 = __float_as_uint(c[0] + c2[0]), u1 = __float_as_uint(c[1] + c2[1]);
                const uint32_t u2 = __float_as_uint(c[2] + c2[2]), u3 = __float_as_uint(c[3] + c2[3]);
                asm volatile(
                    "{\n.reg .pred p;\nsetp.lt.u32 p, %8, 2;\n"
                    "@p st.async.weak.shared::cluster.mbarrier::complete_tx::bytes.v4.b32 [%0], {%4, %5, %6, %7}, [%1];\n"
                    "@!p st.async.weak.shared::cluster.mbarrier::complete_tx::bytes.v2.b32 [%0], {%4, %5}, [%1];\n"
                    "@p st.async.weak.shared::cluster.mbarrier::complete_tx::bytes.v4.b32 [%2], {%4, %5, %6, %7}, [%3];\n"
                    "@!p st.async.weak.shared::cluster.mbarrier::complete_tx::bytes.v2.b32 [%2], {%4, %5}, [%3];\n}"
                    :: "r"(sc_peer), "r"(mapa_u32(bar_sc, rank ^ 1)), "r"(sc_own), "r"(mapa_u32(bar_sc, rank)), "r"(u0), "r"(u1), "r"(u2), "r"(u3), "r"(w4) : "memory");
                bar_arrive<2, 224>();
                fence_async_smem();
                __syncwarp();
                DBGW(4, 2);
            } else {
                bar_arrive<1, 384>();
                fence_async_smem();
                const uint32_t a = pin(sb + C2_SC + lane * 16), a2 = pin(sb + C2_SC + 1024 + lane * 8), pa = pin(sb + C2_PB + lane * 4);
                mbar_wait(bar_sc, s & 1);
                DBG(5);
                float v[10];
                {
                    float4 x0, x1, y0, y1; float2 x2, y2;
                    asm volatile("ld.shared.v4.f32 {%0, %1, %2, %3}, [%4];" : "=f"(x0.x), "=f"(x0.y), "=f"(x0.z), "=f"(x0.w) : "r"(a) : "memory");
                    asm volatile("ld.shared.v4.f32 {%0, %1, %2, %3}, [%4];" : "=f"(y0.x), "=f"(y0.y), "=f"(y0.z), "=f"(y0.w) : "r"(a + 1280) : "memory");
                    asm volatile("ld.shared.v4.f32 {%0, %1, %2, %3}, [%4];" : "=f"(x1.x), "=f"(x1.y), "=f"(x1.z), "=f"(x1.w) : "r"(a + 512) : "memory");
                    asm volatile("ld.shared.v4.f32 {%0, %1, %2, %3}, [%4];" : "=f"(y1.x), "=f"(y1.y), "=f"(y1.z), "=f"(y1.w) : "r"(a + 1792) : "memory");
                    asm volatile("ld.shared.v2.f32 {%0, %1}, [%2];" : "=f"(x2.x), "=f"(x2.y) : "r"(a2) : "memory");
                    asm volatile("ld.shared.v2.f32 {%0, %1}, [%2];" : "=f"(y2.x), "=f"(y2.y) : "r"(a2 + 1280) : "memory");
                    v[0] = x0.x + y0.x; v[1] = x0.y + y0.y; v[2] = x0.z + y0.z; v[3] = x0.w + y0.w;
                    v[4] = x1.x + y1.x; v[5] = x1.y + y1.y; v[6] = x1.z + y1.z; v[7] = x1.w + y1.w;
                    v[8] = x2.x + y2.x; v[9] = x2.y + y2.y;
                }
                float m0 = fmaxf(fmaxf(fmaxf(v[0], v[2]), fmaxf(v[4], v[6])), v[8]);
                float m1 = fmaxf(fmaxf(fmaxf(v[1], v[3]), fmaxf(v[5], v[7])), v[9]);
#pragma unroll
                for (int o = 4; o < 32; o <<= 1) {
                    m0 = fmaxf(m0, __shfl_xor_sync(0xffffffff, m0, o));
                    m1 = fmaxf(m1, __shfl_xor_sync(0xffffffff, m1, o));
                }
                const float sl = scale * l2e;
                m0 *= sl; m1 *= sl;
#pragma unroll
                for (int j = 0; j < 5; j++)
                    sts32(pa + j * 128, pack_bf16(ex2f(fmaf(v[2 * j], sl, -m0)), ex2f(fmaf(v[2 * j + 1], sl, -m1))));
                bar_arrive<3, 160>();
                DBG(6);
            }
        }
        bar_arrive<1, 384>();
        fence_async_smem();
        bar_arrive<6, 384>();
        TS_MARK(8, 0);
        CYC(2);
        TM(0);
        const uint32_t lane = fresh_lane();
        pace(CH_LD);
        {
            const uint32_t a = sb + C2_WO + ((lane >> 4) * 8 + (lane & 7)) * 128 + (((2 * w4 + ((lane >> 3) & 1)) ^ (lane & 7)) << 4);
#pragma unroll
            for (int e = C2_NS; e < 32; e++)
                asm volatile("ldmatrix.sync.aligned.m8n8.x4.trans.shared.b16 {%0,%1,%2,%3}, [%4];" : "=r"(w[e][0]), "=r"(w[e][1]), "=r"(w[e][2]), "=r"(w[e][3]) : "r"(a + e * 2048) : "memory");
        }
        fence_async_smem();
        if (CH_TS && w4 == 0) bar_sync<12, 160>();
        if (lane < 8) asm volatile("mbarrier.arrive.relaxed.cluster.shared::cluster.b64 _, [%0];" :: "r"(mapa_u32(bar_h, lane)) : "memory");
        __syncwarp();
        TM(9);
        if (w4 == 0) {
            if (!CH_TS) bar_sync<12, 160>();
            if (!CH_TS) asm volatile("fence.acq_rel.gpu;" ::: "memory");
            if (!CH_TS) asm volatile("fence.proxy.async.global;" ::: "memory");
            mbar_wait(bar_h, 0);
            if (elect_one()) tma_load_2d_mc(sb + c2_ts(rank) * 1024, &P.mapC, bar_x, (rank & 1) * 64, h * SEQ + SEQ - 128, (uint16_t)0xff);
            __syncwarp();
            TM(10);
        }
        if (w4 == 1) {
            wait_ctr(CT_P, FA_GRID);
            float4 v;
            asm volatile("ld.relaxed.gpu.global.v4.f32 {%0, %1, %2, %3}, [%4];" : "=f"(v.x), "=f"(v.y), "=f"(v.z), "=f"(v.w) : "l"(g_gate + SEQ - 128 + lane * 4) : "memory");
            asm volatile("st.shared.v4.f32 [%0], {%1, %2, %3, %4};" :: "r"(sb + C2_GT + lane * 16), "f"(1.f - v.x), "f"(1.f - v.y), "f"(1.f - v.z), "f"(1.f - v.w) : "memory");
            __syncwarp();
            if (lane == 0) mbar_expect_tx(bar_x, 65536);
            finish_launch(lane);
        }
        uint32_t* dst = reinterpret_cast<uint32_t*>(P.out + (SEQ - 128 + 2 * (lane & 3)) * DM + rank * 64 + w4 * 16) + (lane >> 2);
#pragma unroll 1
        for (uint32_t q = 0; q < 4; q++, dst += 16 * DM) {
            float acc[16], gt[8];
#pragma unroll
            for (int i = 0; i < 16; i++) acc[i] = 0.f;
            const uint32_t bar = q < 2 ? bar_x : bar_m - 128 + q * 64, db = dlo + (q & 1) * 256;
#pragma unroll
            for (int i = 0; i < 8; i++) {
                if (i == 0 || (CH_TW && (i == 1 || !(i & 1)))) {
                    if (i == 0 || q > 1) mbar_wait(bar + 8 * c2_grp(i), q >> 1);
                    if (!CH_TW && q > 1)
#pragma unroll 1
                        for (uint32_t j = 8; j < 40; j += 8) mbar_wait(bar + j, 1);
                    if (i == 0) TM(13 + q);
                    wgmma_fence();
                }
                if (i == 6) TM(25 + q);
                const uint32_t d = db + (q < 2 ? c2_ts((rank - i) & 7) * 64 : (i ? C2_WO + i * 8192 : C2_QX) >> 4);
#pragma unroll
                for (int kk = 0; kk < 4; kk++) {
                    if (i == 0) wgmma_ss_n32_ta(acc, dlo + ((C2_WO + kk * 2048) >> 4), d + kk * 2);
                    else wgmma_rs(acc, w[i * 4 + kk], d + kk * 2);
                }
            }
            wgmma_commit();
            if (q == 3) asm volatile("barrier.cluster.arrive.relaxed.aligned;" ::: "memory");
#pragma unroll
            for (int j = 0; j < 4; j++)
                asm volatile("ld.shared.v2.f32 {%0, %1}, [%2];" : "=f"(gt[2 * j]), "=f"(gt[2 * j + 1]) : "r"(sb + C2_GT + q * 128 + (lane & 3) * 8 + j * 32) : "memory");
            wgmma_wait<0>();
#pragma unroll
            for (int j = 0; j < 8; j++)
                asm volatile("red.relaxed.gpu.global.add.noftz.bf16x2 [%0], %1;" :: "l"(dst + ((j >> 1) * 8 + (j & 1)) * (DM / 2)),
                             "r"(pack_bf16(acc[(j >> 1) * 4 + (j & 1)] * gt[j], acc[(j >> 1) * 4 + (j & 1) + 2] * gt[j])) : "memory");
            TS_MARK(9 + q, 0);
            TM(17 + q);
        }
    } else if (wg == 1) {
        bool early = false;
#pragma unroll 1
        for (int s = -1;;) {
            if (s > 0 && (!CH_EARLY || s != NSEG - 1 || early)) {
                mbar_wait(bar_sx + 8 * ((s - 1) & 1), ((s - 1) >> 1) & 1);
                const uint32_t a = sb + C2_SX + w4 * 1280 + lane * 8, ap = a + 10240 - (s & 1) * 5120;
                float v[10];
                const int lim = 8 * w4 + g - 2 * qc;
#pragma unroll
                for (int j = 0; j < 5; j++) {
                    float2 x, y;
                    asm volatile("ld.shared.v2.f32 {%0, %1}, [%2];" : "=f"(x.x), "=f"(x.y) : "r"(a + j * 256) : "memory");
                    asm volatile("ld.shared.v2.f32 {%0, %1}, [%2];" : "=f"(y.x), "=f"(y.y) : "r"(ap + j * 256) : "memory");
                    v[2 * j] = (j < 4 && 8 * j > lim) ? -INFINITY : x.x + y.x;
                    v[2 * j + 1] = (j < 4 && 8 * j + 1 > lim) ? -INFINITY : x.y + y.y;
                }
                float mx = fmaxf(fmaxf(fmaxf(v[0], v[1]), fmaxf(v[2], v[3])), fmaxf(fmaxf(v[4], v[5]), fmaxf(v[6], v[7])));
                mx = fmaxf(mx, fmaxf(v[8], v[9]));
                mx = fmaxf(mx, __shfl_xor_sync(0xffffffff, mx, 1));
                mx = fmaxf(mx, __shfl_xor_sync(0xffffffff, mx, 2));
                const float sl = scale * l2e;
                mx *= sl;
#pragma unroll
                for (int j = 0; j < 10; j++) v[j] = ex2f(fmaf(v[j], sl, -mx));
                float sm = ((v[0] + v[1]) + (v[2] + v[3])) + ((v[4] + v[5]) + (v[6] + v[7])) + (v[8] + v[9]);
                sm += __shfl_xor_sync(0xffffffff, sm, 1);
                sm += __shfl_xor_sync(0xffffffff, sm, 2);
                float inv;
                asm("rcp.approx.ftz.f32 %0, %1;" : "=f"(inv) : "f"(sm));
                const uint32_t pa = sb + C2_PX + w4 * 256 + g * 32 + ((g >> 2) << 4) + qc * 4;
#pragma unroll
                for (int j = 0; j < 5; j++) sts32((pa ^ ((j & 1) << 4)) + (j >> 1) * 1024, pack_bf16(v[2 * j] * inv, v[2 * j + 1] * inv));
            }
            if (!early) {
            if (s >= 0) {
                fence_async_smem();
                if (s < NSEG) bar_sync<6, 384>(); else bar_sync<7, 256>();
                DBGW(20, 0);
                TM(s < NSEG ? 2 : 11);
                uint32_t cp[8];
                {
                    float cx[16];
#pragma unroll
                    for (int i = 0; i < 16; i++) cx[i] = 0.f;
                    wgmma_fence();
#pragma unroll
                    for (int kk = 0; kk < 3; kk++)
                        wgmma_ss<DHI32, DHI32>(cx, dlo + ((C2_VT + ((s - 1) & 1) * 6144 + kk * 2048) >> 4), dlo + ((C2_PX + kk * 1024) >> 4));
                    wgmma_commit();
                    wgmma_wait<0>();
#pragma unroll
                    for (int j = 0; j < 4; j++) { cp[2 * j] = pack_bf16(cx[4 * j], cx[4 * j + 2]); cp[2 * j + 1] = pack_bf16(cx[4 * j + 1], cx[4 * j + 3]); }
                    asm volatile("{\n.reg .pred p;\nsetp.gt.u32 p, %0, 99;\n@p st.shared.v4.b32 [%0], {%1, %2, %3, %4};\n@p st.shared.v4.b32 [%0], {%5, %6, %7, %8};\n}"
                                 :: "r"(rank), "r"(cp[0]), "r"(cp[1]), "r"(cp[2]), "r"(cp[3]), "r"(cp[4]), "r"(cp[5]), "r"(cp[6]), "r"(cp[7]) : "memory");
                }
                if (s < NSEG) {
                    float sx[20];
                    wgmma_fence();
                    wgmma_ss0<DHI128, DHI128>(sx, dlo + (C2_QX >> 4), dlo + (C2_KX >> 4));
#pragma unroll
                    for (int kk = 1; kk < 4; kk++) wgmma_ss<DHI128, DHI128>(sx, dlo + (C2_QX >> 4) + kk * 2, dlo + (C2_KX >> 4) + kk * 2);
                    wgmma_commit();
                    wgmma_wait<0>();
                    if (s < NSEG - 1) bar_arrive<5, 256>();
                    if (CH_TS && s > 0 && s < NSEG - 1) {
                        const uint32_t a = sb + C2_CS + w4 * 1024;
#pragma unroll
                        for (int j = 0; j < 8; j++) sts32(a + qc * 64 + g * 4 + (j >> 1) * 256 + (j & 1) * 32, cp[j]);
                        fence_async_smem();
                        __syncwarp();
                        if (elect_one()) tma_store_2d(&P.mapS, a, (rank & 1) * 64 + w4 * 16, h * SEQ + (s - 1) * SEGL);
                        asm volatile("cp.async.bulk.commit_group;" ::: "memory");
                    }
                    if (!CH_TS && s > 0 && s < NSEG - 1) {
                        uint32_t* dst = reinterpret_cast<uint32_t*>(g_ctxB + ((size_t)h * SEQ + (s - 1) * SEGL + 2 * qc) * HD + (rank & 1) * 64 + w4 * 16 + 2 * g);
#pragma unroll
                        for (int j = 0; j < 4; j++) {
                            asm volatile("st.global.u32 [%0], %1;" :: "l"(dst + j * 8 * (HD / 2)), "r"(cp[2 * j]) : "memory");
                            asm volatile("st.global.u32 [%0], %1;" :: "l"(dst + (j * 8 + 1) * (HD / 2)), "r"(cp[2 * j + 1]) : "memory");
                        }
                    }
                    DBGW(22, 0);
                    TM(3);
                    if (!CH_TS && s == NSEG - 2) bar_arrive<12, 160>();
                    const uint32_t a = sb + C2_SX + w4 * 2560 + lane * 8;
                    if (w4 < 2) {
#pragma unroll
                        for (int j = 0; j < 5; j++) {
                            asm volatile("st.shared.v2.f32 [%0], {%1, %2};" :: "r"(a + j * 256), "f"(sx[4 * j]), "f"(sx[4 * j + 1]) : "memory");
                            asm volatile("st.shared.v2.f32 [%0], {%1, %2};" :: "r"(a + 1280 + j * 256), "f"(sx[4 * j + 2]), "f"(sx[4 * j + 3]) : "memory");
                        }
                    }
                    if (s < NSEG - 1) mbar_wait(bar_x + 8 * ((s + 1) & 1), ((s + 1) >> 1) & 1);
                    const uint32_t pa = mapa_u32(a + 5120 + (s & 1) * 5120, rank ^ 1), pb = mapa_u32(bar_sx + 8 * (s & 1), rank ^ 1);
                    if (s < NSEG - 1) bar_sync<4, 256>(); else bar_sync<9, 128>();
                    if (w4 < 2) {
#pragma unroll
                        for (int j = 0; j < 5; j++) {
                            st_async_v2(pa + j * 256, __float_as_uint(sx[4 * j]), __float_as_uint(sx[4 * j + 1]), pb);
                            st_async_v2(pa + 1280 + j * 256, __float_as_uint(sx[4 * j + 2]), __float_as_uint(sx[4 * j + 3]), pb);
                        }
                    }
                }
                if (s >= NSEG - 1) {
                    const uint32_t a = sb + C2_QX + 4096 - (s & 1) * 4096;
#pragma unroll
                    for (int j = 0; j < 4; j++) {
                        sts32(a + t128 + j * 1024, cp[2 * j]);
                        sts32(a + (t128 ^ 16) + 128 + j * 1024, cp[2 * j + 1]);
                    }
                    fence_async_smem();
                    asm volatile("bar.arrive %0, 160;" :: "r"(s - NSEG + 14) : "memory");
                    TM(s - NSEG + 6);
                    if (s == NSEG) break;
                }
            } else mbar_wait(bar_x, 0);
            s++;
            if (s < NSEG) {
                float acc[16];
                c2_xstream<0, 32, CH_SPK>(acc, w, dlo + ((C2_XB + (s & 1) * C2_XS) >> 4), rank, dlo + (C2_WK >> 4));
                wgmma_wait<0>();
                store_x(acc, sb + C2_KX);
                DBGW(16, 0);
            }
            if (CH_EARLY && s == NSEG - 1) {
                if (CH_TS) {
                    asm volatile("cp.async.bulk.wait_group 0;" ::: "memory");
                    bar_arrive<12, 160>();
                }
                early = true;
                continue;
            }
            }
            early = false;
            if (s < NSEG) TM(4);
            if (s < NSEG) {
                const uint32_t kst = pin(sb + C2_KX + 4096 + t128);
                const uint32_t l128 = pin((lane & 7) * 128 + (((lane >> 3) ^ (lane & 7)) << 4));
                float a[CH_NCH][4];
                proj_mem(a, s, l128);
                sts32(kst, pack_bf16(a[0][0], a[0][2]));
                sts32((kst ^ 16) + 128, pack_bf16(a[0][1], a[0][3]));
                bar_arrive<1, 384>();
                TM(1);
                DBGW(19, 0);
                if (CH_TS) {
                    asm volatile("cp.async.bulk.wait_group 0;" ::: "memory");
                    __syncwarp();
                    if (s >= 4 * CB_FIRST + 5 && (s & 3) == 1 && lane == 0) asm volatile("red.relaxed.gpu.global.add.u32 [%0], 1;" :: "l"(&g_ctr[CT_CB + h * CB_ST - CB_FIRST + ((s - 5) >> 2)]) : "memory");
                }
                if (w4 == 0) {
                    if (CH_ARM && lane == 0) mbar_expect_tx(bar_sc, 2560);
                    if (lane < 16 && (lane & 7) >= 1 && (lane & 7) < 5) mbar_expect_tx(bar_m + 8 * lane, ((lane & 7) == 1 ? 1024 : 2048) << (s < NSEG - 1 ? 0 : 2));
                    if (s < NSEG - 1) {
                        if (!CH_ARM && lane == 0) mbar_expect_tx(bar_sc, 2560);
                        if (lane == 8) {
                            mbar_expect_tx(bar_x + 8 * ((s + 1) & 1), 32768);
                            tma_load_2d_mc(sb + C2_XB + ((s + 1) & 1) * C2_XS + rank * 5120, &mapX, bar_x + 8 * ((s + 1) & 1), rank * 64, (s + 1) * SEGL, (uint16_t)0xff);
                            if (s + 2 < NSEG)
                                asm volatile("cp.async.bulk.prefetch.tensor.2d.L2.global [%0, {%1, %2}];" :: "l"((uint64_t)&mapX), "r"(rank * 64), "r"((s + 2) * SEGL) : "memory");
                        }
                    }
                    if (lane == 16) mbar_expect_tx(bar_sx + 8 * (s & 1), 5120);
                    __syncwarp();
                }
            }
        }
        TS_MARK(12, 128);
        asm volatile("barrier.cluster.arrive.relaxed.aligned;" ::: "memory");
    } else {
        if (CH_WS == 1) *reinterpret_cast<uint32_t*>(P.xb + (rank * 65536 + (C * 4 + w4) * 128 + (w4 & 1) * 20480 + lane * 4)) = 0u;
        c2_wo(sb, tid - 256, 128);
        uint32_t va[5][2] = {};
        auto store_vt = [&](int s) {
            const uint32_t a = sb + C2_VT + (s & 1) * 6144 + a32;
            stmatrix_x4(a, va[0][0], va[0][1], va[1][0], va[1][1]);
            stmatrix_x4(a + 2048, va[2][0], va[2][1], va[3][0], va[3][1]);
            asm volatile("stmatrix.sync.aligned.m8n8.x2.shared.b16 [%0], {%1, %2};" :: "r"(a + 4096), "r"(va[4][0]), "r"(va[4][1]) : "memory");
        };
#pragma unroll 1
        for (int s = -1;;) {
            if (s >= 0) {
                const int t = tid - 256;
                const uint2* src = reinterpret_cast<const uint2*>(P.xb + ((s & 1) * 32768 + rank * 65536 + ((lds32(bar_m + 280) < lds32(bar_m + 284)) != CH_PRM ? 12288 : 4096) + t * 8));
                asm volatile("" : "+l"(src));
                const uint32_t ma = sb + C2_XB + ((s + 1) & 1) * C2_XS + rank * 5120 + 4096 + (t >> 4) * 128 + ((((t >> 1) & 7) ^ (t >> 4)) << 4) + (t & 1) * 8;
                uint32_t ra[8], rb[8];
#pragma unroll
                for (int i = 1; i < 8; i++) {
                    const uint32_t d = (rank + i) & 7;
                    ra[i] = pin(mapa_u32(ma, d)); rb[i] = pin(mapa_u32(bar_m + 8 * c2_grp(i), d));
                }
                if (s == NSEG - 1) break;
                bar_sync<11, 256>();
                DBGW(29, 0);
                pace(CH_POLL_DELAY);
                const uint32_t tag = ((s >> 1) & 1) ^ 1;
                uint32_t p[8][2], m0, m1;
                auto issue = [&](uint32_t (&x)[8][2]) {
#pragma unroll
                    for (int k = 0; k < 8; k++)
                        asm volatile("ld.relaxed.gpu.global.v2.u32 {%0, %1}, [%2];" : "=r"(x[k][0]), "=r"(x[k][1]) : "l"(src + k * 128) : "memory");
                };
                auto check = [&](const uint32_t (&x)[8][2]) {
                    uint32_t bad = 0, bad2 = 0;
                    float r[4];
#pragma unroll
                    for (int k = 0; k < 8; k++) {
                        asm("lop3.b32 %0, %0, %1, %2, 0xf6;" : "+r"(bad) : "r"(x[k][0]), "r"(tag));
                        asm("lop3.b32 %0, %0, %1, %2, 0xf6;" : "+r"(bad2) : "r"(x[k][1]), "r"(tag));
#pragma unroll
                        for (int e = 0; e < 2; e++) {
                            const float lo = __uint_as_float(x[k][e] << 16), hi = __uint_as_float(x[k][e] & 0xffff0000u);
                            r[2 * e] = k ? r[2 * e] + lo : lo;
                            r[2 * e + 1] = k ? r[2 * e + 1] + hi : hi;
                        }
                    }
                    m0 = pack_bf16(r[0], r[1]); m1 = pack_bf16(r[2], r[3]);
                    asm volatile("" : "+r"(m0), "+r"(m1));
                    return __all_sync(0xffffffff, ((bad | bad2) & 1u) == 0u);
                };
                for (int it = 0; it < (1 << 20); it++) {
                    issue(p);
                    if (check(p)) break;
                }
                DBGW(30, 0);
                st_async_v2(ra[1], m0, m1, rb[1]);
                asm volatile("st.shared.v2.b32 [%0], {%1, %2};" :: "r"(ma), "r"(m0), "r"(m1) : "memory");
                __syncwarp();
                if (lane == 0) mbar_arrive(bar_m);
#pragma unroll
                for (int i = 2; i < 8; i++) st_async_v2(ra[i], m0, m1, rb[i]);
                DBGW(31, 0);
                TM(8);
                store_vt(s);
            }
            if ((uint32_t)s < CH_PRN && lane == 0) {
                uint32_t t0, t1, v;
                const char* pr = P.xb + (rank * 65536 + (C * 4 + w4) * 128 + (w4 & 1) * 20480);
                asm volatile("mov.u32 %0, %%clock;" : "=r"(t0) :: "memory");
                asm volatile("atom.relaxed.gpu.global.exch.b32 %0, [%1], %2;" : "=r"(v) : "l"(pr), "r"(s) : "memory");
                asm volatile("{\n.reg .pred p;\nsetp.ne.u32 p, %1, 99;\nmov.u32 %0, 0;\n@p mov.u32 %0, %%clock;\n}" : "=r"(t1) : "r"(v) : "memory");
                asm volatile("red.shared.min.u32 [%0], %1;" :: "r"(bar_m + 280 + (w4 & 1) * 4), "r"(t1 - t0) : "memory");
            }
            __syncwarp();
            s++;
            const uint32_t ost = pin(sb + C2_OB + t32), pla = pin(sb + C2_PB + lane * 16), plb = pin(sb + C2_PB + 512 + (lane & 7) * 16);
            bar_sync<1, 384>();
            fence_async_smem();
            DBGW(24, 0);
            if (s < NSEG - 1) bar_sync<2, 224>();
            else bar_arrive<6, 384>();
            {
                float acc[20];
                c2_xstream<0, 32, CH_SPV>(acc, w, dlo + ((C2_XB + (s & 1) * C2_XS) >> 4), rank, dlo + (C2_WV >> 4));
                wgmma_wait<0>();
#pragma unroll
                for (int j = 0; j < 5; j++) { va[j][0] = pack_bf16(acc[4 * j], acc[4 * j + 1]); va[j][1] = pack_bf16(acc[4 * j + 2], acc[4 * j + 3]); }
            }
            DBGW(26, 0);
            TM(7);
            if (s < NSEG - 1) {
                uint32_t p[5];
                bar_sync<3, 160>();
                DBGW(27, 0);
                ldmatrix_x4_trans(p[0], p[1], p[2], p[3], pla);
                asm volatile("ldmatrix.sync.aligned.m8n8.x1.trans.shared.b16 {%0}, [%1];" : "=r"(p[4]) : "r"(plb) : "memory");
                float oa[4] = {0.f, 0.f, 0.f, 0.f}, ob[4] = {0.f, 0.f, 0.f, 0.f}, sa[4] = {0.f, 0.f, 0.f, 0.f}, sc[4] = {0.f, 0.f, 0.f, 0.f};
                const uint32_t one = 0x3f803f80u;
                mma_16816(sa, one, one, one, one, p[0], p[1]);
                mma_16816(oa, va[0][0], va[0][1], va[1][0], va[1][1], p[0], p[1]);
                mma_16816(sc, one, one, one, one, p[2], p[3]);
                mma_16816(ob, va[2][0], va[2][1], va[3][0], va[3][1], p[2], p[3]);
                mma_16816(sa, one, one, one, one, p[4], 0u);
                mma_16816(oa, va[4][0], va[4][1], 0u, 0u, p[4], 0u);
                bar_arrive<6, 384>();
                float i0, i1;
                asm("rcp.approx.ftz.f32 %0, %1;" : "=f"(i0) : "f"(sa[0] + sc[0]));
                asm("rcp.approx.ftz.f32 %0, %1;" : "=f"(i1) : "f"(sa[1] + sc[1]));
                sts32(ost, pack_bf16((oa[0] + ob[0]) * i0, (oa[2] + ob[2]) * i0));
                sts32(ost + 32, pack_bf16((oa[1] + ob[1]) * i1, (oa[3] + ob[3]) * i1));
                fence_async_smem();
                __syncwarp();
                if (elect_one()) {
#pragma unroll
                    for (int i = 1; i < 8; i++) {
                        const uint32_t d = (rank + i) & 7;
                        bulk_s2s(mapa_u32(sb + C2_OB + i * 1024 + w4 * 256, d), sb + C2_OB + w4 * 256, 256, mapa_u32(bar_o + 8 * c2_grp(i), d));
                        if (i == 1) mbar_arrive(bar_o);
                    }
                }
                __syncwarp();
                DBGW(28, 0);
            }
        }
        store_vt(NSEG - 1);
        fence_async_smem();
        bar_arrive<7, 256>();
        const uint32_t lane = fresh_lane();
        if (w4 == 0) {
            mbar_wait(bar_h, 0);
#pragma unroll 1
            for (uint32_t o = 0; o < 2; o++) {
                asm volatile("bar.sync %0, 160;" :: "r"(13 + o) : "memory");
                if (elect_one()) {
#pragma unroll
                    for (int i = 1; i < 8; i++) {
                        const uint32_t d = (rank + i) & 7;
                        bulk_s2s(mapa_u32(sb + C2_WO + i * 8192 + o * 4096, d), sb + C2_QX + o * 4096, 4096, mapa_u32(bar_m + o * 64 + 8 * c2_grp(i), d));
                    }
                }
                __syncwarp();
                if (lane < 4) mbar_arrive(bar_m + o * 64);
                TM(21 + o);
            }
        }
        __syncwarp();
        asm volatile("barrier.cluster.arrive.relaxed.aligned;" ::: "memory");
#pragma unroll
        for (int c = 0; c < 2; c++) *reinterpret_cast<uint2*>(P.xb + (32768 + 4096 + c * 8192 + rank * 65536 + C * 1024 + (w4 * 32 + lane) * 8)) = make_uint2(0u, 0u);
    }
    asm volatile("barrier.cluster.wait.aligned;" ::: "memory");
    TS_END(2);
    CYC(3);
    if (wg == 0) TM(23);
}

constexpr int P3_LEN = 24;
struct SideParams {
    CUtensorMap mapA[2];
    CUtensorMap mapW[3];
    CUtensorMap mapQ, mapK, mapV;
    CUtensorMap mapO;
    CUtensorMap mapCtx[2];
    CUtensorMap mapWo[2];
    CUtensorMap mapOut;
    bf16* qkv[3];
    const bf16 *x, *gate_w;
    bf16* out;
    uint32_t jobs[34 * 2];
    uint16_t sched[34 * P3_LEN];
    uint8_t first[34];
};
constexpr int P3_STAGES = 14;
#define P3_LAG 2
#define SD_GD 12000
#define SD_D0 0
#define SD_EFW 0
#define SD_EFA 0
#define SD_EFS 0
#define SD_EFK 0
#define SD_ALIAS 1
#define SD_JN 1
#define SD_PB 1
#define SD_GW 2
#define SD_NS 1
#define SD_PAD 0
#define SD_FD 0
#define SD_LF 0
#define SD_PK 5
#define SD_CT 384
#define PT(i)
#define SC(i)
#define ST(i, c)
#define OT(i)
constexpr uint32_t SD_PF = FA_BAR + 256, SD_PE = SD_PF + 8 * P3_STAGES, SD_OF = SD_PE + 8 * P3_STAGES, SD_OE = SD_OF + 32, SD_CL = SD_OE + 32, SD_DONE = FA_BAR + 576;
constexpr int SD_SMEM = SD_DONE + 2 * P3_LEN * 8;
__device__ __forceinline__ void tma_load_3d(uint32_t dst, const CUtensorMap* map, uint32_t bar, int c0, int c1, int c2) {
    asm volatile(
        "cp.async.bulk.tensor.3d.shared::cluster.global.mbarrier::complete_tx::bytes [%0], [%1, {%3, %4, %5}], [%2];"
        :: "r"(dst), "l"((uint64_t)map), "r"(bar), "r"(c0), "r"(c1), "r"(c2) : "memory");
}
__global__ void __cluster_dims__(2, 1, 1) __launch_bounds__(384, 1) side_kernel(const __grid_constant__ SideParams P) {
    extern __shared__ __align__(1024) uint8_t smem_side[];
    ST(0, threadIdx.x == 0);
    const uint32_t sb = smem_u32(smem_side);
    const uint32_t full = sb + SD_PF, empty = sb + SD_PE, done = sb + SD_DONE;
    const uint32_t bar_q = sb + FA_BAR, bar_qe = bar_q + 16, bar_kf = bar_q + 32, bar_vf = bar_q + 48, bar_ke = bar_q + 64, bar_ve = bar_q + 80,
                   bar_of = bar_q + 96, bar_oe = bar_q + 112, oslot = bar_q + 144;
    const int warp = __shfl_sync(0xffffffff, threadIdx.x >> 5, 0), lane = threadIdx.x & 31;
    const uint32_t rank = cluster_ctarank();
    const uint16_t* sched = P.sched + (blockIdx.x >> 1) * P3_LEN;
    const uint32_t so0 = P.first[blockIdx.x >> 1] * 8;
    TS_BEGIN_T(0, 320);
    {
        const uint32_t n = lane * 12 + warp, a = bar_q + 8 * (n < 16 ? n : n + 16);
        if (a < sb + SD_SMEM) mbar_init(a, n < 16 ? (0x14881181u >> (n >> 1) * 4) & 15 : a < empty ? 1 : a < sb + SD_OF || a >= done ? 4 : ((a - sb - SD_OF) >> 5 & 1) + 1);
        asm volatile("fence.mbarrier_init.release.cluster;" ::: "memory");
    }
    __syncthreads();
    if (threadIdx.x * 8 < so0) {
        mbar_arrive(full + 8 * lane);
        asm volatile("mbarrier.arrive.shared::cta.b64 _, [%0], 4;" :: "r"(empty + 8 * lane) : "memory");
    }
    __syncwarp();
    cluster_sync_relaxed();
    if (warp >= 8) {
        asm volatile("setmaxnreg.dec.sync.aligned.u32 %0;" :: "n"(FA_RLO));
        if (warp == 8) {
            uint32_t so = so0, ph = 1;
            pace(SD_D0);
#pragma unroll 1
            for (;; sched++) {
                const uint32_t e = *sched, z = (e >> 5) & 3, na = e >> 10;
                if (z == 3) break;
#pragma unroll 1
                for (int i = 1 - na; i < 16; i += 2 - na) {
                    mbar_wait(empty + so, ph);
                    if (elect_one()) {
                        mbar_expect_tx(full + so, 16384);
                        if (i & 1) tma_load_2d_mc(sb + so * 2048 + rank * 8192, &P.mapW[z], full + so, (e & 31) * 128 + rank * 64, (i >> 1) * 64, (uint16_t)3, SD_EFW ? L2_FIRST : L2_NORMAL);
                        else tma_load_2d(sb + so * 2048, &P.mapA[z != 0], full + so, (i >> 1) * 64, (((e >> 7) & 7) * 2 + rank) * 128, SD_EFA && z ? L2_FIRST : L2_NORMAL);
                    }
                    ST(3, lane == 0 && i == 0 && sched == P.sched + (blockIdx.x >> 1) * P3_LEN);
                    so += 8;
                    if (so == 8 * P3_STAGES) { so = 0; ph ^= 1; }
                }
            }
            TS_MARK(13, 256);
            PT(0);
            int it = 0, t = blockIdx.x, hp_ready = 0;
            auto load = [&](uint32_t dst, const CUtensorMap* map, uint32_t bar, int row) {
                if (elect_one()) {
                    mbar_expect_tx(bar, 32768);
                    tma_load_2d(dst, map, bar, 0, row, SD_EFK && map != &P.mapQ ? L2_FIRST : L2_NORMAL);
                    tma_load_2d(dst + 16384, map, bar, 64, row, SD_EFK && map != &P.mapQ ? L2_FIRST : L2_NORMAL);
                }
            };
            auto load_q = [&](int item) {
                const uint32_t b = bar_q + 8 * (item & 1);
                sts32(b + 128, t);
                if (t < 0) { mbar_arrive_if(b, lane == 0); return; }
                const int hp = fa_head(t) >> 1;
                if (!((hp_ready >> hp) & 1)) { wait_ctr(CT_AP + hp, 192u); hp_ready |= 1 << hp; }
                load(sb + FA_Q + (item & 1) * 32768, &P.mapQ, b, fa_head(t) * SEQ + fa_qt(t) * 128);
            };
            auto load_v = [&](int it, int row) {
                const int s = it & 1;
                if (it < 2) mbar_wait(empty + 56 + 32 * s, ph);
                mbar_wait(bar_ve + 8 * s, ((it >> 1) & 1) ^ 1);
                load(sb + FA_KV + s * 65536 + 32768, &P.mapV, bar_vf + 8 * s, row);
            };
            int vrow = 0;
            mbar_wait(empty + 8, ph);
            PT(1);
            load_q(0);
            PT(2);
#pragma unroll 1
            for (int item = 0; t >= 0; item++) {
                const int h = fa_head(t), jn = min(fa_qt(t), SD_JN);
                if (item == 1 && blockIdx.x < 8) TS_MARK(14, 256);
#pragma unroll 1
                for (int j = fa_qt(t); j >= 0; j--, it++) {
                    const int s = it & 1;
                    uint32_t tn = 0;
                    asm volatile("{\n.reg .pred p;\nsetp.eq.u32 p, %2, 0;\n@p atom.relaxed.gpu.global.add.u32 %0, [%1], 1;\n}" : "+r"(tn) : "l"(&g_ctr[CT_ATTN] + lane), "r"((j ^ jn) | lane) : "memory");
                    if (it < 2) mbar_wait(empty + 40 + 32 * s, ph);
                    mbar_wait(bar_ke + 8 * s, ((it >> 1) & 1) ^ 1);
                    PT(4 + it);
                    load(sb + FA_KV + s * 65536, &P.mapK, bar_kf + 8 * s, h * SEQ + j * 128);
                    if (it > 0) load_v(it - 1, vrow);
                    vrow = h * SEQ + j * 128;
                    if (j == jn) {
                        const int tp = t;
                        t = FA_GRID + __shfl_sync(0xffffffff, tn, 0);
                        mbar_arrive_if(sb + SD_CL, tp < SD_CT && t >= SD_CT && lane == 0);
                        if (t >= FA_ITEMS) t = FA_ITEMS - 1 - t;
                        mbar_wait(bar_qe + 8 * ((item + 1) & 1), (((item + 1) >> 1) & 1) ^ 1);
                        load_q(item + 1);
                    }
                }
            }
            load_v(it - 1, vrow);
            TS_MARK(15, 256);
            const uint32_t tk = ~t;
            so = 0; ph = 1;
            TS_BEGIN_T(4, 256);
            wait_ctr(CT_P, FA_GRID);
#pragma unroll 1
            for (uint32_t e = P.jobs[tk & ~1u], en = P.jobs[tk | 1u]; e; e = en, en = 0) {
                const uint32_t mt = e & 15, na = e >> 10 & 127, n = na + (e >> 23);
#pragma unroll 1
                for (uint32_t i = 0; i < n; i++) {
                    const uint32_t b = i >= na, k = b ? (e >> 17 & 63) + i - na : (e >> 4 & 63) + i;
                    mbar_wait(so < 16 ? bar_ke + 8 * (~it & 1) : bar_ve - 16 + so, ((it - 1 - (so == 24)) >> 1) & 1);
                    mbar_wait(sb + SD_OE + so, ph);
                    if (elect_one()) {
                        mbar_expect_tx(sb + SD_OF + so, 49152);
                        tma_load_3d(sb + so * 6144 + 16384, &P.mapWo[b], sb + SD_OF + so, 0, k * 64, (tk & 1) * 4);
                    }
                    const bool late = k >= 2 * O2_HE;
                    if (i == 0 || i == na || k == 2 * O2_HE) {
                        wait_ctr(b ? CT_CB + lane * CB_ST - CB_FIRST + max(mt, CB_FIRST) : CT_CA + mt * 2 + late, b ? (CB_ST ? 8u : 256u) : late ? 2u * (NH - O2_HE) : 2u * O2_HE);
                        __syncwarp();
                    }
                    if (elect_one()) tma_load_2d(sb + so * 6144, &P.mapCtx[b], sb + SD_OF + so, (k & 1) * 64, (k >> 1) * SEQ + mt * 128);
                    so = (so + 8) & 31;
                    if (so == 0) ph ^= 1;
                }
            }
            TS_END_T(4, 256);
            finish_launch(lane);
        } else if (warp == 11) {
#pragma unroll 1
            for (int i = 0; i < 4000 && !mbar_test(done + 8 * SD_GW, 0); i++) __nanosleep(500);
            const uint4 gv0 = __ldg(reinterpret_cast<const uint4*>(P.gate_w) + lane), gv1 = __ldg(reinterpret_cast<const uint4*>(P.gate_w) + 32 + lane);
            const uint32_t gw[8] = {gv0.x, gv0.y, gv0.z, gv0.w, gv1.x, gv1.y, gv1.z, gv1.w};
#pragma unroll 1
            for (int r = blockIdx.x; r < SEQ; r += gridDim.x) {
                const uint4 x0 = __ldg(reinterpret_cast<const uint4*>(P.x + (size_t)r * DM) + lane), x1 = __ldg(reinterpret_cast<const uint4*>(P.x + (size_t)r * DM) + 32 + lane);
                const uint32_t xw[8] = {x0.x, x0.y, x0.z, x0.w, x1.x, x1.y, x1.z, x1.w};
                float sum = 0.f;
#pragma unroll
                for (int e = 0; e < 8; e++) {
                    const uint32_t pr = pack_bf16(__uint_as_float(xw[e] << 16) * __uint_as_float(gw[e] << 16), __uint_as_float(xw[e] & 0xffff0000u) * __uint_as_float(gw[e] & 0xffff0000u));
                    sum += __uint_as_float(pr << 16) + __uint_as_float(pr & 0xffff0000u);
                }
#pragma unroll
                for (int o = 16; o; o >>= 1) sum += __shfl_xor_sync(0xffffffff, sum, o);
                if (lane == 0) g_gate[r] = bf16r(__fdividef(1.f, 1.f + __expf(-bf16r(sum))));
            }
#pragma unroll 1
            for (int i = 0; i < 4000 && !mbar_test(sb + SD_CL, 0); i++) __nanosleep(500);
#pragma unroll 1
            for (int i = blockIdx.x * 32 + lane; i < SEQ * DM / 8; i += gridDim.x * 32) reinterpret_cast<uint4*>(P.out)[i] = make_uint4(0u, 0u, 0u, 0u);
            asm volatile("fence.proxy.async.global;" ::: "memory");
            __syncwarp();
            if (lane == 0) signal_ctr(CT_P);
        } else if (lane == 0) {
            const int wg = warp - 9;
            SC(0);
#pragma unroll 1
            for (uint32_t d = done + wg * P3_LEN * 8;; d += 8, sched++) {
                const uint32_t e = *sched;
                if (((e >> 5) & 3) == 3) break;
                mbar_wait(d, 0);
                signal_ctr(CT_AP + ((e & 31) >> 1));
            }
            const uint32_t stg = sb + FA_O + wg * 16384;
            TS_END_T(0, 320);
            SC(1);
            TS_BEGIN_T(1, 320);
#pragma unroll 1
            for (int n = 0;; n++) {
                mbar_wait(bar_of + 8 * wg, n & 1);
                int t;
                asm volatile("ld.shared.s32 %0, [%1];" : "=r"(t) : "r"(oslot + wg * 4) : "memory");
                asm volatile("fence.proxy.async.shared::cta;" ::: "memory");
                const bool last = t < 0;
                t &= 0xffff;
                const int qt = fa_qt(t), h = fa_head(t);
                tma_store_2d(&P.mapO, stg, 0, h * SEQ + qt * 128 + wg * 64);
                tma_store_2d(&P.mapO, stg + 8192, 64, h * SEQ + qt * 128 + wg * 64);
                asm volatile("cp.async.bulk.commit_group;" ::: "memory");
                asm volatile("cp.async.bulk.wait_group.read 0;" ::: "memory");
                mbar_arrive(bar_oe + 8 * wg);
                asm volatile("cp.async.bulk.wait_group 0;" ::: "memory");
                signal_ctr(CT_CA + qt * 2 + (h >= O2_HE));
                if (last) break;
            }
            TS_END_T(1, 320);
            SC(2);
        }
    } else {
        asm volatile("setmaxnreg.inc.sync.aligned.u32 %0;" :: "n"(FA_RHI));
        const int wg = warp >> 2;
#pragma unroll
        for (int i = 0; i < SD_PAD; i++) asm volatile("pmevent 0;");
        {
            uint32_t a[32][4];
            float acc[64];
            const uint32_t b_lo = desc_lo(sb, 8192);
            const int r = warp * 16 + (lane & 15);
            const uint32_t la = sb + r * 128 + (((lane >> 4) ^ (r & 7)) << 4);
#pragma unroll
            for (int i = 0; i < 32; i++) ldsm_x4(a[i], la + i * 1024);
            const uint32_t rel = mapa_u32(empty, lane & 1);
            const int tw = threadIdx.x & 127;
            uint32_t so = so0, ph = 0;
            const uint32_t b1 = SD_PB ? pin(1 + wg) : 1 + wg;
            if (wg == 1) asm volatile("bar.arrive 1, 256;" ::: "memory");
#pragma unroll 1
            for (uint32_t d = done + wg * P3_LEN * 8;; d += 8, sched++) {
                const uint32_t e = *sched;
                if (((e >> 5) & 3) == 3) break;
                const bool na = e >> 10;
                const bool sig = tw < (na ? 4 : 2);
                uint32_t old = 0;
                auto release = [&]() { asm volatile("{\n.reg .pred p;\nsetp.ne.u32 p, %1, 0;\n@p mbarrier.arrive.shared::cluster.b64 _, [%0];\n}" :: "r"(rel + old), "r"((uint32_t)sig) : "memory"); };
                bf16* dst;
                if (SD_LF & 2) dst = P.qkv[(e >> 5) & 3] + ((size_t)(e & 31) * SEQ + (((e >> 7) & 7) * 2 + rank) * 128 + warp * 16 + (lane >> 2)) * HD + (lane & 3) * 8;
                asm volatile("bar.sync %0, 256;" :: "r"(b1) : "memory");
#pragma unroll
                for (int k = 0; k < 8; k++) {
                    const uint32_t sa = so;
                    if (na) {
                        if (k == 0) ST(1, threadIdx.x == 0 && d == done);
                        mbar_wait(full + so, ph);
                        if (k == 0) ST(2, threadIdx.x == 0 && d == done);
#pragma unroll
                        for (int kk = 0; kk < 4; kk++) ldsm_x4(a[k * 4 + kk], (la + so * 2048) ^ (kk * 32));
                        so += 8;
                        if (so == 8 * P3_STAGES) { so = 0; ph ^= 1; }
                    }
                    mbar_wait(full + so, ph);
                    if (k == 0 || k == 3 || k == 7) ST(k == 0 ? 4 : k == 3 ? 5 : 6, threadIdx.x == 0 && d == done);
                    wgmma_fence();
#pragma unroll
                    for (int kk = 0; kk < 4; kk++) wgmma_rs_n128_tb_lo(acc, a[k * 4 + kk], b_lo + so * 128 + kk * 128, (k | kk) != 0);
                    wgmma_commit();
                    if (k == P3_LAG) asm volatile("bar.arrive %0, 256;" :: "r"(2 - wg) : "memory");
                    if ((SD_LF & 4) && k == SD_PK)
                        asm volatile("{\n.reg .pred p;\nsetp.gt.u32 p, %0, 99;\n@p st.global.u32 [%1], %0;\n}" :: "r"(rank), "l"(dst) : "memory");
                    if (k > 0) { wgmma_wait<1>(); release(); }
                    old = (lane & 2) ? sa : so;
                    so += 8;
                    if (so == 8 * P3_STAGES) { so = 0; ph ^= 1; }
                }
                wgmma_wait<0>();
                release();
                if (!(SD_LF & 2)) dst = P.qkv[(e >> 5) & 3] + ((size_t)(e & 31) * SEQ + (((e >> 7) & 7) * 2 + rank) * 128 + warp * 16 + (lane >> 2)) * HD + (lane & 3) * 8;
#pragma unroll
                for (int i = 0; i < 8; i++) {
                    const float* c = &acc[(i >> 1) * 16 + (i & 1) * 2];
                    *reinterpret_cast<uint4*>(dst + (i & 1) * 8 * HD + (i >> 1) * 32) =
                        make_uint4(pack_bf16(c[0], c[1]), pack_bf16(c[4], c[5]), pack_bf16(c[8], c[9]), pack_bf16(c[12], c[13]));
                }
                __syncwarp();
                mbar_arrive_if(d, lane == 0);
            }
        }
        const uint32_t tk = attn_consumer(sb, wg, warp & 3, lane);
        float acc[128];
#pragma unroll
        for (int i = 0; i < 128; i++) asm volatile("" : "=f"(acc[i]));
        const uint32_t a_lo = desc_lo(sb + wg * 8192, 16), b_lo = desc_lo(sb + 16384, 8192);
        const uint32_t st = sb + FA_O + warp * 4096, sl = st + (lane & 15) * 128 + (((lane >> 4) ^ (lane & 7)) << 4);
        const bool sig = (threadIdx.x & 127) == 0;
        uint32_t so = 0, ph = 0;
        uint32_t pk[64], part = 4, row0 = 0;
#pragma unroll
        for (int i = 0; i < 64; i++) asm volatile("" : "=r"(pk[i]));
        auto drain = [&](const uint32_t* c, uint32_t q) {
            asm volatile("cp.async.bulk.wait_group.read 1;" ::: "memory");
            __syncwarp();
#pragma unroll
            for (int t = 0; t < 4; t++) stmatrix_x4((sl ^ (t * 32)) + (q & 1) * 2048, c[4 * t], c[4 * t + 1], c[4 * t + 2], c[4 * t + 3]);
            fence_async_smem();
            __syncwarp();
            if (elect_one())
                asm volatile("cp.reduce.async.bulk.tensor.2d.global.shared::cta.add.bulk_group [%0, {%2, %3}], [%1];"
                             :: "l"((uint64_t)&P.mapOut), "r"(st + (q & 1) * 2048), "r"((tk & 2) * 128 + q * 64), "r"(row0) : "memory");
            asm volatile("cp.async.bulk.commit_group;" ::: "memory");
        };
#pragma unroll 1
        for (uint32_t e = P.jobs[(tk >> 1) & ~1u], en = P.jobs[(tk >> 1) | 1u]; e; e = en, en = 0) {
            const uint32_t row = (e & 15) * 128 + warp * 16, na = e >> 10 & 127, n = na + (e >> 23);
            float g0, g1;
#pragma unroll 1
            for (uint32_t i = 0;; i++) {
                if (i == n || (i == na && i)) {
                    const float w0 = fmaxf(1.f - g0, 0x1p-40f), w1 = fmaxf(1.f - g1, 0x1p-40f);
                    const float r0 = i < n ? __fdividef(g0, w0) : na < n ? w0 : g0, r1 = i < n ? __fdividef(g1, w1) : na < n ? w1 : g1;
                    wgmma_wait<0>();
                    mbar_arrive_if(sb + SD_OE + ((so - 8) & 31), sig && i == n);
                    if (i == n) OT(3); else OT(2);
#pragma unroll
                    for (int c = 0; c < 32; c++) { acc[4 * c] *= r0; acc[4 * c + 1] *= r0; acc[4 * c + 2] *= r1; acc[4 * c + 3] *= r1; }
                    if (i == n) break;
                }
                mbar_wait(sb + SD_OF + so, ph);
                if (i == 0) OT(1);
                wgmma_fence();
#pragma unroll
                for (int kk = 0; kk < 4; kk++) wgmma_ss_n256_tb(acc, a_lo + so * 384 + kk * 2, b_lo + so * 384 + kk * 128, i | kk);
                wgmma_commit();
                if (i > 0) { wgmma_wait<1>(); mbar_arrive_if(sb + SD_OE + ((so - 8) & 31), sig); }
                else {
                    asm volatile("ld.relaxed.gpu.global.f32 %0, [%1];" : "=f"(g0) : "l"(g_gate + row + (lane >> 2)) : "memory");
                    asm volatile("ld.relaxed.gpu.global.f32 %0, [%1 + 32];" : "=f"(g1) : "l"(g_gate + row + (lane >> 2)) : "memory");
                }
                if (part < 4) {
                    drain(pk, part++);
#pragma unroll
                    for (int c = 0; c < 48; c++) pk[c] = pk[c + 16];
                }
                so = (so + 8) & 31;
                if (so == 0) ph ^= 1;
            }
#pragma unroll
            for (int c = 0; c < 64; c++) pk[c] = pack_bf16(acc[2 * c], acc[2 * c + 1]);
            part = 0; row0 = row;
            mbar_wait(bar_oe + 8 * wg, tk & 1);
            OT(4);
        }
        if (SD_FD) {
            const uint32_t d = warp * 2048 - FA_O - warp * 4096;
#pragma unroll
            for (int q = 0; q < 4; q++) {
#pragma unroll
                for (int t = 0; t < 4; t++) stmatrix_x4((sl ^ (t * 32)) + d + q * 49152, pk[16 * q + 4 * t], pk[16 * q + 4 * t + 1], pk[16 * q + 4 * t + 2], pk[16 * q + 4 * t + 3]);
                if (SD_FD == 2 && !(q & 1)) continue;
                fence_async_smem();
                __syncwarp();
                if (elect_one())
#pragma unroll
                    for (int r = q + 1 - SD_FD; r <= q; r++)
                        asm volatile("cp.reduce.async.bulk.tensor.2d.global.shared::cta.add.bulk_group [%0, {%2, %3}], [%1];"
                                     :: "l"((uint64_t)&P.mapOut), "r"(st + d + r * 49152), "r"((tk & 2) * 128 + r * 64), "r"(row0) : "memory");
            }
            asm volatile("cp.async.bulk.commit_group;" ::: "memory");
        } else {
#pragma unroll
        for (int q = 0; q < 4; q++) drain(pk + 16 * q, q);
        }
        asm volatile("cp.async.bulk.wait_group.read 0;" ::: "memory");
    }
}

typedef CUresult (*PFN_encodeTiled)(CUtensorMap*, CUtensorMapDataType, cuuint32_t, void*, const cuuint64_t*,
                                    const cuuint64_t*, const cuuint32_t*, const cuuint32_t*, CUtensorMapInterleave,
                                    CUtensorMapSwizzle, CUtensorMapL2promotion, CUtensorMapFloatOOBfill);
static PFN_encodeTiled g_encode = nullptr;

static void make_map(CUtensorMap* m, const void* ptr, uint64_t rows, uint64_t cols, uint32_t box_rows, bool narrow = false) {
    cuuint64_t dims[2] = {cols, rows};
    cuuint64_t strides[1] = {cols * 2};
    cuuint32_t box[2] = {narrow ? 16u : 64u, box_rows};
    cuuint32_t es[2] = {1, 1};
    g_encode(m, CU_TENSOR_MAP_DATA_TYPE_BFLOAT16, 2, const_cast<void*>(ptr), dims, strides, box, es,
             CU_TENSOR_MAP_INTERLEAVE_NONE, narrow ? CU_TENSOR_MAP_SWIZZLE_NONE : CU_TENSOR_MAP_SWIZZLE_128B, CU_TENSOR_MAP_L2_PROMOTION_L2_256B,
             CU_TENSOR_MAP_FLOAT_OOB_FILL_NONE);
}

static void make_map3(CUtensorMap* m, const void* ptr, uint64_t rows, uint64_t cols, uint32_t box_rows, uint32_t nblk) {
    cuuint64_t dims[3] = {64, rows, cols / 64};
    cuuint64_t strides[2] = {cols * 2, 128};
    cuuint32_t box[3] = {64u, box_rows, nblk};
    cuuint32_t es[3] = {1, 1, 1};
    g_encode(m, CU_TENSOR_MAP_DATA_TYPE_BFLOAT16, 3, const_cast<void*>(ptr), dims, strides, box, es,
             CU_TENSOR_MAP_INTERLEAVE_NONE, CU_TENSOR_MAP_SWIZZLE_128B, CU_TENSOR_MAP_L2_PROMOTION_L2_256B, CU_TENSOR_MAP_FLOAT_OOB_FILL_NONE);
}

template <typename... KArgs, typename... Args>
static void launch_pdl(void (*kernel)(KArgs...), int grid, int block, size_t smem, cudaStream_t st, bool pdl, Args... args) {
    cudaLaunchConfig_t cfg = {};
    cfg.gridDim = dim3(grid); cfg.blockDim = dim3(block); cfg.dynamicSmemBytes = smem; cfg.stream = st;
    cudaLaunchAttribute at[1];
    at[0].id = cudaLaunchAttributeProgrammaticStreamSerialization;
    at[0].val.programmaticStreamSerializationAllowed = 1;
    cfg.attrs = at; cfg.numAttrs = pdl ? 1 : 0;
    cudaLaunchKernelEx(&cfg, kernel, KArgs(args)...);
}

extern "C" void kernel_launch(void* const* d_in, const int* in_sizes, int n_in, void* d_out, int out_size) {
    const bf16* x = (const bf16*)d_in[0];
    const bf16* ckv = (const bf16*)d_in[1];
    const bf16* wq = (const bf16*)d_in[2];
    const bf16* wuk = (const bf16*)d_in[3];
    const bf16* wuv = (const bf16*)d_in[4];
    const bf16* wo = (const bf16*)d_in[5];
    const bf16* mem0 = (const bf16*)d_in[7];
    const bf16* Wq = (const bf16*)d_in[8];
    const bf16* Wk = (const bf16*)d_in[9];
    const bf16* Wv = (const bf16*)d_in[10];
    const bf16* Wo = (const bf16*)d_in[11];
    const bf16* gate_w = (const bf16*)d_in[13];
    bf16* out = (bf16*)d_out;

    static SideParams SP;
    static ChainParams CP;
    static bool init = false;
    static const void* last_in[15];
    bool same = init;
    for (int i = 0; i < 14 && same; i++) same = last_in[i] == d_in[i];
    same = same && last_in[14] == d_out;
    if (!init) {
        cudaDriverEntryPointQueryResult qr;
        cudaGetDriverEntryPoint("cuTensorMapEncodeTiled", (void**)&g_encode, cudaEnableDefault, &qr);
        cudaFuncSetAttribute(chain_kernel, cudaFuncAttributeMaxDynamicSharedMemorySize, C2_SMEM);
        cudaFuncSetAttribute(side_kernel, cudaFuncAttributeMaxDynamicSharedMemorySize, SD_SMEM);
        for (int p = 0; p < 34; p++) {
            uint16_t* t = SP.sched + p * P3_LEN;
            int n = 0, rows = -1;
            auto add = [&](int z, int mp, int head) {
#define P3_RQ 12
#define P3_RK 22
                head = (head + 32 - (z ? P3_RK : P3_RQ)) & 31;
                t[n++] = (uint16_t)(head | z << 5 | mp << 7 | (rows != (z ? 8 : 0) + mp) << 10);
                rows = (z ? 8 : 0) + mp;
            };
            const int mp = p & 7, kind = p >> 3;
            if (kind == 0) for (int h = 0; h < 23; h++) add(0, mp, h);
            else if (kind < 4) {
                for (int i = kind - 1; i < 54; i += 3) add(1 + (i & 1), mp, i >> 1);
                if (kind < 3) for (int h = 27; h < 32; h++) add(kind, mp, h);
                else for (int h = 23; h < 27; h++) add(0, mp, h);
            } else for (int i = 0; i < 20; i++) add(0, mp * 4 + i / 5, 27 + i % 5);
            int stages = 0;
            for (int i = 0; i < n; i++) stages += 8 << (t[i] >> 10);
            SP.first[p] = (uint8_t)((P3_STAGES - stages % P3_STAGES) % P3_STAGES);
            while (n < P3_LEN) t[n++] = 3 << 5;
        }
#define O6_SCHED 0x1f040400, 0x0, 0xfc10, 0x0, 0x1000000, 0xec51, 0x1f040001, 0x0, 0x278c002, 0x1001401, 0x1e000002, 0x0, 0xad53, 0x4302, 0x1e000003, 0x0, 0x2785403, 0x2807004, 0x1d8a0004, 0x0, 0xb000005, 0x91c4, 0x4eec8e5, 0x0, 0x16280006, 0x3805, 0xa0099a6, 0x0, 0x6806, 0xb542b67, 0xd807, 0x13c8, 0xec18, 0x0, 0x1d8a0008, 0x0, 0x2800408, 0xd009, 0xb80000a, 0xbd23349, 0xec5a, 0x0, 0x648000b, 0x14ae140a, 0xec5b, 0x0, 0x860000b, 0x1500000c, 0xb54900c, 0x0, 0x724c, 0xdca0bed, 0xd947dfd, 0x0, 0x5007c0d, 0x4ee1bae, 0x1200140b, 0x4ba1a8e, 0x14800009, 0x44c1eee, 0x15000007, 0x4dc175e, 0x10ac0005, 0x4a839ae, 0x7c0f, 0x51438ce, 0x85ff, 0x500300e
        const uint32_t sched[68] = {O6_SCHED};
        for (int i = 0; i < 68; i++) SP.jobs[i] = sched[i];
        init = true;
    }
    if (!same) {
        for (int i = 0; i < 14; i++) last_in[i] = d_in[i];
        last_in[14] = d_out;
        void *pQA, *pKA, *pVA, *pCA, *pCB;
        cudaGetSymbolAddress(&pQA, g_QA); cudaGetSymbolAddress(&pKA, g_KA); cudaGetSymbolAddress(&pVA, g_VA);
        cudaGetSymbolAddress(&pCA, g_ctxA); cudaGetSymbolAddress(&pCB, g_ctxB);
        pCA = pQA;
        make_map(&SP.mapA[0], x, SEQ, DM, 128);
        make_map(&SP.mapA[1], ckv, SEQ, DM, 128);
        const void* ws[3] = {wq, wuk, wuv};
        void* cs[3] = {pQA, pKA, pVA};
        for (int i = 0; i < 3; i++) { make_map(&SP.mapW[i], ws[i], DM, NQ, 64); SP.qkv[i] = (bf16*)cs[i]; }
        make_map(&CP.mapX, x, SEQ, DM, SEGL);
        make_map(&CP.mapM, mem0, NMEM, DM, NMEM);
        make_map(&CP.mapW[0], Wq, DM, NQ, 64);
        make_map(&CP.mapW[1], Wk, DM, NQ, 64);
        make_map(&CP.mapW[2], Wv, DM, NQ, 64);
        make_map(&CP.mapWo, Wo, NQ, DM, 64);
        make_map(&SP.mapQ, pQA, NH * SEQ, HD, 128);
        make_map(&SP.mapK, pKA, NH * SEQ, HD, 128);
        make_map(&SP.mapV, pVA, NH * SEQ, HD, 128);
        make_map(&SP.mapO, pCA, NH * SEQ, HD, 64);
        make_map(&SP.mapCtx[0], pCA, NH * SEQ, HD, 128);
        make_map(&SP.mapCtx[1], pCB, NH * SEQ, HD, 128);
        make_map3(&SP.mapWo[0], wo, NQ, DM, 64, 4);
        make_map3(&SP.mapWo[1], Wo, NQ, DM, 64, 4);
        make_map(&SP.mapOut, out, SEQ, DM, 16);
        SP.out = out;
        make_map(&CP.mapC, pCB, NH * SEQ, HD, 64);
        make_map(&CP.mapS, pCB, NH * SEQ, HD, 32, true);
        CP.out = out;
        void* pXB;
        cudaGetSymbolAddress(&pXB, g_xbuf);
        CP.xb = (char*)(((uintptr_t)pXB + 65535) & ~(uintptr_t)65535);
        SP.x = x; SP.gate_w = gate_w;
    }
    cudaStream_t s1 = cudaStreamPerThread;
    const bool pdl = true;
    launch_pdl(chain_kernel, 64, 384, C2_SMEM, s1, false, CP);
    launch_pdl(side_kernel, FA_GRID, 384, SD_SMEM, s1, pdl, SP);
}
```

```cpp
#include <cuda_runtime.h>
#include <cuda_bf16.h>
#include <cuda.h>
#include <stdint.h>
#include <type_traits>

constexpr int SEQ = 2048;
constexpr int DM = 512;
constexpr int NH = 32;
constexpr int HD = 128;
constexpr int NQ = NH * HD;
constexpr int SEGL = 32;
constexpr int NMEM = 8;
constexpr int NSEG = SEQ / SEGL;

typedef __nv_bfloat16 bf16;

#define BIG_AL 4096
__device__ __align__(BIG_AL) bf16 g_QA[SEQ * NQ];
__device__ __align__(BIG_AL) bf16 g_KA[SEQ * NQ];
__device__ __align__(BIG_AL) bf16 g_VA[SEQ * NQ];
__device__ __align__(BIG_AL) bf16 g_ctxA[SEQ * NQ];
__device__ __align__(BIG_AL) bf16 g_ctxB[SEQ * NQ];
constexpr int CT_ATTN = 1, CT_FIN = 5;
constexpr int CT_P = 48;
constexpr int CT_AP = 64;
#define O2_HE 24
constexpr int CT_CA = 128;
constexpr int CT_CB = 160;
#define CB_ST 32
#define CB_FIRST 11
constexpr int CT_N = CT_CB + 32 * (CB_ST ? CB_ST : 1);
__device__ __align__(128) unsigned int g_ctr[CT_N];
__device__ float g_gate[SEQ];
__device__ __align__(4096) char g_xbuf[9 * 65536];

#define FA_GRID 68

#define P2_MARK 0
#define TS_MARK(id, tid)
#define TS_MARK2(id, tid)
#define TS_BEGIN(id)
#define TS_END(id)
#define TS_BEGIN_T(id, tid)
#define TS_END_T(id, tid)
__device__ __forceinline__ void pdl_launch_dependents() { asm volatile("griddepcontrol.launch_dependents;" ::: "memory"); }
__device__ __forceinline__ void wait_ctr(int idx, unsigned int n) {
    unsigned int v; int it = 0;
    do { asm volatile("ld.acquire.gpu.global.u32 %0, [%1];" : "=r"(v) : "l"(&g_ctr[idx]) : "memory"); } while (v < n && ++it < (1 << 22));
}
__device__ __forceinline__ void signal_ctr(int idx) {
    asm volatile("fence.proxy.async.global;" ::: "memory");
    asm volatile("red.release.gpu.global.add.u32 [%0], 1;" :: "l"(&g_ctr[idx]) : "memory");
}
__device__ __forceinline__ void signal_ctr_generic(int idx) {
    asm volatile("red.release.gpu.global.add.u32 [%0], 1;" :: "l"(&g_ctr[idx]) : "memory");
}
__device__ __forceinline__ void finish_launch(int lane) {
    unsigned int tk = 0;
    if (lane == 0) tk = atomicAdd(&g_ctr[CT_FIN], 1u);
    tk = __shfl_sync(0xffffffff, tk, 0);
    if (tk == 64 + 68 - 1) {
#pragma unroll 1
        for (int i = lane; i < CT_CB; i += 32) g_ctr[i] = 0u;
        *reinterpret_cast<uint4*>(&g_ctr[CT_CB + lane * CB_ST]) = make_uint4(0u, 0u, 0u, 0u);
    }
}
__device__ __forceinline__ uint4 quad_transpose(uint32_t p0, uint32_t p1, uint32_t p2, uint32_t p3, int lane) {
    const bool o1 = lane & 1, o2 = lane & 2;
    uint32_t s0 = o1 ? p0 : p1, s1 = o1 ? p2 : p3;
    s0 = __shfl_xor_sync(0xffffffff, s0, 1); s1 = __shfl_xor_sync(0xffffffff, s1, 1);
    const uint32_t a_lo = o1 ? s0 : p0, a_hi = o1 ? p1 : s0, b_lo = o1 ? s1 : p2, b_hi = o1 ? p3 : s1;
    uint32_t t0 = o2 ? a_lo : b_lo, t1 = o2 ? a_hi : b_hi;
    t0 = __shfl_xor_sync(0xffffffff, t0, 2); t1 = __shfl_xor_sync(0xffffffff, t1, 2);
    return o2 ? make_uint4(t0, t1, b_lo, b_hi) : make_uint4(a_lo, a_hi, t0, t1);
}
__device__ __forceinline__ uint32_t smem_u32(const void* p) {
    return (uint32_t)__cvta_generic_to_shared(p);
}
__device__ __forceinline__ void mbar_init(uint32_t bar, uint32_t count) {
    asm volatile("mbarrier.init.shared::cta.b64 [%0], %1;" :: "r"(bar), "r"(count));
}
__device__ __forceinline__ void mbar_expect_tx(uint32_t bar, uint32_t bytes) {
    asm volatile("mbarrier.arrive.expect_tx.shared::cta.b64 _, [%0], %1;" :: "r"(bar), "r"(bytes) : "memory");
}
__device__ __forceinline__ void mbar_arrive(uint32_t bar) {
    asm volatile("mbarrier.arrive.shared::cta.b64 _, [%0];" :: "r"(bar) : "memory");
}
__device__ __forceinline__ void mbar_wait(uint32_t bar, uint32_t parity) {
    asm volatile(
        "{\n"
        ".reg .pred p, q;\n"
        ".reg .u32 c;\n"
        "mov.u32 c, 0;\n"
        "WAIT_LOOP:\n"
        "mbarrier.try_wait.parity.shared::cta.b64 p, [%0], %1;\n"
        "@p bra WAIT_DONE;\n"
        "add.u32 c, c, 1;\n"
        "setp.lt.u32 q, c, 4000000;\n"
        "@q bra WAIT_LOOP;\n"
        "WAIT_DONE:\n"
        "}\n" :: "r"(bar), "r"(parity) : "memory");
}
__device__ __forceinline__ void tma_load_2d(uint32_t dst, const CUtensorMap* map, uint32_t bar, int c0, int c1) {
    asm volatile(
        "cp.async.bulk.tensor.2d.shared::cluster.global.mbarrier::complete_tx::bytes [%0], [%1, {%3, %4}], [%2];"
        :: "r"(dst), "l"((uint64_t)map), "r"(bar), "r"(c0), "r"(c1) : "memory");
}
constexpr uint64_t L2_NORMAL = 0x1000000000000000ull, L2_FIRST = 0x12F0000000000000ull;
__device__ __forceinline__ void tma_load_2d(uint32_t dst, const CUtensorMap* map, uint32_t bar, int c0, int c1, uint64_t hint) {
    asm volatile(
        "cp.async.bulk.tensor.2d.shared::cluster.global.mbarrier::complete_tx::bytes.L2::cache_hint [%0], [%1, {%3, %4}], [%2], %5;"
        :: "r"(dst), "l"((uint64_t)map), "r"(bar), "r"(c0), "r"(c1), "l"(hint) : "memory");
}
__device__ __forceinline__ void wgmma_fence() { asm volatile("wgmma.fence.sync.aligned;" ::: "memory"); }
__device__ __forceinline__ void wgmma_commit() { asm volatile("wgmma.commit_group.sync.aligned;" ::: "memory"); }
template <int N> __device__ __forceinline__ void wgmma_wait() {
    asm volatile("wgmma.wait_group.sync.aligned %0;" :: "n"(N) : "memory");
}
__device__ __forceinline__ uint64_t make_desc(uint32_t addr, uint32_t lbo, uint32_t sbo) {
    uint64_t d = 0;
    d |= (uint64_t)((addr & 0x3FFFF) >> 4);
    d |= (uint64_t)((lbo >> 4) & 0x3FFF) << 16;
    d |= (uint64_t)((sbo >> 4) & 0x3FFF) << 32;
    d |= (uint64_t)1 << 62;
    return d;
}

#define ACC64(d) \
    "+f"(d[0]), "+f"(d[1]), "+f"(d[2]), "+f"(d[3]), "+f"(d[4]), "+f"(d[5]), "+f"(d[6]), "+f"(d[7]), \
    "+f"(d[8]), "+f"(d[9]), "+f"(d[10]), "+f"(d[11]), "+f"(d[12]), "+f"(d[13]), "+f"(d[14]), "+f"(d[15]), \
    "+f"(d[16]), "+f"(d[17]), "+f"(d[18]), "+f"(d[19]), "+f"(d[20]), "+f"(d[21]), "+f"(d[22]), "+f"(d[23]), \
    "+f"(d[24]), "+f"(d[25]), "+f"(d[26]), "+f"(d[27]), "+f"(d[28]), "+f"(d[29]), "+f"(d[30]), "+f"(d[31]), \
    "+f"(d[32]), "+f"(d[33]), "+f"(d[34]), "+f"(d[35]), "+f"(d[36]), "+f"(d[37]), "+f"(d[38]), "+f"(d[39]), \
    "+f"(d[40]), "+f"(d[41]), "+f"(d[42]), "+f"(d[43]), "+f"(d[44]), "+f"(d[45]), "+f"(d[46]), "+f"(d[47]), \
    "+f"(d[48]), "+f"(d[49]), "+f"(d[50]), "+f"(d[51]), "+f"(d[52]), "+f"(d[53]), "+f"(d[54]), "+f"(d[55]), \
    "+f"(d[56]), "+f"(d[57]), "+f"(d[58]), "+f"(d[59]), "+f"(d[60]), "+f"(d[61]), "+f"(d[62]), "+f"(d[63])
#define ACC64_STR \
    "{%0, %1, %2, %3, %4, %5, %6, %7, %8, %9, %10, %11, %12, %13, %14, %15, " \
    "%16, %17, %18, %19, %20, %21, %22, %23, %24, %25, %26, %27, %28, %29, %30, %31, " \
    "%32, %33, %34, %35, %36, %37, %38, %39, %40, %41, %42, %43, %44, %45, %46, %47, " \
    "%48, %49, %50, %51, %52, %53, %54, %55, %56, %57, %58, %59, %60, %61, %62, %63}"

template <int TB>
__device__ __forceinline__ void wgmma_ss_n128(float (&d)[64], uint64_t da, uint64_t db, int scale_d) {
    asm volatile(
        "{\n.reg .pred p;\nsetp.ne.b32 p, %66, 0;\n"
        "wgmma.mma_async.sync.aligned.m64n128k16.f32.bf16.bf16 " ACC64_STR ", %64, %65, p, 1, 1, 0, %67;\n}\n"
        : ACC64(d) : "l"(da), "l"(db), "r"(scale_d), "n"(TB));
}
__device__ __forceinline__ uint32_t desc_lo(uint32_t addr, uint32_t lbo) { return ((addr & 0x3FFFF) >> 4) | ((lbo >> 4) << 16); }
template <int TB>
__device__ __forceinline__ void wgmma_ss_n128_lo(float (&d)[64], uint32_t da_lo, uint32_t db_lo, int scale_d) {
    asm volatile(
        "{\n.reg .pred p;\n.reg .b64 da, db;\nsetp.ne.b32 p, %66, 0;\n"
        "mov.b64 da, {%64, 0x40000040};\nmov.b64 db, {%65, 0x40000040};\n"
        "wgmma.mma_async.sync.aligned.m64n128k16.f32.bf16.bf16 " ACC64_STR ", da, db, p, 1, 1, 0, %67;\n}\n"
        : ACC64(d) : "r"(da_lo), "r"(db_lo), "r"(scale_d), "n"(TB));
}
__device__ __forceinline__ void wgmma_rs_n128_tb(float (&d)[64], uint32_t a0, uint32_t a1, uint32_t a2, uint32_t a3,
                                                 uint64_t db, int scale_d) {
    asm volatile(
        "{\n.reg .pred p;\nsetp.ne.b32 p, %69, 0;\n"
        "wgmma.mma_async.sync.aligned.m64n128k16.f32.bf16.bf16 " ACC64_STR ", {%64, %65, %66, %67}, %68, p, 1, 1, 1;\n}\n"
        : ACC64(d) : "r"(a0), "r"(a1), "r"(a2), "r"(a3), "l"(db), "r"(scale_d));
}
__device__ __forceinline__ void wgmma_rs_n80(float (&d)[40], const uint32_t (&a)[4], uint32_t db_lo, int scale_d) {
    asm volatile(
        "{\n.reg .pred p;\n.reg .b64 db;\nsetp.ne.b32 p, %45, 0;\nmov.b64 db, {%44, 0x40000040};\n"
        "wgmma.mma_async.sync.aligned.m64n80k16.f32.bf16.bf16 "
        "{%0, %1, %2, %3, %4, %5, %6, %7, %8, %9, %10, %11, %12, %13, %14, %15, %16, %17, %18, %19, %20, %21, %22, %23, %24, %25, %26, %27, %28, %29, %30, %31, %32, %33, %34, %35, %36, %37, %38, %39}, "
        "{%40, %41, %42, %43}, db, p, 1, 1, 0;\n}\n"
        : "+f"(d[0]), "+f"(d[1]), "+f"(d[2]), "+f"(d[3]), "+f"(d[4]), "+f"(d[5]), "+f"(d[6]), "+f"(d[7]), "+f"(d[8]), "+f"(d[9]), "+f"(d[10]), "+f"(d[11]), "+f"(d[12]), "+f"(d[13]), "+f"(d[14]), "+f"(d[15]), "+f"(d[16]), "+f"(d[17]), "+f"(d[18]), "+f"(d[19]), "+f"(d[20]), "+f"(d[21]), "+f"(d[22]), "+f"(d[23]), "+f"(d[24]), "+f"(d[25]), "+f"(d[26]), "+f"(d[27]), "+f"(d[28]), "+f"(d[29]), "+f"(d[30]), "+f"(d[31]), "+f"(d[32]), "+f"(d[33]), "+f"(d[34]), "+f"(d[35]), "+f"(d[36]), "+f"(d[37]), "+f"(d[38]), "+f"(d[39])
        : "r"(a[0]), "r"(a[1]), "r"(a[2]), "r"(a[3]), "r"(db_lo), "r"(scale_d));
}
__device__ __forceinline__ void wgmma_ss_n256_tb(float (&d)[128], uint32_t da_lo, uint32_t db_lo, int scale_d) {
    asm volatile(
        "{\n.reg .pred p;\n.reg .b64 da, db;\nsetp.ne.b32 p, %130, 0;\nmov.b64 da, {%128, 0x40000040};\nmov.b64 db, {%129, 0x40000040};\n"
        "wgmma.mma_async.sync.aligned.m64n256k16.f32.bf16.bf16 {%0, %1, %2, %3, %4, %5, %6, %7, %8, %9, %10, %11, %12, %13, %14, %15, %16, %17, %18, %19, %20, %21, %22, %23, %24, %25, %26, %27, %28, %29, %30, %31, %32, %33, %34, %35, %36, %37, %38, %39, %40, %41, %42, %43, %44, %45, %46, %47, %48, %49, %50, %51, %52, %53, %54, %55, %56, %57, %58, %59, %60, %61, %62, %63, %64, %65, %66, %67, %68, %69, %70, %71, %72, %73, %74, %75, %76, %77, %78, %79, %80, %81, %82, %83, %84, %85, %86, %87, %88, %89, %90, %91, %92, %93, %94, %95, %96, %97, %98, %99, %100, %101, %102, %103, %104, %105, %106, %107, %108, %109, %110, %111, %112, %113, %114, %115, %116, %117, %118, %119, %120, %121, %122, %123, %124, %125, %126, %127}, da, db, p, 1, 1, 0, 1;\n}\n"
        : "+f"(d[0]), "+f"(d[1]), "+f"(d[2]), "+f"(d[3]), "+f"(d[4]), "+f"(d[5]), "+f"(d[6]), "+f"(d[7]), "+f"(d[8]), "+f"(d[9]), "+f"(d[10]), "+f"(d[11]), "+f"(d[12]), "+f"(d[13]), "+f"(d[14]), "+f"(d[15]), "+f"(d[16]), "+f"(d[17]), "+f"(d[18]), "+f"(d[19]), "+f"(d[20]), "+f"(d[21]), "+f"(d[22]), "+f"(d[23]), "+f"(d[24]), "+f"(d[25]), "+f"(d[26]), "+f"(d[27]), "+f"(d[28]), "+f"(d[29]), "+f"(d[30]), "+f"(d[31]), "+f"(d[32]), "+f"(d[33]), "+f"(d[34]), "+f"(d[35]), "+f"(d[36]), "+f"(d[37]), "+f"(d[38]), "+f"(d[39]), "+f"(d[40]), "+f"(d[41]), "+f"(d[42]), "+f"(d[43]), "+f"(d[44]), "+f"(d[45]), "+f"(d[46]), "+f"(d[47]), "+f"(d[48]), "+f"(d[49]), "+f"(d[50]), "+f"(d[51]), "+f"(d[52]), "+f"(d[53]), "+f"(d[54]), "+f"(d[55]), "+f"(d[56]), "+f"(d[57]), "+f"(d[58]), "+f"(d[59]), "+f"(d[60]), "+f"(d[61]), "+f"(d[62]), "+f"(d[63]), "+f"(d[64]), "+f"(d[65]), "+f"(d[66]), "+f"(d[67]), "+f"(d[68]), "+f"(d[69]), "+f"(d[70]), "+f"(d[71]), "+f"(d[72]), "+f"(d[73]), "+f"(d[74]), "+f"(d[75]), "+f"(d[76]), "+f"(d[77]), "+f"(d[78]), "+f"(d[79]), "+f"(d[80]), "+f"(d[81]), "+f"(d[82]), "+f"(d[83]), "+f"(d[84]), "+f"(d[85]), "+f"(d[86]), "+f"(d[87]), "+f"(d[88]), "+f"(d[89]), "+f"(d[90]), "+f"(d[91]), "+f"(d[92]), "+f"(d[93]), "+f"(d[94]), "+f"(d[95]), "+f"(d[96]), "+f"(d[97]), "+f"(d[98]), "+f"(d[99]), "+f"(d[100]), "+f"(d[101]), "+f"(d[102]), "+f"(d[103]), "+f"(d[104]), "+f"(d[105]), "+f"(d[106]), "+f"(d[107]), "+f"(d[108]), "+f"(d[109]), "+f"(d[110]), "+f"(d[111]), "+f"(d[112]), "+f"(d[113]), "+f"(d[114]), "+f"(d[115]), "+f"(d[116]), "+f"(d[117]), "+f"(d[118]), "+f"(d[119]), "+f"(d[120]), "+f"(d[121]), "+f"(d[122]), "+f"(d[123]), "+f"(d[124]), "+f"(d[125]), "+f"(d[126]), "+f"(d[127])
        : "r"(da_lo), "r"(db_lo), "r"(scale_d));
}
__device__ __forceinline__ void stmatrix_x4(uint32_t addr, uint32_t r0, uint32_t r1, uint32_t r2, uint32_t r3) {
    asm volatile("stmatrix.sync.aligned.m8n8.x4.shared.b16 [%0], {%1, %2, %3, %4};" :: "r"(addr), "r"(r0), "r"(r1), "r"(r2), "r"(r3) : "memory");
}
__device__ __forceinline__ void tma_store_2d(const CUtensorMap* map, uint32_t src, int c0, int c1) {
    asm volatile("cp.async.bulk.tensor.2d.global.shared::cta.bulk_group [%0, {%2, %3}], [%1];"
                 :: "l"((uint64_t)map), "r"(src), "r"(c0), "r"(c1) : "memory");
}
__device__ __forceinline__ float ex2f(float x) { float y; asm("ex2.approx.ftz.f32 %0, %1;" : "=f"(y) : "f"(x)); return y; }
__device__ __forceinline__ uint32_t pack_bf16(float lo, float hi) {
    __nv_bfloat162 v = __floats2bfloat162_rn(lo, hi);
    return *reinterpret_cast<uint32_t*>(&v);
}
__device__ __forceinline__ float bf16r(float x) { return __uint_as_float(pack_bf16(0.f, x) & 0xffff0000u); }
__device__ __forceinline__ void mma_16816(float (&c)[4], uint32_t a0, uint32_t a1, uint32_t a2, uint32_t a3,
                                          uint32_t b0, uint32_t b1) {
    asm volatile(
        "mma.sync.aligned.m16n8k16.row.col.f32.bf16.bf16.f32 {%0,%1,%2,%3}, {%4,%5,%6,%7}, {%8,%9}, {%0,%1,%2,%3};"
        : "+f"(c[0]), "+f"(c[1]), "+f"(c[2]), "+f"(c[3])
        : "r"(a0), "r"(a1), "r"(a2), "r"(a3), "r"(b0), "r"(b1));
}
__device__ __forceinline__ void ldmatrix_x4_trans(uint32_t& r0, uint32_t& r1, uint32_t& r2, uint32_t& r3, uint32_t addr) {
    asm volatile("ldmatrix.sync.aligned.m8n8.x4.trans.shared.b16 {%0,%1,%2,%3}, [%4];"
                 : "=r"(r0), "=r"(r1), "=r"(r2), "=r"(r3) : "r"(addr));
}

constexpr uint32_t FA_Q = 0, FA_KV = 65536, FA_O = 196608, FA_BAR = 229376;
constexpr int FA_ITEMS = 16 * NH;
__device__ __forceinline__ int fa_qt(int t) { return 15 - ((t & 127) >> 3); }
__device__ __forceinline__ int fa_head(int t) { return (t >> 7) * 8 + (t & 7); }
__device__ __forceinline__ uint32_t mbar_test(uint32_t bar, uint32_t parity) {
    uint32_t done;
    asm volatile(
        "{\n.reg .pred p;\n"
        "mbarrier.test_wait.parity.shared::cta.b64 p, [%1], %2;\n"
        "selp.u32 %0, 1, 0, p;\n}\n" : "=r"(done) : "r"(bar), "r"(parity) : "memory");
    return done;
}
__device__ __forceinline__ void mbar_arrive_if(uint32_t bar, bool c) {
    asm volatile("{\n.reg .pred p;\nsetp.ne.u32 p, %1, 0;\n@p mbarrier.arrive.shared::cta.b64 _, [%0];\n}" :: "r"(bar), "r"((uint32_t)c) : "memory");
}
__device__ __forceinline__ uint32_t pin(uint32_t v) { asm volatile("" : "+r"(v)); return v; }
__device__ __forceinline__ void sts128_if(bool c, uint32_t a, uint32_t v0, uint32_t v1, uint32_t v2, uint32_t v3) {
    asm volatile("{\n.reg .pred p;\nsetp.ne.u32 p, %5, 0;\n@p st.shared.v4.b32 [%0], {%1, %2, %3, %4};\n}" :: "r"(a), "r"(v0), "r"(v1), "r"(v2), "r"(v3), "r"((uint32_t)c) : "memory");
}
__device__ __forceinline__ void wgmma_rs_n128_tb_lo(float (&d)[64], const uint32_t* a, uint32_t db_lo, int scale_d) {
    asm volatile(
        "{\n.reg .pred p;\n.reg .b64 db;\nsetp.ne.b32 p, %69, 0;\nmov.b64 db, {%68, 0x40000040};\n"
        "wgmma.mma_async.sync.aligned.m64n128k16.f32.bf16.bf16 " ACC64_STR ", {%64, %65, %66, %67}, db, p, 1, 1, 1;\n}\n"
        : ACC64(d) : "r"(a[0]), "r"(a[1]), "r"(a[2]), "r"(a[3]), "r"(db_lo), "r"(scale_d));
}
#define FA_TEST 48
#define FA_PIN 32

__device__ __forceinline__ void wgmma_ss_n64_lo(float (&d)[64], uint32_t da_lo, uint32_t db_lo, int scale_d) {
    asm volatile(
        "{\n.reg .pred p;\n.reg .b64 da, db;\nsetp.ne.b32 p, %34, 0;\n"
        "mov.b64 da, {%32, 0x40000040};\nmov.b64 db, {%33, 0x40000040};\n"
        "wgmma.mma_async.sync.aligned.m64n64k16.f32.bf16.bf16 {%0, %1, %2, %3, %4, %5, %6, %7, %8, %9, %10, %11, %12, %13, %14, %15, "
        "%16, %17, %18, %19, %20, %21, %22, %23, %24, %25, %26, %27, %28, %29, %30, %31}, da, db, p, 1, 1, 0, 0;\n}\n"
        : "+f"(d[0]), "+f"(d[1]), "+f"(d[2]), "+f"(d[3]), "+f"(d[4]), "+f"(d[5]), "+f"(d[6]), "+f"(d[7]), "+f"(d[8]), "+f"(d[9]), "+f"(d[10]),
          "+f"(d[11]), "+f"(d[12]), "+f"(d[13]), "+f"(d[14]), "+f"(d[15]), "+f"(d[16]), "+f"(d[17]), "+f"(d[18]), "+f"(d[19]), "+f"(d[20]),
          "+f"(d[21]), "+f"(d[22]), "+f"(d[23]), "+f"(d[24]), "+f"(d[25]), "+f"(d[26]), "+f"(d[27]), "+f"(d[28]), "+f"(d[29]), "+f"(d[30]), "+f"(d[31])
        : "r"(da_lo), "r"(db_lo), "r"(scale_d));
}
#define FA_UD 1
#define FA_PP 0
#define FA_NOFB 0
#define FA_DPIN 16
#define FA_RLO 40
#define FA_RHI 232
#define FA_LIM 0x1p40f
__device__ __forceinline__ uint32_t attn_consumer(const uint32_t sb, const int wg, const int w4, const int lane) {
    const uint32_t bar_q = sb + FA_BAR, bar_of = bar_q + 96, bar_oe = bar_q + 112, oslot = bar_q + 144;
    const bool lane0 = lane == 0;
    float o[64], sacc[64];
    uint32_t pa[32];
    float ms0 = 0.f, ms1 = 0.f, lrow0 = 1.f, lrow1 = 1.f;
    const float sc = 0.08838834764831845f * 1.4426950408889634f;
    const uint32_t q_lo = desc_lo(sb + FA_Q + wg * 8192, 16), k_lo = desc_lo(sb + FA_KV, 16), v_lo = desc_lo(sb + FA_KV + 32768, 16384);
    uint32_t qd = q_lo + 2048, kd = k_lo + 4096, vd = v_lo, bs = bar_q + 8, bi = bar_q + 8;
    auto issue_qk = [&](uint32_t a, bool half) {
        const uint32_t b = kd;
#pragma unroll
        for (int i = 0; i < 64; i++) asm volatile("" : "=f"(sacc[i]));
#pragma unroll
        for (int kk = 0; kk < 8; kk++) {
            if (half) wgmma_ss_n64_lo(sacc, a + (kk >> 2) * 1024 + (kk & 3) * 2, b + (kk >> 2) * 1024 + (kk & 3) * 2, kk != 0);
            else wgmma_ss_n128_lo<0>(sacc, a + (kk >> 2) * 1024 + (kk & 3) * 2, b + (kk >> 2) * 1024 + (kk & 3) * 2, kk != 0);
        }
        wgmma_commit();
    };
    auto issue_pv = [&](bool acc) {
        const uint32_t b = vd;
#pragma unroll
        for (int kk = 0; kk < 8; kk++) wgmma_rs_n128_tb_lo(o, &pa[kk * 4], b + kk * 128, kk != 0 || acc);
        wgmma_commit();
    };
    auto turn_wait = [&]() { asm volatile("bar.sync %0, 256;" :: "r"(1 + wg) : "memory"); };
    auto turn_pass = [&]() { asm volatile("bar.arrive %0, 256;" :: "r"(2 - wg) : "memory"); };
    int item = -1, it = -1, j = 0, nkv = 1, t = 0;
    auto redo = [&](float& l0, float& l1) {
        const size_t row0 = (size_t)fa_head(t) * SEQ + (lane >> 2);
        const uint32_t* qg = reinterpret_cast<const uint32_t*>(g_QA + (row0 + (nkv - 1) * 128 + wg * 64 + w4 * 16) * HD) + (lane & 3);
        const uint32_t* kg = reinterpret_cast<const uint32_t*>(g_KA + (row0 + (nkv - 1 - j) * 128) * HD) + (lane & 3);
        auto ldg = [](const uint32_t* p) { uint32_t v; asm volatile("ld.relaxed.gpu.global.u32 %0, [%1];" : "=r"(v) : "l"(p) : "memory"); return v; };
        const int r0 = j ? 1 << 20 : wg * 64 + w4 * 16 + (lane >> 2) - (lane & 3) * 2;
        float mx0 = -INFINITY, mx1 = -INFINITY;
        const float m0 = ms0, m1 = ms1;
        uint4 tmp[8];
        l0 = 0.f; l1 = 0.f;
#pragma unroll 1
        for (int ps = 0; ps < 32; ps++) {
            const int nb = ps & 15;
            float c[4] = {0.f, 0.f, 0.f, 0.f};
#pragma unroll 1
            for (int kk = 0; kk < 64; kk += 8)
                mma_16816(c, ldg(qg + kk), ldg(qg + kk + 8 * 64), ldg(qg + kk + 4), ldg(qg + kk + 8 * 64 + 4), ldg(kg + nb * 8 * 64 + kk), ldg(kg + nb * 8 * 64 + kk + 4));
#pragma unroll
            for (int i = 0; i < 4; i++)
                if (nb * 8 + (i & 1) - ((i & 2) ? 8 : 0) > r0) c[i] = -INFINITY;
            mx0 = fmaxf(mx0, fmaxf(c[0], c[1])); mx1 = fmaxf(mx1, fmaxf(c[2], c[3]));
#pragma unroll
            for (int i = 0; i < 4; i++) c[i] = ex2f(fmaf(c[i], sc, (i & 2) ? ms1 : ms0));
            l0 += c[0] + c[1]; l1 += c[2] + c[3];
            reinterpret_cast<uint2*>(tmp)[nb] = make_uint2(pack_bf16(c[0], c[1]), pack_bf16(c[2], c[3]));
            if (ps == 15) {
                mx0 = fmaxf(mx0, __shfl_xor_sync(0xffffffff, mx0, 1)); mx1 = fmaxf(mx1, __shfl_xor_sync(0xffffffff, mx1, 1));
                mx0 = fmaxf(mx0, __shfl_xor_sync(0xffffffff, mx0, 2)); mx1 = fmaxf(mx1, __shfl_xor_sync(0xffffffff, mx1, 2));
                ms0 = fminf(-mx0 * sc, ms0); ms1 = fminf(-mx1 * sc, ms1);
                l0 = 0.f; l1 = 0.f;
            }
        }
        const float a0 = ex2f(ms0 - m0), a1 = ex2f(ms1 - m1);
        lrow0 *= a0; lrow1 *= a1;
#pragma unroll
        for (int i = 0; i < 64; i++) o[i] *= (i & 2) ? a1 : a0;
#pragma unroll
        for (int i = 0; i < 8; i++) { pa[4 * i] = tmp[i].x; pa[4 * i + 1] = tmp[i].y; pa[4 * i + 2] = tmp[i].z; pa[4 * i + 3] = tmp[i].w; }
    };
    auto pin_after = [&](float v) {
        asm volatile("{\n.reg .pred p;\nsetp.eq.f32 p, %1, %2;\n@p st.shared.f32 [%0], %1;\n}" :: "r"(oslot + 16), "f"(v), "f"(ms0) : "memory");
    };
    auto pack_p = [&](int i) {
        if (i >= FA_PP) pa[i >> 1] = pack_bf16(sacc[i - 1], sacc[i]);
        else asm volatile("{\n.reg .pred p;\nsetp.ne.b32 p, %3, 0x7fc12345;\n@p cvt.rn.bf16x2.f32 %0, %2, %1;\n}" : "+r"(pa[i >> 1]) : "f"(sacc[i - 1]), "f"(sacc[i]), "r"(__float_as_uint(o[0])));
    };
    uint32_t ok = 0, okq = 0;
    int tn = 0;
    auto tests = [&]() {
        ok = mbar_test(bs + 48, (it >> 1) & 1);
        asm volatile("ld.shared.s32 %0, [%1];" : "=r"(tn) : "r"((bi ^ 8) + 128) : "memory");
        ok &= mbar_test((bs ^ 8) + 32, ((it + 1) >> 1) & 1);
        okq = mbar_test(bi ^ 8, ((item + 1) >> 1) & 1);
    };
    auto epilogue = [&](int tag, bool real) {
        float l0 = lrow0, l1 = lrow1;
        l0 += __shfl_xor_sync(0xffffffff, l0, 1); l1 += __shfl_xor_sync(0xffffffff, l1, 1);
        l0 += __shfl_xor_sync(0xffffffff, l0, 2); l1 += __shfl_xor_sync(0xffffffff, l1, 2);
        float i0, i1;
        asm("rcp.approx.ftz.f32 %0, %1;" : "=f"(i0) : "f"(l0));
        asm("rcp.approx.ftz.f32 %0, %1;" : "=f"(i1) : "f"(l1));
        const int row = w4 * 16 + (lane >> 2);
        const uint32_t stg = sb + FA_O + wg * 16384 + row * 128;
#pragma unroll
        for (int i = 0; i < 4; i++) {
            const int ch = i * 4 + (lane & 3);
            const uint32_t a = stg + (ch >> 3) * 8192 + (((ch & 7) ^ (row & 7)) << 4);
            const float* q = &o[i * 16];
            sts128_if(real, a, pack_bf16(q[0] * i0, q[1] * i0), pack_bf16(q[4] * i0, q[5] * i0), pack_bf16(q[8] * i0, q[9] * i0), pack_bf16(q[12] * i0, q[13] * i0));
            sts128_if(real, a + 1024, pack_bf16(q[2] * i1, q[3] * i1), pack_bf16(q[6] * i1, q[7] * i1), pack_bf16(q[10] * i1, q[11] * i1), pack_bf16(q[14] * i1, q[15] * i1));
        }
        asm volatile("st.shared.s32 [%0], %1;" :: "r"(oslot + wg * 4), "r"(tag) : "memory");
        __syncwarp();
        mbar_arrive_if(bar_of + 8 * wg, lane0 && real);
    };
    auto transition = [&](auto wgc, float& l0, float& l1) {
        constexpr int WG = decltype(wgc)::value;
        constexpr int NE = WG == 0 ? 32 : 64;
        turn_wait();
        wgmma_fence();
        issue_qk(qd, WG == 0);
        issue_pv(nkv > 1);
        turn_pass();
        const int tc = t;
        t = __shfl_sync(0xffffffff, tn, 0);
        nkv = fa_qt(t) + 1;
        mbar_wait(bar_oe + 8 * wg, (max(item, 0) & 1) ^ 1);
        item++; bi ^= 8;
        wgmma_wait<1>();
        mbar_arrive_if(bs + 64, lane0);
        mbar_arrive_if(bi + 16, lane0 && nkv == 1);
        ms0 = -sc * __shfl_sync(0xffffffff, sacc[0], lane & 28); ms1 = -sc * __shfl_sync(0xffffffff, sacc[2], lane & 28);
        const int r0 = w4 * 16 + (lane >> 2) - (lane & 3) * 2;
#pragma unroll
        for (int i = 0; i < 32; i++)
            if ((i >> 2) * 8 + (i & 1) - ((i & 2) ? 8 : 0) > r0) sacc[WG * 32 + i] = -INFINITY;
        float sum[4];
#pragma unroll
        for (int i = 0; i < FA_DPIN; i++) { sacc[i] = ex2f(fmaf(sacc[i], sc, (i & 2) ? ms1 : ms0)); sum[i & 3] = i < 4 ? sacc[i] : sum[i & 3] + sacc[i]; }
        pin_after((sum[0] + sum[1]) + (sum[2] + sum[3]));
        wgmma_wait<0>();
        mbar_arrive_if((bs ^ 8) + 80, lane0 && item > 0);
        epilogue(tc, item > 0);
#pragma unroll
        for (int i = 0; i < NE; i++) {
            if (i >= FA_DPIN) { sacc[i] = ex2f(fmaf(sacc[i], sc, (i & 2) ? ms1 : ms0)); sum[i & 3] += sacc[i]; }
            if (i & 1) pack_p(i);
            if (i == NE - 16) { pin_after(sum[0]); tests(); }
        }
        if (NE == 32)
#pragma unroll
            for (int i = 16; i < 32; i++) asm volatile("mov.u32 %0, 0;" : "=r"(pa[i]));
        l0 = sum[0] + sum[1]; l1 = sum[2] + sum[3];
    };
#pragma unroll
    for (int i = 0; i < 32; i++) pa[i] = 0u;
#pragma unroll 1
    for (;;) {
        float l0, l1;
        it++;
        kd = 2 * k_lo + 4096 - kd; vd = 2 * v_lo + 4096 - vd; bs ^= 8;
        if (++j < nkv) {
            if (__builtin_expect(!ok, 0)) {
                mbar_wait(bs + 32, (it >> 1) & 1);
                mbar_wait((bs ^ 8) + 48, ((it - 1) >> 1) & 1);
            }
            turn_wait();
            wgmma_fence();
            issue_qk(qd, false);
            issue_pv(j > 1);
            turn_pass();
            wgmma_wait<1>();
            mbar_arrive_if(bs + 64, lane0);
            mbar_arrive_if(bi + 16, lane0 && j == nkv - 1);
            float sum[4];
#pragma unroll
            for (int i = 0; i < FA_PIN; i++) { sacc[i] = ex2f(fmaf(sacc[i], sc, (i & 2) ? ms1 : ms0)); sum[i & 3] = i < 4 ? sacc[i] : sum[i & 3] + sacc[i]; }
            pin_after((sum[0] + sum[1]) + (sum[2] + sum[3]));
            wgmma_wait<0>();
            mbar_arrive_if((bs ^ 8) + 80, lane0);
#pragma unroll
            for (int i = 0; i < 64; i++) {
                if (i >= FA_PIN) { sacc[i] = ex2f(fmaf(sacc[i], sc, (i & 2) ? ms1 : ms0)); sum[i & 3] = i < 4 ? sacc[i] : sum[i & 3] + sacc[i]; }
                if (i & 1) pack_p(i);
                if (i == FA_TEST) { pin_after(sum[0]); tests(); }
            }
            l0 = sum[0] + sum[1]; l1 = sum[2] + sum[3];
        } else {
            if (__builtin_expect(!(ok & okq), 0)) {
                mbar_wait(bi ^ 8, ((item + 1) >> 1) & 1);
                asm volatile("ld.shared.s32 %0, [%1];" : "=r"(tn) : "r"((bi ^ 8) + 128) : "memory");
                mbar_wait((bs ^ 8) + 48, ((it - 1) >> 1) & 1);
                if (tn < 0) break;
                mbar_wait(bs + 32, (it >> 1) & 1);
            }
            qd = 2 * q_lo + 2048 - qd;
            if (wg == 0) transition(std::integral_constant<int, 0>(), l0, l1); else transition(std::integral_constant<int, 1>(), l0, l1);
            j = 0;
            lrow0 = 0.f; lrow1 = 0.f;
        }
        if (!FA_NOFB && __builtin_expect(__any_sync(0xffffffff, !(l0 + l1 < FA_LIM)), 0)) redo(l0, l1);
        lrow0 += l0; lrow1 += l1;
    }
    wgmma_fence();
    issue_pv(nkv > 1);
    mbar_wait(bar_oe + 8 * wg, (item & 1) ^ 1);
    wgmma_wait<0>();
    mbar_arrive_if((bs ^ 8) + 80, lane0);
    epilogue(t | 0x80000000, true);
    return __shfl_sync(0xffffffff, ~tn * 2 + (item & 1), 0);
}

__device__ __forceinline__ uint32_t cluster_ctarank() {
    uint32_t r; asm volatile("mov.u32 %0, %%cluster_ctarank;" : "=r"(r)); return r;
}
__device__ __forceinline__ uint32_t mapa_u32(uint32_t addr, uint32_t rank) {
    uint32_t r; asm volatile("mapa.shared::cluster.u32 %0, %1, %2;" : "=r"(r) : "r"(addr), "r"(rank)); return r;
}
__device__ __forceinline__ void cluster_sync_all() {
    asm volatile("barrier.cluster.arrive.release.aligned;\nbarrier.cluster.wait.acquire.aligned;" ::: "memory");
}
__device__ __forceinline__ void cluster_sync_relaxed() {
    asm volatile("barrier.cluster.arrive.relaxed.aligned;\nbarrier.cluster.wait.aligned;" ::: "memory");
}
__device__ __forceinline__ void st_async_v4(uint32_t addr, uint32_t a, uint32_t b, uint32_t c, uint32_t d, uint32_t mbar) {
    asm volatile("st.async.weak.shared::cluster.mbarrier::complete_tx::bytes.v4.b32 [%0], {%1, %2, %3, %4}, [%5];"
                 :: "r"(addr), "r"(a), "r"(b), "r"(c), "r"(d), "r"(mbar) : "memory");
}
__device__ __forceinline__ void st_async_v2(uint32_t addr, uint32_t a, uint32_t b, uint32_t mbar) {
    asm volatile("st.async.weak.shared::cluster.mbarrier::complete_tx::bytes.v2.b32 [%0], {%1, %2}, [%3];"
                 :: "r"(addr), "r"(a), "r"(b), "r"(mbar) : "memory");
}
__device__ __forceinline__ void st_async_b32(uint32_t addr, uint32_t a, uint32_t mbar) {
    asm volatile("st.async.weak.shared::cluster.mbarrier::complete_tx::bytes.b32 [%0], %1, [%2];" :: "r"(addr), "r"(a), "r"(mbar) : "memory");
}
__device__ __forceinline__ void pace(int cycles) {
    if (cycles > 0) {
        uint32_t t0, t;
        asm volatile("mov.u32 %0, %%clock;" : "=r"(t0));
        do { asm volatile("mov.u32 %0, %%clock;" : "=r"(t)); } while (t - t0 < (uint32_t)cycles);
    }
}
__device__ __forceinline__ void mbar_wait_cl(uint32_t bar, uint32_t parity) {
    uint32_t done = 0;
    for (int it = 0; it < (1 << 22) && !done; it++) {
        asm volatile(
            "{\n.reg .pred p;\n"
            "mbarrier.try_wait.parity.shared::cta.b64 p, [%1], %2;\n"
            "selp.u32 %0, 1, 0, p;\n}\n" : "=r"(done) : "r"(bar), "r"(parity) : "memory");
    }
}
__device__ __forceinline__ void ldmatrix_x4(uint32_t& r0, uint32_t& r1, uint32_t& r2, uint32_t& r3, uint32_t addr) {
    asm volatile("ldmatrix.sync.aligned.m8n8.x4.shared.b16 {%0,%1,%2,%3}, [%4];"
                 : "=r"(r0), "=r"(r1), "=r"(r2), "=r"(r3) : "r"(addr));
}
__device__ __forceinline__ void cp_async16(uint32_t dst, const void* src) {
    asm volatile("cp.async.cg.shared.global [%0], [%1], 16;" :: "r"(dst), "l"(src) : "memory");
}

#define DBG(i)
#define DBGW(i, w)
#define CYC(i)
#define PM(i)
#define TM(i)
__device__ __forceinline__ void tma_load_2d_mc(uint32_t dst, const CUtensorMap* map, uint32_t bar, int c0, int c1, uint16_t mask) {
    asm volatile(
        "cp.async.bulk.tensor.2d.shared::cluster.global.mbarrier::complete_tx::bytes.multicast::cluster [%0], [%1, {%3, %4}], [%2], %5;"
        :: "r"(dst), "l"((uint64_t)map), "r"(bar), "r"(c0), "r"(c1), "h"(mask) : "memory");
}
__device__ __forceinline__ void tma_load_2d_mc(uint32_t dst, const CUtensorMap* map, uint32_t bar, int c0, int c1, uint16_t mask, uint64_t hint) {
    asm volatile(
        "cp.async.bulk.tensor.2d.shared::cluster.global.mbarrier::complete_tx::bytes.multicast::cluster.L2::cache_hint [%0], [%1, {%3, %4}], [%2], %5, %6;"
        :: "r"(dst), "l"((uint64_t)map), "r"(bar), "r"(c0), "r"(c1), "h"(mask), "l"(hint) : "memory");
}
__device__ __forceinline__ void bulk_s2s(uint32_t dst_cl, uint32_t src, uint32_t bytes, uint32_t bar_cl) {
    asm volatile("cp.async.bulk.shared::cluster.shared::cta.mbarrier::complete_tx::bytes [%0], [%1], %2, [%3];"
                 :: "r"(dst_cl), "r"(src), "r"(bytes), "r"(bar_cl) : "memory");
}
__device__ __forceinline__ bool elect_one() {
    uint32_t p;
    asm volatile("{\n.reg .pred p;\nelect.sync _|p, 0xffffffff;\nselp.u32 %0, 1, 0, p;\n}" : "=r"(p));
    return p;
}
__device__ __forceinline__ void fence_async_smem() { asm volatile("fence.proxy.async.shared::cta;" ::: "memory"); }
template <int ID, int N> __device__ __forceinline__ void bar_sync() { asm volatile("bar.sync %0, %1;" :: "n"(ID), "n"(N) : "memory"); }
template <int ID, int N> __device__ __forceinline__ void bar_arrive() { asm volatile("bar.arrive %0, %1;" :: "n"(ID), "n"(N) : "memory"); }
__device__ __forceinline__ void sts32(uint32_t a, uint32_t v) { asm volatile("st.shared.u32 [%0], %1;" :: "r"(a), "r"(v) : "memory"); }
__device__ __forceinline__ void ldsm_x4(uint32_t* r, uint32_t addr) {
    asm volatile("ldmatrix.sync.aligned.m8n8.x4.shared.b16 {%0,%1,%2,%3}, [%4];" : "=r"(r[0]), "=r"(r[1]), "=r"(r[2]), "=r"(r[3]) : "r"(addr) : "memory");
}
constexpr uint32_t DHI128 = 0x40000040u, DHI32 = 0xC0000010u;
#define ACC16(d) "+f"(d[0]), "+f"(d[1]), "+f"(d[2]), "+f"(d[3]), "+f"(d[4]), "+f"(d[5]), "+f"(d[6]), "+f"(d[7]), "+f"(d[8]), "+f"(d[9]), "+f"(d[10]), \
    "+f"(d[11]), "+f"(d[12]), "+f"(d[13]), "+f"(d[14]), "+f"(d[15])
#define ACC20(d) ACC16(d), "+f"(d[16]), "+f"(d[17]), "+f"(d[18]), "+f"(d[19])
__device__ __forceinline__ void wgmma_rs(float (&d)[16], const uint32_t (&a)[4], uint32_t db_lo) {
    asm volatile(
        "{\n.reg .b64 db;\nmov.b64 db, {%20, %21};\n"
        "wgmma.mma_async.sync.aligned.m64n32k16.f32.bf16.bf16 {%0,%1,%2,%3,%4,%5,%6,%7,%8,%9,%10,%11,%12,%13,%14,%15}, {%16,%17,%18,%19}, db, 1, 1, 1, 0;\n}\n"
        : ACC16(d) : "r"(a[0]), "r"(a[1]), "r"(a[2]), "r"(a[3]), "r"(db_lo), "n"(DHI128));
}
__device__ __forceinline__ void wgmma_rs(float (&d)[20], const uint32_t (&a)[4], uint32_t db_lo) {
    asm volatile(
        "{\n.reg .b64 db;\nmov.b64 db, {%24, %25};\n"
        "wgmma.mma_async.sync.aligned.m64n40k16.f32.bf16.bf16 {%0,%1,%2,%3,%4,%5,%6,%7,%8,%9,%10,%11,%12,%13,%14,%15,%16,%17,%18,%19}, {%20,%21,%22,%23}, db, 1, 1, 1, 0;\n}\n"
        : ACC20(d) : "r"(a[0]), "r"(a[1]), "r"(a[2]), "r"(a[3]), "r"(db_lo), "n"(DHI128));
}
template <uint32_t AHI, uint32_t BHI>
__device__ __forceinline__ void wgmma_ss(float (&d)[16], uint32_t da_lo, uint32_t db_lo) {
    asm volatile(
        "{\n.reg .b64 da, db;\nmov.b64 da, {%16, %18};\nmov.b64 db, {%17, %19};\n"
        "wgmma.mma_async.sync.aligned.m64n32k16.f32.bf16.bf16 {%0,%1,%2,%3,%4,%5,%6,%7,%8,%9,%10,%11,%12,%13,%14,%15}, da, db, 1, 1, 1, 0, 0;\n}\n"
        : ACC16(d) : "r"(da_lo), "r"(db_lo), "n"(AHI), "n"(BHI));
}
template <uint32_t AHI, uint32_t BHI>
__device__ __forceinline__ void wgmma_ss(float (&d)[20], uint32_t da_lo, uint32_t db_lo) {
    asm volatile(
        "{\n.reg .b64 da, db;\nmov.b64 da, {%20, %22};\nmov.b64 db, {%21, %23};\n"
        "wgmma.mma_async.sync.aligned.m64n40k16.f32.bf16.bf16 {%0,%1,%2,%3,%4,%5,%6,%7,%8,%9,%10,%11,%12,%13,%14,%15,%16,%17,%18,%19}, da, db, 1, 1, 1, 0, 0;\n}\n"
        : ACC20(d) : "r"(da_lo), "r"(db_lo), "n"(AHI), "n"(BHI));
}
template <uint32_t AHI, uint32_t BHI>
__device__ __forceinline__ void wgmma_ss0(float (&d)[20], uint32_t da_lo, uint32_t db_lo) {
    asm volatile(
        "{\n.reg .b64 da, db;\nmov.b64 da, {%20, %22};\nmov.b64 db, {%21, %23};\n"
        "wgmma.mma_async.sync.aligned.m64n40k16.f32.bf16.bf16 {%0,%1,%2,%3,%4,%5,%6,%7,%8,%9,%10,%11,%12,%13,%14,%15,%16,%17,%18,%19}, da, db, 0, 1, 1, 0, 0;\n}\n"
        : "=f"(d[0]), "=f"(d[1]), "=f"(d[2]), "=f"(d[3]), "=f"(d[4]), "=f"(d[5]), "=f"(d[6]), "=f"(d[7]), "=f"(d[8]), "=f"(d[9]), "=f"(d[10]),
          "=f"(d[11]), "=f"(d[12]), "=f"(d[13]), "=f"(d[14]), "=f"(d[15]), "=f"(d[16]), "=f"(d[17]), "=f"(d[18]), "=f"(d[19])
        : "r"(da_lo), "r"(db_lo), "n"(AHI), "n"(BHI));
}
__device__ __forceinline__ void wgmma_ss_n8(float (&d)[4], uint32_t da_lo, uint32_t db_lo) {
    asm volatile(
        "{\n.reg .b64 da, db;\nmov.b64 da, {%4, %6};\nmov.b64 db, {%5, %7};\n"
        "wgmma.mma_async.sync.aligned.m64n8k16.f32.bf16.bf16 {%0,%1,%2,%3}, da, db, 1, 1, 1, 1, 0;\n}\n"
        : "+f"(d[0]), "+f"(d[1]), "+f"(d[2]), "+f"(d[3]) : "r"(da_lo), "r"(db_lo), "n"(DHI128), "n"(DHI32));
}

__device__ __forceinline__ void wgmma_ss_n32_ta(float (&d)[16], uint32_t da_lo, uint32_t db_lo) {
    asm volatile(
        "{\n.reg .b64 da, db;\nmov.b64 da, {%16, %18};\nmov.b64 db, {%17, %18};\n"
        "wgmma.mma_async.sync.aligned.m64n32k16.f32.bf16.bf16 {%0,%1,%2,%3,%4,%5,%6,%7,%8,%9,%10,%11,%12,%13,%14,%15}, da, db, 1, 1, 1, 1, 0;\n}\n"
        : ACC16(d) : "r"(da_lo), "r"(db_lo), "n"(DHI128));
}

constexpr int C2_NS = 4;
#define LAY         160, 127, 0, 16, 24, 8, 47, 87, 150, 135, 147, 32, 159, 0, 87, 119
constexpr uint32_t c2_lay(int i) { constexpr uint32_t t[16] = {LAY}; return t[i] * 1024; }
constexpr uint32_t C2_WO = c2_lay(0);
constexpr uint32_t C2_WQ = c2_lay(1), C2_WK = c2_lay(2), C2_WV = c2_lay(3);
constexpr uint32_t C2_OB = c2_lay(4);
constexpr uint32_t C2_QM = c2_lay(5);
constexpr uint32_t C2_SC = C2_QM + 1024;
constexpr uint32_t C2_PB = c2_lay(12) + 320;
#define CH_CS (C2_QM + 4096)
constexpr uint32_t C2_CS = CH_CS;
constexpr uint32_t C2_XB = c2_lay(6), C2_XS = c2_lay(7) - c2_lay(6);
constexpr uint32_t C2_QX = c2_lay(8);
constexpr uint32_t C2_KX = C2_QX + 4096;
constexpr uint32_t C2_VT = c2_lay(9);
constexpr uint32_t C2_PX = c2_lay(10);
constexpr uint32_t C2_SX = c2_lay(11);
constexpr uint32_t C2_BAR = c2_lay(12), C2_S0 = c2_lay(13), C2_S1 = c2_lay(14), C2_S2 = c2_lay(15);
constexpr uint32_t C2_GT = C2_BAR + 320;
constexpr uint32_t C2_T0 = (C2_XB >> 10) * 0x01010101u + 0x18100800u, C2_T1 = ((C2_XB >> 10) + 32) | C2_OB >> 10 << 8 | C2_QM >> 10 << 16 | C2_WQ >> 10 << 24;
__device__ __forceinline__ uint32_t c2_ts(uint32_t r) { return __byte_perm(C2_T0, C2_T1, r) & 0xff; }
constexpr int C2_SMEM = 232448;
#define CH_SPQ 28
#define CH_SPK 0
#define CH_SPV 0
#define CH_EARLY 1
#define CH_ARM 0
#define CH_MB 1
#define CH_TW 1
#define CH_LD 0
#define CH_PT 6000
#define CH_PI 5
#define CH_PF2 0
#define CH_EFW 0
#define CH_TS 1
#define CH_WL 2
#define CH_WU 2
#define CH_PS 0
#define CH_PSZ 16384
#define CH_PSI 0
#define CH_WR 5
#define CH_WOT 1
#define CH_NCH 4
#define CH_NQ1 12
#define CH_XO 4096
#define CH_POLL_DELAY 478

__device__ __forceinline__ uint32_t c2_stage(int wg, int i) { return (wg == 0 ? C2_S0 : wg == 1 ? C2_S1 : C2_S2) + i * 8192; }
__device__ __forceinline__ void c2_stage_load(const CUtensorMap* map, uint32_t sb, int wg, int rank, int col0, int i) {
    const uint32_t bar = sb + C2_BAR + 176 + (wg * 4 + (i & 3)) * 8;
    mbar_expect_tx(bar, 8192);
    tma_load_2d(sb + c2_stage(wg, i & 3), map, bar, col0, ((rank - i) & 7) * 64);
}
__device__ __forceinline__ uint32_t lds32(uint32_t a) { uint32_t v; asm volatile("ld.shared.b32 %0, [%1];" : "=r"(v) : "r"(a) : "memory"); return v; }
__device__ __forceinline__ void c2_wo(uint32_t sb, int t, int n) {
    mbar_wait(sb + C2_BAR + 168, 0);
    constexpr int U = CH_WU;
#pragma unroll U
    for (int i = t; i < 2048; i += n) {
        const int k = i >> 2, b = i & 3;
        const uint32_t a0 = sb + C2_WO + k * 128 + (((2 * b) ^ (k & 7)) << 4), a1 = a0 ^ 16;
        uint4 u, v;
        asm volatile("ld.shared.v4.b32 {%0, %1, %2, %3}, [%4];" : "=r"(u.x), "=r"(u.y), "=r"(u.z), "=r"(u.w) : "r"(a0) : "memory");
        asm volatile("ld.shared.v4.b32 {%0, %1, %2, %3}, [%4];" : "=r"(v.x), "=r"(v.y), "=r"(v.z), "=r"(v.w) : "r"(a1) : "memory");
        asm volatile("st.shared.v4.b32 [%0], {%1, %2, %3, %4};" :: "r"(a0), "r"(__byte_perm(u.x, u.y, 0x5410)),
                     "r"(__byte_perm(u.z, u.w, 0x5410)), "r"(__byte_perm(v.x, v.y, 0x5410)), "r"(__byte_perm(v.z, v.w, 0x5410)) : "memory");
        asm volatile("st.shared.v4.b32 [%0], {%1, %2, %3, %4};" :: "r"(a1), "r"(__byte_perm(u.x, u.y, 0x7632)),
                     "r"(__byte_perm(u.z, u.w, 0x7632)), "r"(__byte_perm(v.x, v.y, 0x7632)), "r"(__byte_perm(v.z, v.w, 0x7632)) : "memory");
    }
}
__device__ __forceinline__ void c2_load_w(uint32_t (&w)[32][4], const CUtensorMap* map, const CUtensorMap* mapWo, int wg, int rank, int col0, uint32_t t128, uint32_t ws, uint32_t sb) {
    const uint32_t s0 = pin(sb + c2_stage(wg, 0) + t128), s1 = pin(sb + c2_stage(wg, 0) + (t128 ^ 16) + 128);
#pragma unroll
    for (int r = 0; r < 8; r++) {
        mbar_wait(sb + C2_BAR + 176 + (wg * 4 + (r & 3)) * 8, r >> 2);
        if (r == 0) PM(2);
        if (r == 3) PM(3);
        if (r == 7) PM(4);
#pragma unroll
        for (int e = (r & 3) * 4; e < (r & 3) * 4 + 4; e++) {
            uint32_t w0, w1, w2, w3;
            asm volatile("ld.shared.b32 %0, [%1];" : "=r"(w0) : "r"(s0 + e * 2048) : "memory");
            asm volatile("ld.shared.b32 %0, [%1];" : "=r"(w1) : "r"(s1 + e * 2048) : "memory");
            asm volatile("ld.shared.b32 %0, [%1];" : "=r"(w2) : "r"(s0 + e * 2048 + 1024) : "memory");
            asm volatile("ld.shared.b32 %0, [%1];" : "=r"(w3) : "r"(s1 + e * 2048 + 1024) : "memory");
            uint32_t* d = w[(r >> 2) * 16 + e];
            d[0] = __byte_perm(w0, w1, 0x5410); d[1] = __byte_perm(w0, w1, 0x7632);
            d[2] = __byte_perm(w2, w3, 0x5410); d[3] = __byte_perm(w2, w3, 0x7632);
        }
        if (r < 4) asm volatile("bar.sync %0, 128;" :: "r"(8 + wg) : "memory");
        if ((threadIdx.x & 96) == 32 && elect_one()) {
            if (r < 4) c2_stage_load(map, sb, wg, rank, col0, r + 4);
            const int j = wg + (r - CH_WR) * 3;
            if (r >= CH_WR && j < 8) tma_load_2d(sb + C2_WO + j * 8192, mapWo, sb + C2_BAR + 168, rank * 64, (blockIdx.x >> 3) * 512 + ((rank - j) & 7) * 64);
        }
    }
    PM(5);
    cluster_sync_relaxed();
    PM(6);
#pragma unroll
    for (int e = 0; e < C2_NS; e++) stmatrix_x4(ws + e * 2048, w[e][0], w[e][1], w[e][2], w[e][3]);
#pragma unroll 1
    for (int i = threadIdx.x; i < 2 * 512 + 256; i += 384)
        sts32(sb + (i < 1024 ? C2_VT + (i >> 9) * 6144 + 4096 + (i & 511) * 4 : C2_PX + 2048 + (i - 1024) * 4), 0u);
    fence_async_smem();
    asm volatile("bar.sync %0, 128;" :: "r"(8 + wg) : "memory");
}
template <int E0, int E1, int SP, int NA>
__device__ __forceinline__ void c2_xstream(float (&acc)[NA], const uint32_t (&w)[32][4], uint32_t xlo, uint32_t rank, uint32_t wslo) {
    if (E0 == 0)
#pragma unroll
        for (int i = 0; i < NA; i++) acc[i] = 0.f;
    wgmma_fence();
#pragma unroll
    for (int n = E0; n < E1; n++) {
        const int e = n < SP ? n + C2_NS : n < SP + C2_NS ? n - SP : n;
        if (e < C2_NS) wgmma_ss<DHI32, DHI128>(acc, wslo + e * 128, xlo + ((rank - (e >> 2)) & 7) * 320 + (e & 3) * 2);
        else wgmma_rs(acc, w[e], xlo + ((rank - (e >> 2)) & 7) * 320 + (e & 3) * 2);
    }
    wgmma_commit();
}
__device__ __forceinline__ constexpr int c2_grp(int i) { return i < 2 ? i : 1 + (i >> 1); }

struct ChainParams {
    CUtensorMap mapX;
    CUtensorMap mapM;
    CUtensorMap mapW[3];
    CUtensorMap mapWo;
    CUtensorMap mapC;
    CUtensorMap mapS;
    bf16* out;
    char* xb;
};
__global__ void __cluster_dims__(8, 1, 1) __launch_bounds__(384, 1)
chain_kernel(const __grid_constant__ ChainParams P) {
    const CUtensorMap& mapX = P.mapX;
    extern __shared__ __align__(1024) uint8_t smem_chain[];
    const uint32_t sb = smem_u32(smem_chain);
    const uint32_t dlo = ((sb & 0x3FFFF) >> 4) | (1u << 16);
    const int tid = __shfl_sync(0xffffffff, threadIdx.x, threadIdx.x & 31), lane = tid & 31;
    const int warp = __shfl_sync(0xffffffff, tid >> 5, 0), wg = warp >> 2, w4 = warp & 3;
    const uint32_t rank = cluster_ctarank();
    const int C = blockIdx.x >> 3;
    const int h = C * 4 + (rank >> 1);
    const int g = lane >> 2, qc = lane & 3;
    pdl_launch_dependents();
    TS_BEGIN(2);
    CYC(0);
    PM(0);
    const uint32_t bar_m = sb + C2_BAR, bar_o = bar_m + 64, bar_sc = bar_m + 128, bar_x = bar_m + 136, bar_sx = bar_m + 152;
    const uint32_t bar_w = bar_m + 168, bar_h = bar_m + 40;
    const int col0 = h * HD + (rank & 1) * 64;
    if (lane < 3) {
        const uint32_t n = lane * 12 + warp;
        if (n < 34) mbar_init(bar_m + 8 * n, n == 5 ? 32 : (n & ~8) == 0 ? 4 : 1);
        asm volatile("fence.mbarrier_init.release.cluster;" ::: "memory");
    }
    __syncwarp();
    cluster_sync_relaxed();
    PM(1);
    if (tid == 0) {
        mbar_expect_tx(bar_x, 32768 + 8192);
        tma_load_2d_mc(sb + C2_XB + rank * 5120, &mapX, bar_x, rank * 64, 0, (uint16_t)0xff);
#pragma unroll 1
        for (int j = 0; j < 8; j++) tma_load_2d(sb + C2_XB + j * 5120 + 4096, &P.mapM, bar_x, j * 64, 0);
        mbar_expect_tx(bar_w, 65536);
    }
    if ((tid & 127) == 32) {
#pragma unroll 1
        for (int i = 0; i < 4; i++) {
            c2_stage_load(&P.mapW[wg], sb, wg, rank, col0, i);
            if (i == CH_PI) pace(CH_PT);
        }
    }
    __syncwarp();

    const uint32_t t32 = w4 * 256 + qc * 64 + (((g >> 2) ^ (qc >> 1)) << 4) + (g & 3) * 4;
    const uint32_t t128 = qc * 256 + (((2 * w4 + (g >> 2)) ^ (2 * qc)) << 4) + (g & 3) * 4;
    const uint32_t a32 = (w4 * 16 + (lane & 15)) * 32 + (((lane >> 4) ^ ((lane >> 2) & 1)) << 4);
    const uint32_t ws = sb + (wg == 0 ? C2_WQ : wg == 1 ? C2_WK : C2_WV) + a32;
    uint32_t w[32][4];
    static_assert(C2_NS == 4, "slot 0");
    auto proj_mem = [&](float (&a)[CH_NCH][4], int s, uint32_t l128) {
        uint32_t b[4][8];
#pragma unroll
        for (int i = 0; i < 4 * CH_NCH; i++) a[i >> 2][i & 3] = 0.f;
        const uint32_t par = (s & 1) ^ 1;
        const uint32_t mb = sb + C2_XB + (s & 1) * C2_XS + 4096;
        auto L = [&](int i) {
            ldsm_x4(b[i & 3], mb + ((rank - i) & 7) * 5120 + l128);
            ldsm_x4(b[i & 3] + 4, mb + ((rank - i) & 7) * 5120 + (l128 ^ 64));
        };
        auto H = [&](int i) {
#pragma unroll
            for (int kk = 0; kk < 4; kk++) {
                const uint32_t* f = i ? w[i * 4 + kk] : &b[2 + (kk >> 1)][(kk & 1) * 4];
                mma_16816(a[(i * 4 + kk) % CH_NCH], f[0], f[1], f[2], f[3], b[i & 3][2 * kk], b[i & 3][2 * kk + 1]);
            }
        };
#pragma unroll
        for (int e = 0; e < 4; e++) ldsm_x4(&b[2 + (e >> 1)][(e & 1) * 4], ws + e * 2048);
        mbar_wait(bar_m, par);
        L(0);
        H(0);
        mbar_wait(bar_m + 8, par);
        DBGW(1 + 16 * wg, 0);
        L(1);
        mbar_wait(bar_m + 16, par);
        uint32_t nxt = mbar_test(bar_m + 24, par);
        L(2); L(3);
        H(1);
        if (__builtin_expect(!nxt, 0)) mbar_wait(bar_m + 24, par);
        nxt = mbar_test(bar_m + 32, par);
        L(4); L(5);
        H(2); H(3);
        if (__builtin_expect(!nxt, 0)) mbar_wait(bar_m + 32, par);
        DBGW(2 + 16 * wg, 0);
        L(6); L(7);
        H(4); H(5); H(6); H(7);
#pragma unroll
        for (int i = 0; i < 4; i++) a[0][i] = CH_NCH == 4 ? (a[0][i] + a[1][i]) + (a[2][i] + a[3 % CH_NCH][i]) : CH_NCH == 3 ? a[0][i] + a[1][i] + a[2 % CH_NCH][i] : a[0][i] + a[1][i];
    };
    auto store_x = [&](const float (&acc)[16], uint32_t base) {
#pragma unroll
        for (int j = 0; j < 4; j++) {
            sts32(base + t128 + j * 1024, pack_bf16(acc[4 * j], acc[4 * j + 2]));
            sts32(base + (t128 ^ 16) + 128 + j * 1024, pack_bf16(acc[4 * j + 1], acc[4 * j + 3]));
        }
    };
    auto fresh_lane = [&]() { uint32_t l; asm volatile("mov.u32 %0, %%laneid;" : "=r"(l)); return l; };
    const float scale = 0.08838834764831845f, l2e = 1.4426950408889634f;
    c2_load_w(w, &P.mapW[wg], &P.mapWo, wg, rank, col0, t128, ws, sb);
    TS_END(6);
    TS_BEGIN(5);
    CYC(1);
    PM(7);

    if (wg == 0) {
#pragma unroll 1
        for (int s = -1;;) {
            float qx[16];
            uint32_t* dst = reinterpret_cast<uint32_t*>(P.xb + ((s & 1) * 32768 + rank * 65536 + CH_XO + C * 1024 + (qc * 64 + w4 * 8 + g) * 4));
            asm volatile("" : "+l"(dst));
            mbar_wait(bar_x + 8 * ((s + 1) & 1), ((s + 1) >> 1) & 1);
            if (s >= 0) bar_sync<6, 384>();
            c2_xstream<0, CH_NQ1, CH_SPQ>(qx, w, dlo + ((C2_XB + ((s + 1) & 1) * C2_XS) >> 4), rank, dlo + (C2_WQ >> 4));
            if (s >= 0) {
                float acc[4] = {0.f, 0.f, 0.f, 0.f};
                const uint32_t tag = ((s >> 1) & 1) ^ 1;
                uint32_t nxt = 0;
#pragma unroll
                for (int i = 0; i < 8; i++) {
                    if (i < 2 || !(i & 1)) {
                        if (i < 2 || __builtin_expect(!nxt, 0)) mbar_wait(bar_o + 8 * c2_grp(i), s & 1);
                        if (i == 0) DBGW(7, 0);
                        if (i == 1) DBGW(8, 0);
                        if (i == 6) DBGW(9, 0);
                        wgmma_fence();
                    }
#pragma unroll
                    for (int kk = 0; kk < 4; kk++) {
                        if ((i & 1) && i < 7 && kk == CH_WOT) nxt = mbar_test(bar_o + 8 * c2_grp(i + 1), s & 1);
                        wgmma_ss_n8(acc, dlo + ((C2_WO + i * 8192 + kk * 2048) >> 4), dlo + ((C2_OB + i * 1024 + kk * 256) >> 4));
                    }
                }
                wgmma_commit();
                bar_arrive<11, 256>();
                wgmma_wait<0>();
                asm volatile("st.relaxed.gpu.global.u32 [%0], %1;" :: "l"(dst), "r"((pack_bf16(acc[0], acc[2]) & ~1u) | tag) : "memory");
                asm volatile("st.relaxed.gpu.global.u32 [%0 + 128], %1;" :: "l"(dst), "r"((pack_bf16(acc[1], acc[3]) & ~1u) | tag) : "memory");
                bar_arrive<4, 256>();
                DBGW(10, 0);
            }
            s++;
            c2_xstream<CH_NQ1, 32, CH_SPQ>(qx, w, dlo + ((C2_XB + (s & 1) * C2_XS) >> 4), rank, dlo + (C2_WQ >> 4));
            const uint32_t sca = pin(w4 < 2 ? sb + C2_SC + w4 * 512 + lane * 16 : sb + C2_SC + 1024 + lane * 8);
            const uint32_t krow = w4 * 16 + (lane & 15);
            const uint32_t ka0 = pin(sb + C2_KX + krow * 128 + (((lane >> 4) ^ (krow & 7)) << 4));
            const uint32_t l32 = pin(sb + C2_QM + (lane >> 4) * 256 + (lane & 7) * 32 + ((((lane >> 3) & 1) ^ ((lane >> 2) & 1)) << 4));
            const uint32_t qst = pin(sb + C2_QM + t32);
            const uint32_t l128 = pin((lane & 7) * 128 + (((lane >> 3) ^ (lane & 7)) << 4));
            if (s > 0) bar_sync<5, 256>();
            wgmma_wait<0>();
            store_x(qx, sb + C2_QX);
            DBGW(0, 0);
            if (s == NSEG - 1) break;
            {
                float a[CH_NCH][4];
                proj_mem(a, s, l128);
                sts32(qst, pack_bf16(a[0][0], a[0][2]));
                sts32(qst + 32, pack_bf16(a[0][1], a[0][3]));
            }
            DBGW(3, 0);
            if (w4 < 3) {
                uint32_t ka[4][4], qb[8];
                float c[4] = {0.f, 0.f, 0.f, 0.f}, c2[4] = {0.f, 0.f, 0.f, 0.f};
                const uint32_t sc_peer = pin(mapa_u32(sca + 1280, rank ^ 1)), sc_own = pin(mapa_u32(sca, rank));
                bar_sync<1, 384>();
                ldsm_x4(qb, l32);
                ldsm_x4(ka[0], ka0);
                ldsm_x4(ka[1], ka0 ^ 32);
                ldsm_x4(qb + 4, l32 + 512);
                ldsm_x4(ka[2], ka0 ^ 64);
                ldsm_x4(ka[3], ka0 ^ 96);
                mma_16816(c, ka[0][0], ka[0][1], ka[0][2], ka[0][3], qb[0], qb[1]);
                mma_16816(c2, ka[1][0], ka[1][1], ka[1][2], ka[1][3], qb[2], qb[3]);
                mma_16816(c, ka[2][0], ka[2][1], ka[2][2], ka[2][3], qb[4], qb[5]);
                mma_16816(c2, ka[3][0], ka[3][1], ka[3][2], ka[3][3], qb[6], qb[7]);
                const uint32_t u0 = __float_as_uint(c[0] + c2[0]), u1 = __float_as_uint(c[1] + c2[1]);
                const uint32_t u2 = __float_as_uint(c[2] + c2[2]), u3 = __float_as_uint(c[3] + c2[3]);
                asm volatile(
                    "{\n.reg .pred p;\nsetp.lt.u32 p, %8, 2;\n"
                    "@p st.async.weak.shared::cluster.mbarrier::complete_tx::bytes.v4.b32 [%0], {%4, %5, %6, %7}, [%1];\n"
                    "@!p st.async.weak.shared::cluster.mbarrier::complete_tx::bytes.v2.b32 [%0], {%4, %5}, [%1];\n"
                    "@p st.async.weak.shared::cluster.mbarrier::complete_tx::bytes.v4.b32 [%2], {%4, %5, %6, %7}, [%3];\n"
                    "@!p st.async.weak.shared::cluster.mbarrier::complete_tx::bytes.v2.b32 [%2], {%4, %5}, [%3];\n}"
                    :: "r"(sc_peer), "r"(mapa_u32(bar_sc, rank ^ 1)), "r"(sc_own), "r"(mapa_u32(bar_sc, rank)), "r"(u0), "r"(u1), "r"(u2), "r"(u3), "r"(w4) : "memory");
                bar_arrive<2, 224>();
                fence_async_smem();
                __syncwarp();
                DBGW(4, 2);
            } else {
                bar_arrive<1, 384>();
                fence_async_smem();
                const uint32_t a = pin(sb + C2_SC + lane * 16), a2 = pin(sb + C2_SC + 1024 + lane * 8), pa = pin(sb + C2_PB + lane * 4);
                mbar_wait(bar_sc, s & 1);
                DBG(5);
                float v[10];
                {
                    float4 x0, x1, y0, y1; float2 x2, y2;
                    asm volatile("ld.shared.v4.f32 {%0, %1, %2, %3}, [%4];" : "=f"(x0.x), "=f"(x0.y), "=f"(x0.z), "=f"(x0.w) : "r"(a) : "memory");
                    asm volatile("ld.shared.v4.f32 {%0, %1, %2, %3}, [%4];" : "=f"(y0.x), "=f"(y0.y), "=f"(y0.z), "=f"(y0.w) : "r"(a + 1280) : "memory");
                    asm volatile("ld.shared.v4.f32 {%0, %1, %2, %3}, [%4];" : "=f"(x1.x), "=f"(x1.y), "=f"(x1.z), "=f"(x1.w) : "r"(a + 512) : "memory");
                    asm volatile("ld.shared.v4.f32 {%0, %1, %2, %3}, [%4];" : "=f"(y1.x), "=f"(y1.y), "=f"(y1.z), "=f"(y1.w) : "r"(a + 1792) : "memory");
                    asm volatile("ld.shared.v2.f32 {%0, %1}, [%2];" : "=f"(x2.x), "=f"(x2.y) : "r"(a2) : "memory");
                    asm volatile("ld.shared.v2.f32 {%0, %1}, [%2];" : "=f"(y2.x), "=f"(y2.y) : "r"(a2 + 1280) : "memory");
                    v[0] = x0.x + y0.x; v[1] = x0.y + y0.y; v[2] = x0.z + y0.z; v[3] = x0.w + y0.w;
                    v[4] = x1.x + y1.x; v[5] = x1.y + y1.y; v[6] = x1.z + y1.z; v[7] = x1.w + y1.w;
                    v[8] = x2.x + y2.x; v[9] = x2.y + y2.y;
                }
                float m0 = fmaxf(fmaxf(fmaxf(v[0], v[2]), fmaxf(v[4], v[6])), v[8]);
                float m1 = fmaxf(fmaxf(fmaxf(v[1], v[3]), fmaxf(v[5], v[7])), v[9]);
#pragma unroll
                for (int o = 4; o < 32; o <<= 1) {
                    m0 = fmaxf(m0, __shfl_xor_sync(0xffffffff, m0, o));
                    m1 = fmaxf(m1, __shfl_xor_sync(0xffffffff, m1, o));
                }
                const float sl = scale * l2e;
                m0 *= sl; m1 *= sl;
#pragma unroll
                for (int j = 0; j < 5; j++)
                    sts32(pa + j * 128, pack_bf16(ex2f(fmaf(v[2 * j], sl, -m0)), ex2f(fmaf(v[2 * j + 1], sl, -m1))));
                bar_arrive<3, 160>();
                DBG(6);
            }
        }
        bar_arrive<1, 384>();
        fence_async_smem();
        bar_arrive<6, 384>();
        TS_MARK(8, 0);
        CYC(2);
        TM(0);
        const uint32_t lane = fresh_lane();
        pace(CH_LD);
        {
            const uint32_t a = sb + C2_WO + ((lane >> 4) * 8 + (lane & 7)) * 128 + (((2 * w4 + ((lane >> 3) & 1)) ^ (lane & 7)) << 4);
#pragma unroll
            for (int e = C2_NS; e < 32; e++)
                asm volatile("ldmatrix.sync.aligned.m8n8.x4.trans.shared.b16 {%0,%1,%2,%3}, [%4];" : "=r"(w[e][0]), "=r"(w[e][1]), "=r"(w[e][2]), "=r"(w[e][3]) : "r"(a + e * 2048) : "memory");
        }
        fence_async_smem();
        if (CH_TS && w4 == 0) bar_sync<12, 160>();
        if (lane < 8) asm volatile("mbarrier.arrive.relaxed.cluster.shared::cluster.b64 _, [%0];" :: "r"(mapa_u32(bar_h, lane)) : "memory");
        __syncwarp();
        TM(9);
        if (w4 == 0) {
            if (!CH_TS) bar_sync<12, 160>();
            if (!CH_TS) asm volatile("fence.acq_rel.gpu;" ::: "memory");
            if (!CH_TS) asm volatile("fence.proxy.async.global;" ::: "memory");
            mbar_wait(bar_h, 0);
            if (elect_one()) tma_load_2d_mc(sb + c2_ts(rank) * 1024, &P.mapC, bar_x, (rank & 1) * 64, h * SEQ + SEQ - 128, (uint16_t)0xff);
            __syncwarp();
            TM(10);
        }
        if (w4 == 1) {
            wait_ctr(CT_P, FA_GRID);
            float4 v;
            asm volatile("ld.relaxed.gpu.global.v4.f32 {%0, %1, %2, %3}, [%4];" : "=f"(v.x), "=f"(v.y), "=f"(v.z), "=f"(v.w) : "l"(g_gate + SEQ - 128 + lane * 4) : "memory");
            asm volatile("st.shared.v4.f32 [%0], {%1, %2, %3, %4};" :: "r"(sb + C2_GT + lane * 16), "f"(1.f - v.x), "f"(1.f - v.y), "f"(1.f - v.z), "f"(1.f - v.w) : "memory");
            __syncwarp();
            if (lane == 0) mbar_expect_tx(bar_x, 65536);
            finish_launch(lane);
        }
        uint32_t* dst = reinterpret_cast<uint32_t*>(P.out + (SEQ - 128 + 2 * (lane & 3)) * DM + rank * 64 + w4 * 16) + (lane >> 2);
#pragma unroll 1
        for (uint32_t q = 0; q < 4; q++, dst += 16 * DM) {
            float acc[16], gt[8];
#pragma unroll
            for (int i = 0; i < 16; i++) acc[i] = 0.f;
            const uint32_t bar = q < 2 ? bar_x : bar_m - 128 + q * 64, db = dlo + (q & 1) * 256;
#pragma unroll
            for (int i = 0; i < 8; i++) {
                if (i == 0 || (CH_TW && (i == 1 || !(i & 1)))) {
                    if (i == 0 || q > 1) mbar_wait(bar + 8 * c2_grp(i), q >> 1);
                    if (!CH_TW && q > 1)
#pragma unroll 1
                        for (uint32_t j = 8; j < 40; j += 8) mbar_wait(bar + j, 1);
                    if (i == 0) TM(13 + q);
                    wgmma_fence();
                }
                if (i == 6) TM(25 + q);
                const uint32_t d = db + (q < 2 ? c2_ts((rank - i) & 7) * 64 : (i ? C2_WO + i * 8192 : C2_QX) >> 4);
#pragma unroll
                for (int kk = 0; kk < 4; kk++) {
                    if (i == 0) wgmma_ss_n32_ta(acc, dlo + ((C2_WO + kk * 2048) >> 4), d + kk * 2);
                    else wgmma_rs(acc, w[i * 4 + kk], d + kk * 2);
                }
            }
            wgmma_commit();
            if (q == 3) asm volatile("barrier.cluster.arrive.relaxed.aligned;" ::: "memory");
#pragma unroll
            for (int j = 0; j < 4; j++)
                asm volatile("ld.shared.v2.f32 {%0, %1}, [%2];" : "=f"(gt[2 * j]), "=f"(gt[2 * j + 1]) : "r"(sb + C2_GT + q * 128 + (lane & 3) * 8 + j * 32) : "memory");
            wgmma_wait<0>();
#pragma unroll
            for (int j = 0; j < 8; j++)
                asm volatile("red.relaxed.gpu.global.add.noftz.bf16x2 [%0], %1;" :: "l"(dst + ((j >> 1) * 8 + (j & 1)) * (DM / 2)),
                             "r"(pack_bf16(acc[(j >> 1) * 4 + (j & 1)] * gt[j], acc[(j >> 1) * 4 + (j & 1) + 2] * gt[j])) : "memory");
            TS_MARK(9 + q, 0);
            TM(17 + q);
        }
    } else if (wg == 1) {
        bool early = false;
#pragma unroll 1
        for (int s = -1;;) {
            if (s > 0 && (!CH_EARLY || s != NSEG - 1 || early)) {
                mbar_wait(bar_sx + 8 * ((s - 1) & 1), ((s - 1) >> 1) & 1);
                const uint32_t a = sb + C2_SX + w4 * 1280 + lane * 8, ap = a + 10240 - (s & 1) * 5120;
                float v[10];
                const int lim = 8 * w4 + g - 2 * qc;
#pragma unroll
                for (int j = 0; j < 5; j++) {
                    float2 x, y;
                    asm volatile("ld.shared.v2.f32 {%0, %1}, [%2];" : "=f"(x.x), "=f"(x.y) : "r"(a + j * 256) : "memory");
                    asm volatile("ld.shared.v2.f32 {%0, %1}, [%2];" : "=f"(y.x), "=f"(y.y) : "r"(ap + j * 256) : "memory");
                    v[2 * j] = (j < 4 && 8 * j > lim) ? -INFINITY : x.x + y.x;
                    v[2 * j + 1] = (j < 4 && 8 * j + 1 > lim) ? -INFINITY : x.y + y.y;
                }
                float mx = fmaxf(fmaxf(fmaxf(v[0], v[1]), fmaxf(v[2], v[3])), fmaxf(fmaxf(v[4], v[5]), fmaxf(v[6], v[7])));
                mx = fmaxf(mx, fmaxf(v[8], v[9]));
                mx = fmaxf(mx, __shfl_xor_sync(0xffffffff, mx, 1));
                mx = fmaxf(mx, __shfl_xor_sync(0xffffffff, mx, 2));
                const float sl = scale * l2e;
                mx *= sl;
#pragma unroll
                for (int j = 0; j < 10; j++) v[j] = ex2f(fmaf(v[j], sl, -mx));
                float sm = ((v[0] + v[1]) + (v[2] + v[3])) + ((v[4] + v[5]) + (v[6] + v[7])) + (v[8] + v[9]);
                sm += __shfl_xor_sync(0xffffffff, sm, 1);
                sm += __shfl_xor_sync(0xffffffff, sm, 2);
                float inv;
                asm("rcp.approx.ftz.f32 %0, %1;" : "=f"(inv) : "f"(sm));
                const uint32_t pa = sb + C2_PX + w4 * 256 + g * 32 + ((g >> 2) << 4) + qc * 4;
#pragma unroll
                for (int j = 0; j < 5; j++) sts32((pa ^ ((j & 1) << 4)) + (j >> 1) * 1024, pack_bf16(v[2 * j] * inv, v[2 * j + 1] * inv));
            }
            if (!early) {
            if (s >= 0) {
                fence_async_smem();
                if (s < NSEG) bar_sync<6, 384>(); else bar_sync<7, 256>();
                DBGW(20, 0);
                TM(s < NSEG ? 2 : 11);
                uint32_t cp[8];
                {
                    float cx[16];
#pragma unroll
                    for (int i = 0; i < 16; i++) cx[i] = 0.f;
                    wgmma_fence();
#pragma unroll
                    for (int kk = 0; kk < 3; kk++)
                        wgmma_ss<DHI32, DHI32>(cx, dlo + ((C2_VT + ((s - 1) & 1) * 6144 + kk * 2048) >> 4), dlo + ((C2_PX + kk * 1024) >> 4));
                    wgmma_commit();
                    wgmma_wait<0>();
#pragma unroll
                    for (int j = 0; j < 4; j++) { cp[2 * j] = pack_bf16(cx[4 * j], cx[4 * j + 2]); cp[2 * j + 1] = pack_bf16(cx[4 * j + 1], cx[4 * j + 3]); }
                    asm volatile("{\n.reg .pred p;\nsetp.gt.u32 p, %0, 99;\n@p st.shared.v4.b32 [%0], {%1, %2, %3, %4};\n@p st.shared.v4.b32 [%0], {%5, %6, %7, %8};\n}"
                                 :: "r"(rank), "r"(cp[0]), "r"(cp[1]), "r"(cp[2]), "r"(cp[3]), "r"(cp[4]), "r"(cp[5]), "r"(cp[6]), "r"(cp[7]) : "memory");
                }
                if (s < NSEG) {
                    float sx[20];
                    wgmma_fence();
                    wgmma_ss0<DHI128, DHI128>(sx, dlo + (C2_QX >> 4), dlo + (C2_KX >> 4));
#pragma unroll
                    for (int kk = 1; kk < 4; kk++) wgmma_ss<DHI128, DHI128>(sx, dlo + (C2_QX >> 4) + kk * 2, dlo + (C2_KX >> 4) + kk * 2);
                    wgmma_commit();
                    wgmma_wait<0>();
                    if (s < NSEG - 1) bar_arrive<5, 256>();
                    if (CH_TS && s > 0 && s < NSEG - 1) {
                        const uint32_t a = sb + C2_CS + w4 * 1024;
#pragma unroll
                        for (int j = 0; j < 8; j++) sts32(a + qc * 64 + g * 4 + (j >> 1) * 256 + (j & 1) * 32, cp[j]);
                        fence_async_smem();
                        __syncwarp();
                        if (elect_one()) tma_store_2d(&P.mapS, a, (rank & 1) * 64 + w4 * 16, h * SEQ + (s - 1) * SEGL);
                        asm volatile("cp.async.bulk.commit_group;" ::: "memory");
                    }
                    if (!CH_TS && s > 0 && s < NSEG - 1) {
                        uint32_t* dst = reinterpret_cast<uint32_t*>(g_ctxB + ((size_t)h * SEQ + (s - 1) * SEGL + 2 * qc) * HD + (rank & 1) * 64 + w4 * 16 + 2 * g);
#pragma unroll
                        for (int j = 0; j < 4; j++) {
                            asm volatile("st.global.u32 [%0], %1;" :: "l"(dst + j * 8 * (HD / 2)), "r"(cp[2 * j]) : "memory");
                            asm volatile("st.global.u32 [%0], %1;" :: "l"(dst + (j * 8 + 1) * (HD / 2)), "r"(cp[2 * j + 1]) : "memory");
                        }
                    }
                    DBGW(22, 0);
                    TM(3);
                    if (!CH_TS && s == NSEG - 2) bar_arrive<12, 160>();
                    const uint32_t a = sb + C2_SX + w4 * 2560 + lane * 8;
                    if (w4 < 2) {
#pragma unroll
                        for (int j = 0; j < 5; j++) {
                            asm volatile("st.shared.v2.f32 [%0], {%1, %2};" :: "r"(a + j * 256), "f"(sx[4 * j]), "f"(sx[4 * j + 1]) : "memory");
                            asm volatile("st.shared.v2.f32 [%0], {%1, %2};" :: "r"(a + 1280 + j * 256), "f"(sx[4 * j + 2]), "f"(sx[4 * j + 3]) : "memory");
                        }
                    }
                    if (s < NSEG - 1) mbar_wait(bar_x + 8 * ((s + 1) & 1), ((s + 1) >> 1) & 1);
                    const uint32_t pa = mapa_u32(a + 5120 + (s & 1) * 5120, rank ^ 1), pb = mapa_u32(bar_sx + 8 * (s & 1), rank ^ 1);
                    if (s < NSEG - 1) bar_sync<4, 256>(); else bar_sync<9, 128>();
                    if (w4 < 2) {
#pragma unroll
                        for (int j = 0; j < 5; j++) {
                            st_async_v2(pa + j * 256, __float_as_uint(sx[4 * j]), __float_as_uint(sx[4 * j + 1]), pb);
                            st_async_v2(pa + 1280 + j * 256, __float_as_uint(sx[4 * j + 2]), __float_as_uint(sx[4 * j + 3]), pb);
                        }
                    }
                }
                if (s >= NSEG - 1) {
                    const uint32_t a = sb + C2_QX + 4096 - (s & 1) * 4096;
#pragma unroll
                    for (int j = 0; j < 4; j++) {
                        sts32(a + t128 + j * 1024, cp[2 * j]);
                        sts32(a + (t128 ^ 16) + 128 + j * 1024, cp[2 * j + 1]);
                    }
                    fence_async_smem();
                    asm volatile("bar.arrive %0, 160;" :: "r"(s - NSEG + 14) : "memory");
                    TM(s - NSEG + 6);
                    if (s == NSEG) break;
                }
            } else mbar_wait(bar_x, 0);
            s++;
            if (s < NSEG) {
                float acc[16];
                c2_xstream<0, 32, CH_SPK>(acc, w, dlo + ((C2_XB + (s & 1) * C2_XS) >> 4), rank, dlo + (C2_WK >> 4));
                wgmma_wait<0>();
                store_x(acc, sb + C2_KX);
                DBGW(16, 0);
            }
            if (CH_EARLY && s == NSEG - 1) {
                if (CH_TS) {
                    asm volatile("cp.async.bulk.wait_group 0;" ::: "memory");
                    bar_arrive<12, 160>();
                }
                early = true;
                continue;
            }
            }
            early = false;
            if (s < NSEG) TM(4);
            if (s < NSEG) {
                const uint32_t kst = pin(sb + C2_KX + 4096 + t128);
                const uint32_t l128 = pin((lane & 7) * 128 + (((lane >> 3) ^ (lane & 7)) << 4));
                float a[CH_NCH][4];
                proj_mem(a, s, l128);
                sts32(kst, pack_bf16(a[0][0], a[0][2]));
                sts32((kst ^ 16) + 128, pack_bf16(a[0][1], a[0][3]));
                bar_arrive<1, 384>();
                TM(1);
                DBGW(19, 0);
                if (CH_TS) {
                    asm volatile("cp.async.bulk.wait_group 0;" ::: "memory");
                    __syncwarp();
                    if (s >= 4 * CB_FIRST + 5 && (s & 3) == 1 && lane == 0) asm volatile("red.relaxed.gpu.global.add.u32 [%0], 1;" :: "l"(&g_ctr[CT_CB + h * CB_ST - CB_FIRST + ((s - 5) >> 2)]) : "memory");
                }
                if (w4 == 0) {
                    if (CH_ARM && lane == 0) mbar_expect_tx(bar_sc, 2560);
                    if (lane < 16 && (lane & 7) >= 1 && (lane & 7) < 5) mbar_expect_tx(bar_m + 8 * lane, ((lane & 7) == 1 ? 1024 : 2048) << (s < NSEG - 1 ? 0 : 2));
                    if (s < NSEG - 1) {
                        if (!CH_ARM && lane == 0) mbar_expect_tx(bar_sc, 2560);
                        if (lane == 8) {
                            mbar_expect_tx(bar_x + 8 * ((s + 1) & 1), 32768);
                            tma_load_2d_mc(sb + C2_XB + ((s + 1) & 1) * C2_XS + rank * 5120, &mapX, bar_x + 8 * ((s + 1) & 1), rank * 64, (s + 1) * SEGL, (uint16_t)0xff);
                            if (s + 2 < NSEG)
                                asm volatile("cp.async.bulk.prefetch.tensor.2d.L2.global [%0, {%1, %2}];" :: "l"((uint64_t)&mapX), "r"(rank * 64), "r"((s + 2) * SEGL) : "memory");
                        }
                    }
                    if (lane == 16) mbar_expect_tx(bar_sx + 8 * (s & 1), 5120);
                    __syncwarp();
                }
            }
        }
        TS_MARK(12, 128);
        asm volatile("barrier.cluster.arrive.relaxed.aligned;" ::: "memory");
    } else {
        c2_wo(sb, tid - 256, 128);
        uint32_t va[5][2] = {};
        auto store_vt = [&](int s) {
            const uint32_t a = sb + C2_VT + (s & 1) * 6144 + a32;
            stmatrix_x4(a, va[0][0], va[0][1], va[1][0], va[1][1]);
            stmatrix_x4(a + 2048, va[2][0], va[2][1], va[3][0], va[3][1]);
            asm volatile("stmatrix.sync.aligned.m8n8.x2.shared.b16 [%0], {%1, %2};" :: "r"(a + 4096), "r"(va[4][0]), "r"(va[4][1]) : "memory");
        };
#pragma unroll 1
        for (int s = -1;;) {
            if (s >= 0) {
                const int t = tid - 256;
                const uint2* src = reinterpret_cast<const uint2*>(P.xb + ((s & 1) * 32768 + rank * 65536 + CH_XO + t * 8));
                asm volatile("" : "+l"(src));
                const uint32_t ma = sb + C2_XB + ((s + 1) & 1) * C2_XS + rank * 5120 + 4096 + (t >> 4) * 128 + ((((t >> 1) & 7) ^ (t >> 4)) << 4) + (t & 1) * 8;
                uint32_t ra[8], rb[8];
#pragma unroll
                for (int i = 1; i < 8; i++) {
                    const uint32_t d = (rank + i) & 7;
                    ra[i] = pin(mapa_u32(ma, d)); rb[i] = pin(mapa_u32(bar_m + 8 * c2_grp(i), d));
                }
                if (s == NSEG - 1) break;
                bar_sync<11, 256>();
                DBGW(29, 0);
                pace(CH_POLL_DELAY);
                const uint32_t tag = ((s >> 1) & 1) ^ 1;
                uint32_t p[8][2], m0, m1;
                auto issue = [&](uint32_t (&x)[8][2]) {
#pragma unroll
                    for (int k = 0; k < 8; k++)
                        asm volatile("ld.relaxed.gpu.global.v2.u32 {%0, %1}, [%2];" : "=r"(x[k][0]), "=r"(x[k][1]) : "l"(src + k * 128) : "memory");
                };
                auto check = [&](const uint32_t (&x)[8][2]) {
                    uint32_t bad = 0, bad2 = 0;
                    float r[4];
#pragma unroll
                    for (int k = 0; k < 8; k++) {
                        asm("lop3.b32 %0, %0, %1, %2, 0xf6;" : "+r"(bad) : "r"(x[k][0]), "r"(tag));
                        asm("lop3.b32 %0, %0, %1, %2, 0xf6;" : "+r"(bad2) : "r"(x[k][1]), "r"(tag));
#pragma unroll
                        for (int e = 0; e < 2; e++) {
                            const float lo = __uint_as_float(x[k][e] << 16), hi = __uint_as_float(x[k][e] & 0xffff0000u);
                            r[2 * e] = k ? r[2 * e] + lo : lo;
                            r[2 * e + 1] = k ? r[2 * e + 1] + hi : hi;
                        }
                    }
                    m0 = pack_bf16(r[0], r[1]); m1 = pack_bf16(r[2], r[3]);
                    asm volatile("" : "+r"(m0), "+r"(m1));
                    return __all_sync(0xffffffff, ((bad | bad2) & 1u) == 0u);
                };
                for (int it = 0; it < (1 << 20); it++) {
                    issue(p);
                    if (check(p)) break;
                }
                DBGW(30, 0);
                st_async_v2(ra[1], m0, m1, rb[1]);
                asm volatile("st.shared.v2.b32 [%0], {%1, %2};" :: "r"(ma), "r"(m0), "r"(m1) : "memory");
                __syncwarp();
                if (lane == 0) mbar_arrive(bar_m);
#pragma unroll
                for (int i = 2; i < 8; i++) st_async_v2(ra[i], m0, m1, rb[i]);
                DBGW(31, 0);
                TM(8);
                store_vt(s);
            }
            __syncwarp();
            s++;
            const uint32_t ost = pin(sb + C2_OB + t32), pla = pin(sb + C2_PB + lane * 16), plb = pin(sb + C2_PB + 512 + (lane & 7) * 16);
            bar_sync<1, 384>();
            fence_async_smem();
            DBGW(24, 0);
            if (s < NSEG - 1) bar_sync<2, 224>();
            else bar_arrive<6, 384>();
            {
                float acc[20];
                c2_xstream<0, 32, CH_SPV>(acc, w, dlo + ((C2_XB + (s & 1) * C2_XS) >> 4), rank, dlo + (C2_WV >> 4));
                wgmma_wait<0>();
#pragma unroll
                for (int j = 0; j < 5; j++) { va[j][0] = pack_bf16(acc[4 * j], acc[4 * j + 1]); va[j][1] = pack_bf16(acc[4 * j + 2], acc[4 * j + 3]); }
            }
            DBGW(26, 0);
            TM(7);
            if (s < NSEG - 1) {
                uint32_t p[5];
                bar_sync<3, 160>();
                DBGW(27, 0);
                ldmatrix_x4_trans(p[0], p[1], p[2], p[3], pla);
                asm volatile("ldmatrix.sync.aligned.m8n8.x1.trans.shared.b16 {%0}, [%1];" : "=r"(p[4]) : "r"(plb) : "memory");
                float oa[4] = {0.f, 0.f, 0.f, 0.f}, ob[4] = {0.f, 0.f, 0.f, 0.f}, sa[4] = {0.f, 0.f, 0.f, 0.f}, sc[4] = {0.f, 0.f, 0.f, 0.f};
                const uint32_t one = 0x3f803f80u;
                mma_16816(sa, one, one, one, one, p[0], p[1]);
                mma_16816(oa, va[0][0], va[0][1], va[1][0], va[1][1], p[0], p[1]);
                mma_16816(sc, one, one, one, one, p[2], p[3]);
                mma_16816(ob, va[2][0], va[2][1], va[3][0], va[3][1], p[2], p[3]);
                mma_16816(sa, one, one, one, one, p[4], 0u);
                mma_16816(oa, va[4][0], va[4][1], 0u, 0u, p[4], 0u);
                bar_arrive<6, 384>();
                float i0, i1;
                asm("rcp.approx.ftz.f32 %0, %1;" : "=f"(i0) : "f"(sa[0] + sc[0]));
                asm("rcp.approx.ftz.f32 %0, %1;" : "=f"(i1) : "f"(sa[1] + sc[1]));
                sts32(ost, pack_bf16((oa[0] + ob[0]) * i0, (oa[2] + ob[2]) * i0));
                sts32(ost + 32, pack_bf16((oa[1] + ob[1]) * i1, (oa[3] + ob[3]) * i1));
                fence_async_smem();
                __syncwarp();
                if (elect_one()) {
#pragma unroll
                    for (int i = 1; i < 8; i++) {
                        const uint32_t d = (rank + i) & 7;
                        bulk_s2s(mapa_u32(sb + C2_OB + i * 1024 + w4 * 256, d), sb + C2_OB + w4 * 256, 256, mapa_u32(bar_o + 8 * c2_grp(i), d));
                        if (i == 1) mbar_arrive(bar_o);
                    }
                }
                __syncwarp();
                DBGW(28, 0);
            }
        }
        store_vt(NSEG - 1);
        fence_async_smem();
        bar_arrive<7, 256>();
        const uint32_t lane = fresh_lane();
        if (w4 == 0) {
            mbar_wait(bar_h, 0);
#pragma unroll 1
            for (uint32_t o = 0; o < 2; o++) {
                asm volatile("bar.sync %0, 160;" :: "r"(13 + o) : "memory");
                if (elect_one()) {
#pragma unroll
                    for (int i = 1; i < 8; i++) {
                        const uint32_t d = (rank + i) & 7;
                        bulk_s2s(mapa_u32(sb + C2_WO + i * 8192 + o * 4096, d), sb + C2_QX + o * 4096, 4096, mapa_u32(bar_m + o * 64 + 8 * c2_grp(i), d));
                    }
                }
                __syncwarp();
                if (lane < 4) mbar_arrive(bar_m + o * 64);
                TM(21 + o);
            }
        }
        __syncwarp();
        asm volatile("barrier.cluster.arrive.relaxed.aligned;" ::: "memory");
        *reinterpret_cast<uint2*>(P.xb + (32768 + CH_XO + rank * 65536 + C * 1024 + (w4 * 32 + lane) * 8)) = make_uint2(0u, 0u);
    }
    asm volatile("barrier.cluster.wait.aligned;" ::: "memory");
    TS_END(2);
    CYC(3);
    if (wg == 0) TM(23);
}

constexpr int P3_LEN = 24;
struct SideParams {
    CUtensorMap mapA[2];
    CUtensorMap mapW[3];
    CUtensorMap mapQ, mapK, mapV;
    CUtensorMap mapO;
    CUtensorMap mapCtx[2];
    CUtensorMap mapWo[2];
    CUtensorMap mapOut;
    bf16* qkv[3];
    const bf16 *x, *gate_w;
    bf16* out;
    uint32_t jobs[34 * 2];
    uint16_t sched[34 * P3_LEN];
    uint8_t first[34];
};
constexpr int P3_STAGES = 14;
#define P3_LAG 2
#define SD_GD 12000
#define SD_D0 0
#define SD_EFW 0
#define SD_EFA 0
#define SD_EFS 0
#define SD_EFK 0
#define SD_ALIAS 1
#define SD_JN 1
#define SD_PB 1
#define SD_GW 2
#define SD_NS 1
#define SD_PAD 0
#define SD_FD 0
#define SD_LF 0
#define SD_PK 5
#define SD_CT 384
#define PT(i)
#define SC(i)
#define ST(i, c)
#define OT(i)
constexpr uint32_t SD_PF = FA_BAR + 256, SD_PE = SD_PF + 8 * P3_STAGES, SD_OF = SD_PE + 8 * P3_STAGES, SD_OE = SD_OF + 32, SD_CL = SD_OE + 32, SD_DONE = FA_BAR + 576;
constexpr int SD_SMEM = SD_DONE + 2 * P3_LEN * 8;
__device__ __forceinline__ void tma_load_3d(uint32_t dst, const CUtensorMap* map, uint32_t bar, int c0, int c1, int c2) {
    asm volatile(
        "cp.async.bulk.tensor.3d.shared::cluster.global.mbarrier::complete_tx::bytes [%0], [%1, {%3, %4, %5}], [%2];"
        :: "r"(dst), "l"((uint64_t)map), "r"(bar), "r"(c0), "r"(c1), "r"(c2) : "memory");
}
__global__ void __cluster_dims__(2, 1, 1) __launch_bounds__(384, 1) side_kernel(const __grid_constant__ SideParams P) {
    extern __shared__ __align__(1024) uint8_t smem_side[];
    ST(0, threadIdx.x == 0);
    const uint32_t sb = smem_u32(smem_side);
    const uint32_t full = sb + SD_PF, empty = sb + SD_PE, done = sb + SD_DONE;
    const uint32_t bar_q = sb + FA_BAR, bar_qe = bar_q + 16, bar_kf = bar_q + 32, bar_vf = bar_q + 48, bar_ke = bar_q + 64, bar_ve = bar_q + 80,
                   bar_of = bar_q + 96, bar_oe = bar_q + 112, oslot = bar_q + 144;
    const int warp = __shfl_sync(0xffffffff, threadIdx.x >> 5, 0), lane = threadIdx.x & 31;
    const uint32_t rank = cluster_ctarank();
    const uint16_t* sched = P.sched + (blockIdx.x >> 1) * P3_LEN;
    const uint32_t so0 = P.first[blockIdx.x >> 1] * 8;
    TS_BEGIN_T(0, 320);
    {
        const uint32_t n = lane * 12 + warp, a = bar_q + 8 * (n < 16 ? n : n + 16);
        if (a < sb + SD_SMEM) mbar_init(a, n < 16 ? (0x14881181u >> (n >> 1) * 4) & 15 : a < empty ? 1 : a < sb + SD_OF || a >= done ? 4 : ((a - sb - SD_OF) >> 5 & 1) + 1);
        asm volatile("fence.mbarrier_init.release.cluster;" ::: "memory");
    }
    __syncthreads();
    if (threadIdx.x * 8 < so0) {
        mbar_arrive(full + 8 * lane);
        asm volatile("mbarrier.arrive.shared::cta.b64 _, [%0], 4;" :: "r"(empty + 8 * lane) : "memory");
    }
    __syncwarp();
    cluster_sync_relaxed();
    if (warp >= 8) {
        asm volatile("setmaxnreg.dec.sync.aligned.u32 %0;" :: "n"(FA_RLO));
        if (warp == 8) {
            uint32_t so = so0, ph = 1;
            pace(SD_D0);
#pragma unroll 1
            for (;; sched++) {
                const uint32_t e = *sched, z = (e >> 5) & 3, na = e >> 10;
                if (z == 3) break;
#pragma unroll 1
                for (int i = 1 - na; i < 16; i += 2 - na) {
                    mbar_wait(empty + so, ph);
                    if (elect_one()) {
                        mbar_expect_tx(full + so, 16384);
                        if (i & 1) tma_load_2d_mc(sb + so * 2048 + rank * 8192, &P.mapW[z], full + so, (e & 31) * 128 + rank * 64, (i >> 1) * 64, (uint16_t)3, SD_EFW ? L2_FIRST : L2_NORMAL);
                        else tma_load_2d(sb + so * 2048, &P.mapA[z != 0], full + so, (i >> 1) * 64, (((e >> 7) & 7) * 2 + rank) * 128, SD_EFA && z ? L2_FIRST : L2_NORMAL);
                    }
                    ST(3, lane == 0 && i == 0 && sched == P.sched + (blockIdx.x >> 1) * P3_LEN);
                    so += 8;
                    if (so == 8 * P3_STAGES) { so = 0; ph ^= 1; }
                }
            }
            TS_MARK(13, 256);
            PT(0);
            int it = 0, t = blockIdx.x, hp_ready = 0;
            auto load = [&](uint32_t dst, const CUtensorMap* map, uint32_t bar, int row) {
                if (elect_one()) {
                    mbar_expect_tx(bar, 32768);
                    tma_load_2d(dst, map, bar, 0, row, SD_EFK && map != &P.mapQ ? L2_FIRST : L2_NORMAL);
                    tma_load_2d(dst + 16384, map, bar, 64, row, SD_EFK && map != &P.mapQ ? L2_FIRST : L2_NORMAL);
                }
            };
            auto load_q = [&](int item) {
                const uint32_t b = bar_q + 8 * (item & 1);
                sts32(b + 128, t);
                if (t < 0) { mbar_arrive_if(b, lane == 0); return; }
                const int hp = fa_head(t) >> 1;
                if (!((hp_ready >> hp) & 1)) { wait_ctr(CT_AP + hp, 192u); hp_ready |= 1 << hp; }
                load(sb + FA_Q + (item & 1) * 32768, &P.mapQ, b, fa_head(t) * SEQ + fa_qt(t) * 128);
            };
            auto load_v = [&](int it, int row) {
                const int s = it & 1;
                if (it < 2) mbar_wait(empty + 56 + 32 * s, ph);
                mbar_wait(bar_ve + 8 * s, ((it >> 1) & 1) ^ 1);
                load(sb + FA_KV + s * 65536 + 32768, &P.mapV, bar_vf + 8 * s, row);
            };
            int vrow = 0;
            mbar_wait(empty + 8, ph);
            PT(1);
            load_q(0);
            PT(2);
#pragma unroll 1
            for (int item = 0; t >= 0; item++) {
                const int h = fa_head(t), jn = min(fa_qt(t), SD_JN);
                if (item == 1 && blockIdx.x < 8) TS_MARK(14, 256);
#pragma unroll 1
                for (int j = fa_qt(t); j >= 0; j--, it++) {
                    const int s = it & 1;
                    uint32_t tn = 0;
                    asm volatile("{\n.reg .pred p;\nsetp.eq.u32 p, %2, 0;\n@p atom.relaxed.gpu.global.add.u32 %0, [%1], 1;\n}" : "+r"(tn) : "l"(&g_ctr[CT_ATTN] + lane), "r"((j ^ jn) | lane) : "memory");
                    if (it < 2) mbar_wait(empty + 40 + 32 * s, ph);
                    mbar_wait(bar_ke + 8 * s, ((it >> 1) & 1) ^ 1);
                    PT(4 + it);
                    load(sb + FA_KV + s * 65536, &P.mapK, bar_kf + 8 * s, h * SEQ + j * 128);
                    if (it > 0) load_v(it - 1, vrow);
                    vrow = h * SEQ + j * 128;
                    if (j == jn) {
                        const int tp = t;
                        t = FA_GRID + __shfl_sync(0xffffffff, tn, 0);
                        mbar_arrive_if(sb + SD_CL, tp < SD_CT && t >= SD_CT && lane == 0);
                        if (t >= FA_ITEMS) t = FA_ITEMS - 1 - t;
                        mbar_wait(bar_qe + 8 * ((item + 1) & 1), (((item + 1) >> 1) & 1) ^ 1);
                        load_q(item + 1);
                    }
                }
            }
            load_v(it - 1, vrow);
            TS_MARK(15, 256);
            const uint32_t tk = ~t;
            so = 0; ph = 1;
            TS_BEGIN_T(4, 256);
            wait_ctr(CT_P, FA_GRID);
#pragma unroll 1
            for (uint32_t e = P.jobs[tk & ~1u], en = P.jobs[tk | 1u]; e; e = en, en = 0) {
                const uint32_t mt = e & 15, na = e >> 10 & 127, n = na + (e >> 23);
#pragma unroll 1
                for (uint32_t i = 0; i < n; i++) {
                    const uint32_t b = i >= na, k = b ? (e >> 17 & 63) + i - na : (e >> 4 & 63) + i;
                    mbar_wait(so < 16 ? bar_ke + 8 * (~it & 1) : bar_ve - 16 + so, ((it - 1 - (so == 24)) >> 1) & 1);
                    mbar_wait(sb + SD_OE + so, ph);
                    if (elect_one()) {
                        mbar_expect_tx(sb + SD_OF + so, 49152);
                        tma_load_3d(sb + so * 6144 + 16384, &P.mapWo[b], sb + SD_OF + so, 0, k * 64, (tk & 1) * 4);
                    }
                    const bool late = k >= 2 * O2_HE;
                    if (i == 0 || i == na || k == 2 * O2_HE) {
                        wait_ctr(b ? CT_CB + lane * CB_ST - CB_FIRST + max(mt, CB_FIRST) : CT_CA + mt * 2 + late, b ? (CB_ST ? 8u : 256u) : late ? 2u * (NH - O2_HE) : 2u * O2_HE);
                        __syncwarp();
                    }
                    if (elect_one()) tma_load_2d(sb + so * 6144, &P.mapCtx[b], sb + SD_OF + so, (k & 1) * 64, (k >> 1) * SEQ + mt * 128);
                    so = (so + 8) & 31;
                    if (so == 0) ph ^= 1;
                }
            }
            TS_END_T(4, 256);
            finish_launch(lane);
        } else if (warp == 11) {
#pragma unroll 1
            for (int i = 0; i < 4000 && !mbar_test(done + 8 * SD_GW, 0); i++) __nanosleep(500);
            const uint4 gv0 = __ldg(reinterpret_cast<const uint4*>(P.gate_w) + lane), gv1 = __ldg(reinterpret_cast<const uint4*>(P.gate_w) + 32 + lane);
            const uint32_t gw[8] = {gv0.x, gv0.y, gv0.z, gv0.w, gv1.x, gv1.y, gv1.z, gv1.w};
#pragma unroll 1
            for (int r = blockIdx.x; r < SEQ; r += gridDim.x) {
                const uint4 x0 = __ldg(reinterpret_cast<const uint4*>(P.x + (size_t)r * DM) + lane), x1 = __ldg(reinterpret_cast<const uint4*>(P.x + (size_t)r * DM) + 32 + lane);
                const uint32_t xw[8] = {x0.x, x0.y, x0.z, x0.w, x1.x, x1.y, x1.z, x1.w};
                float sum = 0.f;
#pragma unroll
                for (int e = 0; e < 8; e++) {
                    const uint32_t pr = pack_bf16(__uint_as_float(xw[e] << 16) * __uint_as_float(gw[e] << 16), __uint_as_float(xw[e] & 0xffff0000u) * __uint_as_float(gw[e] & 0xffff0000u));
                    sum += __uint_as_float(pr << 16) + __uint_as_float(pr & 0xffff0000u);
                }
#pragma unroll
                for (int o = 16; o; o >>= 1) sum += __shfl_xor_sync(0xffffffff, sum, o);
                if (lane == 0) g_gate[r] = bf16r(__fdividef(1.f, 1.f + __expf(-bf16r(sum))));
            }
#pragma unroll 1
            for (int i = 0; i < 4000 && !mbar_test(sb + SD_CL, 0); i++) __nanosleep(500);
#pragma unroll 1
            for (int i = blockIdx.x * 32 + lane; i < SEQ * DM / 8; i += gridDim.x * 32) reinterpret_cast<uint4*>(P.out)[i] = make_uint4(0u, 0u, 0u, 0u);
            asm volatile("fence.proxy.async.global;" ::: "memory");
            __syncwarp();
            if (lane == 0) signal_ctr(CT_P);
        } else if (lane == 0) {
            const int wg = warp - 9;
            SC(0);
#pragma unroll 1
            for (uint32_t d = done + wg * P3_LEN * 8;; d += 8, sched++) {
                const uint32_t e = *sched;
                if (((e >> 5) & 3) == 3) break;
                mbar_wait(d, 0);
                signal_ctr(CT_AP + ((e & 31) >> 1));
            }
            const uint32_t stg = sb + FA_O + wg * 16384;
            TS_END_T(0, 320);
            SC(1);
            TS_BEGIN_T(1, 320);
#pragma unroll 1
            for (int n = 0;; n++) {
                mbar_wait(bar_of + 8 * wg, n & 1);
                int t;
                asm volatile("ld.shared.s32 %0, [%1];" : "=r"(t) : "r"(oslot + wg * 4) : "memory");
                asm volatile("fence.proxy.async.shared::cta;" ::: "memory");
                const bool last = t < 0;
                t &= 0xffff;
                const int qt = fa_qt(t), h = fa_head(t);
                tma_store_2d(&P.mapO, stg, 0, h * SEQ + qt * 128 + wg * 64);
                tma_store_2d(&P.mapO, stg + 8192, 64, h * SEQ + qt * 128 + wg * 64);
                asm volatile("cp.async.bulk.commit_group;" ::: "memory");
                asm volatile("cp.async.bulk.wait_group.read 0;" ::: "memory");
                mbar_arrive(bar_oe + 8 * wg);
                asm volatile("cp.async.bulk.wait_group 0;" ::: "memory");
                signal_ctr(CT_CA + qt * 2 + (h >= O2_HE));
                if (last) break;
            }
            TS_END_T(1, 320);
            SC(2);
        }
    } else {
        asm volatile("setmaxnreg.inc.sync.aligned.u32 %0;" :: "n"(FA_RHI));
        const int wg = warp >> 2;
#pragma unroll
        for (int i = 0; i < SD_PAD; i++) asm volatile("pmevent 0;");
        {
            uint32_t a[32][4];
            float acc[64];
            const uint32_t b_lo = desc_lo(sb, 8192);
            const int r = warp * 16 + (lane & 15);
            const uint32_t la = sb + r * 128 + (((lane >> 4) ^ (r & 7)) << 4);
#pragma unroll
            for (int i = 0; i < 32; i++) ldsm_x4(a[i], la + i * 1024);
            const uint32_t rel = mapa_u32(empty, lane & 1);
            const int tw = threadIdx.x & 127;
            uint32_t so = so0, ph = 0;
            const uint32_t b1 = SD_PB ? pin(1 + wg) : 1 + wg;
            if (wg == 1) asm volatile("bar.arrive 1, 256;" ::: "memory");
#pragma unroll 1
            for (uint32_t d = done + wg * P3_LEN * 8;; d += 8, sched++) {
                const uint32_t e = *sched;
                if (((e >> 5) & 3) == 3) break;
                const bool na = e >> 10;
                const bool sig = tw < (na ? 4 : 2);
                uint32_t old = 0;
                auto release = [&]() { asm volatile("{\n.reg .pred p;\nsetp.ne.u32 p, %1, 0;\n@p mbarrier.arrive.shared::cluster.b64 _, [%0];\n}" :: "r"(rel + old), "r"((uint32_t)sig) : "memory"); };
                bf16* dst;
                if (SD_LF & 2) dst = P.qkv[(e >> 5) & 3] + ((size_t)(e & 31) * SEQ + (((e >> 7) & 7) * 2 + rank) * 128 + warp * 16 + (lane >> 2)) * HD + (lane & 3) * 8;
                asm volatile("bar.sync %0, 256;" :: "r"(b1) : "memory");
#pragma unroll
                for (int k = 0; k < 8; k++) {
                    const uint32_t sa = so;
                    if (na) {
                        if (k == 0) ST(1, threadIdx.x == 0 && d == done);
                        mbar_wait(full + so, ph);
                        if (k == 0) ST(2, threadIdx.x == 0 && d == done);
#pragma unroll
                        for (int kk = 0; kk < 4; kk++) ldsm_x4(a[k * 4 + kk], (la + so * 2048) ^ (kk * 32));
                        so += 8;
                        if (so == 8 * P3_STAGES) { so = 0; ph ^= 1; }
                    }
                    mbar_wait(full + so, ph);
                    if (k == 0 || k == 3 || k == 7) ST(k == 0 ? 4 : k == 3 ? 5 : 6, threadIdx.x == 0 && d == done);
                    wgmma_fence();
#pragma unroll
                    for (int kk = 0; kk < 4; kk++) wgmma_rs_n128_tb_lo(acc, a[k * 4 + kk], b_lo + so * 128 + kk * 128, (k | kk) != 0);
                    wgmma_commit();
                    if (k == P3_LAG) asm volatile("bar.arrive %0, 256;" :: "r"(2 - wg) : "memory");
                    if ((SD_LF & 4) && k == SD_PK)
                        asm volatile("{\n.reg .pred p;\nsetp.gt.u32 p, %0, 99;\n@p st.global.u32 [%1], %0;\n}" :: "r"(rank), "l"(dst) : "memory");
                    if (k > 0) { wgmma_wait<1>(); release(); }
                    old = (lane & 2) ? sa : so;
                    so += 8;
                    if (so == 8 * P3_STAGES) { so = 0; ph ^= 1; }
                }
                wgmma_wait<0>();
                release();
                if (!(SD_LF & 2)) dst = P.qkv[(e >> 5) & 3] + ((size_t)(e & 31) * SEQ + (((e >> 7) & 7) * 2 + rank) * 128 + warp * 16 + (lane >> 2)) * HD + (lane & 3) * 8;
#pragma unroll
                for (int i = 0; i < 8; i++) {
                    const float* c = &acc[(i >> 1) * 16 + (i & 1) * 2];
                    *reinterpret_cast<uint4*>(dst + (i & 1) * 8 * HD + (i >> 1) * 32) =
                        make_uint4(pack_bf16(c[0], c[1]), pack_bf16(c[4], c[5]), pack_bf16(c[8], c[9]), pack_bf16(c[12], c[13]));
                }
                __syncwarp();
                mbar_arrive_if(d, lane == 0);
            }
        }
        const uint32_t tk = attn_consumer(sb, wg, warp & 3, lane);
        float acc[128];
#pragma unroll
        for (int i = 0; i < 128; i++) asm volatile("" : "=f"(acc[i]));
        const uint32_t a_lo = desc_lo(sb + wg * 8192, 16), b_lo = desc_lo(sb + 16384, 8192);
        const uint32_t st = sb + FA_O + warp * 4096, sl = st + (lane & 15) * 128 + (((lane >> 4) ^ (lane & 7)) << 4);
        const bool sig = (threadIdx.x & 127) == 0;
        uint32_t so = 0, ph = 0;
        uint32_t pk[64], part = 4, row0 = 0;
#pragma unroll
        for (int i = 0; i < 64; i++) asm volatile("" : "=r"(pk[i]));
        auto drain = [&](const uint32_t* c, uint32_t q) {
            asm volatile("cp.async.bulk.wait_group.read 1;" ::: "memory");
            __syncwarp();
#pragma unroll
            for (int t = 0; t < 4; t++) stmatrix_x4((sl ^ (t * 32)) + (q & 1) * 2048, c[4 * t], c[4 * t + 1], c[4 * t + 2], c[4 * t + 3]);
            fence_async_smem();
            __syncwarp();
            if (elect_one())
                asm volatile("cp.reduce.async.bulk.tensor.2d.global.shared::cta.add.bulk_group [%0, {%2, %3}], [%1];"
                             :: "l"((uint64_t)&P.mapOut), "r"(st + (q & 1) * 2048), "r"((tk & 2) * 128 + q * 64), "r"(row0) : "memory");
            asm volatile("cp.async.bulk.commit_group;" ::: "memory");
        };
#pragma unroll 1
        for (uint32_t e = P.jobs[(tk >> 1) & ~1u], en = P.jobs[(tk >> 1) | 1u]; e; e = en, en = 0) {
            const uint32_t row = (e & 15) * 128 + warp * 16, na = e >> 10 & 127, n = na + (e >> 23);
            float g0, g1;
#pragma unroll 1
            for (uint32_t i = 0;; i++) {
                if (i == n || (i == na && i)) {
                    const float w0 = fmaxf(1.f - g0, 0x1p-40f), w1 = fmaxf(1.f - g1, 0x1p-40f);
                    const float r0 = i < n ? __fdividef(g0, w0) : na < n ? w0 : g0, r1 = i < n ? __fdividef(g1, w1) : na < n ? w1 : g1;
                    wgmma_wait<0>();
                    mbar_arrive_if(sb + SD_OE + ((so - 8) & 31), sig && i == n);
                    if (i == n) OT(3); else OT(2);
#pragma unroll
                    for (int c = 0; c < 32; c++) { acc[4 * c] *= r0; acc[4 * c + 1] *= r0; acc[4 * c + 2] *= r1; acc[4 * c + 3] *= r1; }
                    if (i == n) break;
                }
                mbar_wait(sb + SD_OF + so, ph);
                if (i == 0) OT(1);
                wgmma_fence();
#pragma unroll
                for (int kk = 0; kk < 4; kk++) wgmma_ss_n256_tb(acc, a_lo + so * 384 + kk * 2, b_lo + so * 384 + kk * 128, i | kk);
                wgmma_commit();
                if (i > 0) { wgmma_wait<1>(); mbar_arrive_if(sb + SD_OE + ((so - 8) & 31), sig); }
                else {
                    asm volatile("ld.relaxed.gpu.global.f32 %0, [%1];" : "=f"(g0) : "l"(g_gate + row + (lane >> 2)) : "memory");
                    asm volatile("ld.relaxed.gpu.global.f32 %0, [%1 + 32];" : "=f"(g1) : "l"(g_gate + row + (lane >> 2)) : "memory");
                }
                if (part < 4) {
                    drain(pk, part++);
#pragma unroll
                    for (int c = 0; c < 48; c++) pk[c] = pk[c + 16];
                }
                so = (so + 8) & 31;
                if (so == 0) ph ^= 1;
            }
#pragma unroll
            for (int c = 0; c < 64; c++) pk[c] = pack_bf16(acc[2 * c], acc[2 * c + 1]);
            part = 0; row0 = row;
            mbar_wait(bar_oe + 8 * wg, tk & 1);
            OT(4);
        }
        if (SD_FD) {
            const uint32_t d = warp * 2048 - FA_O - warp * 4096;
#pragma unroll
            for (int q = 0; q < 4; q++) {
#pragma unroll
                for (int t = 0; t < 4; t++) stmatrix_x4((sl ^ (t * 32)) + d + q * 49152, pk[16 * q + 4 * t], pk[16 * q + 4 * t + 1], pk[16 * q + 4 * t + 2], pk[16 * q + 4 * t + 3]);
                if (SD_FD == 2 && !(q & 1)) continue;
                fence_async_smem();
                __syncwarp();
                if (elect_one())
#pragma unroll
                    for (int r = q + 1 - SD_FD; r <= q; r++)
                        asm volatile("cp.reduce.async.bulk.tensor.2d.global.shared::cta.add.bulk_group [%0, {%2, %3}], [%1];"
                                     :: "l"((uint64_t)&P.mapOut), "r"(st + d + r * 49152), "r"((tk & 2) * 128 + r * 64), "r"(row0) : "memory");
            }
            asm volatile("cp.async.bulk.commit_group;" ::: "memory");
        } else {
#pragma unroll
        for (int q = 0; q < 4; q++) drain(pk + 16 * q, q);
        }
        asm volatile("cp.async.bulk.wait_group.read 0;" ::: "memory");
    }
}

typedef CUresult (*PFN_encodeTiled)(CUtensorMap*, CUtensorMapDataType, cuuint32_t, void*, const cuuint64_t*,
                                    const cuuint64_t*, const cuuint32_t*, const cuuint32_t*, CUtensorMapInterleave,
                                    CUtensorMapSwizzle, CUtensorMapL2promotion, CUtensorMapFloatOOBfill);
static PFN_encodeTiled g_encode = nullptr;

static void make_map(CUtensorMap* m, const void* ptr, uint64_t rows, uint64_t cols, uint32_t box_rows, bool narrow = false) {
    cuuint64_t dims[2] = {cols, rows};
    cuuint64_t strides[1] = {cols * 2};
    cuuint32_t box[2] = {narrow ? 16u : 64u, box_rows};
    cuuint32_t es[2] = {1, 1};
    g_encode(m, CU_TENSOR_MAP_DATA_TYPE_BFLOAT16, 2, const_cast<void*>(ptr), dims, strides, box, es,
             CU_TENSOR_MAP_INTERLEAVE_NONE, narrow ? CU_TENSOR_MAP_SWIZZLE_NONE : CU_TENSOR_MAP_SWIZZLE_128B, CU_TENSOR_MAP_L2_PROMOTION_L2_256B,
             CU_TENSOR_MAP_FLOAT_OOB_FILL_NONE);
}

static void make_map3(CUtensorMap* m, const void* ptr, uint64_t rows, uint64_t cols, uint32_t box_rows, uint32_t nblk) {
    cuuint64_t dims[3] = {64, rows, cols / 64};
    cuuint64_t strides[2] = {cols * 2, 128};
    cuuint32_t box[3] = {64u, box_rows, nblk};
    cuuint32_t es[3] = {1, 1, 1};
    g_encode(m, CU_TENSOR_MAP_DATA_TYPE_BFLOAT16, 3, const_cast<void*>(ptr), dims, strides, box, es,
             CU_TENSOR_MAP_INTERLEAVE_NONE, CU_TENSOR_MAP_SWIZZLE_128B, CU_TENSOR_MAP_L2_PROMOTION_L2_256B, CU_TENSOR_MAP_FLOAT_OOB_FILL_NONE);
}

template <typename... KArgs, typename... Args>
static void launch_pdl(void (*kernel)(KArgs...), int grid, int block, size_t smem, cudaStream_t st, bool pdl, Args... args) {
    cudaLaunchConfig_t cfg = {};
    cfg.gridDim = dim3(grid); cfg.blockDim = dim3(block); cfg.dynamicSmemBytes = smem; cfg.stream = st;
    cudaLaunchAttribute at[1];
    at[0].id = cudaLaunchAttributeProgrammaticStreamSerialization;
    at[0].val.programmaticStreamSerializationAllowed = 1;
    cfg.attrs = at; cfg.numAttrs = pdl ? 1 : 0;
    cudaLaunchKernelEx(&cfg, kernel, KArgs(args)...);
}

extern "C" void kernel_launch(void* const* d_in, const int* in_sizes, int n_in, void* d_out, int out_size) {
    const bf16* x = (const bf16*)d_in[0];
    const bf16* ckv = (const bf16*)d_in[1];
    const bf16* wq = (const bf16*)d_in[2];
    const bf16* wuk = (const bf16*)d_in[3];
    const bf16* wuv = (const bf16*)d_in[4];
    const bf16* wo = (const bf16*)d_in[5];
    const bf16* mem0 = (const bf16*)d_in[7];
    const bf16* Wq = (const bf16*)d_in[8];
    const bf16* Wk = (const bf16*)d_in[9];
    const bf16* Wv = (const bf16*)d_in[10];
    const bf16* Wo = (const bf16*)d_in[11];
    const bf16* gate_w = (const bf16*)d_in[13];
    bf16* out = (bf16*)d_out;

    static SideParams SP;
    static ChainParams CP;
    static bool init = false;
    static const void* last_in[15];
    bool same = init;
    for (int i = 0; i < 14 && same; i++) same = last_in[i] == d_in[i];
    same = same && last_in[14] == d_out;
    if (!init) {
        cudaDriverEntryPointQueryResult qr;
        cudaGetDriverEntryPoint("cuTensorMapEncodeTiled", (void**)&g_encode, cudaEnableDefault, &qr);
        cudaFuncSetAttribute(chain_kernel, cudaFuncAttributeMaxDynamicSharedMemorySize, C2_SMEM);
        cudaFuncSetAttribute(side_kernel, cudaFuncAttributeMaxDynamicSharedMemorySize, SD_SMEM);
        for (int p = 0; p < 34; p++) {
            uint16_t* t = SP.sched + p * P3_LEN;
            int n = 0, rows = -1;
            auto add = [&](int z, int mp, int head) {
#define P3_RQ 12
#define P3_RK 22
                head = (head + 32 - (z ? P3_RK : P3_RQ)) & 31;
                t[n++] = (uint16_t)(head | z << 5 | mp << 7 | (rows != (z ? 8 : 0) + mp) << 10);
                rows = (z ? 8 : 0) + mp;
            };
            const int mp = p & 7, kind = p >> 3;
            if (kind == 0) for (int h = 0; h < 23; h++) add(0, mp, h);
            else if (kind < 4) {
                for (int i = kind - 1; i < 54; i += 3) add(1 + (i & 1), mp, i >> 1);
                if (kind < 3) for (int h = 27; h < 32; h++) add(kind, mp, h);
                else for (int h = 23; h < 27; h++) add(0, mp, h);
            } else for (int i = 0; i < 20; i++) add(0, mp * 4 + i / 5, 27 + i % 5);
            int stages = 0;
            for (int i = 0; i < n; i++) stages += 8 << (t[i] >> 10);
            SP.first[p] = (uint8_t)((P3_STAGES - stages % P3_STAGES) % P3_STAGES);
            while (n < P3_LEN) t[n++] = 3 << 5;
        }
#define O6_SCHED 0x1f040400, 0x0, 0xfc10, 0x0, 0x1000000, 0xec51, 0x1f040001, 0x0, 0x278c002, 0x1001401, 0x1e000002, 0x0, 0xad53, 0x4302, 0x1e000003, 0x0, 0x2785403, 0x2807004, 0x1d8a0004, 0x0, 0xb000005, 0x91c4, 0x4eec8e5, 0x0, 0x16280006, 0x3805, 0xa0099a6, 0x0, 0x6806, 0xb542b67, 0xd807, 0x13c8, 0xec18, 0x0, 0x1d8a0008, 0x0, 0x2800408, 0xd009, 0xb80000a, 0xbd23349, 0xec5a, 0x0, 0x648000b, 0x14ae140a, 0xec5b, 0x0, 0x860000b, 0x1500000c, 0xb54900c, 0x0, 0x724c, 0xdca0bed, 0xd947dfd, 0x0, 0x5007c0d, 0x4ee1bae, 0x1200140b, 0x4ba1a8e, 0x14800009, 0x44c1eee, 0x15000007, 0x4dc175e, 0x10ac0005, 0x4a839ae, 0x7c0f, 0x51438ce, 0x85ff, 0x500300e
        const uint32_t sched[68] = {O6_SCHED};
        for (int i = 0; i < 68; i++) SP.jobs[i] = sched[i];
        init = true;
    }
    if (!same) {
        for (int i = 0; i < 14; i++) last_in[i] = d_in[i];
        last_in[14] = d_out;
        void *pQA, *pKA, *pVA, *pCA, *pCB;
        cudaGetSymbolAddress(&pQA, g_QA); cudaGetSymbolAddress(&pKA, g_KA); cudaGetSymbolAddress(&pVA, g_VA);
        cudaGetSymbolAddress(&pCA, g_ctxA); cudaGetSymbolAddress(&pCB, g_ctxB);
        pCA = pQA;
        make_map(&SP.mapA[0], x, SEQ, DM, 128);
        make_map(&SP.mapA[1], ckv, SEQ, DM, 128);
        const void* ws[3] = {wq, wuk, wuv};
        void* cs[3] = {pQA, pKA, pVA};
        for (int i = 0; i < 3; i++) { make_map(&SP.mapW[i], ws[i], DM, NQ, 64); SP.qkv[i] = (bf16*)cs[i]; }
        make_map(&CP.mapX, x, SEQ, DM, SEGL);
        make_map(&CP.mapM, mem0, NMEM, DM, NMEM);
        make_map(&CP.mapW[0], Wq, DM, NQ, 64);
        make_map(&CP.mapW[1], Wk, DM, NQ, 64);
        make_map(&CP.mapW[2], Wv, DM, NQ, 64);
        make_map(&CP.mapWo, Wo, NQ, DM, 64);
        make_map(&SP.mapQ, pQA, NH * SEQ, HD, 128);
        make_map(&SP.mapK, pKA, NH * SEQ, HD, 128);
        make_map(&SP.mapV, pVA, NH * SEQ, HD, 128);
        make_map(&SP.mapO, pCA, NH * SEQ, HD, 64);
        make_map(&SP.mapCtx[0], pCA, NH * SEQ, HD, 128);
        make_map(&SP.mapCtx[1], pCB, NH * SEQ, HD, 128);
        make_map3(&SP.mapWo[0], wo, NQ, DM, 64, 4);
        make_map3(&SP.mapWo[1], Wo, NQ, DM, 64, 4);
        make_map(&SP.mapOut, out, SEQ, DM, 16);
        SP.out = out;
        make_map(&CP.mapC, pCB, NH * SEQ, HD, 64);
        make_map(&CP.mapS, pCB, NH * SEQ, HD, 32, true);
        CP.out = out;
        void* pXB;
        cudaGetSymbolAddress(&pXB, g_xbuf);
        CP.xb = (char*)(((uintptr_t)pXB + 65535) & ~(uintptr_t)65535);
        SP.x = x; SP.gate_w = gate_w;
    }
    cudaStream_t s1 = cudaStreamPerThread;
    const bool pdl = true;
    launch_pdl(chain_kernel, 64, 384, C2_SMEM, s1, false, CP);
    launch_pdl(side_kernel, FA_GRID, 384, SD_SMEM, s1, pdl, SP);
}
```
